```python
import torch

def _softmax(x, axis=-1):
    return torch.softmax(x, dim=axis)
def _gelu(x):
    return torch.nn.functional.gelu(x, approximate="tanh")
def _silu(x):
    return torch.nn.functional.silu(x)
def _sigmoid(x):
    return torch.sigmoid(x)
def _layernorm(x, axis=-1, eps=1e-5):
    m = x.mean(dim=axis, keepdim=True)
    v = x.var(dim=axis, keepdim=True, unbiased=False)
    return (x - m) / torch.sqrt(v + eps)
def _scatter_add(tgt, idx, src, axis=0):
    return tgt.clone().index_add_(axis, idx, src)
def _segment_sum(src, seg, n):
    out = torch.zeros((n,) + src.shape[1:], dtype=src.dtype)
    return out.index_add_(0, seg, src)
def _pad(x, pw):
    flat = tuple(v for pair in reversed(pw) for v in pair)
    return torch.nn.functional.pad(x, flat)

kernel_name = 'sequential_preLN__spectral_fnet__moe_arch_mod__prompt'

def setup_inputs():

    _w = (lambda a: (lambda t: t.to(torch.bfloat16) if t.is_floating_point() else t)(torch.as_tensor(a)))
    def _A_setup():
        B, S, D = 1, 2048, 1024
        ns = torch.arange(S)[:, None] * torch.arange(S)[None, :]
        nd = torch.arange(D)[:, None] * torch.arange(D)[None, :]
        Ws_re = torch.cos(-2.0 * torch.pi * ns / S).to(float)
        Ws_im = torch.sin(-2.0 * torch.pi * ns / S).to(float)
        Wd_re = torch.cos(-2.0 * torch.pi * nd / D).to(float)
        Wd_im = torch.sin(-2.0 * torch.pi * nd / D).to(float)
        return {
            "x": _w((lambda *s: torch.randn(*s, dtype=torch.bfloat16) * 0.05)(B, S, D)),
            "dft_seq_re": _w(Ws_re),
            "dft_seq_im": _w(Ws_im),
            "dft_hid_re": _w(Wd_re),
            "dft_hid_im": _w(Wd_im),
        }
    _A_in = _A_setup()

    def _B_setup():
        B, S, D, F, C = 1, 2048, 1024, 3584, 1
        return {
            "x": _w((lambda *s: torch.randn(*s, dtype=torch.bfloat16) * 0.05)(B, S, D)),
            "w_r": _w((lambda *s: torch.randn(*s, dtype=torch.bfloat16) * 1.6)(D)),
            "w_gate": _w((lambda *s: torch.randn(*s, dtype=torch.bfloat16) * 0.4)(D, F)),
            "w_up": _w((lambda *s: torch.randn(*s, dtype=torch.bfloat16) * 0.4)(D, F)),
            "w_down": _w((lambda *s: torch.randn(*s, dtype=torch.bfloat16) * 0.4)(F, D)),
        }
    _B_in = _B_setup()

    return {
        "A_x": _A_in["x"],
        "A_dft_seq_re": _A_in["dft_seq_re"],
        "A_dft_seq_im": _A_in["dft_seq_im"],
        "A_dft_hid_re": _A_in["dft_hid_re"],
        "A_dft_hid_im": _A_in["dft_hid_im"],
        "B_x": _B_in["x"],
        "B_w_r": _B_in["w_r"],
        "B_w_gate": _B_in["w_gate"],
        "B_w_up": _B_in["w_up"],
        "B_w_down": _B_in["w_down"],
    }

def reference(A_x, A_dft_seq_re, A_dft_seq_im, A_dft_hid_re, A_dft_hid_im, B_x, B_w_r, B_w_gate, B_w_up, B_w_down):
    def _A_ref(x, dft_seq_re, dft_seq_im, dft_hid_re, dft_hid_im):
        a = torch.einsum("bsd,ed->bse", x, dft_hid_re)
        b = torch.einsum("bsd,ed->bse", x, dft_hid_im)
        y = torch.einsum("ts,bse->bte", dft_seq_re, a) - torch.einsum("ts,bse->bte", dft_seq_im, b)
        return y

    def _B_ref(x, w_r, w_gate, w_up, w_down):
        B, S, D = x.shape
        C = 1
        r = x @ w_r
        idx = torch.argsort(-r, axis=-1)[:, :C]
        idx_e = (lambda x, n, axis: torch.repeat_interleave(x, n, dim=axis))(idx.reshape(B, C, 1), D, axis=2)
        x_sel = (lambda x, i, axis: torch.take_along_dim(x, i, dim=axis))(x, idx_e, axis=1)
        g = _silu(x_sel @ w_gate)
        u = x_sel @ w_up
        y = (g * u) @ w_down
        r_sel = _sigmoid((lambda x, i, axis: torch.take_along_dim(x, i, dim=axis))(r, idx, axis=1))
        y = y * r_sel.reshape(B, C, 1)
        b_off = (torch.arange(B) * S).reshape(B, 1)
        flat_idx = (idx + b_off).reshape(B * C)
        zero = (x * 0.0).reshape(B * S, D)
        upd = _scatter_add(zero, flat_idx, y.reshape(B * C, D), axis=0)
        return x + upd.reshape(B, S, D)

    x = A_x
    h = x + _A_ref(_layernorm(x, axis=-1), A_dft_seq_re, A_dft_seq_im, A_dft_hid_re, A_dft_hid_im)
    h2 = h + _B_ref(_layernorm(h, axis=-1), B_w_r, B_w_gate, B_w_up, B_w_down)
    return h2
```

```cpp
#include <cuda.h>
#include <cuda_runtime.h>
#include <cuda_bf16.h>
#include <stdint.h>
#include <stdlib.h>
#include <type_traits>

typedef __nv_bfloat16 bf16;

#define REG_C 232
#define REG_P 40
#define KEY_RMASK 31
__device__ __forceinline__ int kblock(int tau, int j) {
  const int i = j - 4, c = (i * 37) >> 8;
  return j < 4 ? tau * 4 + j : ((tau + 1 + i - 7 * c) & 7) * 4 + c;
}
#define PUB_K1 22
#define NREG_H 4
#define MR_K0 29
__host__ __device__ constexpr int mr_k(int h) { return MR_K0 + 6 * (h >> 1) + 2 * (h & 1); }
constexpr int A_BYTES = 128 * 64 * 2;
constexpr int B_BYTES = 256 * 64 * 2;
constexpr int ST_BYTES = A_BYTES + B_BYTES;
constexpr int OFF_XCH = 4 * ST_BYTES;
constexpr int OFF_BAR = OFF_XCH + 32768;
constexpr int OFF_WR = OFF_BAR + 384;
constexpr int OFF_RS = OFF_WR + 384;
constexpr int OFF_PUB = OFF_RS + 1152;
constexpr int OFF_MISC = OFF_PUB + 256;
constexpr int SMEM_TOTAL = OFF_MISC + 256;
constexpr int OFF_WSUM = OFF_MISC, OFF_TAG = OFF_MISC + 4;
constexpr int OFF_SEEN = OFF_MISC + 8;
constexpr int OFF_WKEY = OFF_MISC + 32;
constexpr int OFF_EXA = OFF_XCH;
constexpr int OFF_EXB = OFF_XCH + 4096;
__host__ __device__ constexpr int chunk_off(int c, int w) { return (c < 2 ? (c + 2) * ST_BYTES : OFF_XCH + (c - 2) * 16384) + w * 8192; }
__host__ __device__ constexpr int late_off(int i) { return i < 4 ? i * 16384 : 2 * ST_BYTES + A_BYTES + (i - 4) * 16384; }
__host__ __device__ constexpr int round_off(int h) { return h < NREG_H + 2 ? OFF_XCH + (h & 1) * 16384 : late_off(h - NREG_H - 2); }
__host__ __device__ constexpr int down_off(int i) { return late_off(6 - NREG_H + i); }
constexpr int OFF_PEER = ST_BYTES + A_BYTES;
constexpr int OFF_OUT = 3 * ST_BYTES + A_BYTES;
constexpr int OFF_XSEL = OFF_PEER;
constexpr int OFF_HSEL = OFF_PEER + 4096;
constexpr int OFF_GP = OFF_PEER + 8192;
constexpr int OFF_FIN = OFF_PEER + 9216;
__device__ __forceinline__ int slot_of(int k) { return k & 3; }
__device__ __forceinline__ int use_of(int k) { return k >> 2; }
enum { B_FULL = 0, B_EMPTY = 4, B_EPI = 8, B_STD = 12, B_EPI0B = 16, B_LATE = 17, B_STAT = 18, B_XCH = 19, B_MR = 20  , B_GU = 22,
       B_DN = 23, B_AUX = 24  , B_OUT = 30, B_COUNT = 31 };
enum { NB_TURN0 = 1, NB_TURN1 = 2, NB_BOTH = 5, NB_AUX = 6 };

struct Params {
  CUtensorMap tmD0, tmD1, tmX, tmXr, tmAbS, tmAbL, tmW0, tmW1, tmOut, tmG, tmU, tmDn;
  const bf16* x; const bf16* Dre; const bf16* Dim; const bf16* wr; const bf16* wdown; const bf16* wgate; const bf16* wup;
  bf16* out;
};

__device__ __align__(1024) bf16 g_abT[2048 * 2048];
__device__ __align__(128) uint2 g_xstat[2048];
__device__ __align__(128) uint2 g_dsum[2048];
__device__ __align__(128) uint4 g_abflag[16 * 8 * 2];
__device__ __align__(128) uint4 g_hstat[16 * 8 * 128];
__device__ __align__(128) uint4 g_cand[16 * 256];
__device__ __align__(128) uint4 g_key[32 * 16 * 2];
__device__ __align__(128) uint4 g_ypart[128 * 256];
__device__ __align__(128) uint4 g_done[128 * 2];
__device__ uint32_t g_epoch;

#define SPIN_LIMIT (1u << 17)
constexpr int PROLOGUE_CLK = 1800;
#define GATHER_CLK 9000
#define PF_R0 8
#define PF_STEP_CLK 250
#define PF_START2_CLK 26000
#define PF_STEP2_CLK 500
#define MOE_PACE_CLK 600
constexpr int IDLE_WAIT_CLK = 1200;
__device__ __forceinline__ uint32_t smem_u32(const void* p) { return (uint32_t)__cvta_generic_to_shared(p); }
__device__ __forceinline__ void mbar_init(uint32_t bar, uint32_t cnt) { asm volatile("mbarrier.init.shared::cta.b64 [%0], %1;" :: "r"(bar), "r"(cnt) : "memory"); }
__device__ __forceinline__ void mbar_expect_tx(uint32_t bar, uint32_t bytes) { asm volatile("mbarrier.arrive.expect_tx.shared::cta.b64 _, [%0], %1;" :: "r"(bar), "r"(bytes) : "memory"); }
__device__ __forceinline__ void mbar_arrive(uint32_t bar) { asm volatile("mbarrier.arrive.shared::cta.b64 _, [%0];" :: "r"(bar) : "memory"); }
__device__ __forceinline__ void mbar_wait(uint32_t bar, uint32_t parity) {
  uint32_t ok, n = 0;
  do {
    asm volatile("{\n.reg .pred p;\nmbarrier.try_wait.parity.shared::cta.b64 p, [%1], %2;\nselp.u32 %0, 1, 0, p;\n}\n" : "=r"(ok) : "r"(bar), "r"(parity) : "memory");
  } while (!ok && ++n < SPIN_LIMIT);
}
__device__ __forceinline__ bool mbar_test(uint32_t bar, uint32_t parity) {
  uint32_t ok;
  asm volatile("{\n.reg .pred p;\nmbarrier.test_wait.parity.shared::cta.b64 p, [%1], %2;\nselp.u32 %0, 1, 0, p;\n}\n" : "=r"(ok) : "r"(bar), "r"(parity) : "memory");
  return ok != 0;
}
__device__ __forceinline__ void mbar_wait_cluster(uint32_t bar, uint32_t parity) {
  uint32_t ok, n = 0;
  do {
    asm volatile("{\n.reg .pred p;\nmbarrier.try_wait.parity.acquire.cluster.shared::cta.b64 p, [%1], %2;\nselp.u32 %0, 1, 0, p;\n}\n" : "=r"(ok) : "r"(bar), "r"(parity) : "memory");
  } while (!ok && ++n < SPIN_LIMIT);
}
__device__ __forceinline__ void tma_load_2d(uint32_t dst, const CUtensorMap* tm, uint32_t bar, int c0, int c1) {
  asm volatile("cp.async.bulk.tensor.2d.shared::cluster.global.mbarrier::complete_tx::bytes [%0], [%1, {%3, %4}], [%2];"
    :: "r"(dst), "l"(tm), "r"(bar), "r"(c0), "r"(c1) : "memory");
}
__device__ __forceinline__ void tma_load_2d_hint(uint32_t dst, const CUtensorMap* tm, uint32_t bar, int c0, int c1, uint64_t pol) {
  asm volatile("cp.async.bulk.tensor.2d.shared::cluster.global.mbarrier::complete_tx::bytes.L2::cache_hint [%0], [%1, {%3, %4}], [%2], %5;"
    :: "r"(dst), "l"(tm), "r"(bar), "r"(c0), "r"(c1), "l"(pol) : "memory");
}
__device__ __forceinline__ uint64_t policy_evict_first() { uint64_t p; asm volatile("createpolicy.fractional.L2::evict_first.b64 %0, 1.0;" : "=l"(p)); return p; }
__device__ __forceinline__ void tma_store_2d(const CUtensorMap* tm, uint32_t src, int c0, int c1) {
  asm volatile("cp.async.bulk.tensor.2d.global.shared::cta.bulk_group [%0, {%2, %3}], [%1];" :: "l"(tm), "r"(src), "r"(c0), "r"(c1) : "memory");
}
__device__ __forceinline__ void bulk_load(uint32_t dst, const void* src, uint32_t bytes, uint32_t bar) {
  asm volatile("cp.async.bulk.shared::cluster.global.mbarrier::complete_tx::bytes [%0], [%1], %2, [%3];" :: "r"(dst), "l"(src), "r"(bytes), "r"(bar) : "memory");
}
__device__ __forceinline__ void bulk_commit() { asm volatile("cp.async.bulk.commit_group;" ::: "memory"); }
__device__ __forceinline__ void bulk_wait_all() { asm volatile("cp.async.bulk.wait_group 0;" ::: "memory"); }
__device__ __forceinline__ void fence_async_smem() { asm volatile("fence.proxy.async.shared::cta;" ::: "memory"); }
__device__ __forceinline__ void wgmma_fence() { asm volatile("wgmma.fence.sync.aligned;" ::: "memory"); }
__device__ __forceinline__ void wgmma_commit() { asm volatile("wgmma.commit_group.sync.aligned;" ::: "memory"); }
__device__ __forceinline__ void wgmma_wait0() { asm volatile("wgmma.wait_group.sync.aligned 0;" ::: "memory"); }
__device__ __forceinline__ void bar_sync(int id, int n) { asm volatile("bar.sync %0, %1;" :: "r"(id), "r"(n) : "memory"); }
__device__ __forceinline__ void bar_arrive(int id, int n) { asm volatile("bar.arrive %0, %1;" :: "r"(id), "r"(n) : "memory"); }
template<int R> __device__ __forceinline__ void reg_inc() { asm volatile("setmaxnreg.inc.sync.aligned.u32 %0;" :: "n"(R)); }
template<int R> __device__ __forceinline__ void reg_dec() { asm volatile("setmaxnreg.dec.sync.aligned.u32 %0;" :: "n"(R)); }
__device__ __forceinline__ bool elect_one() {
  uint32_t p;
  asm volatile("{\n.reg .pred q;\nelect.sync _|q, 0xffffffff;\nselp.u32 %0, 1, 0, q;\n}\n" : "=r"(p));
  return p != 0;
}
__device__ __forceinline__ uint32_t mapa(uint32_t addr, uint32_t cta) { uint32_t r; asm volatile("mapa.shared::cluster.u32 %0, %1, %2;" : "=r"(r) : "r"(addr), "r"(cta)); return r; }
__device__ __forceinline__ void st_async_v4(uint32_t addr, uint32_t bar, uint32_t a, uint32_t b, uint32_t c, uint32_t d) {
  asm volatile("st.async.weak.shared::cluster.mbarrier::complete_tx::bytes.v4.b32 [%0], {%2, %3, %4, %5}, [%1];" :: "r"(addr), "r"(bar), "r"(a), "r"(b), "r"(c), "r"(d) : "memory");
}
__device__ __forceinline__ void stsm_x4(uint32_t addr, uint32_t a, uint32_t b, uint32_t c, uint32_t d) {
  asm volatile("stmatrix.sync.aligned.m8n8.x4.shared.b16 [%0], {%1, %2, %3, %4};" :: "r"(addr), "r"(a), "r"(b), "r"(c), "r"(d));
}
__device__ __forceinline__ uint4 lds128_v(uint32_t addr) { uint4 v; asm volatile("ld.shared.v4.b32 {%0, %1, %2, %3}, [%4];" : "=r"(v.x), "=r"(v.y), "=r"(v.z), "=r"(v.w) : "r"(addr)); return v; }
extern __shared__ __align__(1024) uint8_t smem_raw[];
template<class T> __device__ __forceinline__ T& SM(int off) { return *reinterpret_cast<T*>(smem_raw + off); }
__device__ __forceinline__ uint4 ldg_nc128(const void* p) { uint4 v; asm volatile("ld.global.nc.v4.b32 {%0, %1, %2, %3}, [%4];" : "=r"(v.x), "=r"(v.y), "=r"(v.z), "=r"(v.w) : "l"(p)); return v; }
__device__ __forceinline__ void pkt_st128(void* p, uint32_t a, uint32_t b, uint32_t c, uint32_t d) {
  asm volatile("{\n.reg .b128 v;\n.reg .b64 lo, hi;\nmov.b64 lo, {%1, %2};\nmov.b64 hi, {%3, %4};\nmov.b128 v, {lo, hi};\nst.relaxed.gpu.global.b128 [%0], v;\n}\n"
    :: "l"(p), "r"(a), "r"(b), "r"(c), "r"(d) : "memory");
}
__device__ __forceinline__ uint4 pkt_ld128(const void* p) {
  uint4 r;
  asm volatile("{\n.reg .b128 v;\n.reg .b64 lo, hi;\nld.relaxed.gpu.global.b128 v, [%4];\nmov.b128 {lo, hi}, v;\nmov.b64 {%0, %1}, lo;\nmov.b64 {%2, %3}, hi;\n}\n"
    : "=r"(r.x), "=r"(r.y), "=r"(r.z), "=r"(r.w) : "l"(p) : "memory");
  return r;
}
__device__ __forceinline__ void pkt_st64(void* p, uint32_t a, uint32_t b) {
  asm volatile("{\n.reg .b64 v;\nmov.b64 v, {%1, %2};\nst.relaxed.gpu.global.b64 [%0], v;\n}\n" :: "l"(p), "r"(a), "r"(b) : "memory");
}
__device__ __forceinline__ uint2 pkt_ld64(const void* p) {
  uint2 r;
  asm volatile("{\n.reg .b64 v;\nld.relaxed.gpu.global.b64 v, [%2];\nmov.b64 {%0, %1}, v;\n}\n" : "=r"(r.x), "=r"(r.y) : "l"(p) : "memory");
  return r;
}
__device__ __forceinline__ uint32_t ld_relaxed32(const void* p) { uint32_t v; asm volatile("ld.relaxed.gpu.global.b32 %0, [%1];" : "=r"(v) : "l"(p) : "memory"); return v; }
__device__ __forceinline__ void st_relaxed32(void* p, uint32_t v) { asm volatile("st.relaxed.gpu.global.b32 [%0], %1;" :: "l"(p), "r"(v) : "memory"); }
__device__ __forceinline__ void backoff() { __nanosleep(80); }
__device__ __forceinline__ uint32_t code_of(uint32_t tag) { return tag % 3u + 1u; }
__device__ __forceinline__ uint32_t with_bit(float v, uint32_t bit) { return (__float_as_uint(v) & ~1u) | (bit & 1u); }
__device__ __forceinline__ uint32_t pair_code(uint32_t a, uint32_t b) { return (a & 1u) | ((b & 1u) << 1); }
__device__ __forceinline__ uint32_t pack_bf16(float lo, float hi) { uint32_t r; asm("cvt.rn.bf16x2.f32 %0, %1, %2;" : "=r"(r) : "f"(hi), "f"(lo)); return r; }
__device__ __forceinline__ float bf_lo(uint32_t v) { return __uint_as_float(v << 16); }
__device__ __forceinline__ float bf_hi(uint32_t v) { return __uint_as_float(v & 0xFFFF0000u); }
__device__ __forceinline__ float bf16r(float x) { return __bfloat162float(__float2bfloat16_rn(x)); }
__device__ __forceinline__ uint32_t badd2(uint32_t a, uint32_t b) { uint32_t r; asm("add.rn.bf16x2 %0, %1, %2;" : "=r"(r) : "r"(a), "r"(b)); return r; }
__device__ __forceinline__ float warp_sum(float v) {
#pragma unroll
  for (int o = 16; o > 0; o >>= 1) v += __shfl_xor_sync(0xffffffffu, v, o);
  return v;
}
__device__ __forceinline__ uint64_t make_desc(uint32_t addr) {
  return (uint64_t)((addr & 0x3FFFF) >> 4) | ((uint64_t)1 << 16) | ((uint64_t)64 << 32) | ((uint64_t)1 << 62);
}
__device__ __forceinline__ uint64_t make_desc_noswz(uint32_t addr) {
  return (uint64_t)((addr & 0x3FFFF) >> 4) | ((uint64_t)8 << 16) | ((uint64_t)16 << 32);
}
__device__ __forceinline__ void wgmma_n256(float (&d)[128], uint64_t da, uint64_t db, int scale_d) {
  asm volatile("{\n.reg .pred p;\nsetp.ne.b32 p, %130, 0;\n"
    "wgmma.mma_async.sync.aligned.m64n256k16.f32.bf16.bf16 "
    "{%0, %1, %2, %3, %4, %5, %6, %7, %8, %9, %10, %11, %12, %13, %14, %15, %16, %17, %18, %19, %20, %21, %22, %23, %24, %25, %26, %27, %28, %29, %30, %31, "
    "%32, %33, %34, %35, %36, %37, %38, %39, %40, %41, %42, %43, %44, %45, %46, %47, %48, %49, %50, %51, %52, %53, %54, %55, %56, %57, %58, %59, %60, %61, %62, %63, "
    "%64, %65, %66, %67, %68, %69, %70, %71, %72, %73, %74, %75, %76, %77, %78, %79, %80, %81, %82, %83, %84, %85, %86, %87, %88, %89, %90, %91, %92, %93, %94, %95, "
    "%96, %97, %98, %99, %100, %101, %102, %103, %104, %105, %106, %107, %108, %109, %110, %111, %112, %113, %114, %115, %116, %117, %118, %119, %120, %121, %122, %123, %124, %125, %126, %127}, "
    "%128, %129, p, 1, 1, 0, 0;\n}\n"
    : "+f"(d[0]), "+f"(d[1]), "+f"(d[2]), "+f"(d[3]), "+f"(d[4]), "+f"(d[5]), "+f"(d[6]), "+f"(d[7]),
      "+f"(d[8]), "+f"(d[9]), "+f"(d[10]), "+f"(d[11]), "+f"(d[12]), "+f"(d[13]), "+f"(d[14]), "+f"(d[15]),
      "+f"(d[16]), "+f"(d[17]), "+f"(d[18]), "+f"(d[19]), "+f"(d[20]), "+f"(d[21]), "+f"(d[22]), "+f"(d[23]),
      "+f"(d[24]), "+f"(d[25]), "+f"(d[26]), "+f"(d[27]), "+f"(d[28]), "+f"(d[29]), "+f"(d[30]), "+f"(d[31]),
      "+f"(d[32]), "+f"(d[33]), "+f"(d[34]), "+f"(d[35]), "+f"(d[36]), "+f"(d[37]), "+f"(d[38]), "+f"(d[39]),
      "+f"(d[40]), "+f"(d[41]), "+f"(d[42]), "+f"(d[43]), "+f"(d[44]), "+f"(d[45]), "+f"(d[46]), "+f"(d[47]),
      "+f"(d[48]), "+f"(d[49]), "+f"(d[50]), "+f"(d[51]), "+f"(d[52]), "+f"(d[53]), "+f"(d[54]), "+f"(d[55]),
      "+f"(d[56]), "+f"(d[57]), "+f"(d[58]), "+f"(d[59]), "+f"(d[60]), "+f"(d[61]), "+f"(d[62]), "+f"(d[63]),
      "+f"(d[64]), "+f"(d[65]), "+f"(d[66]), "+f"(d[67]), "+f"(d[68]), "+f"(d[69]), "+f"(d[70]), "+f"(d[71]),
      "+f"(d[72]), "+f"(d[73]), "+f"(d[74]), "+f"(d[75]), "+f"(d[76]), "+f"(d[77]), "+f"(d[78]), "+f"(d[79]),
      "+f"(d[80]), "+f"(d[81]), "+f"(d[82]), "+f"(d[83]), "+f"(d[84]), "+f"(d[85]), "+f"(d[86]), "+f"(d[87]),
      "+f"(d[88]), "+f"(d[89]), "+f"(d[90]), "+f"(d[91]), "+f"(d[92]), "+f"(d[93]), "+f"(d[94]), "+f"(d[95]),
      "+f"(d[96]), "+f"(d[97]), "+f"(d[98]), "+f"(d[99]), "+f"(d[100]), "+f"(d[101]), "+f"(d[102]), "+f"(d[103]),
      "+f"(d[104]), "+f"(d[105]), "+f"(d[106]), "+f"(d[107]), "+f"(d[108]), "+f"(d[109]), "+f"(d[110]), "+f"(d[111]),
      "+f"(d[112]), "+f"(d[113]), "+f"(d[114]), "+f"(d[115]), "+f"(d[116]), "+f"(d[117]), "+f"(d[118]), "+f"(d[119]),
      "+f"(d[120]), "+f"(d[121]), "+f"(d[122]), "+f"(d[123]), "+f"(d[124]), "+f"(d[125]), "+f"(d[126]), "+f"(d[127])
    : "l"(da), "l"(db), "r"(scale_d));
}
__device__ __forceinline__ void wgmma_n256_rs(float (&d)[128], uint32_t a0, uint32_t a1, uint32_t a2, uint32_t a3, uint64_t db, int scale_d) {
  asm volatile("{\n.reg .pred p;\nsetp.ne.b32 p, %133, 0;\n"
    "wgmma.mma_async.sync.aligned.m64n256k16.f32.bf16.bf16 "
    "{%0, %1, %2, %3, %4, %5, %6, %7, %8, %9, %10, %11, %12, %13, %14, %15, %16, %17, %18, %19, %20, %21, %22, %23, %24, %25, %26, %27, %28, %29, %30, %31, "
    "%32, %33, %34, %35, %36, %37, %38, %39, %40, %41, %42, %43, %44, %45, %46, %47, %48, %49, %50, %51, %52, %53, %54, %55, %56, %57, %58, %59, %60, %61, %62, %63, "
    "%64, %65, %66, %67, %68, %69, %70, %71, %72, %73, %74, %75, %76, %77, %78, %79, %80, %81, %82, %83, %84, %85, %86, %87, %88, %89, %90, %91, %92, %93, %94, %95, "
    "%96, %97, %98, %99, %100, %101, %102, %103, %104, %105, %106, %107, %108, %109, %110, %111, %112, %113, %114, %115, %116, %117, %118, %119, %120, %121, %122, %123, %124, %125, %126, %127}, "
    "{%128, %129, %130, %131}, %132, p, 1, 1, 0;\n}\n"
    : "+f"(d[0]), "+f"(d[1]), "+f"(d[2]), "+f"(d[3]), "+f"(d[4]), "+f"(d[5]), "+f"(d[6]), "+f"(d[7]),
      "+f"(d[8]), "+f"(d[9]), "+f"(d[10]), "+f"(d[11]), "+f"(d[12]), "+f"(d[13]), "+f"(d[14]), "+f"(d[15]),
      "+f"(d[16]), "+f"(d[17]), "+f"(d[18]), "+f"(d[19]), "+f"(d[20]), "+f"(d[21]), "+f"(d[22]), "+f"(d[23]),
      "+f"(d[24]), "+f"(d[25]), "+f"(d[26]), "+f"(d[27]), "+f"(d[28]), "+f"(d[29]), "+f"(d[30]), "+f"(d[31]),
      "+f"(d[32]), "+f"(d[33]), "+f"(d[34]), "+f"(d[35]), "+f"(d[36]), "+f"(d[37]), "+f"(d[38]), "+f"(d[39]),
      "+f"(d[40]), "+f"(d[41]), "+f"(d[42]), "+f"(d[43]), "+f"(d[44]), "+f"(d[45]), "+f"(d[46]), "+f"(d[47]),
      "+f"(d[48]), "+f"(d[49]), "+f"(d[50]), "+f"(d[51]), "+f"(d[52]), "+f"(d[53]), "+f"(d[54]), "+f"(d[55]),
      "+f"(d[56]), "+f"(d[57]), "+f"(d[58]), "+f"(d[59]), "+f"(d[60]), "+f"(d[61]), "+f"(d[62]), "+f"(d[63]),
      "+f"(d[64]), "+f"(d[65]), "+f"(d[66]), "+f"(d[67]), "+f"(d[68]), "+f"(d[69]), "+f"(d[70]), "+f"(d[71]),
      "+f"(d[72]), "+f"(d[73]), "+f"(d[74]), "+f"(d[75]), "+f"(d[76]), "+f"(d[77]), "+f"(d[78]), "+f"(d[79]),
      "+f"(d[80]), "+f"(d[81]), "+f"(d[82]), "+f"(d[83]), "+f"(d[84]), "+f"(d[85]), "+f"(d[86]), "+f"(d[87]),
      "+f"(d[88]), "+f"(d[89]), "+f"(d[90]), "+f"(d[91]), "+f"(d[92]), "+f"(d[93]), "+f"(d[94]), "+f"(d[95]),
      "+f"(d[96]), "+f"(d[97]), "+f"(d[98]), "+f"(d[99]), "+f"(d[100]), "+f"(d[101]), "+f"(d[102]), "+f"(d[103]),
      "+f"(d[104]), "+f"(d[105]), "+f"(d[106]), "+f"(d[107]), "+f"(d[108]), "+f"(d[109]), "+f"(d[110]), "+f"(d[111]),
      "+f"(d[112]), "+f"(d[113]), "+f"(d[114]), "+f"(d[115]), "+f"(d[116]), "+f"(d[117]), "+f"(d[118]), "+f"(d[119]),
      "+f"(d[120]), "+f"(d[121]), "+f"(d[122]), "+f"(d[123]), "+f"(d[124]), "+f"(d[125]), "+f"(d[126]), "+f"(d[127])
    : "r"(a0), "r"(a1), "r"(a2), "r"(a3), "l"(db), "r"(scale_d));
}
__device__ __forceinline__ void wgmma_n128(float (&d)[64], uint64_t da, uint64_t db) {
  asm volatile("{\n.reg .pred p;\nsetp.ne.b32 p, 1, 0;\n"
    "wgmma.mma_async.sync.aligned.m64n128k16.f32.bf16.bf16 "
    "{%0, %1, %2, %3, %4, %5, %6, %7, %8, %9, %10, %11, %12, %13, %14, %15, %16, %17, %18, %19, %20, %21, %22, %23, %24, %25, %26, %27, %28, %29, %30, %31, %32, %33, %34, %35, %36, %37, %38, %39, %40, %41, %42, %43, %44, %45, %46, %47, %48, %49, %50, %51, %52, %53, %54, %55, %56, %57, %58, %59, %60, %61, %62, %63}, "
    "%64, %65, p, 1, 1, 0, 0;\n}\n"
    : "+f"(d[0]), "+f"(d[1]), "+f"(d[2]), "+f"(d[3]), "+f"(d[4]), "+f"(d[5]), "+f"(d[6]), "+f"(d[7]), "+f"(d[8]), "+f"(d[9]), "+f"(d[10]), "+f"(d[11]), "+f"(d[12]), "+f"(d[13]), "+f"(d[14]), "+f"(d[15]), "+f"(d[16]), "+f"(d[17]), "+f"(d[18]), "+f"(d[19]), "+f"(d[20]), "+f"(d[21]), "+f"(d[22]), "+f"(d[23]), "+f"(d[24]), "+f"(d[25]), "+f"(d[26]), "+f"(d[27]), "+f"(d[28]), "+f"(d[29]), "+f"(d[30]), "+f"(d[31]), "+f"(d[32]), "+f"(d[33]), "+f"(d[34]), "+f"(d[35]), "+f"(d[36]), "+f"(d[37]), "+f"(d[38]), "+f"(d[39]), "+f"(d[40]), "+f"(d[41]), "+f"(d[42]), "+f"(d[43]), "+f"(d[44]), "+f"(d[45]), "+f"(d[46]), "+f"(d[47]), "+f"(d[48]), "+f"(d[49]), "+f"(d[50]), "+f"(d[51]), "+f"(d[52]), "+f"(d[53]), "+f"(d[54]), "+f"(d[55]), "+f"(d[56]), "+f"(d[57]), "+f"(d[58]), "+f"(d[59]), "+f"(d[60]), "+f"(d[61]), "+f"(d[62]), "+f"(d[63])
    : "l"(da), "l"(db));
}
__device__ __forceinline__ void fence_acc64(float (&d)[64]) {
#pragma unroll
  for (int i = 0; i < 64; i++) asm volatile("" : "+f"(d[i]) :: "memory");
}
__device__ __forceinline__ void fence_acc(float (&d)[128]) {
#pragma unroll
  for (int i = 0; i < 128; i++) asm volatile("" : "+f"(d[i]) :: "memory");
}

template<int N, int I = 0, class F> __device__ __forceinline__ void static_for(F&& f) {
  if constexpr (I < N) { f(std::integral_constant<int, I>()); static_for<N, I + 1>(f); }
}

__device__ __forceinline__ void ldsm_x4_t(uint32_t addr, uint32_t& a, uint32_t& b, uint32_t& c, uint32_t& d) {
  asm volatile("ldmatrix.sync.aligned.m8n8.x4.trans.shared.b16 {%0, %1, %2, %3}, [%4];" : "=r"(a), "=r"(b), "=r"(c), "=r"(d) : "r"(addr));
}
__device__ __forceinline__ void sts128(uint32_t addr, uint32_t a, uint32_t b, uint32_t c, uint32_t d) {
  asm volatile("st.shared.v4.b32 [%0], {%1, %2, %3, %4};" :: "r"(addr), "r"(a), "r"(b), "r"(c), "r"(d));
}
__device__ __forceinline__ void mma16816(float (&c)[4], uint32_t a0, uint32_t a1, uint32_t a2, uint32_t a3, uint32_t b0, uint32_t b1) {
  asm("mma.sync.aligned.m16n8k16.row.col.f32.bf16.bf16.f32 {%0, %1, %2, %3}, {%4, %5, %6, %7}, {%8, %9}, {%0, %1, %2, %3};"
      : "+f"(c[0]), "+f"(c[1]), "+f"(c[2]), "+f"(c[3]) : "r"(a0), "r"(a1), "r"(a2), "r"(a3), "r"(b0), "r"(b1));
}
__device__ __forceinline__ void tma_store_5d(const CUtensorMap* tm, uint32_t src, int c0, int c4) {
  asm volatile("cp.async.bulk.tensor.5d.global.shared::cta.bulk_group [%0, {%2, %3, %3, %3, %4}], [%1];" :: "l"(tm), "r"(src), "r"(c0), "r"(0), "r"(c4) : "memory");
}
__device__ __forceinline__ float rcp_fast(float x) { float r; asm("rcp.approx.ftz.f32 %0, %1;" : "=f"(r) : "f"(x)); return r; }
__device__ __forceinline__ float sqrt_fast(float x) { float r; asm("sqrt.approx.f32 %0, %1;" : "=f"(r) : "f"(x)); return r; }
__device__ __forceinline__ float ln_sd(float var) { return bf16r(sqrt_fast(bf16r(bf16r(fmaxf(var, 0.f)) + 1e-5f))); }
__device__ __forceinline__ uint32_t norm2(uint32_t h, uint32_t neg_mean2, float inv_sd) {
  const uint32_t d = badd2(h, neg_mean2);
  return pack_bf16(bf_lo(d) * inv_sd, bf_hi(d) * inv_sd);
}
template<int V> using IC = std::integral_constant<int, V>;

#define CT(slot) do {} while (0)
#define PT(slot) do {} while (0)

template<int MAP>
__global__ void __cluster_dims__(2, 1, 1) __launch_bounds__(384, 1)
fnet_moe_kernel(const __grid_constant__ Params p) {
  const uint32_t sb = smem_u32(smem_raw);
  const int tid = threadIdx.x, lane = tid & 31;
  const int warp = __shfl_sync(0xffffffffu, tid >> 5, 0);
  const int m = blockIdx.x & 1;
  int tau, eps;
  if (MAP == 0) {
    uint32_t smid;
    asm volatile("mov.u32 %0, %%smid;" : "=r"(smid));
    const int c = smid >> 1, e7 = ((c - 32) * 37) >> 8;
    if (c == 60 || c == 61) {
      const uint32_t t16 = (ld_relaxed32(&g_epoch) + 1) & 0xFFFFu;
      uint32_t n = 0;
      do { __nanosleep(1000); } while (!__all_sync(0xffffffffu, (pkt_ld64(&g_xstat[(tid & 127) * 16]).x & 0xFFFFu) == t16) && ++n < 4096);
      return;
    }
    tau = c < 32 ? (c & 7) : (c < 60 ? c - 31 - 7 * e7 : 0);
    eps = c < 32 ? (c >> 3) : (c < 60 ? 4 + e7 : c - 58);
  } else {
    tau = (blockIdx.x >> 1) & 7; eps = blockIdx.x >> 4;
  }
  const int cid = tau * 16 + eps * 2 + m;
  const bool moe = tau > 0;
  auto BAR = [&](int i) { return sb + OFF_BAR + 8 * i; };
  const CUtensorMap* tmD = m ? &p.tmD1 : &p.tmD0;

  const uint64_t pol_ef = policy_evict_first();
#define LOAD_STREAM(d, tm, bar, c0, c1) tma_load_2d_hint(d, tm, bar, c0, c1, pol_ef)
  if (__builtin_expect(warp == 0, 1)) {
    if (elect_one()) {
      mbar_init(BAR(B_FULL), 1);
      asm volatile("fence.mbarrier_init.release.cluster;" ::: "memory");
      mbar_expect_tx(BAR(B_FULL), ST_BYTES);
      tma_load_2d(sb + A_BYTES, &p.tmX, BAR(B_FULL), 0, tau * 256);
      tma_load_2d(sb, tmD, BAR(B_FULL), 0, eps * 128);
#pragma unroll 1
      for (int k = 1; k < 4; k++) {
        mbar_init(BAR(B_FULL + k), 1);
        asm volatile("fence.mbarrier_init.release.cluster;" ::: "memory");
        mbar_expect_tx(BAR(B_FULL + k), ST_BYTES);
        LOAD_STREAM(sb + k * ST_BYTES, tmD, BAR(B_FULL + k), k * 64, eps * 128);
        tma_load_2d(sb + k * ST_BYTES + A_BYTES, &p.tmX, BAR(B_FULL + k), k * 64, tau * 256);
      }
    }
    PT(0);
  }
  if (warp == 8) {
    if (elect_one()) {
#pragma unroll
      for (int b = B_EMPTY; b < B_COUNT; b++)
        mbar_init(BAR(b), b < B_EPI ? 2 : (b == B_EPI || b == B_EPI0B) ? 4 : (b < B_STD || b == B_OUT) ? 8 : b == B_STAT ? 3 : 1);
      asm volatile("fence.mbarrier_init.release.cluster;" ::: "memory");
      mbar_expect_tx(BAR(B_XCH), 32768);
      SM<uint32_t>(OFF_SEEN) = 0;
    }
  }
  __syncthreads();

  if (warp >= 8) {
    reg_dec<REG_P>();
    asm volatile("barrier.cluster.arrive.relaxed.aligned;" ::: "memory");
    const int abrow = m * 1024 + eps * 128;
    const int f0 = (cid - 16) * 32;
    if (warp == 8) {
      const CUtensorMap* tmW = m ? &p.tmW1 : &p.tmW0;
      const int tA = tau * 256 + m * 128, tB = tau * 256 + (1 - m) * 128;
      uint32_t seen = 0;
#pragma unroll 1
      for (int k = 4; k < 48; k++) {
        const int s = slot_of(k);
        const uint32_t sa = sb + s * ST_BYTES, sbb = sa + A_BYTES;
        const int kb = kblock(tau, k - 16);
        mbar_wait(BAR(B_EMPTY + s), (use_of(k) & 1) ^ 1);
        PT(64 + k);
        if (elect_one()) {
          mbar_expect_tx(BAR(B_FULL + s), (k >> 1) == 9 ? B_BYTES : ST_BYTES);
          if (k < 16) {
            LOAD_STREAM(sa, tmD, BAR(B_FULL + s), k * 64, eps * 128);
            tma_load_2d(sbb, &p.tmX, BAR(B_FULL + s), k * 64, tau * 256);
          } else {
            LOAD_STREAM(sbb, tmW, BAR(B_FULL + s), kb * 64, tA);
            LOAD_STREAM(sbb + 16384, tmW, BAR(B_FULL + s), kb * 64, tB);
            if (k < 18) {
              tma_load_2d(sa, &p.tmXr, BAR(B_FULL + s), eps * 128, tA + s * 64);
              tma_load_2d(sa + 8192, &p.tmXr, BAR(B_FULL + s), eps * 128 + 64, tA + s * 64);
            }
          }
        }
        if (k >= 24) {
          uint32_t n = 0;
          while (!((seen >> kb) & 1) && ++n < SPIN_LIMIT * 16) seen = *(volatile uint32_t*)&SM<uint32_t>(OFF_SEEN);
          if (elect_one()) tma_load_2d(sa, &p.tmAbL, BAR(B_FULL + s), kb * 64, abrow);
        }
        if (k == PUB_K1 && elect_one()) mbar_arrive(BAR(B_LATE));
        if (moe && k >= MR_K0) {
          const int i = k - MR_K0, r6 = (i * 43) >> 8, u = i - 6 * r6, h = 2 * r6 + (u >> 1);
          if (u < 4 && h < NREG_H + 2) {
            if (h < 2) mbar_wait(BAR(B_STD + 2 + h), 0);
            if (elect_one()) {
              const uint32_t bar = BAR(h < NREG_H ? B_MR + (h & 1) : B_GU);
              if (!(u & 1) && h <= NREG_H) mbar_expect_tx(bar, h < NREG_H ? 16384 : (8 - NREG_H) * 16384);
              LOAD_STREAM(sb + OFF_XCH + u * 8192, (u & 1) ? &p.tmU : &p.tmG, bar, f0, h * 128);
            }
          }
        }
      }
      if (moe) {
        mbar_wait(BAR(B_EMPTY + 0), 1);
        if (elect_one()) mbar_expect_tx(BAR(B_DN), 65536);
#pragma unroll 1
        for (int i = 0; i < 10 - NREG_H; i++) {
          if (i == 3) { mbar_wait(BAR(B_EMPTY + 2), 1); mbar_wait(BAR(B_XCH), 0); }
          const uint32_t dst = sb + late_off(i);
          if (elect_one()) {
            if (i < 6 - NREG_H) {
              LOAD_STREAM(dst, &p.tmG, BAR(B_GU), f0, (NREG_H + 2 + i) * 128);
              LOAD_STREAM(dst + 8192, &p.tmU, BAR(B_GU), f0, (NREG_H + 2 + i) * 128);
            } else {
#pragma unroll
              for (int b = 0; b < 4; b++) LOAD_STREAM(dst + b * 4096, &p.tmDn, BAR(B_DN), (4 * (i - 6 + NREG_H) + b) * 64, f0);
            }
          }
          const long long t0 = clock64();
          while (clock64() - t0 < MOE_PACE_CLK) {}
        }
      }
    } else {
      const int a = warp - 9;
      const long long t_aux = clock64() - PROLOGUE_CLK;
      const int r0 = a ? 5 * a + 1 : 0;
      auto stage = [&](const bf16* src, int g) {
        const uint32_t bytes = (g && a) ? 4096 : 6144;
        if (elect_one()) {
          mbar_expect_tx(BAR(B_AUX + 2 * a + g), bytes);
          bulk_load(sb + OFF_XCH + (r0 + 3 * g) * 2048, src + (r0 + 3 * g) * 1024, bytes, BAR(B_AUX + 2 * a + g));
        }
      };
      const uint32_t tag = ld_relaxed32(&g_epoch) + 1;
      if (a == 2) {
        float s = 0.f;
#pragma unroll
        for (int q = 0; q < 4; q++) {
          const uint4 v = ldg_nc128(p.wr + (q * 32 + lane) * 8);
          s += ((bf_lo(v.x) + bf_hi(v.x)) + (bf_lo(v.y) + bf_hi(v.y))) + ((bf_lo(v.z) + bf_hi(v.z)) + (bf_lo(v.w) + bf_hi(v.w)));
          const int ch = q * 32 + lane - eps * 16;
          if (ch >= 0 && ch < 16) {
            SM<uint32_t>(OFF_WR + ch * 4) = v.x; SM<uint32_t>(OFF_WR + 80 + ch * 4) = v.y;
            SM<uint32_t>(OFF_WR + 160 + ch * 4) = v.z; SM<uint32_t>(OFF_WR + 240 + ch * 4) = v.w;
          }
        }
        s = warp_sum(s);
        if (lane == 0) { SM<float>(OFF_WSUM) = s; SM<uint32_t>(OFF_TAG) = tag; }
      }
      mbar_wait(BAR(B_FULL + 0), 0);
      if (a == 0) PT(1);
      stage(p.x + (size_t)cid * 16 * 1024, 0);
      stage(p.x + (size_t)cid * 16 * 1024, 1);
#pragma unroll 1
      for (int it = 0; it < 4; it++) {
        const int g = it & 1;
        mbar_wait(BAR(B_AUX + 2 * a + g), it >> 1);
        if (a == 0) PT(2 + it);
        float sm_[3], sq_[3];
        auto rows = [&](auto sq) {
        constexpr bool SQ = decltype(sq)::value;
#pragma unroll
        for (int u = 0; u < 3; u++) {
          const int row = r0 + 3 * g + ((u == 2 && g && a) ? 1 : u);
          float s0 = 0.f, s1 = 0.f, q0 = 0.f, q1 = 0.f;
#pragma unroll
          for (int q = 0; q < 4; q++) {
            const uint4 v = lds128_v(sb + OFF_XCH + row * 2048 + (q * 32 + lane) * 16);
            const uint32_t ww[4] = {v.x, v.y, v.z, v.w};
#pragma unroll
            for (int z = 0; z < 4; z++) {
              const float d0 = bf_lo(ww[z]), d1 = bf_hi(ww[z]);
              s0 += d0; s1 += d1;
              if (SQ) { q0 = fmaf(d0, d0, q0); q1 = fmaf(d1, d1, q1); }
            }
          }
          sm_[u] = s0 + s1; sq_[u] = q0 + q1;
        }
        };
        if (it < 2) rows(IC<1>()); else rows(IC<0>());
        __syncwarp();
        if (it < 2) stage(cid < 64 ? p.Dre + (size_t)cid * 16 * 1024 : p.Dim + (size_t)(cid - 64) * 16 * 1024, g);
#pragma unroll
        for (int o = 16; o > 0; o >>= 1) {
#pragma unroll
          for (int u = 0; u < 3; u++) { sm_[u] += __shfl_xor_sync(0xffffffffu, sm_[u], o); sq_[u] += __shfl_xor_sync(0xffffffffu, sq_[u], o); }
        }
        const float s = lane == 0 ? sm_[0] : lane == 1 ? sm_[1] : sm_[2], q = lane == 0 ? sq_[0] : lane == 1 ? sq_[1] : sq_[2];
        const float mean = s * (1.f / 1024.f);
        const float rs = rcp_fast(ln_sd(q * (1.f / 1024.f) - mean * mean));
        if (lane < ((g && a) ? 2 : 3))
          SM<uint2>(OFF_PUB + (it >> 1) * 128 + (r0 + 3 * g + lane) * 8) =
              it < 2 ? make_uint2(__float_as_uint(bf16r(mean)) | (tag & 0xFFFFu), __float_as_uint(rs)) : make_uint2(__float_as_uint(s), tag);
      }
      bar_sync(NB_AUX, 96);
      if (a == 1) {
        const uint2 v = SM<uint2>(OFF_PUB + lane * 8);
        pkt_st64((lane < 16 ? g_xstat : g_dsum) + cid * 16 + (lane & 15), v.x, v.y);
        PT(6);
      }
      while (clock64() - t_aux < GATHER_CLK) __nanosleep(100);
      {
        const int i0 = a * 32 + lane;
        uint2 v[3], c0, c1; uint32_t n = 0;
        const uint2* dp = &g_dsum[abrow];
        const uint32_t t16 = tag & 0xFFFFu;
        while (true) {
#pragma unroll
          for (int q = 0; q < 3; q++) v[q] = pkt_ld64(&g_xstat[tau * 256 + min(i0 + 96 * q, 255)]);
          c0 = pkt_ld64(dp + i0); c1 = pkt_ld64(dp + min(i0 + 96, 127));
          const bool ok = (v[0].x & 0xFFFFu) == t16 && (v[1].x & 0xFFFFu) == t16 && (v[2].x & 0xFFFFu) == t16 && c0.y == tag && c1.y == tag;
          if (__all_sync(0xffffffffu, ok) || ++n > SPIN_LIMIT) break;
          __nanosleep(200);
        }
#pragma unroll
        for (int q = 0; q < 3; q++) {
          const float rs = __uint_as_float(v[q].y);
          const int col = min(i0 + 96 * q, 255);
          SM<float>(OFF_RS + ((col & 7) >> 1) * 272 + (col >> 3) * 8 + (col & 1) * 4) = m ? -rs : rs;
          const uint32_t nm = (v[q].x >> 16) ^ 0x8000u;
          SM<uint4>(OFF_EXB + (col >> 3) * 256 + (col & 7) * 16) = make_uint4(nm | (nm << 16), nm, 0, 0);
          SM<uint4>(OFF_EXB + (col >> 3) * 256 + 128 + (col & 7) * 16) = make_uint4(0, 0, 0, 0);
        }
#pragma unroll
        for (int q = 0; q < 2; q++) {
          const int e = min(i0 + 96 * q, 127);
          const float c = __uint_as_float(q ? c1.x : c0.x);
          const float hi = bf16r(c), mid = bf16r(c - hi), lo = bf16r((c - hi) - mid);
          SM<uint4>(OFF_EXA + (e >> 3) * 256 + (e & 7) * 16) = make_uint4((__float_as_uint(hi) >> 16) | (__float_as_uint(mid) & 0xFFFF0000u), __float_as_uint(lo) >> 16, 0, 0);
          SM<uint4>(OFF_EXA + (e >> 3) * 256 + 128 + (e & 7) * 16) = make_uint4(0, 0, 0, 0);
        }
        fence_async_smem();
      }
      __syncwarp();
      if (lane == 0) mbar_arrive(BAR(B_STAT));
      if (a == 0) PT(7);
      if (a == 0) {
        const uint32_t* flg = reinterpret_cast<const uint32_t*>(&g_abflag[((eps * 2 + m) * 8 + (lane >> 2)) * 2]) + (lane & 3);
        uint32_t seen = 0;
        auto poll = [&]() {
          seen = __ballot_sync(0xffffffffu, ld_relaxed32(flg) == tag);
          asm volatile("fence.proxy.async.global;" ::: "memory");
          *(volatile uint32_t*)&SM<uint32_t>(OFF_SEEN) = seen;
        };
        mbar_wait(BAR(B_STD + 0), 0);
#pragma unroll 1
        for (int s = 0; s < 4; s++) {
          const int kb = kblock(tau, 4 + s);
          uint32_t n = 0;
          while (!((seen >> kb) & 1) && ++n < SPIN_LIMIT) poll();
          if (s == 3) mbar_wait(BAR(B_STD + 1), 0);
          mbar_wait(BAR(B_FULL + s), 0);
          PT(16 + s);
          if (elect_one()) tma_load_2d(sb + (s < 2 ? OFF_XCH + s * 16384 : s * ST_BYTES), &p.tmAbL, BAR(B_FULL + s), kb * 64, abrow);
        }
        uint32_t n = 0;
        while (seen != 0xFFFFFFFFu && ++n < SPIN_LIMIT) { poll(); __nanosleep(100); }
        mbar_wait(BAR(B_OUT), 0);
        if (lane == 0) {
          tma_store_5d(&p.tmOut, sb + OFF_OUT, eps * 128, tau * 8 + m * 4);
          tma_store_5d(&p.tmOut, sb + OFF_OUT + 16384, eps * 128 + 64, tau * 8 + m * 4);
          bulk_commit();
          bulk_wait_all();
          st_relaxed32(&g_done[cid * 2], tag);
        }
        PT(22);
      } else if (a == 1) {
#pragma unroll 1
        for (int c = 0; c < 4; c++) {
          uint32_t* flag = reinterpret_cast<uint32_t*>(&g_abflag[((eps * 2 + m) * 8 + tau) * 2]) + c;
          mbar_wait(BAR(B_EPI + c), 0);
          if (c == 1) mbar_wait(BAR(B_LATE), 0);
          PT(8 + c);
          if (c >= 2) {
            bf16* dst = g_abT + (size_t)(abrow + (lane >> 3)) * 2048 + tau * 256 + c * 64;
#pragma unroll 4
            for (int i = 0; i < 32; i++) {
              const int row = 4 * i + (lane >> 3);
              const uint4 v = lds128_v(sb + chunk_off(c, 0) + i * 512 + lane * 16);
              *reinterpret_cast<uint4*>(dst + i * 4 * 2048 + (((lane & 7) ^ (row & 7)) << 3)) = v;
            }
            __syncwarp();
            if (lane == 0) mbar_arrive(BAR(B_STD + c));
            if (c == 3) {
              __threadfence();
              if (lane < 2) st_relaxed32(flag - lane, tag);
            }
            PT(12 + c);
            continue;
          }
          if (lane == 0) tma_store_2d(&p.tmAbS, sb + chunk_off(c, 0), tau * 256 + c * 64, abrow);
          mbar_wait(BAR(B_EPI0B), 0);
          if (lane == 0) {
            tma_store_2d(&p.tmAbS, sb + chunk_off(c, 1), tau * 256 + c * 64, abrow + 64);
            bulk_commit();
            bulk_wait_all();
            st_relaxed32(flag, tag);
            mbar_arrive(BAR(B_STD + c));
          }
          PT(12 + c);
        }
      } else if (moe) {
        long long tn = clock64();
#pragma unroll 1
        for (int r = 0; r < 48; r++) {
          if (r == PF_R0) tn = t_aux + PF_START2_CLK;
          const int l = r * 32 + lane;
          const bf16* ad = l < 1024 ? (((l >> 6) & 1) ? p.wup : p.wgate) + (size_t)((l >> 7) * 128 + m * 64 + (l & 63)) * 3584 + (f0 & ~63)
                                    : p.wdown + (size_t)f0 * 1024 + (l - 1024) * 64;
          while (clock64() < tn) __nanosleep(50);
          tn += r < PF_R0 ? PF_STEP_CLK : PF_STEP2_CLK;
          asm volatile("prefetch.global.L2 [%0];" :: "l"(ad));
        }
        PT(23);
      }
    }
    asm volatile("barrier.cluster.wait.aligned;" ::: "memory");
  } else {
    reg_inc<REG_C>();
    const int w = warp >> 2, wi = warp & 3, t = tid & 127;
    const int g = lane >> 2, q = lane & 3;
    const int turn_me = NB_TURN0 + w, turn_other = NB_TURN1 - w;
    float acc[128];
#pragma unroll
    for (int i = 0; i < 128; i++) acc[i] = 0.f;
    if (w == 1) bar_arrive(NB_TURN0, 256);
    auto kstep = [&](int k, bool first, bool a_in_xch = false) {
      const int s = slot_of(k);
      mbar_wait(BAR(B_FULL + s), use_of(k) & 1);
      CT(64 + k);
      bar_sync(turn_me, 256);
      const uint64_t da = make_desc(sb + (a_in_xch ? OFF_XCH + s * 16384 : s * ST_BYTES) + w * 8192), db = make_desc(sb + s * ST_BYTES + A_BYTES);
      wgmma_fence();
      wgmma_n256(acc, da, db, !first);
#pragma unroll
      for (int kk = 1; kk < 4; kk++) wgmma_n256(acc, da + kk * 2, db + kk * 2, 1);
      wgmma_commit();
      bar_arrive(turn_other, 256);
    };
    auto release = [&](int s) { if (t == 0) mbar_arrive(BAR(B_EMPTY + s)); };
    auto kdone = [&](int k) { wgmma_wait0(); release(slot_of(k)); };
    auto wgmma_wait1 = [&]() { asm volatile("wgmma.wait_group.sync.aligned 1;" ::: "memory"); };

#pragma unroll 1
    for (int k = 0; k < 14; k++) {
      kstep(k, k == 0);
      if (k == 0) CT(0);
      if (k == 8 && warp == 2 && lane < 2) pkt_st128(&g_abflag[((eps * 2 + m) * 8 + tau) * 2 + lane], 0, 0, 0, 0);
      kdone(k);
    }
    uint32_t R[64];
    uint32_t tag;
    {
      const uint32_t rsa = sb + OFF_RS + q * 272;
      const uint64_t da2 = make_desc(sb + 2 * ST_BYTES + w * 8192), db2 = make_desc(sb + 2 * ST_BYTES + A_BYTES);
      const uint64_t da3 = make_desc(sb + 3 * ST_BYTES + w * 8192), db3 = make_desc(sb + 3 * ST_BYTES + A_BYTES);
      mbar_wait(BAR(B_FULL + 2), 1);
      CT(64 + 14);
      bar_sync(turn_me, 256);
      wgmma_fence();
#pragma unroll
      for (int kk = 0; kk < 4; kk++) wgmma_n256(acc, da2 + kk * 2, db2 + kk * 2, 1);
      wgmma_commit();
      mbar_wait(BAR(B_FULL + 3), 1);
      CT(64 + 15);
      wgmma_fence();
      wgmma_n256(acc, da3, db3, 1);
      wgmma_n256(acc, da3 + 2, db3 + 2, 1);
      wgmma_commit();
      mbar_wait(BAR(B_STAT), 0);
      wgmma_wait1();
      release(2);
      wgmma_fence();
      wgmma_n256(acc, da3 + 4, db3 + 4, 1);
      wgmma_n256(acc, da3 + 6, db3 + 6, 1);
      wgmma_n256(acc, make_desc_noswz(sb + OFF_EXA + w * 2048), make_desc_noswz(sb + OFF_EXB), 1);
      wgmma_commit();
      bar_arrive(turn_other, 256);
      tag = SM<uint32_t>(OFF_TAG);
#pragma unroll
      for (int i = 0; i < 16; i++) { const uint4 v = lds128_v(rsa + i * 16); R[4 * i] = v.x; R[4 * i + 1] = v.y; R[4 * i + 2] = v.z; R[4 * i + 3] = v.w; }
      kdone(15);
      mbar_wait(BAR(B_FULL + 0), 0);
    }
    fence_acc(acc);
    CT(1);
    auto pack = [&](auto cc) {
      constexpr int c = decltype(cc)::value;
#pragma unroll
      for (int j = 8 * c; j < 8 * c + 8; j++) {
        const float r0 = __uint_as_float(R[2 * j]), r1 = __uint_as_float(R[2 * j + 1]);
        const float* ac = &acc[4 * j];
        R[2 * j] = pack_bf16(ac[0] * r0, ac[1] * r1);
        R[2 * j + 1] = pack_bf16(ac[2] * r0, ac[3] * r1);
      }
    };
    auto put_chunk = [&](auto cc) {
      constexpr int c = decltype(cc)::value;
      const int rho = 16 * wi + (lane & 15);
#pragma unroll
      for (int j = 8 * c; j < 8 * c + 8; j += 2) {
        const int chunk = (j & 7) + (lane >> 4);
        stsm_x4(sb + chunk_off(c, w) + rho * 128 + ((chunk ^ (lane & 7)) << 4), R[2 * j], R[2 * j + 1], R[2 * j + 2], R[2 * j + 3]);
      }
    };
    auto staged = [&](int bar) {
      fence_async_smem();
      __syncwarp();
      if (lane == 0) mbar_arrive(BAR(bar));
    };
    auto mma_rs = [&](auto cc, auto k0, auto k1) {
      constexpr int c = decltype(cc)::value;
      const uint64_t db = make_desc(sb + c * ST_BYTES + A_BYTES);
#pragma unroll
      for (int kk = decltype(k0)::value; kk < decltype(k1)::value; kk++)
        wgmma_n256_rs(acc, R[16 * c + 4 * kk], R[16 * c + 4 * kk + 1], R[16 * c + 4 * kk + 2], R[16 * c + 4 * kk + 3], db + kk * 2, c + kk > 0);
      wgmma_commit();
    };
    auto kdone_x = [&](int k, auto ic) {
      constexpr int i = decltype(ic)::value;
      uint32_t r[8];
#pragma unroll
      for (int z = 0; z < 2; z++) {
        const int tr = 32 * (i & 1) + 16 * z + 8 * (lane >> 4) + (lane & 7), chunk = 2 * wi + ((lane >> 3) & 1);
        ldsm_x4_t(sb + (i >> 1) * ST_BYTES + w * 8192 + tr * 128 + ((chunk ^ (lane & 7)) << 4), r[4 * z], r[4 * z + 1], r[4 * z + 2], r[4 * z + 3]);
      }
      float f[16];
#pragma unroll
      for (int z = 0; z < 8; z++) { f[2 * z] = bf_lo(r[z]); f[2 * z + 1] = bf_hi(r[z]); }
#pragma unroll
      for (int z = 0; z < 16; z++) asm volatile("" : "+f"(f[z]));
      kdone(k);
#pragma unroll
      for (int z = 0; z < 16; z++) asm volatile("add.f32 %0, %0, %1;" : "+f"(acc[16 * i + z]) : "f"(f[z]));
    };
    pack(IC<0>());
    put_chunk(IC<0>());
    staged(w ? B_EPI0B : B_EPI);
    mbar_wait(BAR(B_STAT), 0);
    pack(IC<1>());
    pack(IC<2>());
    pack(IC<3>());
    CT(2);
    CT(64 + 16);
    bar_sync(turn_me, 256);
    wgmma_fence();
    mma_rs(IC<0>(), IC<0>(), IC<4>());
    mbar_wait(BAR(B_FULL + 1), 0);
    CT(64 + 17);
    wgmma_fence();
    mma_rs(IC<1>(), IC<0>(), IC<2>());
    wgmma_wait1();
    release(0);
    mma_rs(IC<1>(), IC<2>(), IC<4>());
    bar_arrive(turn_other, 256);
    kdone_x(17, IC<0>());
    static_for<2>([&](auto ic) {
      constexpr int c = 2 + decltype(ic)::value;
      mbar_wait(BAR(B_FULL + c), 0);
      CT(64 + 16 + c);
      bar_sync(turn_me, 256);
      wgmma_fence();
      mma_rs(IC<c>(), IC<0>(), IC<4>());
      bar_arrive(turn_other, 256);
      if (c == 2) { put_chunk(IC<1>()); staged(B_EPI + 1); }
      kdone_x(16 + c, IC<c - 1>());
    });
#pragma unroll 1
    for (int k = 20; k < 23; k++) {
      kstep(k, false, k < 22);
      if (k == 20) {
        kdone_x(k, IC<3>());
      } else {
        if (k == 21) put_chunk(IC<2>()); else put_chunk(IC<3>());
        staged(B_EPI + k - 19);
        kdone(k);
      }
    }
    uint32_t wf[32][4];
    auto load_wf = [&](auto hc) {
      constexpr int h = decltype(hc)::value;
      const int d = w * 64 + (lane >> 4) * 8 + (lane & 7);
      const uint32_t ad = sb + round_off(h) + (lane & 8) * 1024 + d * 64 + ((wi ^ ((lane >> 1) & 3)) << 4);
#pragma unroll
      for (int i = 0; i < 4; i++) ldsm_x4_t(ad + i * 1024, wf[4 * h + i][0], wf[4 * h + i][1], wf[4 * h + i][2], wf[4 * h + i][3]);
    };
    auto load_wf_rest = [&]() { static_for<8 - NREG_H>([&](auto ic) { load_wf(IC<NREG_H + decltype(ic)::value>()); }); };
#pragma unroll
    for (int i = 0; i < 4 * NREG_H; i++) { wf[i][0] = 0; wf[i][1] = 0; wf[i][2] = 0; wf[i][3] = 0; }
    const int grp = tau * 2 + m;
#pragma unroll 1
    for (int k = 23; k < 46; k++) {
      kstep(k, false);
      if (moe) {
        static_for<NREG_H>([&](auto hc) {
          constexpr int h = decltype(hc)::value;
          if (k == mr_k(h) + 1) { mbar_wait(BAR(B_MR + (h & 1)), (h >> 1) & 1); load_wf(hc); }
        });
      }
      if (k == 43) {
        if (moe) pkt_st128(&g_ypart[cid * 256 + tid], 0, 0, 0, 0);
        if (w == 1) pkt_st128(&g_hstat[(grp * 8 + eps) * 128 + t], 0, 0, 0, 0);
        if (warp == 0) pkt_st128(&g_cand[grp * 256 + eps * 32 + lane], 0, 0, 0, 0);
        if (eps == 0 && (warp == 1 || warp == 2)) pkt_st128(&g_key[(lane * 16 + grp) * 2 + warp - 1], 0, 0, 0, 0);
        if (warp == 3 && lane < 2) pkt_st128(&g_done[cid * 2 + lane], 0, 0, 0, 0);
      }
      kdone(k);
    }
    asm volatile("barrier.cluster.arrive.relaxed.aligned;" ::: "memory");
    const uint32_t vec_off = (2 * wi) * 512 + q * 128 + ((g ^ (2 * q)) << 4);
    {
      float as[64], ak[64];
      fence_acc(acc);
#pragma unroll
      for (int i = 0; i < 64; i++) asm volatile("mov.b32 %0, %1;" : "=f"(as[i]) : "f"(acc[64 + i]));
#pragma unroll
      for (int i = 0; i < 64; i++) asm volatile("mov.b32 %0, %1;" : "=f"(ak[i]) : "f"(acc[i]));
      const uint64_t da1 = make_desc(sb + 2 * ST_BYTES + w * 8192), db1 = make_desc(sb + 2 * ST_BYTES + A_BYTES);
      const uint64_t da2 = make_desc(sb + 3 * ST_BYTES + w * 8192), db2 = make_desc(sb + 3 * ST_BYTES + A_BYTES);
      mbar_wait(BAR(B_FULL + 2), 1);
      CT(64 + 46);
      mbar_wait(BAR(B_FULL + 3), 1);
      CT(64 + 47);
      bar_sync(turn_me, 256);
      wgmma_fence();
#pragma unroll
      for (int kk = 0; kk < 4; kk++) wgmma_n128(as, da1 + kk * 2, db1 + 1024 + kk * 2);
#pragma unroll
      for (int kk = 0; kk < 4; kk++) wgmma_n128(as, da2 + kk * 2, db2 + 1024 + kk * 2);
      wgmma_commit();
      bar_arrive(turn_other, 256);
      const uint32_t rx = mapa(sb + OFF_PEER + w * 4096 + vec_off, 1 - m), rb = mapa(BAR(B_XCH), 1 - m);
      asm volatile("barrier.cluster.wait.aligned;" ::: "memory");
      wgmma_wait0();
      fence_acc64(as);
#pragma unroll
      for (int i = 0; i < 8; i++) {
        const float* ac = &as[16 * (i >> 1) + 2 * (i & 1)];
        st_async_v4(rx + (i >> 1) * 8192 + (i & 1) * 512, rb, pack_bf16(ac[0], ac[1]), pack_bf16(ac[4], ac[5]), pack_bf16(ac[8], ac[9]), pack_bf16(ac[12], ac[13]));
      }
      bar_sync(turn_me, 256);
      wgmma_fence();
#pragma unroll
      for (int kk = 0; kk < 4; kk++) wgmma_n128(ak, da1 + kk * 2, db1 + kk * 2);
      wgmma_commit();
#pragma unroll
      for (int kk = 0; kk < 4; kk++) wgmma_n128(ak, da2 + kk * 2, db2 + kk * 2);
      wgmma_commit();
      if (w == 0) bar_arrive(turn_other, 256);
      wgmma_wait1();
      release(2);
      wgmma_wait0();
      fence_acc64(ak);
      CT(3);
#pragma unroll
      for (int i = 0; i < 8; i++) {
        const float* ac = &ak[16 * (i >> 1) + 2 * (i & 1)];
        sts128(sb + (2 + (i >> 2)) * ST_BYTES + w * 8192 + ((i >> 1) & 1) * 4096 + (i & 1) * 512 + vec_off,
               pack_bf16(ac[0], ac[1]), pack_bf16(ac[4], ac[5]), pack_bf16(ac[8], ac[9]), pack_bf16(ac[12], ac[13]));
      }
    }
    uint32_t h[8][4];
    const uint32_t cd = code_of(tag);
    {
      uint32_t wb[16];
#pragma unroll
      for (int i = 0; i < 4; i++) {
        const uint4 v = lds128_v(sb + OFF_WR + q * 80 + i * 16);
        wb[4 * i] = (g & 1) ? v.x : 0x3F803F80u; wb[4 * i + 1] = (g & 1) ? v.y : 0x3F803F80u;
        wb[4 * i + 2] = (g & 1) ? v.z : 0x3F803F80u; wb[4 * i + 3] = (g & 1) ? v.w : 0x3F803F80u;
      }
      const int qq = 2 * (warp & 1) + ((lane >> 3) & 1);
      const uint32_t lo = (lane >> 4) * 512 + qq * 128 + (((lane & 7) ^ (2 * qq)) << 4);
      bar_sync(NB_BOTH, 256);
#pragma unroll
      for (int ks = 0; ks < 8; ks++)
        ldsm_x4_t(sb + (2 + w) * ST_BYTES + (ks >> 2) * 8192 + (wi >> 1) * 4096 + (ks & 3) * 1024 + lo, h[ks][0], h[ks][1], h[ks][2], h[ks][3]);
      mbar_wait_cluster(BAR(B_XCH), 0);
      CT(4);
      float d1[2][4] = {}, d2[2][4] = {}, d3[2][4] = {};
#pragma unroll
      for (int ks = 0; ks < 8; ks++) {
        uint32_t r0, r1, r2, r3;
        ldsm_x4_t(sb + OFF_PEER + (warp >> 1) * 8192 + ks * 1024 + lo, r0, r1, r2, r3);
        h[ks][0] = badd2(h[ks][0], r0); h[ks][1] = badd2(h[ks][1], r1); h[ks][2] = badd2(h[ks][2], r2); h[ks][3] = badd2(h[ks][3], r3);
        mma16816(d1[ks & 1], h[ks][0], h[ks][1], h[ks][2], h[ks][3], wb[2 * ks], wb[2 * ks + 1]);
        mma16816(d2[ks & 1], h[ks][0], h[ks][1], h[ks][2], h[ks][3], h[ks][0], h[ks][2]);
        mma16816(d3[ks & 1], h[ks][0], h[ks][1], h[ks][2], h[ks][3], h[ks][1], h[ks][3]);
      }
      if (q == (g >> 1)) {
        uint4* hp = &g_hstat[(grp * 8 + eps) * 128 + warp * 16 + g];
        const float s0 = (g & 1) ? d2[0][1] + d2[1][1] : d2[0][0] + d2[1][0], s1 = (g & 1) ? d3[0][3] + d3[1][3] : d3[0][2] + d3[1][2];
        pkt_st128(hp, with_bit(d1[0][0] + d1[1][0], cd), with_bit(s0, cd >> 1), __float_as_uint(d1[0][1] + d1[1][1]), tag);
        pkt_st128(hp + 8, with_bit(d1[0][2] + d1[1][2], cd), with_bit(s1, cd >> 1), __float_as_uint(d1[0][3] + d1[1][3]), tag);
      }
    }
    CT(5);
    bool wf_loaded = false;
    if (moe) {
      wf_loaded = __all_sync(0xffffffffu, mbar_test(BAR(B_GU), 0));
      if (wf_loaded) load_wf_rest();
    }
    const uint4* kp = &g_key[(((cid * 8 + warp) & KEY_RMASK) * 16 + (lane & 15)) * 2];
    uint4 kq;
    float m_bf, sd, inv_sd, r_bf;
    {
      uint4 u[4];
      const uint4* hp = &g_hstat[(grp * 8 + 2 * q) * 128 + warp * 16 + g];
      uint32_t n = 0;
      while (true) {
#pragma unroll
        for (int i = 0; i < 4; i++) u[i] = pkt_ld128(hp + (i & 1) * 128 + (i >> 1) * 8);
        kq = pkt_ld128(kp);
        bool ok = true;
#pragma unroll
        for (int i = 0; i < 4; i++) ok = ok && u[i].w == tag && pair_code(u[i].x, u[i].y) == cd;
        if (__all_sync(0xffffffffu, ok) || ++n > SPIN_LIMIT) break;
        backoff();
      }
      CT(6);
      float a[3], b[3];
      a[0] = __uint_as_float(u[0].x & ~1u) + __uint_as_float(u[1].x & ~1u); b[0] = __uint_as_float(u[2].x & ~1u) + __uint_as_float(u[3].x & ~1u);
      a[1] = __uint_as_float(u[0].y & ~1u) + __uint_as_float(u[1].y & ~1u); b[1] = __uint_as_float(u[2].y & ~1u) + __uint_as_float(u[3].y & ~1u);
      a[2] = __uint_as_float(u[0].z) + __uint_as_float(u[1].z); b[2] = __uint_as_float(u[2].z) + __uint_as_float(u[3].z);
#pragma unroll
      for (int i = 0; i < 3; i++) {
        a[i] = ((q & 2) ? b[i] : a[i]) + __shfl_xor_sync(0xffffffffu, (q & 2) ? a[i] : b[i], 2);
        a[i] += __shfl_xor_sync(0xffffffffu, a[i], 1);
      }
      const float mu = a[0] * (1.f / 1024.f);
      m_bf = bf16r(mu);
      sd = ln_sd(a[1] * (1.f / 1024.f) - mu * mu);
      inv_sd = rcp_fast(sd);
      r_bf = bf16r((a[2] - m_bf * SM<float>(OFF_WSUM)) * inv_sd);
    }
    int gspec;
    uint4 cv;
    {
      const int trow = grp * 128 + 32 * (warp >> 1) + 8 * (g >> 1) + 4 * (warp & 1) + (q & 2) + (g & 1);
      const uint32_t u = __float_as_uint(r_bf);
      const uint32_t ord = (u & 0x80000000u) ? ~u : (u | 0x80000000u);
      const uint32_t key = (ord & 0xFFFF0000u) | (0xFFFFu - (uint32_t)trow);
      const uint32_t wk = __reduce_max_sync(0xffffffffu, key);
      if (lane == 0) SM<uint32_t>(OFF_WKEY + warp * 4) = wk;
      bar_sync(NB_BOTH, 256);
      const uint4 k0 = SM<uint4>(OFF_WKEY), k1 = SM<uint4>(OFF_WKEY + 16);
      const uint32_t bk = max(max(max(k0.x, k0.y), max(k0.z, k0.w)), max(max(k1.x, k1.y), max(k1.z, k1.w)));
      if (wk == bk) {
        const int src = __ffs(__ballot_sync(0xffffffffu, key == bk)) - 1;
        const uint32_t ms = __shfl_sync(0xffffffffu, (__float_as_uint(m_bf) >> 16) | __float_as_uint(sd), src);
        if (eps == 0) pkt_st128(&g_key[(lane * 16 + grp) * 2], bk, tag, ms, tag);
        if (g == (src >> 2)) {
#pragma unroll
          for (int ks = 0; ks < 8; ks++)
            pkt_st128(&g_cand[grp * 256 + (eps * 8 + ks) * 4 + q], (src & 2) ? h[ks][1] : h[ks][0], tag, (src & 2) ? h[ks][3] : h[ks][2], tag);
        }
      }
      CT(7);
      const uint32_t kv = max(bk, __reduce_max_sync(0xffffffffu, (kq.y == tag) ? kq.x : 0u));
      gspec = (0xFFFF - (int)(kv & 0xFFFFu)) >> 7;
    }
    {
      const uint32_t nm = pack_bf16(-m_bf, -m_bf);
      const uint32_t nm_o = __shfl_xor_sync(0xffffffffu, nm, 2);
      const float is_o = __shfl_xor_sync(0xffffffffu, inv_sd, 2);
      const uint32_t nm0 = (q & 2) ? nm_o : nm, nm1 = (q & 2) ? nm : nm_o;
      const float is0 = (q & 2) ? is_o : inv_sd, is1 = (q & 2) ? inv_sd : is_o;
      const uint32_t oa = sb + OFF_OUT + (warp * 16 + (lane & 15)) * 128;
#pragma unroll
      for (int ks = 0; ks < 8; ks++) {
        if (ks == 4) { kq = pkt_ld128(kp); cv = pkt_ld128(&g_cand[gspec * 256 + tid]); }
        stsm_x4(oa + (ks >> 2) * 16384 + (((2 * (ks & 3) + (lane >> 4)) ^ (lane & 7)) << 4),
                badd2(h[ks][0], norm2(h[ks][0], nm0, is0)), badd2(h[ks][1], norm2(h[ks][1], nm1, is1)),
                badd2(h[ks][2], norm2(h[ks][2], nm0, is0)), badd2(h[ks][3], norm2(h[ks][3], nm1, is1)));
      }
      staged(B_OUT);
    }
    CT(8);
    uint32_t df[16][4];
    auto load_df = [&]() {
      const int frow = (lane & 7) + ((lane >> 4) << 3), hi = (lane >> 3) & 1;
      const uint32_t base = sb + down_off(warp >> 1) + (warp & 1) * 8192 + frow * 128;
#pragma unroll
      for (int mt = 0; mt < 8; mt++) {
#pragma unroll
        for (int ks = 0; ks < 2; ks++)
          ldsm_x4_t(base + (mt >> 2) * 4096 + ks * 2048 + (((2 * (mt & 3) + hi) ^ (lane & 7)) << 4),
                    df[2 * mt + ks][0], df[2 * mt + ks][1], df[2 * mt + ks][2], df[2 * mt + ks][3]);
      }
    };
    bool df_loaded = false;
    if (moe) {
      if (!wf_loaded) {
        mbar_wait(BAR(B_GU), 0);
        load_wf_rest();
      }
      df_loaded = __all_sync(0xffffffffu, mbar_test(BAR(B_DN), 0));
      if (df_loaded) load_df();
    }
    int tsel; float sig;
    {
      uint32_t n = 0, kv;
      while (true) {
        const bool ok = kq.y == tag && kq.w == tag;
        kv = __reduce_max_sync(0xffffffffu, ok ? kq.x : 0u);
        const int gs = (0xFFFF - (int)(kv & 0xFFFFu)) >> 7;
        if (__all_sync(0xffffffffu, ok && gs == gspec && cv.y == tag && cv.w == tag) || ++n > SPIN_LIMIT) break;
        if (!__all_sync(0xffffffffu, ok)) { backoff(); kq = pkt_ld128(kp); }
        if (kv) gspec = gs;
        cv = pkt_ld128(&g_cand[gspec * 256 + tid]);
      }
      CT(9);
      tsel = 0xFFFF - (int)(kv & 0xFFFFu);
      const uint32_t ms = __shfl_sync(0xffffffffu, kq.z, gspec);
      const uint32_t nm = ((ms & 0xFFFFu) ^ 0x8000u) * 0x10001u;
      const float is = rcp_fast(bf_hi(ms));
      SM<uint2>(OFF_XSEL + q * 528 + (tid >> 2) * 8) = make_uint2(norm2(cv.x, nm, is), norm2(cv.z, nm, is));
      SM<uint2>(OFF_HSEL + q * 528 + (tid >> 2) * 8) = make_uint2(cv.x, cv.z);
      const uint32_t ord = kv & 0xFFFF0000u;
      const float r_sel = __uint_as_float((ord & 0x80000000u) ? (ord & 0x7FFFFFFFu) : (~ord & 0xFFFF0000u));
      sig = bf16r(__fdividef(1.f, 1.f + __expf(-r_sel)));
    }
    bar_sync(NB_BOTH, 256);
    if (moe) {
      float gd[4][4] = {};
#pragma unroll
      for (int r = 0; r < 4; r++) {
        uint4 bx[4];
#pragma unroll
        for (int i = 0; i < 4; i++) bx[i] = lds128_v(sb + OFF_XSEL + q * 528 + r * 128 + (i >> 1) * 64 + w * 32 + (i & 1) * 16);
#pragma unroll
        for (int i = 0; i < 8; i++)
          mma16816(gd[i & 3], wf[8 * r + i][0], wf[8 * r + i][1], wf[8 * r + i][2], wf[8 * r + i][3], (i & 1) ? bx[i >> 1].z : bx[i >> 1].x, (i & 1) ? bx[i >> 1].w : bx[i >> 1].y);
      }
      if (q == 0) SM<float2>(OFF_GP + (w * 32 + wi * 8 + g) * 8) = make_float2((gd[0][0] + gd[1][0]) + (gd[2][0] + gd[3][0]), (gd[0][2] + gd[1][2]) + (gd[2][2] + gd[3][2]));
      CT(10);
      if (!df_loaded) { mbar_wait(BAR(B_DN), 0); load_df(); }
      bar_sync(NB_BOTH, 256);
      uint32_t bq[4];
      {
        const float2 p0 = SM<float2>(OFF_GP + lane * 8), p1 = SM<float2>(OFF_GP + 256 + lane * 8);
        const float gt = bf16r(p0.x + p1.x), up = bf16r(p0.y + p1.y);
        const float act = bf16r(__fdividef(gt, 1.f + __expf(-gt))) * up;
        const uint32_t pr = pack_bf16(act, __shfl_down_sync(0xffffffffu, act, 1));
#pragma unroll
        for (int i = 0; i < 4; i++) bq[i] = __shfl_sync(0xffffffffu, pr, 8 * i + 2 * q);
      }
      CT(11);
      float yd[8][4] = {};
#pragma unroll
      for (int ks = 0; ks < 2; ks++) {
#pragma unroll
        for (int mt = 0; mt < 8; mt++) mma16816(yd[mt], df[2 * mt + ks][0], df[2 * mt + ks][1], df[2 * mt + ks][2], df[2 * mt + ks][3], bq[2 * ks], bq[2 * ks + 1]);
      }
      const float y0 = q == 0 ? yd[0][0] : q == 1 ? yd[2][0] : q == 2 ? yd[4][0] : yd[6][0];
      const float y1 = q == 0 ? yd[0][2] : q == 1 ? yd[2][2] : q == 2 ? yd[4][2] : yd[6][2];
      const float y2 = q == 0 ? yd[1][0] : q == 1 ? yd[3][0] : q == 2 ? yd[5][0] : yd[7][0];
      const float y3 = q == 0 ? yd[1][2] : q == 1 ? yd[3][2] : q == 2 ? yd[5][2] : yd[7][2];
      pkt_st128(&g_ypart[cid * 256 + tid], with_bit(y0, cd), with_bit(y1, cd >> 1), with_bit(y2, cd), with_bit(y3, cd >> 1));
    } else {
      const long long tw = clock64();
      while (clock64() - tw < IDLE_WAIT_CLK) __nanosleep(100);
    }
    CT(12);
    const int pfin = 2 * cid + (tid & 1);
    const int col_fin = (pfin >> 5) * 128 + (pfin & 3) * 32 + ((pfin & 31) >> 2) + 8 * ((tid >> 1) & 3);
    const int sel_off = ((col_fin & 7) >> 1) * 528 + (col_fin >> 3) * 4 + (col_fin & 1) * 2;
    const float hn_fin = __uint_as_float((uint32_t)SM<uint16_t>(OFF_XSEL + sel_off) << 16), h_fin = __uint_as_float((uint32_t)SM<uint16_t>(OFF_HSEL + sel_off) << 16);
    {
      const uint4* src = warp < 7 ? &g_ypart[(16 + (tid >> 1)) * 256 + pfin]
                                  : &g_done[((tsel >> 8) * 16 + (cid >> 4) * 2 + ((tsel >> 7) & 1)) * 2];
      uint4 v = pkt_ld128(src); uint32_t n = 0;
      while (true) {
        const bool ok = warp < 7 ? (pair_code(v.x, v.y) == cd && pair_code(v.z, v.w) == cd) : v.x == tag;
        if (__all_sync(0xffffffffu, ok) || ++n > SPIN_LIMIT) break;
        backoff();
        v = pkt_ld128(src);
      }
      CT(13);
      const float y0 = __uint_as_float(v.x & ~1u), y1 = __uint_as_float(v.y & ~1u), y2 = __uint_as_float(v.z & ~1u), y3 = __uint_as_float(v.w & ~1u);
      const float a0 = ((lane & 2) ? y1 : y0) + __shfl_xor_sync(0xffffffffu, (lane & 2) ? y0 : y1, 2);
      const float a1 = ((lane & 2) ? y3 : y2) + __shfl_xor_sync(0xffffffffu, (lane & 2) ? y2 : y3, 2);
      float b = ((lane & 4) ? a1 : a0) + __shfl_xor_sync(0xffffffffu, (lane & 4) ? a0 : a1, 4);
      b += __shfl_xor_sync(0xffffffffu, b, 8);
      b += __shfl_xor_sync(0xffffffffu, b, 16);
      if (lane < 8) SM<float>(OFF_FIN + warp * 32 + lane * 4) = b;
    }
    bar_sync(NB_BOTH, 256);
    if (tid < 8) {
      float y = 0.f;
#pragma unroll
      for (int i = 0; i < 7; i++) y += SM<float>(OFF_FIN + i * 32 + tid * 4);
      p.out[(size_t)tsel * 1024 + col_fin] = __float2bfloat16_rn(h_fin + bf16r(hn_fin + bf16r(bf16r(y) * sig)));
      if (cid == 0 && tid == 0) st_relaxed32(&g_epoch, tag);
    }
    CT(14);
  }
}

__global__ void __launch_bounds__(384, 1) occupancy_probe_kernel() {}

typedef CUresult (*EncodeFn)(CUtensorMap*, CUtensorMapDataType, cuuint32_t, void*, const cuuint64_t*, const cuuint64_t*, const cuuint32_t*, const cuuint32_t*,
                             CUtensorMapInterleave, CUtensorMapSwizzle, CUtensorMapL2promotion, CUtensorMapFloatOOBfill);

static void make_tm(EncodeFn enc, CUtensorMap* tm, const void* ptr, uint64_t rows, uint64_t cols, uint32_t brows, uint32_t bcols, CUtensorMapSwizzle sw,
                    CUtensorMapL2promotion promo = CU_TENSOR_MAP_L2_PROMOTION_L2_256B) {
  cuuint64_t dims[2] = {cols, rows};
  cuuint64_t strides[1] = {cols * 2};
  cuuint32_t box[2] = {bcols, brows};
  cuuint32_t es[2] = {1, 1};
  enc(tm, CU_TENSOR_MAP_DATA_TYPE_BFLOAT16, 2, const_cast<void*>(ptr), dims, strides, box, es, CU_TENSOR_MAP_INTERLEAVE_NONE, sw,
      promo, CU_TENSOR_MAP_FLOAT_OOB_FILL_NONE);
}

extern "C" void kernel_launch(void* const* d_in, const int* in_sizes, int n_in, void* d_out, int out_size) {
  (void)in_sizes; (void)n_in; (void)out_size;
  static EncodeFn enc = nullptr;
  static void* abT = nullptr;
  static int map = 0;
  if (!enc) {
    void* fn = nullptr; cudaDriverEntryPointQueryResult st;
    cudaGetDriverEntryPoint("cuTensorMapEncodeTiled", &fn, cudaEnableDefault, &st);
    enc = (EncodeFn)fn;
    cudaGetSymbolAddress(&abT, g_abT);
    cudaFuncSetAttribute(fnet_moe_kernel<0>, cudaFuncAttributeMaxDynamicSharedMemorySize, SMEM_TOTAL);
    cudaFuncSetAttribute(fnet_moe_kernel<1>, cudaFuncAttributeMaxDynamicSharedMemorySize, SMEM_TOTAL);
    cudaFuncSetAttribute(occupancy_probe_kernel, cudaFuncAttributeMaxDynamicSharedMemorySize, SMEM_TOTAL);
    cudaFuncSetAttribute(occupancy_probe_kernel, cudaFuncAttributeNonPortableClusterSizeAllowed, 1);
    auto max_clusters = [&](int size) {
      cudaLaunchConfig_t cfg = {};
      cfg.gridDim = dim3(128); cfg.blockDim = dim3(384); cfg.dynamicSmemBytes = SMEM_TOTAL;
      cudaLaunchAttribute at[1];
      at[0].id = cudaLaunchAttributeClusterDimension; at[0].val.clusterDim.x = size; at[0].val.clusterDim.y = 1; at[0].val.clusterDim.z = 1;
      cfg.attrs = at; cfg.numAttrs = 1;
      int ncl = 0;
      return cudaOccupancyMaxActiveClusters(&ncl, occupancy_probe_kernel, &cfg) == cudaSuccess ? ncl : 0;
    };
    int dev = 0, sms = 0;
    cudaGetDevice(&dev);
    cudaDeviceGetAttribute(&sms, cudaDevAttrMultiProcessorCount, dev);
    map = (!getenv("MAP1") && sms == 132 && max_clusters(2) == 66 && max_clusters(16) == 7) ? 0 : 1;
    (void)cudaGetLastError();
  }
  Params p;
  const bf16* x = (const bf16*)d_in[0];
  make_tm(enc, &p.tmD0, d_in[3], 1024, 1024, 128, 64, CU_TENSOR_MAP_SWIZZLE_128B);
  make_tm(enc, &p.tmD1, d_in[4], 1024, 1024, 128, 64, CU_TENSOR_MAP_SWIZZLE_128B);
  make_tm(enc, &p.tmX, x, 2048, 1024, 256, 64, CU_TENSOR_MAP_SWIZZLE_128B);
  make_tm(enc, &p.tmXr, x, 2048, 1024, 64, 64, CU_TENSOR_MAP_SWIZZLE_128B);
  make_tm(enc, &p.tmAbS, abT, 2048, 2048, 64, 64, CU_TENSOR_MAP_SWIZZLE_128B);
  make_tm(enc, &p.tmAbL, abT, 2048, 2048, 128, 64, CU_TENSOR_MAP_SWIZZLE_128B);
  make_tm(enc, &p.tmW0, d_in[1], 2048, 2048, 128, 64, CU_TENSOR_MAP_SWIZZLE_128B);
  make_tm(enc, &p.tmW1, d_in[2], 2048, 2048, 128, 64, CU_TENSOR_MAP_SWIZZLE_128B);
  {
    cuuint64_t dims[5] = {1024, 2, 4, 4, 64};
    cuuint64_t strides[4] = {2048, 8 * 2048, 2 * 2048, 32 * 2048};
    cuuint32_t box[5] = {64, 2, 4, 4, 4};
    cuuint32_t es[5] = {1, 1, 1, 1, 1};
    enc(&p.tmOut, CU_TENSOR_MAP_DATA_TYPE_BFLOAT16, 5, d_out, dims, strides, box, es, CU_TENSOR_MAP_INTERLEAVE_NONE, CU_TENSOR_MAP_SWIZZLE_128B,
        CU_TENSOR_MAP_L2_PROMOTION_NONE, CU_TENSOR_MAP_FLOAT_OOB_FILL_NONE);
  }
  make_tm(enc, &p.tmG, d_in[7], 1024, 3584, 128, 32, CU_TENSOR_MAP_SWIZZLE_64B, CU_TENSOR_MAP_L2_PROMOTION_L2_128B);
  make_tm(enc, &p.tmU, d_in[8], 1024, 3584, 128, 32, CU_TENSOR_MAP_SWIZZLE_64B, CU_TENSOR_MAP_L2_PROMOTION_L2_128B);
  make_tm(enc, &p.tmDn, d_in[9], 3584, 1024, 32, 64, CU_TENSOR_MAP_SWIZZLE_128B);
  p.x = x; p.Dre = (const bf16*)d_in[3]; p.Dim = (const bf16*)d_in[4];
  p.wr = (const bf16*)d_in[6]; p.wdown = (const bf16*)d_in[9]; p.wgate = (const bf16*)d_in[7]; p.wup = (const bf16*)d_in[8];
  p.out = (bf16*)d_out;
  if (map == 1) fnet_moe_kernel<1><<<128, 384, SMEM_TOTAL>>>(p);
  else fnet_moe_kernel<0><<<132, 384, SMEM_TOTAL>>>(p);
}
```

```cpp
#include <cuda.h>
#include <cuda_runtime.h>
#include <cuda_bf16.h>
#include <stdint.h>
#include <stdlib.h>
#include <type_traits>

typedef __nv_bfloat16 bf16;

#define REG_C 232
#define REG_P 40
#define KEY_RMASK 31
__device__ __forceinline__ int kblock(int tau, int j) {
  const int i = j - 4, c = (i * 37) >> 8;
  return j < 4 ? tau * 4 + j : ((tau + 1 + i - 7 * c) & 7) * 4 + c;
}
#define PUB_K1 22
#define NREG_H 4
#define MR_K0 29
__host__ __device__ constexpr int mr_k(int h) { return MR_K0 + 6 * (h >> 1) + 2 * (h & 1); }
constexpr int A_BYTES = 128 * 64 * 2;
constexpr int B_BYTES = 256 * 64 * 2;
constexpr int ST_BYTES = A_BYTES + B_BYTES;
constexpr int OFF_XCH = 4 * ST_BYTES;
constexpr int OFF_BAR = OFF_XCH + 32768;
constexpr int OFF_WR = OFF_BAR + 384;
constexpr int OFF_RS = OFF_WR + 384;
constexpr int OFF_PUB = OFF_RS + 640;
constexpr int OFF_MISC = OFF_PUB + 768;
constexpr int SMEM_TOTAL = OFF_MISC + 256;
constexpr int OFF_WSUM = OFF_MISC, OFF_TAG = OFF_MISC + 4;
constexpr int OFF_SEEN = OFF_MISC + 8;
constexpr int OFF_WKEY = OFF_MISC + 32;
constexpr int OFF_EXA = OFF_XCH;
constexpr int OFF_EXB = OFF_XCH + 4096;
__host__ __device__ constexpr int chunk_off(int c, int w) { return (c < 2 ? (c + 2) * ST_BYTES : OFF_XCH + (c - 2) * 16384) + w * 8192; }
__host__ __device__ constexpr int late_off(int i) { return i < 4 ? i * 16384 : 2 * ST_BYTES + A_BYTES + (i - 4) * 16384; }
__host__ __device__ constexpr int round_off(int h) { return h < NREG_H + 2 ? OFF_XCH + (h & 1) * 16384 : late_off(h - NREG_H - 2); }
__host__ __device__ constexpr int down_off(int i) { return late_off(6 - NREG_H + i); }
constexpr int OFF_PEER = ST_BYTES + A_BYTES;
constexpr int OFF_OUT = 3 * ST_BYTES + A_BYTES;
constexpr int OFF_XSEL = OFF_PEER;
constexpr int OFF_HSEL = OFF_PEER + 4096;
constexpr int OFF_GP = OFF_PEER + 8192;
constexpr int OFF_FIN = OFF_PEER + 9216;
__device__ __forceinline__ int slot_of(int k) { return k & 3; }
__device__ __forceinline__ int use_of(int k) { return k >> 2; }
enum { B_FULL = 0, B_EMPTY = 4, B_EPI = 8, B_STD = 12, B_EPI0B = 16, B_LATE = 17, B_STAT = 18, B_XCH = 19, B_MR = 20  , B_GU = 22,
       B_DN = 23, B_AUX = 24  , B_OUT = 26, B_COUNT = 27 };
enum { NB_TURN0 = 1, NB_TURN1 = 2, NB_BOTH = 5, NB_AUX = 6 };

struct Scratch {
  bf16 abT[2048 * 2048];
  uint2 xstat[2048];
  uint2 dsum[2048];
  uint4 abflag[16 * 8 * 2];
  uint4 hstat[16 * 8 * 128];
  uint4 cand[16 * 256];
  uint4 key[32 * 16 * 2];
  uint4 ypart[128 * 256];
  uint4 done[128 * 2];
  uint32_t epoch;
};
__device__ __align__(1024) Scratch g_scratch;

struct Params {
  Scratch* s; bf16* out;
  const bf16* x; const bf16* Dre; const bf16* Dim; const bf16* wr; const bf16* wdown; const bf16* wgate; const bf16* wup;
  CUtensorMap tmX, tmD0, tmD1, tmXr, tmAbS, tmAbL, tmW0, tmW1, tmOut, tmG, tmU, tmDn;
};

#define SPIN_LIMIT (1u << 17)
constexpr int PROLOGUE_CLK = 1800;
#define GATHER_NS 400
#define PF_R1 99
#define PF_START3_CLK 43000
#define W_PROMO CU_TENSOR_MAP_L2_PROMOTION_L2_128B
#define PF_R0 16
#define PF_STEP_CLK 300
#define PF_START2_CLK 26000
#define PF_STEP2_CLK 600
#define MOE_PACE_CLK 600
constexpr int IDLE_WAIT_CLK = 1200;
__device__ __forceinline__ uint32_t smem_u32(const void* p) { return (uint32_t)__cvta_generic_to_shared(p); }
__device__ __forceinline__ void mbar_init(uint32_t bar, uint32_t cnt) { asm volatile("mbarrier.init.shared::cta.b64 [%0], %1;" :: "r"(bar), "r"(cnt) : "memory"); }
__device__ __forceinline__ void mbar_expect_tx(uint32_t bar, uint32_t bytes) { asm volatile("mbarrier.arrive.expect_tx.shared::cta.b64 _, [%0], %1;" :: "r"(bar), "r"(bytes) : "memory"); }
__device__ __forceinline__ void mbar_arrive(uint32_t bar) { asm volatile("mbarrier.arrive.shared::cta.b64 _, [%0];" :: "r"(bar) : "memory"); }
__device__ __forceinline__ void mbar_wait(uint32_t bar, uint32_t parity) {
  uint32_t ok, n = 0;
  do {
    asm volatile("{\n.reg .pred p;\nmbarrier.try_wait.parity.shared::cta.b64 p, [%1], %2;\nselp.u32 %0, 1, 0, p;\n}\n" : "=r"(ok) : "r"(bar), "r"(parity) : "memory");
  } while (!ok && ++n < SPIN_LIMIT);
}
__device__ __forceinline__ bool mbar_test(uint32_t bar, uint32_t parity) {
  uint32_t ok;
  asm volatile("{\n.reg .pred p;\nmbarrier.test_wait.parity.shared::cta.b64 p, [%1], %2;\nselp.u32 %0, 1, 0, p;\n}\n" : "=r"(ok) : "r"(bar), "r"(parity) : "memory");
  return ok != 0;
}
__device__ __forceinline__ void mbar_wait_cluster(uint32_t bar, uint32_t parity) {
  uint32_t ok, n = 0;
  do {
    asm volatile("{\n.reg .pred p;\nmbarrier.try_wait.parity.acquire.cluster.shared::cta.b64 p, [%1], %2;\nselp.u32 %0, 1, 0, p;\n}\n" : "=r"(ok) : "r"(bar), "r"(parity) : "memory");
  } while (!ok && ++n < SPIN_LIMIT);
}
__device__ __forceinline__ void tma_load_2d(uint32_t dst, const CUtensorMap* tm, uint32_t bar, int c0, int c1) {
  asm volatile("cp.async.bulk.tensor.2d.shared::cluster.global.mbarrier::complete_tx::bytes [%0], [%1, {%3, %4}], [%2];"
    :: "r"(dst), "l"(tm), "r"(bar), "r"(c0), "r"(c1) : "memory");
}
__device__ __forceinline__ void tma_load_2d_hint(uint32_t dst, const CUtensorMap* tm, uint32_t bar, int c0, int c1, uint64_t pol) {
  asm volatile("cp.async.bulk.tensor.2d.shared::cluster.global.mbarrier::complete_tx::bytes.L2::cache_hint [%0], [%1, {%3, %4}], [%2], %5;"
    :: "r"(dst), "l"(tm), "r"(bar), "r"(c0), "r"(c1), "l"(pol) : "memory");
}
__device__ __forceinline__ uint64_t policy_evict_first() { uint64_t p; asm volatile("createpolicy.fractional.L2::evict_first.b64 %0, 1.0;" : "=l"(p)); return p; }
__device__ __forceinline__ void tma_store_2d(const CUtensorMap* tm, uint32_t src, int c0, int c1) {
  asm volatile("cp.async.bulk.tensor.2d.global.shared::cta.bulk_group [%0, {%2, %3}], [%1];" :: "l"(tm), "r"(src), "r"(c0), "r"(c1) : "memory");
}
__device__ __forceinline__ void bulk_load(uint32_t dst, const void* src, uint32_t bytes, uint32_t bar) {
  asm volatile("cp.async.bulk.shared::cluster.global.mbarrier::complete_tx::bytes [%0], [%1], %2, [%3];" :: "r"(dst), "l"(src), "r"(bytes), "r"(bar) : "memory");
}
__device__ __forceinline__ void bulk_commit() { asm volatile("cp.async.bulk.commit_group;" ::: "memory"); }
__device__ __forceinline__ void bulk_wait_all() { asm volatile("cp.async.bulk.wait_group 0;" ::: "memory"); }
__device__ __forceinline__ void fence_async_smem() { asm volatile("fence.proxy.async.shared::cta;" ::: "memory"); }
__device__ __forceinline__ void wgmma_fence() { asm volatile("wgmma.fence.sync.aligned;" ::: "memory"); }
__device__ __forceinline__ void wgmma_commit() { asm volatile("wgmma.commit_group.sync.aligned;" ::: "memory"); }
__device__ __forceinline__ void wgmma_wait0() { asm volatile("wgmma.wait_group.sync.aligned 0;" ::: "memory"); }
__device__ __forceinline__ void bar_sync(int id, int n) { asm volatile("bar.sync %0, %1;" :: "r"(id), "r"(n) : "memory"); }
__device__ __forceinline__ void bar_arrive(int id, int n) { asm volatile("bar.arrive %0, %1;" :: "r"(id), "r"(n) : "memory"); }
template<int R> __device__ __forceinline__ void reg_inc() { asm volatile("setmaxnreg.inc.sync.aligned.u32 %0;" :: "n"(R)); }
template<int R> __device__ __forceinline__ void reg_dec() { asm volatile("setmaxnreg.dec.sync.aligned.u32 %0;" :: "n"(R)); }
__device__ __forceinline__ bool elect_one() {
  uint32_t p;
  asm volatile("{\n.reg .pred q;\nelect.sync _|q, 0xffffffff;\nselp.u32 %0, 1, 0, q;\n}\n" : "=r"(p));
  return p != 0;
}
__device__ __forceinline__ uint32_t mapa(uint32_t addr, uint32_t cta) { uint32_t r; asm volatile("mapa.shared::cluster.u32 %0, %1, %2;" : "=r"(r) : "r"(addr), "r"(cta)); return r; }
__device__ __forceinline__ void st_async_v4(uint32_t addr, uint32_t bar, uint32_t a, uint32_t b, uint32_t c, uint32_t d) {
  asm volatile("st.async.weak.shared::cluster.mbarrier::complete_tx::bytes.v4.b32 [%0], {%2, %3, %4, %5}, [%1];" :: "r"(addr), "r"(bar), "r"(a), "r"(b), "r"(c), "r"(d) : "memory");
}
__device__ __forceinline__ void stsm_x4(uint32_t addr, uint32_t a, uint32_t b, uint32_t c, uint32_t d) {
  asm volatile("stmatrix.sync.aligned.m8n8.x4.shared.b16 [%0], {%1, %2, %3, %4};" :: "r"(addr), "r"(a), "r"(b), "r"(c), "r"(d));
}
__device__ __forceinline__ uint4 lds128_v(uint32_t addr) { uint4 v; asm volatile("ld.shared.v4.b32 {%0, %1, %2, %3}, [%4];" : "=r"(v.x), "=r"(v.y), "=r"(v.z), "=r"(v.w) : "r"(addr)); return v; }
extern __shared__ __align__(1024) uint8_t smem_raw[];
template<class T> __device__ __forceinline__ T& smem_at(uint32_t addr) { return *reinterpret_cast<T*>(__cvta_shared_to_generic(addr)); }
#define SM_(T, off) smem_at<T>(sb + (off))
__device__ __forceinline__ uint4 ldg_nc128(const void* p) { uint4 v; asm volatile("ld.global.nc.v4.b32 {%0, %1, %2, %3}, [%4];" : "=r"(v.x), "=r"(v.y), "=r"(v.z), "=r"(v.w) : "l"(p)); return v; }
__device__ __forceinline__ void pkt_st128(void* p, uint32_t a, uint32_t b, uint32_t c, uint32_t d) {
  asm volatile("{\n.reg .b128 v;\n.reg .b64 lo, hi;\nmov.b64 lo, {%1, %2};\nmov.b64 hi, {%3, %4};\nmov.b128 v, {lo, hi};\nst.relaxed.gpu.global.b128 [%0], v;\n}\n"
    :: "l"(p), "r"(a), "r"(b), "r"(c), "r"(d) : "memory");
}
__device__ __forceinline__ uint4 pkt_ld128(const void* p) {
  uint4 r;
  asm volatile("{\n.reg .b128 v;\n.reg .b64 lo, hi;\nld.relaxed.gpu.global.b128 v, [%4];\nmov.b128 {lo, hi}, v;\nmov.b64 {%0, %1}, lo;\nmov.b64 {%2, %3}, hi;\n}\n"
    : "=r"(r.x), "=r"(r.y), "=r"(r.z), "=r"(r.w) : "l"(p) : "memory");
  return r;
}
__device__ __forceinline__ void pkt_st64(void* p, uint32_t a, uint32_t b) {
  asm volatile("{\n.reg .b64 v;\nmov.b64 v, {%1, %2};\nst.relaxed.gpu.global.b64 [%0], v;\n}\n" :: "l"(p), "r"(a), "r"(b) : "memory");
}
__device__ __forceinline__ uint2 pkt_ld64(const void* p) {
  uint2 r;
  asm volatile("{\n.reg .b64 v;\nld.relaxed.gpu.global.b64 v, [%2];\nmov.b64 {%0, %1}, v;\n}\n" : "=r"(r.x), "=r"(r.y) : "l"(p) : "memory");
  return r;
}
__device__ __forceinline__ uint32_t ld_relaxed32(const void* p) { uint32_t v; asm volatile("ld.relaxed.gpu.global.b32 %0, [%1];" : "=r"(v) : "l"(p) : "memory"); return v; }
__device__ __forceinline__ void st_relaxed32(void* p, uint32_t v) { asm volatile("st.relaxed.gpu.global.b32 [%0], %1;" :: "l"(p), "r"(v) : "memory"); }
__device__ __forceinline__ void backoff() { __nanosleep(80); }
__device__ __forceinline__ uint32_t code_of(uint32_t tag) { return tag % 3u + 1u; }
__device__ __forceinline__ uint32_t with_bit(float v, uint32_t bit) { return (__float_as_uint(v) & ~1u) | (bit & 1u); }
__device__ __forceinline__ uint32_t pair_code(uint32_t a, uint32_t b) { return (a & 1u) | ((b & 1u) << 1); }
__device__ __forceinline__ uint32_t pack_bf16(float lo, float hi) { uint32_t r; asm("cvt.rn.bf16x2.f32 %0, %1, %2;" : "=r"(r) : "f"(hi), "f"(lo)); return r; }
__device__ __forceinline__ float bf_lo(uint32_t v) { return __uint_as_float(v << 16); }
__device__ __forceinline__ float bf_hi(uint32_t v) { return __uint_as_float(v & 0xFFFF0000u); }
__device__ __forceinline__ float bf16r(float x) { return __bfloat162float(__float2bfloat16_rn(x)); }
__device__ __forceinline__ uint32_t badd2(uint32_t a, uint32_t b) { uint32_t r; asm("add.rn.bf16x2 %0, %1, %2;" : "=r"(r) : "r"(a), "r"(b)); return r; }
__device__ __forceinline__ uint32_t bmul2(uint32_t a, uint32_t b) { uint32_t r; asm("mul.rn.bf16x2 %0, %1, %2;" : "=r"(r) : "r"(a), "r"(b)); return r; }
__device__ __forceinline__ float warp_sum(float v) {
#pragma unroll
  for (int o = 16; o > 0; o >>= 1) v += __shfl_xor_sync(0xffffffffu, v, o);
  return v;
}
__device__ __forceinline__ uint64_t make_desc(uint32_t addr) {
  return (uint64_t)((addr & 0x3FFFF) >> 4) | ((uint64_t)1 << 16) | ((uint64_t)64 << 32) | ((uint64_t)1 << 62);
}
__device__ __forceinline__ uint64_t make_desc_noswz(uint32_t addr) {
  return (uint64_t)((addr & 0x3FFFF) >> 4) | ((uint64_t)8 << 16) | ((uint64_t)16 << 32);
}
__device__ __forceinline__ void wgmma_n256(float (&d)[128], uint64_t da, uint64_t db, int scale_d) {
  asm volatile("{\n.reg .pred p;\nsetp.ne.b32 p, %130, 0;\n"
    "wgmma.mma_async.sync.aligned.m64n256k16.f32.bf16.bf16 "
    "{%0, %1, %2, %3, %4, %5, %6, %7, %8, %9, %10, %11, %12, %13, %14, %15, %16, %17, %18, %19, %20, %21, %22, %23, %24, %25, %26, %27, %28, %29, %30, %31, "
    "%32, %33, %34, %35, %36, %37, %38, %39, %40, %41, %42, %43, %44, %45, %46, %47, %48, %49, %50, %51, %52, %53, %54, %55, %56, %57, %58, %59, %60, %61, %62, %63, "
    "%64, %65, %66, %67, %68, %69, %70, %71, %72, %73, %74, %75, %76, %77, %78, %79, %80, %81, %82, %83, %84, %85, %86, %87, %88, %89, %90, %91, %92, %93, %94, %95, "
    "%96, %97, %98, %99, %100, %101, %102, %103, %104, %105, %106, %107, %108, %109, %110, %111, %112, %113, %114, %115, %116, %117, %118, %119, %120, %121, %122, %123, %124, %125, %126, %127}, "
    "%128, %129, p, 1, 1, 0, 0;\n}\n"
    : "+f"(d[0]), "+f"(d[1]), "+f"(d[2]), "+f"(d[3]), "+f"(d[4]), "+f"(d[5]), "+f"(d[6]), "+f"(d[7]),
      "+f"(d[8]), "+f"(d[9]), "+f"(d[10]), "+f"(d[11]), "+f"(d[12]), "+f"(d[13]), "+f"(d[14]), "+f"(d[15]),
      "+f"(d[16]), "+f"(d[17]), "+f"(d[18]), "+f"(d[19]), "+f"(d[20]), "+f"(d[21]), "+f"(d[22]), "+f"(d[23]),
      "+f"(d[24]), "+f"(d[25]), "+f"(d[26]), "+f"(d[27]), "+f"(d[28]), "+f"(d[29]), "+f"(d[30]), "+f"(d[31]),
      "+f"(d[32]), "+f"(d[33]), "+f"(d[34]), "+f"(d[35]), "+f"(d[36]), "+f"(d[37]), "+f"(d[38]), "+f"(d[39]),
      "+f"(d[40]), "+f"(d[41]), "+f"(d[42]), "+f"(d[43]), "+f"(d[44]), "+f"(d[45]), "+f"(d[46]), "+f"(d[47]),
      "+f"(d[48]), "+f"(d[49]), "+f"(d[50]), "+f"(d[51]), "+f"(d[52]), "+f"(d[53]), "+f"(d[54]), "+f"(d[55]),
      "+f"(d[56]), "+f"(d[57]), "+f"(d[58]), "+f"(d[59]), "+f"(d[60]), "+f"(d[61]), "+f"(d[62]), "+f"(d[63]),
      "+f"(d[64]), "+f"(d[65]), "+f"(d[66]), "+f"(d[67]), "+f"(d[68]), "+f"(d[69]), "+f"(d[70]), "+f"(d[71]),
      "+f"(d[72]), "+f"(d[73]), "+f"(d[74]), "+f"(d[75]), "+f"(d[76]), "+f"(d[77]), "+f"(d[78]), "+f"(d[79]),
      "+f"(d[80]), "+f"(d[81]), "+f"(d[82]), "+f"(d[83]), "+f"(d[84]), "+f"(d[85]), "+f"(d[86]), "+f"(d[87]),
      "+f"(d[88]), "+f"(d[89]), "+f"(d[90]), "+f"(d[91]), "+f"(d[92]), "+f"(d[93]), "+f"(d[94]), "+f"(d[95]),
      "+f"(d[96]), "+f"(d[97]), "+f"(d[98]), "+f"(d[99]), "+f"(d[100]), "+f"(d[101]), "+f"(d[102]), "+f"(d[103]),
      "+f"(d[104]), "+f"(d[105]), "+f"(d[106]), "+f"(d[107]), "+f"(d[108]), "+f"(d[109]), "+f"(d[110]), "+f"(d[111]),
      "+f"(d[112]), "+f"(d[113]), "+f"(d[114]), "+f"(d[115]), "+f"(d[116]), "+f"(d[117]), "+f"(d[118]), "+f"(d[119]),
      "+f"(d[120]), "+f"(d[121]), "+f"(d[122]), "+f"(d[123]), "+f"(d[124]), "+f"(d[125]), "+f"(d[126]), "+f"(d[127])
    : "l"(da), "l"(db), "r"(scale_d));
}
__device__ __forceinline__ void wgmma_n256_rs(float (&d)[128], uint32_t a0, uint32_t a1, uint32_t a2, uint32_t a3, uint64_t db, int scale_d) {
  asm volatile("{\n.reg .pred p;\nsetp.ne.b32 p, %133, 0;\n"
    "wgmma.mma_async.sync.aligned.m64n256k16.f32.bf16.bf16 "
    "{%0, %1, %2, %3, %4, %5, %6, %7, %8, %9, %10, %11, %12, %13, %14, %15, %16, %17, %18, %19, %20, %21, %22, %23, %24, %25, %26, %27, %28, %29, %30, %31, "
    "%32, %33, %34, %35, %36, %37, %38, %39, %40, %41, %42, %43, %44, %45, %46, %47, %48, %49, %50, %51, %52, %53, %54, %55, %56, %57, %58, %59, %60, %61, %62, %63, "
    "%64, %65, %66, %67, %68, %69, %70, %71, %72, %73, %74, %75, %76, %77, %78, %79, %80, %81, %82, %83, %84, %85, %86, %87, %88, %89, %90, %91, %92, %93, %94, %95, "
    "%96, %97, %98, %99, %100, %101, %102, %103, %104, %105, %106, %107, %108, %109, %110, %111, %112, %113, %114, %115, %116, %117, %118, %119, %120, %121, %122, %123, %124, %125, %126, %127}, "
    "{%128, %129, %130, %131}, %132, p, 1, 1, 0;\n}\n"
    : "+f"(d[0]), "+f"(d[1]), "+f"(d[2]), "+f"(d[3]), "+f"(d[4]), "+f"(d[5]), "+f"(d[6]), "+f"(d[7]),
      "+f"(d[8]), "+f"(d[9]), "+f"(d[10]), "+f"(d[11]), "+f"(d[12]), "+f"(d[13]), "+f"(d[14]), "+f"(d[15]),
      "+f"(d[16]), "+f"(d[17]), "+f"(d[18]), "+f"(d[19]), "+f"(d[20]), "+f"(d[21]), "+f"(d[22]), "+f"(d[23]),
      "+f"(d[24]), "+f"(d[25]), "+f"(d[26]), "+f"(d[27]), "+f"(d[28]), "+f"(d[29]), "+f"(d[30]), "+f"(d[31]),
      "+f"(d[32]), "+f"(d[33]), "+f"(d[34]), "+f"(d[35]), "+f"(d[36]), "+f"(d[37]), "+f"(d[38]), "+f"(d[39]),
      "+f"(d[40]), "+f"(d[41]), "+f"(d[42]), "+f"(d[43]), "+f"(d[44]), "+f"(d[45]), "+f"(d[46]), "+f"(d[47]),
      "+f"(d[48]), "+f"(d[49]), "+f"(d[50]), "+f"(d[51]), "+f"(d[52]), "+f"(d[53]), "+f"(d[54]), "+f"(d[55]),
      "+f"(d[56]), "+f"(d[57]), "+f"(d[58]), "+f"(d[59]), "+f"(d[60]), "+f"(d[61]), "+f"(d[62]), "+f"(d[63]),
      "+f"(d[64]), "+f"(d[65]), "+f"(d[66]), "+f"(d[67]), "+f"(d[68]), "+f"(d[69]), "+f"(d[70]), "+f"(d[71]),
      "+f"(d[72]), "+f"(d[73]), "+f"(d[74]), "+f"(d[75]), "+f"(d[76]), "+f"(d[77]), "+f"(d[78]), "+f"(d[79]),
      "+f"(d[80]), "+f"(d[81]), "+f"(d[82]), "+f"(d[83]), "+f"(d[84]), "+f"(d[85]), "+f"(d[86]), "+f"(d[87]),
      "+f"(d[88]), "+f"(d[89]), "+f"(d[90]), "+f"(d[91]), "+f"(d[92]), "+f"(d[93]), "+f"(d[94]), "+f"(d[95]),
      "+f"(d[96]), "+f"(d[97]), "+f"(d[98]), "+f"(d[99]), "+f"(d[100]), "+f"(d[101]), "+f"(d[102]), "+f"(d[103]),
      "+f"(d[104]), "+f"(d[105]), "+f"(d[106]), "+f"(d[107]), "+f"(d[108]), "+f"(d[109]), "+f"(d[110]), "+f"(d[111]),
      "+f"(d[112]), "+f"(d[113]), "+f"(d[114]), "+f"(d[115]), "+f"(d[116]), "+f"(d[117]), "+f"(d[118]), "+f"(d[119]),
      "+f"(d[120]), "+f"(d[121]), "+f"(d[122]), "+f"(d[123]), "+f"(d[124]), "+f"(d[125]), "+f"(d[126]), "+f"(d[127])
    : "r"(a0), "r"(a1), "r"(a2), "r"(a3), "l"(db), "r"(scale_d));
}
__device__ __forceinline__ void wgmma_n128(float (&d)[64], uint64_t da, uint64_t db) {
  asm volatile("{\n.reg .pred p;\nsetp.ne.b32 p, 1, 0;\n"
    "wgmma.mma_async.sync.aligned.m64n128k16.f32.bf16.bf16 "
    "{%0, %1, %2, %3, %4, %5, %6, %7, %8, %9, %10, %11, %12, %13, %14, %15, %16, %17, %18, %19, %20, %21, %22, %23, %24, %25, %26, %27, %28, %29, %30, %31, %32, %33, %34, %35, %36, %37, %38, %39, %40, %41, %42, %43, %44, %45, %46, %47, %48, %49, %50, %51, %52, %53, %54, %55, %56, %57, %58, %59, %60, %61, %62, %63}, "
    "%64, %65, p, 1, 1, 0, 0;\n}\n"
    : "+f"(d[0]), "+f"(d[1]), "+f"(d[2]), "+f"(d[3]), "+f"(d[4]), "+f"(d[5]), "+f"(d[6]), "+f"(d[7]), "+f"(d[8]), "+f"(d[9]), "+f"(d[10]), "+f"(d[11]), "+f"(d[12]), "+f"(d[13]), "+f"(d[14]), "+f"(d[15]), "+f"(d[16]), "+f"(d[17]), "+f"(d[18]), "+f"(d[19]), "+f"(d[20]), "+f"(d[21]), "+f"(d[22]), "+f"(d[23]), "+f"(d[24]), "+f"(d[25]), "+f"(d[26]), "+f"(d[27]), "+f"(d[28]), "+f"(d[29]), "+f"(d[30]), "+f"(d[31]), "+f"(d[32]), "+f"(d[33]), "+f"(d[34]), "+f"(d[35]), "+f"(d[36]), "+f"(d[37]), "+f"(d[38]), "+f"(d[39]), "+f"(d[40]), "+f"(d[41]), "+f"(d[42]), "+f"(d[43]), "+f"(d[44]), "+f"(d[45]), "+f"(d[46]), "+f"(d[47]), "+f"(d[48]), "+f"(d[49]), "+f"(d[50]), "+f"(d[51]), "+f"(d[52]), "+f"(d[53]), "+f"(d[54]), "+f"(d[55]), "+f"(d[56]), "+f"(d[57]), "+f"(d[58]), "+f"(d[59]), "+f"(d[60]), "+f"(d[61]), "+f"(d[62]), "+f"(d[63])
    : "l"(da), "l"(db));
}
__device__ __forceinline__ void fence_acc64(float (&d)[64]) {
#pragma unroll
  for (int i = 0; i < 64; i++) asm volatile("" : "+f"(d[i]) :: "memory");
}
__device__ __forceinline__ void fence_acc(float (&d)[128]) {
#pragma unroll
  for (int i = 0; i < 128; i++) asm volatile("" : "+f"(d[i]) :: "memory");
}

template<int N, int I = 0, class F> __device__ __forceinline__ void static_for(F&& f) {
  if constexpr (I < N) { f(std::integral_constant<int, I>()); static_for<N, I + 1>(f); }
}

__device__ __forceinline__ void ldsm_x4_t(uint32_t addr, uint32_t& a, uint32_t& b, uint32_t& c, uint32_t& d) {
  asm volatile("ldmatrix.sync.aligned.m8n8.x4.trans.shared.b16 {%0, %1, %2, %3}, [%4];" : "=r"(a), "=r"(b), "=r"(c), "=r"(d) : "r"(addr));
}
__device__ __forceinline__ void sts128(uint32_t addr, uint32_t a, uint32_t b, uint32_t c, uint32_t d) {
  asm volatile("st.shared.v4.b32 [%0], {%1, %2, %3, %4};" :: "r"(addr), "r"(a), "r"(b), "r"(c), "r"(d));
}
__device__ __forceinline__ void mma16816(float (&c)[4], uint32_t a0, uint32_t a1, uint32_t a2, uint32_t a3, uint32_t b0, uint32_t b1) {
  asm("mma.sync.aligned.m16n8k16.row.col.f32.bf16.bf16.f32 {%0, %1, %2, %3}, {%4, %5, %6, %7}, {%8, %9}, {%0, %1, %2, %3};"
      : "+f"(c[0]), "+f"(c[1]), "+f"(c[2]), "+f"(c[3]) : "r"(a0), "r"(a1), "r"(a2), "r"(a3), "r"(b0), "r"(b1));
}
__device__ __forceinline__ void tma_store_5d(const CUtensorMap* tm, uint32_t src, int c0, int c4) {
  asm volatile("cp.async.bulk.tensor.5d.global.shared::cta.bulk_group [%0, {%2, %3, %3, %3, %4}], [%1];" :: "l"(tm), "r"(src), "r"(c0), "r"(0), "r"(c4) : "memory");
}
__device__ __forceinline__ float rcp_fast(float x) { float r; asm("rcp.approx.ftz.f32 %0, %1;" : "=f"(r) : "f"(x)); return r; }
__device__ __forceinline__ float sqrt_fast(float x) { float r; asm("sqrt.approx.f32 %0, %1;" : "=f"(r) : "f"(x)); return r; }
__device__ __forceinline__ float ln_sd(float var) { return bf16r(sqrt_fast(bf16r(bf16r(fmaxf(var, 0.f)) + 1e-5f))); }
__device__ __forceinline__ uint32_t norm2(uint32_t h, uint32_t neg_mean2, float inv_sd) {
  const uint32_t d = badd2(h, neg_mean2);
  return pack_bf16(bf_lo(d) * inv_sd, bf_hi(d) * inv_sd);
}
template<int V> using IC = std::integral_constant<int, V>;

#define CT(slot) do {} while (0)
#define PT(slot) do {} while (0)

template<int MAP>
__global__ void __cluster_dims__(2, 1, 1) __launch_bounds__(384, 1)
fnet_moe_kernel(const __grid_constant__ Params p) {
  uint32_t sb;
  asm volatile("mov.u32 %0, %1;" : "=r"(sb) : "r"(smem_u32(smem_raw)));
  const int warp = __shfl_sync(0xffffffffu, threadIdx.x >> 5, 0);
  const int tid = __shfl_sync(0xffffffffu, threadIdx.x, threadIdx.x & 31), lane = tid & 31;
  const int m = blockIdx.x & 1;
  int tau, eps;
  if (MAP == 0) {
    uint32_t smid;
    asm volatile("mov.u32 %0, %%smid;" : "=r"(smid));
    const int c = smid >> 1, e7 = ((c - 32) * 37) >> 8;
    if (c == 60 || c == 61) {
      const uint32_t tg = ld_relaxed32(&p.s->epoch) + 1;
      uint32_t n = 0;
      do { __nanosleep(1000); } while (!__all_sync(0xffffffffu, pkt_ld64(&p.s->xstat[(tid & 127) * 16]).y == tg) && ++n < 4096);
      return;
    }
    tau = c < 32 ? (c & 7) : (c < 60 ? c - 31 - 7 * e7 : 0);
    eps = c < 32 ? (c >> 3) : (c < 60 ? 4 + e7 : c - 58);
  } else {
    tau = (blockIdx.x >> 1) & 7; eps = blockIdx.x >> 4;
  }
  const int cid = tau * 16 + eps * 2 + m;
  const bool moe = tau > 0;
  auto BAR = [&](int i) { return sb + OFF_BAR + 8 * i; };
  const CUtensorMap* tmD = m ? &p.tmD1 : &p.tmD0;

  const uint64_t pol_ef = policy_evict_first();
#define LOAD_STREAM(d, tm, bar, c0, c1) tma_load_2d_hint(d, tm, bar, c0, c1, pol_ef)
  if (__builtin_expect(warp == 0, 1)) {
    if (elect_one()) {
      mbar_init(BAR(B_FULL), 1);
      asm volatile("fence.mbarrier_init.release.cluster;" ::: "memory");
      mbar_expect_tx(BAR(B_FULL), ST_BYTES);
      tma_load_2d(sb + A_BYTES, &p.tmX, BAR(B_FULL), 0, tau * 256);
      tma_load_2d(sb, tmD, BAR(B_FULL), 0, eps * 128);
#pragma unroll 1
      for (int k = 1; k < 4; k++) {
        mbar_init(BAR(B_FULL + k), 1);
        asm volatile("fence.mbarrier_init.release.cluster;" ::: "memory");
        mbar_expect_tx(BAR(B_FULL + k), ST_BYTES);
        LOAD_STREAM(sb + k * ST_BYTES, tmD, BAR(B_FULL + k), k * 64, eps * 128);
        tma_load_2d(sb + k * ST_BYTES + A_BYTES, &p.tmX, BAR(B_FULL + k), k * 64, tau * 256);
      }
    }
    PT(0);
  }
  if (warp == 8) {
    if (elect_one()) {
#pragma unroll
      for (int b = B_EMPTY; b < B_COUNT; b++)
        mbar_init(BAR(b), b < B_EPI ? 2 : (b == B_EPI || b == B_EPI0B) ? 4 : (b < B_STD || b == B_OUT) ? 8 : b == B_STAT ? 3 : 1);
      asm volatile("fence.mbarrier_init.release.cluster;" ::: "memory");
      mbar_expect_tx(BAR(B_XCH), 32768);
      SM_(uint32_t, OFF_SEEN) = 0;
    }
  }
  __syncthreads();

  if (warp >= 8) {
    reg_dec<REG_P>();
    asm volatile("barrier.cluster.arrive.relaxed.aligned;" ::: "memory");
    const int abrow = m * 1024 + eps * 128;
    const int f0 = (cid - 16) * 32;
    if (warp == 8) {
      const CUtensorMap* tmW = m ? &p.tmW1 : &p.tmW0;
      const int tA = tau * 256 + m * 128, tB = tau * 256 + (1 - m) * 128;
      uint32_t seen = 0;
#pragma unroll 1
      for (int k = 4; k < 48; k++) {
        const int s = slot_of(k);
        const uint32_t sa = sb + s * ST_BYTES, sbb = sa + A_BYTES;
        const int kb = kblock(tau, k - 16);
        mbar_wait(BAR(B_EMPTY + s), (use_of(k) & 1) ^ 1);
        PT(64 + k);
        if (elect_one()) {
          mbar_expect_tx(BAR(B_FULL + s), (k >> 1) == 9 ? B_BYTES : ST_BYTES);
          if (k < 16) {
            LOAD_STREAM(sa, tmD, BAR(B_FULL + s), k * 64, eps * 128);
            tma_load_2d(sbb, &p.tmX, BAR(B_FULL + s), k * 64, tau * 256);
          } else {
            LOAD_STREAM(sbb, tmW, BAR(B_FULL + s), kb * 64, tA);
            LOAD_STREAM(sbb + 16384, tmW, BAR(B_FULL + s), kb * 64, tB);
            if (k < 18) {
              tma_load_2d(sa, &p.tmXr, BAR(B_FULL + s), eps * 128, tA + s * 64);
              tma_load_2d(sa + 8192, &p.tmXr, BAR(B_FULL + s), eps * 128 + 64, tA + s * 64);
            }
          }
        }
        if (k >= 24) {
          uint32_t n = 0;
          while (!((seen >> kb) & 1) && ++n < SPIN_LIMIT * 16) seen = *(volatile uint32_t*)&SM_(uint32_t, OFF_SEEN);
          if (elect_one()) tma_load_2d(sa, &p.tmAbL, BAR(B_FULL + s), kb * 64, abrow);
        }
        if (k == PUB_K1 && elect_one()) mbar_arrive(BAR(B_LATE));
        if (moe && k >= MR_K0) {
          const int i = k - MR_K0, r6 = (i * 43) >> 8, u = i - 6 * r6, h = 2 * r6 + (u >> 1);
          if (u < 4 && h < NREG_H + 2) {
            if (h < 2) mbar_wait(BAR(B_STD + 2 + h), 0);
            if (elect_one()) {
              const uint32_t bar = BAR(h < NREG_H ? B_MR + (h & 1) : B_GU);
              if (!(u & 1) && h <= NREG_H) mbar_expect_tx(bar, h < NREG_H ? 16384 : (8 - NREG_H) * 16384);
              LOAD_STREAM(sb + OFF_XCH + u * 8192, (u & 1) ? &p.tmU : &p.tmG, bar, f0, h * 128);
            }
          }
        }
      }
      if (moe) {
        mbar_wait(BAR(B_EMPTY + 0), 1);
        if (elect_one()) mbar_expect_tx(BAR(B_DN), 65536);
#pragma unroll 1
        for (int i = 0; i < 10 - NREG_H; i++) {
          if (i == 3) { mbar_wait(BAR(B_EMPTY + 2), 1); mbar_wait(BAR(B_XCH), 0); }
          const uint32_t dst = sb + late_off(i);
          if (elect_one()) {
            if (i < 6 - NREG_H) {
              LOAD_STREAM(dst, &p.tmG, BAR(B_GU), f0, (NREG_H + 2 + i) * 128);
              LOAD_STREAM(dst + 8192, &p.tmU, BAR(B_GU), f0, (NREG_H + 2 + i) * 128);
            } else {
#pragma unroll
              for (int b = 0; b < 4; b++) LOAD_STREAM(dst + b * 4096, &p.tmDn, BAR(B_DN), (4 * (i - 6 + NREG_H) + b) * 64, f0);
            }
          }
          const long long t0 = clock64();
          while (clock64() - t0 < MOE_PACE_CLK) {}
        }
      }
    } else {
      const int a = warp - 9;
      const long long t_aux = clock64() - PROLOGUE_CLK;
      auto stage = [&](const bf16* src, int g) {
        if (elect_one()) {
          mbar_expect_tx(BAR(B_AUX + g), 16384);
          bulk_load(sb + OFF_XCH + g * 16384, src + g * 8192, 16384, BAR(B_AUX + g));
        }
      };
      const uint32_t tag = ld_relaxed32(&p.s->epoch) + 1;
      if (a == 2) {
        float s = 0.f;
#pragma unroll
        for (int q = 0; q < 4; q++) {
          const uint4 v = ldg_nc128(p.wr + (q * 32 + lane) * 8);
          s += ((bf_lo(v.x) + bf_hi(v.x)) + (bf_lo(v.y) + bf_hi(v.y))) + ((bf_lo(v.z) + bf_hi(v.z)) + (bf_lo(v.w) + bf_hi(v.w)));
          const int ch = q * 32 + lane - eps * 16;
          if (ch >= 0 && ch < 16) {
            SM_(uint32_t, OFF_WR + ch * 4) = v.x; SM_(uint32_t, OFF_WR + 80 + ch * 4) = v.y;
            SM_(uint32_t, OFF_WR + 160 + ch * 4) = v.z; SM_(uint32_t, OFF_WR + 240 + ch * 4) = v.w;
          }
        }
        s = warp_sum(s);
        if (lane == 0) { SM_(float, OFF_WSUM) = s; SM_(uint32_t, OFF_TAG) = tag; }
      }
      if (a < 2) {
        mbar_wait(BAR(B_FULL + 0), 0);
        if (a == 0) PT(1);
        stage(p.x + (size_t)cid * 16 * 1024, a);
      }
#pragma unroll 1
      for (int it = 0; it < 4; it++) {
        const int g = it & 1;
        mbar_wait(BAR(B_AUX + g), it >> 1);
        if (a == 0) PT(2 + it);
        const uint32_t ad = sb + OFF_XCH + g * 16384 + (lane >> 2) * 2048;
        float s0 = 0.f, s1 = 0.f, q0 = 0.f, q1 = 0.f;
        auto row = [&](auto sq) {
#pragma unroll
          for (int i = 0; i < 11; i++) {
            if (i == 10 && a == 2) break;
            const uint4 v = lds128_v(ad + (((a * 44 + 4 * i + lane) & 127) << 4));
            const uint32_t ww[4] = {v.x, v.y, v.z, v.w};
#pragma unroll
            for (int z = 0; z < 4; z++) {
              const float d0 = bf_lo(ww[z]), d1 = bf_hi(ww[z]);
              s0 += d0; s1 += d1;
              if (decltype(sq)::value) { q0 = fmaf(d0, d0, q0); q1 = fmaf(d1, d1, q1); }
            }
          }
        };
        if (it < 2) row(IC<1>()); else row(IC<0>());
        s0 += s1; q0 += q1;
#pragma unroll
        for (int o = 1; o < 4; o <<= 1) { s0 += __shfl_xor_sync(0xffffffffu, s0, o); q0 += __shfl_xor_sync(0xffffffffu, q0, o); }
        if ((lane & 3) == 0) SM_(float2, OFF_PUB + a * 256 + it * 64 + (lane >> 2) * 8) = make_float2(s0, q0);
        if (it != 2) bar_sync(NB_AUX, 96);
        if (it < 2 && a == 2) stage(cid < 64 ? p.Dre + (size_t)cid * 16 * 1024 : p.Dim + (size_t)(cid - 64) * 16 * 1024, g);
      }
      if (a == 1) {
        const float2 v0 = SM_(float2, OFF_PUB + lane * 8), v1 = SM_(float2, OFF_PUB + 256 + lane * 8), v2 = SM_(float2, OFF_PUB + 512 + lane * 8);
        const float s = v0.x + v1.x + v2.x, mean = s * (1.f / 1024.f);
        const float rs = rcp_fast(ln_sd((v0.y + v1.y + v2.y) * (1.f / 1024.f) - mean * mean));
        pkt_st64((lane < 16 ? p.s->xstat : p.s->dsum) + cid * 16 + (lane & 15), lane < 16 ? pack_bf16(rs, mean) : __float_as_uint(s), tag);
        PT(6);
      }
      auto prefetch = [&](int r) {
        const int l = r * 32 + lane;
        const bf16* ad = l < 1024 ? (((l >> 6) & 1) ? p.wup : p.wgate) + (size_t)((l >> 7) * 128 + m * 64 + (l & 63)) * 3584 + (f0 & ~63)
                                  : p.wdown + (size_t)f0 * 1024 + (l - 1024) * 64;
        if (moe) asm volatile("prefetch.global.L2 [%0];" :: "l"(ad));
      };
      __nanosleep(GATHER_NS);
      {
        const int i0 = a * 32 + lane;
        uint2 v[3], c0, c1; uint32_t n = 0;
        const uint2* dp = &p.s->dsum[abrow];
        while (true) {
#pragma unroll
          for (int q = 0; q < 3; q++) v[q] = pkt_ld64(&p.s->xstat[tau * 256 + min(i0 + 96 * q, 255)]);
          c0 = pkt_ld64(dp + i0); c1 = pkt_ld64(dp + min(i0 + 96, 127));
          if (__all_sync(0xffffffffu, v[0].y == tag && v[1].y == tag && v[2].y == tag && c0.y == tag && c1.y == tag) || ++n > SPIN_LIMIT) break;
          __nanosleep(200);
        }
#pragma unroll
        for (int q = 0; q < 3; q++) {
          const int col = min(i0 + 96 * q, 255);
          SM_(uint16_t, OFF_RS + ((col & 7) >> 1) * 144 + (col >> 3) * 4 + (col & 1) * 2) = (uint16_t)(v[q].x ^ (m << 15));
          const uint32_t nm = (v[q].x >> 16) ^ 0x8000u;
          SM_(uint4, OFF_EXB + (col >> 3) * 256 + (col & 7) * 16) = make_uint4(nm | (nm << 16), nm, 0, 0);
          SM_(uint4, OFF_EXB + (col >> 3) * 256 + 128 + (col & 7) * 16) = make_uint4(0, 0, 0, 0);
        }
#pragma unroll
        for (int q = 0; q < 2; q++) {
          const int e = min(i0 + 96 * q, 127);
          const float c = __uint_as_float(q ? c1.x : c0.x);
          const float hi = bf16r(c), mid = bf16r(c - hi), lo = bf16r((c - hi) - mid);
          SM_(uint4, OFF_EXA + (e >> 3) * 256 + (e & 7) * 16) = make_uint4((__float_as_uint(hi) >> 16) | (__float_as_uint(mid) & 0xFFFF0000u), __float_as_uint(lo) >> 16, 0, 0);
          SM_(uint4, OFF_EXA + (e >> 3) * 256 + 128 + (e & 7) * 16) = make_uint4(0, 0, 0, 0);
        }
        fence_async_smem();
      }
      __syncwarp();
      if (lane == 0) mbar_arrive(BAR(B_STAT));
      if (a == 0) PT(7);
      if (a == 0) {
        const uint32_t* flg = reinterpret_cast<const uint32_t*>(&p.s->abflag[((eps * 2 + m) * 8 + (lane >> 2)) * 2]) + (lane & 3);
        uint32_t seen = 0;
        auto poll = [&]() {
          seen = __ballot_sync(0xffffffffu, ld_relaxed32(flg) == tag);
          asm volatile("fence.proxy.async.global;" ::: "memory");
          *(volatile uint32_t*)&SM_(uint32_t, OFF_SEEN) = seen;
        };
        mbar_wait(BAR(B_STD + 0), 0);
#pragma unroll 1
        for (int s = 0; s < 4; s++) {
          const int kb = kblock(tau, 4 + s);
          uint32_t n = 0;
          while (!((seen >> kb) & 1) && ++n < SPIN_LIMIT) poll();
          if (s == 3) mbar_wait(BAR(B_STD + 1), 0);
          mbar_wait(BAR(B_FULL + s), 0);
          PT(16 + s);
          if (elect_one()) tma_load_2d(sb + (s < 2 ? OFF_XCH + s * 16384 : s * ST_BYTES), &p.tmAbL, BAR(B_FULL + s), kb * 64, abrow);
        }
        uint32_t n = 0;
        while (seen != 0xFFFFFFFFu && ++n < SPIN_LIMIT) { poll(); __nanosleep(100); }
        mbar_wait(BAR(B_OUT), 0);
        if (lane == 0) {
          tma_store_5d(&p.tmOut, sb + OFF_OUT, eps * 128, tau * 8 + m * 4);
          tma_store_5d(&p.tmOut, sb + OFF_OUT + 16384, eps * 128 + 64, tau * 8 + m * 4);
          bulk_commit();
          bulk_wait_all();
          st_relaxed32(&p.s->done[cid * 2], tag);
        }
        PT(22);
      } else if (a == 1) {
#pragma unroll 1
        for (int c = 0; c < 4; c++) {
          uint32_t* flag = reinterpret_cast<uint32_t*>(&p.s->abflag[((eps * 2 + m) * 8 + tau) * 2]) + c;
          mbar_wait(BAR(B_EPI + c), 0);
          if (c == 1) mbar_wait(BAR(B_LATE), 0);
          PT(8 + c);
          if (c >= 2) {
            bf16* dst = p.s->abT + (size_t)(abrow + (lane >> 3)) * 2048 + tau * 256 + c * 64;
#pragma unroll 4
            for (int i = 0; i < 32; i++) {
              const int row = 4 * i + (lane >> 3);
              const uint4 v = lds128_v(sb + chunk_off(c, 0) + i * 512 + lane * 16);
              asm volatile("st.global.v4.b32 [%0], {%1, %2, %3, %4};" :: "l"(dst + i * 4 * 2048 + (((lane & 7) ^ (row & 7)) << 3)), "r"(v.x), "r"(v.y), "r"(v.z), "r"(v.w));
            }
            __syncwarp();
            if (lane == 0) mbar_arrive(BAR(B_STD + c));
            if (c == 3) {
              asm volatile("fence.acq_rel.gpu;" ::: "memory");
              if (lane < 2) st_relaxed32(flag - lane, tag);
            }
            PT(12 + c);
            continue;
          }
          if (lane == 0) tma_store_2d(&p.tmAbS, sb + chunk_off(c, 0), tau * 256 + c * 64, abrow);
          mbar_wait(BAR(B_EPI0B), 0);
          if (lane == 0) {
            tma_store_2d(&p.tmAbS, sb + chunk_off(c, 1), tau * 256 + c * 64, abrow + 64);
            bulk_commit();
            bulk_wait_all();
            st_relaxed32(flag, tag);
            mbar_arrive(BAR(B_STD + c));
          }
          PT(12 + c);
        }
      } else {
        long long tn = clock64();
#pragma unroll 1
        for (int r = 0; r < 48; r++) {
          if (r == PF_R0) tn = t_aux + PF_START2_CLK;
          if (r == PF_R1) tn = t_aux + PF_START3_CLK;
          while (clock64() < tn) __nanosleep(50);
          tn += r < PF_R0 ? PF_STEP_CLK : PF_STEP2_CLK;
          prefetch(r);
        }
        PT(23);
      }
    }
    asm volatile("barrier.cluster.wait.aligned;" ::: "memory");
  } else {
    reg_inc<REG_C>();
    const int w = warp >> 2, wi = warp & 3, t = tid & 127;
    const int g = lane >> 2, q = lane & 3;
    const int turn_me = NB_TURN0 + w, turn_other = NB_TURN1 - w;
    float acc[128];
#pragma unroll
    for (int i = 0; i < 128; i++) acc[i] = 0.f;
    if (w == 1) bar_arrive(NB_TURN0, 256);
    auto kstep = [&](int k, bool first, bool a_in_xch = false) {
      const int s = slot_of(k);
      mbar_wait(BAR(B_FULL + s), use_of(k) & 1);
      CT(64 + k);
      bar_sync(turn_me, 256);
      const uint64_t da = make_desc(sb + (a_in_xch ? OFF_XCH + s * 16384 : s * ST_BYTES) + w * 8192), db = make_desc(sb + s * ST_BYTES + A_BYTES);
      wgmma_fence();
      wgmma_n256(acc, da, db, !first);
#pragma unroll
      for (int kk = 1; kk < 4; kk++) wgmma_n256(acc, da + kk * 2, db + kk * 2, 1);
      wgmma_commit();
      bar_arrive(turn_other, 256);
    };
    auto release = [&](int s) { if (t == 0) mbar_arrive(BAR(B_EMPTY + s)); };
    auto kdone = [&](int k) { wgmma_wait0(); release(slot_of(k)); };
    auto wgmma_wait1 = [&]() { asm volatile("wgmma.wait_group.sync.aligned 1;" ::: "memory"); };

#pragma unroll 1
    for (int k = 0; k < 14; k++) {
      kstep(k, k == 0);
      if (k == 0) CT(0);
      if (k == 8 && warp == 2 && lane < 2) pkt_st128(&p.s->abflag[((eps * 2 + m) * 8 + tau) * 2 + lane], 0, 0, 0, 0);
      kdone(k);
    }
    uint32_t R[64];
    uint32_t tag;
    {
      const uint32_t rsa = sb + OFF_RS + q * 144;
      const uint64_t da2 = make_desc(sb + 2 * ST_BYTES + w * 8192), db2 = make_desc(sb + 2 * ST_BYTES + A_BYTES);
      const uint64_t da3 = make_desc(sb + 3 * ST_BYTES + w * 8192), db3 = make_desc(sb + 3 * ST_BYTES + A_BYTES);
      mbar_wait(BAR(B_FULL + 2), 1);
      CT(64 + 14);
      bar_sync(turn_me, 256);
      wgmma_fence();
#pragma unroll
      for (int kk = 0; kk < 4; kk++) wgmma_n256(acc, da2 + kk * 2, db2 + kk * 2, 1);
      wgmma_commit();
      mbar_wait(BAR(B_FULL + 3), 1);
      CT(64 + 15);
      wgmma_fence();
      wgmma_n256(acc, da3, db3, 1);
      wgmma_n256(acc, da3 + 2, db3 + 2, 1);
      wgmma_commit();
      mbar_wait(BAR(B_STAT), 0);
      tag = SM_(uint32_t, OFF_TAG);
#pragma unroll
      for (int i = 0; i < 8; i++) { const uint4 v = lds128_v(rsa + i * 16); R[8 * i] = v.x; R[8 * i + 2] = v.y; R[8 * i + 4] = v.z; R[8 * i + 6] = v.w; }
      wgmma_wait1();
      release(2);
      wgmma_fence();
      wgmma_n256(acc, da3 + 4, db3 + 4, 1);
      wgmma_n256(acc, da3 + 6, db3 + 6, 1);
      wgmma_n256(acc, make_desc_noswz(sb + OFF_EXA + w * 2048), make_desc_noswz(sb + OFF_EXB), 1);
      wgmma_commit();
      bar_arrive(turn_other, 256);
      kdone(15);
      mbar_wait(BAR(B_STAT), 0);
    }
    fence_acc(acc);
    CT(1);
    auto pack = [&](auto cc) {
      constexpr int c = decltype(cc)::value;
#pragma unroll
      for (int j = 8 * c; j < 8 * c + 8; j++) {
        const uint32_t rs = R[2 * j];
        const float* ac = &acc[4 * j];
        R[2 * j] = bmul2(pack_bf16(ac[0], ac[1]), rs);
        R[2 * j + 1] = bmul2(pack_bf16(ac[2], ac[3]), rs);
      }
    };
    auto put_chunk = [&](auto cc) {
      constexpr int c = decltype(cc)::value;
      const int rho = 16 * wi + (lane & 15);
#pragma unroll
      for (int j = 8 * c; j < 8 * c + 8; j += 2) {
        const int chunk = (j & 7) + (lane >> 4);
        stsm_x4(sb + chunk_off(c, w) + rho * 128 + ((chunk ^ (lane & 7)) << 4), R[2 * j], R[2 * j + 1], R[2 * j + 2], R[2 * j + 3]);
      }
    };
    auto staged = [&](int bar) {
      fence_async_smem();
      __syncwarp();
      if (lane == 0) mbar_arrive(BAR(bar));
    };
    auto mma_rs = [&](auto cc, auto k0, auto k1) {
      constexpr int c = decltype(cc)::value;
      const uint64_t db = make_desc(sb + c * ST_BYTES + A_BYTES);
#pragma unroll
      for (int kk = decltype(k0)::value; kk < decltype(k1)::value; kk++)
        wgmma_n256_rs(acc, R[16 * c + 4 * kk], R[16 * c + 4 * kk + 1], R[16 * c + 4 * kk + 2], R[16 * c + 4 * kk + 3], db + kk * 2, c + kk > 0);
      wgmma_commit();
    };
    auto kdone_x = [&](int k, auto ic) {
      constexpr int i = decltype(ic)::value;
      uint32_t r[8];
#pragma unroll
      for (int z = 0; z < 2; z++) {
        const int tr = 32 * (i & 1) + 16 * z + 8 * (lane >> 4) + (lane & 7), chunk = 2 * wi + ((lane >> 3) & 1);
        ldsm_x4_t(sb + (i >> 1) * ST_BYTES + w * 8192 + tr * 128 + ((chunk ^ (lane & 7)) << 4), r[4 * z], r[4 * z + 1], r[4 * z + 2], r[4 * z + 3]);
      }
      float f[16];
#pragma unroll
      for (int z = 0; z < 8; z++) { f[2 * z] = bf_lo(r[z]); f[2 * z + 1] = bf_hi(r[z]); }
#pragma unroll
      for (int z = 0; z < 16; z++) asm volatile("" : "+f"(f[z]));
      kdone(k);
#pragma unroll
      for (int z = 0; z < 16; z++) asm volatile("add.f32 %0, %0, %1;" : "+f"(acc[16 * i + z]) : "f"(f[z]));
    };
    pack(IC<0>());
    put_chunk(IC<0>());
    staged(w ? B_EPI0B : B_EPI);
    mbar_wait(BAR(B_STAT), 0);
    CT(21);
    pack(IC<1>());
    pack(IC<2>());
    pack(IC<3>());
#pragma unroll
    for (int i = 16; i < 64; i++) asm volatile("" : "+r"(R[i]));
    mbar_wait(BAR(B_FULL + 0), 0);
    CT(2);
    CT(64 + 16);
    bar_sync(turn_me, 256);
    wgmma_fence();
    mma_rs(IC<0>(), IC<0>(), IC<4>());
    mbar_wait(BAR(B_FULL + 1), 0);
    CT(64 + 17);
    wgmma_fence();
    mma_rs(IC<1>(), IC<0>(), IC<2>());
    wgmma_wait1();
    release(0);
    mma_rs(IC<1>(), IC<2>(), IC<4>());
    bar_arrive(turn_other, 256);
    kdone_x(17, IC<0>());
    static_for<2>([&](auto ic) {
      constexpr int c = 2 + decltype(ic)::value;
      mbar_wait(BAR(B_FULL + c), 0);
      CT(64 + 16 + c);
      bar_sync(turn_me, 256);
      wgmma_fence();
      mma_rs(IC<c>(), IC<0>(), IC<4>());
      bar_arrive(turn_other, 256);
      if (c == 2) { put_chunk(IC<1>()); staged(B_EPI + 1); }
      kdone_x(16 + c, IC<c - 1>());
    });
#pragma unroll 1
    for (int k = 20; k < 23; k++) {
      kstep(k, false, k < 22);
      if (k == 20) {
        kdone_x(k, IC<3>());
      } else {
        if (k == 21) put_chunk(IC<2>()); else put_chunk(IC<3>());
        __syncwarp();
        if (lane == 0) mbar_arrive(BAR(B_EPI + k - 19));
        kdone(k);
      }
    }
    uint32_t wf[32][4];
    auto load_wf = [&](auto hc) {
      constexpr int h = decltype(hc)::value;
      const int d = w * 64 + (lane >> 4) * 8 + (lane & 7);
      const uint32_t ad = sb + round_off(h) + (lane & 8) * 1024 + d * 64 + ((wi ^ ((lane >> 1) & 3)) << 4);
#pragma unroll
      for (int i = 0; i < 4; i++) ldsm_x4_t(ad + i * 1024, wf[4 * h + i][0], wf[4 * h + i][1], wf[4 * h + i][2], wf[4 * h + i][3]);
    };
    auto load_wf_rest = [&]() { static_for<8 - NREG_H>([&](auto ic) { load_wf(IC<NREG_H + decltype(ic)::value>()); }); };
#pragma unroll
    for (int i = 0; i < 4 * NREG_H; i++) { wf[i][0] = 0; wf[i][1] = 0; wf[i][2] = 0; wf[i][3] = 0; }
    const int grp = tau * 2 + m;
#pragma unroll 1
    for (int k = 23; k < 46; k++) {
      kstep(k, false);
      if (moe) {
        static_for<NREG_H>([&](auto hc) {
          constexpr int h = decltype(hc)::value;
          if (k == mr_k(h) + 1) { mbar_wait(BAR(B_MR + (h & 1)), (h >> 1) & 1); load_wf(hc); }
        });
      }
      if (k == 43) {
        if (moe) pkt_st128(&p.s->ypart[cid * 256 + tid], 0, 0, 0, 0);
        if (w == 1) pkt_st128(&p.s->hstat[(grp * 8 + eps) * 128 + t], 0, 0, 0, 0);
        if (warp == 0) pkt_st128(&p.s->cand[grp * 256 + eps * 32 + lane], 0, 0, 0, 0);
        if (eps == 0 && (warp == 1 || warp == 2)) pkt_st128(&p.s->key[(lane * 16 + grp) * 2 + warp - 1], 0, 0, 0, 0);
        if (warp == 3 && lane < 2) pkt_st128(&p.s->done[cid * 2 + lane], 0, 0, 0, 0);
      }
      kdone(k);
    }
    asm volatile("barrier.cluster.arrive.relaxed.aligned;" ::: "memory");
    uint32_t wb[16];
    const uint32_t vec_off = (2 * wi) * 512 + q * 128 + ((g ^ (2 * q)) << 4);
    {
      float as[64], ak[64];
      fence_acc(acc);
#pragma unroll
      for (int i = 0; i < 64; i++) asm volatile("mov.b32 %0, %1;" : "=f"(as[i]) : "f"(acc[64 + i]));
#pragma unroll
      for (int i = 0; i < 64; i++) asm volatile("mov.b32 %0, %1;" : "=f"(ak[i]) : "f"(acc[i]));
      const uint64_t da1 = make_desc(sb + 2 * ST_BYTES + w * 8192), db1 = make_desc(sb + 2 * ST_BYTES + A_BYTES);
      const uint64_t da2 = make_desc(sb + 3 * ST_BYTES + w * 8192), db2 = make_desc(sb + 3 * ST_BYTES + A_BYTES);
      mbar_wait(BAR(B_FULL + 2), 1);
      CT(64 + 46);
      mbar_wait(BAR(B_FULL + 3), 1);
      CT(64 + 47);
      bar_sync(turn_me, 256);
      wgmma_fence();
#pragma unroll
      for (int kk = 0; kk < 4; kk++) wgmma_n128(as, da1 + kk * 2, db1 + 1024 + kk * 2);
#pragma unroll
      for (int kk = 0; kk < 4; kk++) wgmma_n128(as, da2 + kk * 2, db2 + 1024 + kk * 2);
      wgmma_commit();
      bar_arrive(turn_other, 256);
      const uint32_t rx = mapa(sb + OFF_PEER + w * 4096 + vec_off, 1 - m), rb = mapa(BAR(B_XCH), 1 - m);
      asm volatile("barrier.cluster.wait.aligned;" ::: "memory");
      wgmma_wait0();
      fence_acc64(as);
#pragma unroll
      for (int i = 0; i < 8; i++) {
        const float* ac = &as[16 * (i >> 1) + 2 * (i & 1)];
        st_async_v4(rx + (i >> 1) * 8192 + (i & 1) * 512, rb, pack_bf16(ac[0], ac[1]), pack_bf16(ac[4], ac[5]), pack_bf16(ac[8], ac[9]), pack_bf16(ac[12], ac[13]));
      }
      bar_sync(turn_me, 256);
      wgmma_fence();
#pragma unroll
      for (int kk = 0; kk < 4; kk++) wgmma_n128(ak, da1 + kk * 2, db1 + kk * 2);
      wgmma_commit();
#pragma unroll
      for (int kk = 0; kk < 4; kk++) wgmma_n128(ak, da2 + kk * 2, db2 + kk * 2);
      wgmma_commit();
      if (w == 0) bar_arrive(turn_other, 256);
#pragma unroll
      for (int i = 0; i < 4; i++) {
        const uint4 v = lds128_v(sb + OFF_WR + q * 80 + i * 16);
        wb[4 * i] = (g & 1) ? v.x : 0x3F803F80u; wb[4 * i + 1] = (g & 1) ? v.y : 0x3F803F80u;
        wb[4 * i + 2] = (g & 1) ? v.z : 0x3F803F80u; wb[4 * i + 3] = (g & 1) ? v.w : 0x3F803F80u;
      }
#pragma unroll
      for (int i = 0; i < 16; i++) asm volatile("" : "+r"(wb[i]));
      wgmma_wait1();
      release(2);
      wgmma_wait0();
      fence_acc64(ak);
      CT(3);
#pragma unroll
      for (int i = 0; i < 8; i++) {
        const float* ac = &ak[16 * (i >> 1) + 2 * (i & 1)];
        sts128(sb + (2 + (i >> 2)) * ST_BYTES + w * 8192 + ((i >> 1) & 1) * 4096 + (i & 1) * 512 + vec_off,
               pack_bf16(ac[0], ac[1]), pack_bf16(ac[4], ac[5]), pack_bf16(ac[8], ac[9]), pack_bf16(ac[12], ac[13]));
      }
    }
    uint32_t h[8][4];
    const uint32_t cd = code_of(tag);
    {
      const int qq = 2 * (warp & 1) + ((lane >> 3) & 1);
      const uint32_t lo = (lane >> 4) * 512 + qq * 128 + (((lane & 7) ^ (2 * qq)) << 4);
      bar_sync(NB_BOTH, 256);
#pragma unroll
      for (int ks = 0; ks < 8; ks++)
        ldsm_x4_t(sb + (2 + w) * ST_BYTES + (ks >> 2) * 8192 + (wi >> 1) * 4096 + (ks & 3) * 1024 + lo, h[ks][0], h[ks][1], h[ks][2], h[ks][3]);
      mbar_wait_cluster(BAR(B_XCH), 0);
      CT(4);
      float d1[2][4] = {}, d2[2][4] = {}, d3[2][4] = {};
#pragma unroll
      for (int ks = 0; ks < 8; ks++) {
        uint32_t r0, r1, r2, r3;
        ldsm_x4_t(sb + OFF_PEER + (warp >> 1) * 8192 + ks * 1024 + lo, r0, r1, r2, r3);
        h[ks][0] = badd2(h[ks][0], r0); h[ks][1] = badd2(h[ks][1], r1); h[ks][2] = badd2(h[ks][2], r2); h[ks][3] = badd2(h[ks][3], r3);
        mma16816(d1[ks & 1], h[ks][0], h[ks][1], h[ks][2], h[ks][3], wb[2 * ks], wb[2 * ks + 1]);
        mma16816(d2[ks & 1], h[ks][0], h[ks][1], h[ks][2], h[ks][3], h[ks][0], h[ks][2]);
        mma16816(d3[ks & 1], h[ks][0], h[ks][1], h[ks][2], h[ks][3], h[ks][1], h[ks][3]);
      }
      if (q == (g >> 1)) {
        uint4* hp = &p.s->hstat[(grp * 8 + eps) * 128 + warp * 16 + g];
        const float s0 = (g & 1) ? d2[0][1] + d2[1][1] : d2[0][0] + d2[1][0], s1 = (g & 1) ? d3[0][3] + d3[1][3] : d3[0][2] + d3[1][2];
        pkt_st128(hp, with_bit(d1[0][0] + d1[1][0], cd), with_bit(s0, cd >> 1), __float_as_uint(d1[0][1] + d1[1][1]), tag);
        pkt_st128(hp + 8, with_bit(d1[0][2] + d1[1][2], cd), with_bit(s1, cd >> 1), __float_as_uint(d1[0][3] + d1[1][3]), tag);
      }
    }
    CT(5);
    bool wf_loaded = false;
    if (moe) {
      wf_loaded = __all_sync(0xffffffffu, mbar_test(BAR(B_GU), 0));
      if (wf_loaded) load_wf_rest();
    }
    const uint4* kp = &p.s->key[(((cid * 8 + warp) & KEY_RMASK) * 16 + (lane & 15)) * 2];
    uint4 kq;
    float m_bf, sd, inv_sd, r_bf;
    {
      uint4 u[4];
      const uint4* hp = &p.s->hstat[(grp * 8 + 2 * q) * 128 + warp * 16 + g];
      uint32_t n = 0;
      while (true) {
#pragma unroll
        for (int i = 0; i < 4; i++) u[i] = pkt_ld128(hp + (i & 1) * 128 + (i >> 1) * 8);
        kq = pkt_ld128(kp);
        bool ok = true;
#pragma unroll
        for (int i = 0; i < 4; i++) ok = ok && u[i].w == tag && pair_code(u[i].x, u[i].y) == cd;
        if (__all_sync(0xffffffffu, ok) || ++n > SPIN_LIMIT) break;
        backoff();
      }
      CT(6);
      float a[3], b[3];
      a[0] = __uint_as_float(u[0].x & ~1u) + __uint_as_float(u[1].x & ~1u); b[0] = __uint_as_float(u[2].x & ~1u) + __uint_as_float(u[3].x & ~1u);
      a[1] = __uint_as_float(u[0].y & ~1u) + __uint_as_float(u[1].y & ~1u); b[1] = __uint_as_float(u[2].y & ~1u) + __uint_as_float(u[3].y & ~1u);
      a[2] = __uint_as_float(u[0].z) + __uint_as_float(u[1].z); b[2] = __uint_as_float(u[2].z) + __uint_as_float(u[3].z);
#pragma unroll
      for (int i = 0; i < 3; i++) {
        a[i] = ((q & 2) ? b[i] : a[i]) + __shfl_xor_sync(0xffffffffu, (q & 2) ? a[i] : b[i], 2);
        a[i] += __shfl_xor_sync(0xffffffffu, a[i], 1);
      }
      const float mu = a[0] * (1.f / 1024.f);
      m_bf = bf16r(mu);
      sd = ln_sd(a[1] * (1.f / 1024.f) - mu * mu);
      inv_sd = rcp_fast(sd);
      r_bf = bf16r((a[2] - m_bf * SM_(float, OFF_WSUM)) * inv_sd);
    }
    int gspec;
    uint4 cv;
    {
      const int trow = grp * 128 + 32 * (warp >> 1) + 8 * (g >> 1) + 4 * (warp & 1) + (q & 2) + (g & 1);
      const uint32_t u = __float_as_uint(r_bf);
      const uint32_t ord = (u & 0x80000000u) ? ~u : (u | 0x80000000u);
      const uint32_t key = (ord & 0xFFFF0000u) | (0xFFFFu - (uint32_t)trow);
      const uint32_t wk = __reduce_max_sync(0xffffffffu, key);
      if (lane == 0) SM_(uint32_t, OFF_WKEY + warp * 4) = wk;
      bar_sync(NB_BOTH, 256);
      const uint4 k0 = SM_(uint4, OFF_WKEY), k1 = SM_(uint4, OFF_WKEY + 16);
      const uint32_t bk = max(max(max(k0.x, k0.y), max(k0.z, k0.w)), max(max(k1.x, k1.y), max(k1.z, k1.w)));
      if (wk == bk) {
        const int src = __ffs(__ballot_sync(0xffffffffu, key == bk)) - 1;
        const uint32_t ms = __shfl_sync(0xffffffffu, (__float_as_uint(m_bf) >> 16) | __float_as_uint(sd), src);
        if (eps == 0) pkt_st128(&p.s->key[(lane * 16 + grp) * 2], bk, tag, ms, tag);
        if (g == (src >> 2)) {
#pragma unroll
          for (int ks = 0; ks < 8; ks++)
            pkt_st128(&p.s->cand[grp * 256 + (eps * 8 + ks) * 4 + q], (src & 2) ? h[ks][1] : h[ks][0], tag, (src & 2) ? h[ks][3] : h[ks][2], tag);
        }
      }
      CT(7);
      const uint32_t kv = max(bk, __reduce_max_sync(0xffffffffu, (kq.y == tag) ? kq.x : 0u));
      gspec = (0xFFFF - (int)(kv & 0xFFFFu)) >> 7;
    }
    {
      const uint32_t nm = pack_bf16(-m_bf, -m_bf);
      const uint32_t nm_o = __shfl_xor_sync(0xffffffffu, nm, 2);
      const float is_o = __shfl_xor_sync(0xffffffffu, inv_sd, 2);
      const uint32_t nm0 = (q & 2) ? nm_o : nm, nm1 = (q & 2) ? nm : nm_o;
      const float is0 = (q & 2) ? is_o : inv_sd, is1 = (q & 2) ? inv_sd : is_o;
      const uint32_t oa = sb + OFF_OUT + (warp * 16 + (lane & 15)) * 128;
#pragma unroll
      for (int ks = 0; ks < 8; ks++) {
        if (ks == 4) { kq = pkt_ld128(kp); cv = pkt_ld128(&p.s->cand[gspec * 256 + tid]); }
        stsm_x4(oa + (ks >> 2) * 16384 + (((2 * (ks & 3) + (lane >> 4)) ^ (lane & 7)) << 4),
                badd2(h[ks][0], norm2(h[ks][0], nm0, is0)), badd2(h[ks][1], norm2(h[ks][1], nm1, is1)),
                badd2(h[ks][2], norm2(h[ks][2], nm0, is0)), badd2(h[ks][3], norm2(h[ks][3], nm1, is1)));
      }
      staged(B_OUT);
    }
    CT(8);
    uint32_t df[16][4];
    auto load_df = [&]() {
      const int frow = (lane & 7) + ((lane >> 4) << 3), hi = (lane >> 3) & 1;
      const uint32_t base = sb + down_off(warp >> 1) + (warp & 1) * 8192 + frow * 128;
#pragma unroll
      for (int mt = 0; mt < 8; mt++) {
#pragma unroll
        for (int ks = 0; ks < 2; ks++)
          ldsm_x4_t(base + (mt >> 2) * 4096 + ks * 2048 + (((2 * (mt & 3) + hi) ^ (lane & 7)) << 4),
                    df[2 * mt + ks][0], df[2 * mt + ks][1], df[2 * mt + ks][2], df[2 * mt + ks][3]);
      }
    };
    bool df_loaded = false;
    if (moe) {
      if (!wf_loaded) {
        mbar_wait(BAR(B_GU), 0);
        load_wf_rest();
      }
      df_loaded = __all_sync(0xffffffffu, mbar_test(BAR(B_DN), 0));
      if (df_loaded) load_df();
    }
    int tsel; float sig;
    {
      uint32_t n = 0, kv;
      while (true) {
        const bool ok = kq.y == tag && kq.w == tag;
        kv = __reduce_max_sync(0xffffffffu, ok ? kq.x : 0u);
        const int gs = (0xFFFF - (int)(kv & 0xFFFFu)) >> 7;
        if (__all_sync(0xffffffffu, ok && gs == gspec && cv.y == tag && cv.w == tag) || ++n > SPIN_LIMIT) break;
        if (!__all_sync(0xffffffffu, ok)) { backoff(); kq = pkt_ld128(kp); }
        if (kv) gspec = gs;
        cv = pkt_ld128(&p.s->cand[gspec * 256 + tid]);
      }
      CT(9);
      tsel = 0xFFFF - (int)(kv & 0xFFFFu);
      const uint32_t ms = __shfl_sync(0xffffffffu, kq.z, gspec);
      const uint32_t nm = ((ms & 0xFFFFu) ^ 0x8000u) * 0x10001u;
      const float is = rcp_fast(bf_hi(ms));
      SM_(uint2, OFF_XSEL + q * 528 + (tid >> 2) * 8) = make_uint2(norm2(cv.x, nm, is), norm2(cv.z, nm, is));
      SM_(uint2, OFF_HSEL + q * 528 + (tid >> 2) * 8) = make_uint2(cv.x, cv.z);
      const uint32_t ord = kv & 0xFFFF0000u;
      const float r_sel = __uint_as_float((ord & 0x80000000u) ? (ord & 0x7FFFFFFFu) : (~ord & 0xFFFF0000u));
      sig = bf16r(__fdividef(1.f, 1.f + __expf(-r_sel)));
    }
    bar_sync(NB_BOTH, 256);
    if (moe) {
      float gd[4][4] = {};
#pragma unroll
      for (int r = 0; r < 4; r++) {
        uint4 bx[4];
#pragma unroll
        for (int i = 0; i < 4; i++) bx[i] = lds128_v(sb + OFF_XSEL + q * 528 + r * 128 + (i >> 1) * 64 + w * 32 + (i & 1) * 16);
#pragma unroll
        for (int i = 0; i < 8; i++)
          mma16816(gd[i & 3], wf[8 * r + i][0], wf[8 * r + i][1], wf[8 * r + i][2], wf[8 * r + i][3], (i & 1) ? bx[i >> 1].z : bx[i >> 1].x, (i & 1) ? bx[i >> 1].w : bx[i >> 1].y);
      }
      if (q == 0) SM_(float2, OFF_GP + (w * 32 + wi * 8 + g) * 8) = make_float2((gd[0][0] + gd[1][0]) + (gd[2][0] + gd[3][0]), (gd[0][2] + gd[1][2]) + (gd[2][2] + gd[3][2]));
      CT(10);
      if (!df_loaded) { mbar_wait(BAR(B_DN), 0); load_df(); }
      bar_sync(NB_BOTH, 256);
      uint32_t bq[4];
      {
        const float2 p0 = SM_(float2, OFF_GP + lane * 8), p1 = SM_(float2, OFF_GP + 256 + lane * 8);
        const float gt = bf16r(p0.x + p1.x), up = bf16r(p0.y + p1.y);
        const float act = bf16r(__fdividef(gt, 1.f + __expf(-gt))) * up;
        const uint32_t pr = pack_bf16(act, __shfl_down_sync(0xffffffffu, act, 1));
#pragma unroll
        for (int i = 0; i < 4; i++) bq[i] = __shfl_sync(0xffffffffu, pr, 8 * i + 2 * q);
      }
      CT(11);
      float yd[8][4] = {};
#pragma unroll
      for (int ks = 0; ks < 2; ks++) {
#pragma unroll
        for (int mt = 0; mt < 8; mt++) mma16816(yd[mt], df[2 * mt + ks][0], df[2 * mt + ks][1], df[2 * mt + ks][2], df[2 * mt + ks][3], bq[2 * ks], bq[2 * ks + 1]);
      }
      const float y0 = q == 0 ? yd[0][0] : q == 1 ? yd[2][0] : q == 2 ? yd[4][0] : yd[6][0];
      const float y1 = q == 0 ? yd[0][2] : q == 1 ? yd[2][2] : q == 2 ? yd[4][2] : yd[6][2];
      const float y2 = q == 0 ? yd[1][0] : q == 1 ? yd[3][0] : q == 2 ? yd[5][0] : yd[7][0];
      const float y3 = q == 0 ? yd[1][2] : q == 1 ? yd[3][2] : q == 2 ? yd[5][2] : yd[7][2];
      pkt_st128(&p.s->ypart[cid * 256 + tid], with_bit(y0, cd), with_bit(y1, cd >> 1), with_bit(y2, cd), with_bit(y3, cd >> 1));
    } else {
      const long long tw = clock64();
      while (clock64() - tw < IDLE_WAIT_CLK) __nanosleep(100);
    }
    CT(12);
    const int pfin = 2 * cid + (tid & 1);
    const int col_fin = (pfin >> 5) * 128 + (pfin & 3) * 32 + ((pfin & 31) >> 2) + 8 * ((tid >> 1) & 3);
    const int sel_off = ((col_fin & 7) >> 1) * 528 + (col_fin >> 3) * 4 + (col_fin & 1) * 2;
    const float hn_fin = __uint_as_float((uint32_t)SM_(uint16_t, OFF_XSEL + sel_off) << 16), h_fin = __uint_as_float((uint32_t)SM_(uint16_t, OFF_HSEL + sel_off) << 16);
    {
      const uint4* src = warp < 7 ? &p.s->ypart[(16 + (tid >> 1)) * 256 + pfin]
                                  : &p.s->done[((tsel >> 8) * 16 + (cid >> 4) * 2 + ((tsel >> 7) & 1)) * 2];
      uint4 v = pkt_ld128(src); uint32_t n = 0;
      while (true) {
        const bool ok = warp < 7 ? (pair_code(v.x, v.y) == cd && pair_code(v.z, v.w) == cd) : v.x == tag;
        if (__all_sync(0xffffffffu, ok) || ++n > SPIN_LIMIT) break;
        backoff();
        v = pkt_ld128(src);
      }
      CT(13);
      const float y0 = __uint_as_float(v.x & ~1u), y1 = __uint_as_float(v.y & ~1u), y2 = __uint_as_float(v.z & ~1u), y3 = __uint_as_float(v.w & ~1u);
      const float a0 = ((lane & 2) ? y1 : y0) + __shfl_xor_sync(0xffffffffu, (lane & 2) ? y0 : y1, 2);
      const float a1 = ((lane & 2) ? y3 : y2) + __shfl_xor_sync(0xffffffffu, (lane & 2) ? y2 : y3, 2);
      float b = ((lane & 4) ? a1 : a0) + __shfl_xor_sync(0xffffffffu, (lane & 4) ? a0 : a1, 4);
      b += __shfl_xor_sync(0xffffffffu, b, 8);
      b += __shfl_xor_sync(0xffffffffu, b, 16);
      if (lane < 8) SM_(float, OFF_FIN + warp * 32 + lane * 4) = b;
    }
    bar_sync(NB_BOTH, 256);
    if (tid < 8) {
      float y = 0.f;
#pragma unroll
      for (int i = 0; i < 7; i++) y += SM_(float, OFF_FIN + i * 32 + tid * 4);
      p.out[(size_t)tsel * 1024 + col_fin] = __float2bfloat16_rn(h_fin + bf16r(hn_fin + bf16r(bf16r(y) * sig)));
      if (cid == 0 && tid == 0) st_relaxed32(&p.s->epoch, tag);
    }
    CT(14);
  }
}

__global__ void __launch_bounds__(384, 1) occupancy_probe_kernel() {}

typedef CUresult (*EncodeFn)(CUtensorMap*, CUtensorMapDataType, cuuint32_t, void*, const cuuint64_t*, const cuuint64_t*, const cuuint32_t*, const cuuint32_t*,
                             CUtensorMapInterleave, CUtensorMapSwizzle, CUtensorMapL2promotion, CUtensorMapFloatOOBfill);

static void make_tm(EncodeFn enc, CUtensorMap* tm, const void* ptr, uint64_t rows, uint64_t cols, uint32_t brows, uint32_t bcols, CUtensorMapSwizzle sw,
                    CUtensorMapL2promotion promo = CU_TENSOR_MAP_L2_PROMOTION_L2_256B) {
  cuuint64_t dims[2] = {cols, rows};
  cuuint64_t strides[1] = {cols * 2};
  cuuint32_t box[2] = {bcols, brows};
  cuuint32_t es[2] = {1, 1};
  enc(tm, CU_TENSOR_MAP_DATA_TYPE_BFLOAT16, 2, const_cast<void*>(ptr), dims, strides, box, es, CU_TENSOR_MAP_INTERLEAVE_NONE, sw,
      promo, CU_TENSOR_MAP_FLOAT_OOB_FILL_NONE);
}

extern "C" void kernel_launch(void* const* d_in, const int* in_sizes, int n_in, void* d_out, int out_size) {
  (void)in_sizes; (void)n_in; (void)out_size;
  static EncodeFn enc = nullptr;
  static void* abT = nullptr;
  static int map = 0;
  if (!enc) {
    void* fn = nullptr; cudaDriverEntryPointQueryResult st;
    cudaGetDriverEntryPoint("cuTensorMapEncodeTiled", &fn, cudaEnableDefault, &st);
    enc = (EncodeFn)fn;
    cudaGetSymbolAddress(&abT, g_scratch);
    cudaFuncSetAttribute(fnet_moe_kernel<0>, cudaFuncAttributeMaxDynamicSharedMemorySize, SMEM_TOTAL);
    cudaFuncSetAttribute(fnet_moe_kernel<1>, cudaFuncAttributeMaxDynamicSharedMemorySize, SMEM_TOTAL);
    cudaFuncSetAttribute(occupancy_probe_kernel, cudaFuncAttributeMaxDynamicSharedMemorySize, SMEM_TOTAL);
    cudaFuncSetAttribute(occupancy_probe_kernel, cudaFuncAttributeNonPortableClusterSizeAllowed, 1);
    auto max_clusters = [&](int size) {
      cudaLaunchConfig_t cfg = {};
      cfg.gridDim = dim3(128); cfg.blockDim = dim3(384); cfg.dynamicSmemBytes = SMEM_TOTAL;
      cudaLaunchAttribute at[1];
      at[0].id = cudaLaunchAttributeClusterDimension; at[0].val.clusterDim.x = size; at[0].val.clusterDim.y = 1; at[0].val.clusterDim.z = 1;
      cfg.attrs = at; cfg.numAttrs = 1;
      int ncl = 0;
      return cudaOccupancyMaxActiveClusters(&ncl, occupancy_probe_kernel, &cfg) == cudaSuccess ? ncl : 0;
    };
    int dev = 0, sms = 0;
    cudaGetDevice(&dev);
    cudaDeviceGetAttribute(&sms, cudaDevAttrMultiProcessorCount, dev);
    map = (!getenv("MAP1") && sms == 132 && max_clusters(2) == 66 && max_clusters(16) == 7) ? 0 : 1;
    (void)cudaGetLastError();
  }
  Params p;
  const bf16* x = (const bf16*)d_in[0];
  make_tm(enc, &p.tmD0, d_in[3], 1024, 1024, 128, 64, CU_TENSOR_MAP_SWIZZLE_128B);
  make_tm(enc, &p.tmD1, d_in[4], 1024, 1024, 128, 64, CU_TENSOR_MAP_SWIZZLE_128B);
  make_tm(enc, &p.tmX, x, 2048, 1024, 256, 64, CU_TENSOR_MAP_SWIZZLE_128B);
  make_tm(enc, &p.tmXr, x, 2048, 1024, 64, 64, CU_TENSOR_MAP_SWIZZLE_128B);
  make_tm(enc, &p.tmAbS, abT, 2048, 2048, 64, 64, CU_TENSOR_MAP_SWIZZLE_128B);
  make_tm(enc, &p.tmAbL, abT, 2048, 2048, 128, 64, CU_TENSOR_MAP_SWIZZLE_128B);
  make_tm(enc, &p.tmW0, d_in[1], 2048, 2048, 128, 64, CU_TENSOR_MAP_SWIZZLE_128B, W_PROMO);
  make_tm(enc, &p.tmW1, d_in[2], 2048, 2048, 128, 64, CU_TENSOR_MAP_SWIZZLE_128B, W_PROMO);
  {
    cuuint64_t dims[5] = {1024, 2, 4, 4, 64};
    cuuint64_t strides[4] = {2048, 8 * 2048, 2 * 2048, 32 * 2048};
    cuuint32_t box[5] = {64, 2, 4, 4, 4};
    cuuint32_t es[5] = {1, 1, 1, 1, 1};
    enc(&p.tmOut, CU_TENSOR_MAP_DATA_TYPE_BFLOAT16, 5, d_out, dims, strides, box, es, CU_TENSOR_MAP_INTERLEAVE_NONE, CU_TENSOR_MAP_SWIZZLE_128B,
        CU_TENSOR_MAP_L2_PROMOTION_NONE, CU_TENSOR_MAP_FLOAT_OOB_FILL_NONE);
  }
  make_tm(enc, &p.tmG, d_in[7], 1024, 3584, 128, 32, CU_TENSOR_MAP_SWIZZLE_64B, CU_TENSOR_MAP_L2_PROMOTION_L2_128B);
  make_tm(enc, &p.tmU, d_in[8], 1024, 3584, 128, 32, CU_TENSOR_MAP_SWIZZLE_64B, CU_TENSOR_MAP_L2_PROMOTION_L2_128B);
  make_tm(enc, &p.tmDn, d_in[9], 3584, 1024, 32, 64, CU_TENSOR_MAP_SWIZZLE_128B);
  p.x = x; p.Dre = (const bf16*)d_in[3]; p.Dim = (const bf16*)d_in[4];
  p.wr = (const bf16*)d_in[6]; p.wdown = (const bf16*)d_in[9]; p.wgate = (const bf16*)d_in[7]; p.wup = (const bf16*)d_in[8];
  p.out = (bf16*)d_out; p.s = (Scratch*)abT;
  if (map == 1) fnet_moe_kernel<1><<<128, 384, SMEM_TOTAL>>>(p);
  else fnet_moe_kernel<0><<<132, 384, SMEM_TOTAL>>>(p);
}
```

```cpp
#include <cuda.h>
#include <cuda_runtime.h>
#include <cuda_bf16.h>
#include <stdint.h>
#include <stdlib.h>
#include <type_traits>

typedef __nv_bfloat16 bf16;

#define REG_C 232
#define REG_P 40
__device__ __forceinline__ int kblock(int tau, int j) {
  const int i = j - 4, c = (i * 37) >> 8;
  return j < 4 ? tau * 4 + j : ((tau + 1 + i - 7 * c) & 7) * 4 + c;
}
#define HOP1_DELAY 150
#define HOP3_DELAY 300
#define BACKOFF_NS 0
#define SPEC_MIN 10
#define PF_K0 10
#define PF_N0 4
#define PF_K1 26
#define OUT_PACE_CLK 100
#define PUB_K1 22
#define NREG_H 5
#define MR_K0 28
__host__ __device__ constexpr int mr_k(int h) { return MR_K0 + 6 * (h >> 1) + 2 * (h & 1); }
constexpr int A_BYTES = 128 * 64 * 2;
constexpr int B_BYTES = 256 * 64 * 2;
constexpr int ST_BYTES = A_BYTES + B_BYTES;
constexpr int OFF_XCH = 4 * ST_BYTES;
constexpr int OFF_BAR = OFF_XCH + 32768;
constexpr int OFF_WR = OFF_BAR + 384;
constexpr int OFF_RS = OFF_WR + 384;
constexpr int OFF_PUB = OFF_RS + 640;
constexpr int OFF_MISC = OFF_PUB + 768;
constexpr int SMEM_TOTAL = OFF_MISC + 256;
constexpr int OFF_WSUM = OFF_MISC, OFF_TAG = OFF_MISC + 4;
constexpr int OFF_SEEN = OFF_MISC + 8;
constexpr int OFF_KV = OFF_MISC + 12;
constexpr int OFF_WKEY = OFF_MISC + 32;
constexpr int OFF_EXA = OFF_XCH;
constexpr int OFF_EXB = OFF_XCH + 4096;
__host__ __device__ constexpr int chunk_off(int c, int w) { return (c < 2 ? (c + 2) * ST_BYTES : OFF_XCH + (c - 2) * 16384) + w * 8192; }
__host__ __device__ constexpr int late_off(int i) { return i < 4 ? i * 16384 : 2 * ST_BYTES + A_BYTES + (i - 4) * 16384; }
__host__ __device__ constexpr int round_off(int h) { return h < NREG_H + 2 ? OFF_XCH + (h & 1) * 16384 : late_off(h - NREG_H - 2); }
__host__ __device__ constexpr int down_off(int i) { return late_off(6 - NREG_H + i); }
constexpr int OFF_PEER = ST_BYTES + A_BYTES;
constexpr int OFF_OUT = 3 * ST_BYTES + A_BYTES;
constexpr int OFF_XSEL = OFF_PEER;
constexpr int OFF_HSEL = OFF_PEER + 4096;
constexpr int OFF_GP = OFF_PEER + 8192;
constexpr int OFF_FIN = OFF_PEER + 9216;
__device__ __forceinline__ int slot_of(int k) { return k & 3; }
__device__ __forceinline__ int use_of(int k) { return k >> 2; }
enum { B_FULL = 0, B_EMPTY = 4, B_EPI = 8, B_STD = 12, B_EPI0B = 16, B_LATE = 17, B_STAT = 18, B_XCH = 19, B_MR = 20  , B_GU = 22,
       B_DN = 23, B_AUX = 24  , B_OUT = 26, B_KEY = 27, B_XS = 28, B_A20 = 29, B_STDA = 30, B_COUNT = 31 };
enum { NB_TURN0 = 1, NB_TURN1 = 2, NB_BOTH = 5, NB_AUX = 6 };

struct Scratch {
  bf16 abT[2048 * 2048];
  uint2 xstat[2048];
  uint2 dsum[2048];
  uint4 abflag[16 * 8 * 2];
  uint4 hstat[16 * 8 * 128];
  uint4 cand[16 * 256];
  uint4 key[8 * 16 * 2];
  uint4 ypart[128 * 256];
  uint32_t epoch;
};
__device__ __align__(1024) Scratch g_scratch;

struct Params {
  Scratch* s; bf16* out;
  const bf16* x; const bf16* Dre; const bf16* Dim; const bf16* wr; const bf16* wdown; const bf16* wgate; const bf16* wup;
  CUtensorMap tmX, tmD0, tmD1, tmXr, tmAbS, tmAbL, tmW0, tmW1, tmOut, tmG, tmU, tmDn;
};

#define SPIN_LIMIT (1u << 14)
#define MBAR_LIMIT (1u << 10)
constexpr int PROLOGUE_CLK = 1800;
#define GATHER_NS 400
#define PF_R1 99
#define PF_START3_CLK 43000
#define W_PROMO CU_TENSOR_MAP_L2_PROMOTION_L2_128B
#define PF_R0 16
#define PF_STEP_CLK 300
#define PF_START2_CLK 26000
#define PF_STEP2_CLK 600
#define MOE_PACE_CLK 300
constexpr int IDLE_WAIT_CLK = 1200;
__device__ __forceinline__ uint32_t smem_u32(const void* p) { return (uint32_t)__cvta_generic_to_shared(p); }
__device__ __forceinline__ void mbar_init(uint32_t bar, uint32_t cnt) { asm volatile("mbarrier.init.shared::cta.b64 [%0], %1;" :: "r"(bar), "r"(cnt) : "memory"); }
__device__ __forceinline__ void mbar_expect_tx(uint32_t bar, uint32_t bytes) { asm volatile("mbarrier.arrive.expect_tx.shared::cta.b64 _, [%0], %1;" :: "r"(bar), "r"(bytes) : "memory"); }
__device__ __forceinline__ void mbar_arrive(uint32_t bar) { asm volatile("mbarrier.arrive.shared::cta.b64 _, [%0];" :: "r"(bar) : "memory"); }
__device__ __forceinline__ void mbar_wait(uint32_t bar, uint32_t parity) {
  uint32_t ok, n = 0;
  do {
    asm volatile("{\n.reg .pred p;\nmbarrier.try_wait.parity.shared::cta.b64 p, [%1], %2;\nselp.u32 %0, 1, 0, p;\n}\n" : "=r"(ok) : "r"(bar), "r"(parity) : "memory");
  } while (!ok && ++n < MBAR_LIMIT);
}
__device__ __forceinline__ bool mbar_test(uint32_t bar, uint32_t parity) {
  uint32_t ok;
  asm volatile("{\n.reg .pred p;\nmbarrier.test_wait.parity.shared::cta.b64 p, [%1], %2;\nselp.u32 %0, 1, 0, p;\n}\n" : "=r"(ok) : "r"(bar), "r"(parity) : "memory");
  return ok != 0;
}
__device__ __forceinline__ void mbar_wait_cluster(uint32_t bar, uint32_t parity) {
  uint32_t ok, n = 0;
  do {
    asm volatile("{\n.reg .pred p;\nmbarrier.try_wait.parity.acquire.cluster.shared::cta.b64 p, [%1], %2;\nselp.u32 %0, 1, 0, p;\n}\n" : "=r"(ok) : "r"(bar), "r"(parity) : "memory");
  } while (!ok && ++n < MBAR_LIMIT);
}
__device__ __forceinline__ void tma_load_2d(uint32_t dst, const CUtensorMap* tm, uint32_t bar, int c0, int c1) {
  asm volatile("cp.async.bulk.tensor.2d.shared::cluster.global.mbarrier::complete_tx::bytes [%0], [%1, {%3, %4}], [%2];"
    :: "r"(dst), "l"(tm), "r"(bar), "r"(c0), "r"(c1) : "memory");
}
__device__ __forceinline__ void tma_load_2d_hint(uint32_t dst, const CUtensorMap* tm, uint32_t bar, int c0, int c1, uint64_t pol) {
  asm volatile("cp.async.bulk.tensor.2d.shared::cluster.global.mbarrier::complete_tx::bytes.L2::cache_hint [%0], [%1, {%3, %4}], [%2], %5;"
    :: "r"(dst), "l"(tm), "r"(bar), "r"(c0), "r"(c1), "l"(pol) : "memory");
}
__device__ __forceinline__ uint64_t policy_evict_first() { uint64_t p; asm volatile("createpolicy.fractional.L2::evict_first.b64 %0, 1.0;" : "=l"(p)); return p; }
__device__ __forceinline__ void tma_store_2d(const CUtensorMap* tm, uint32_t src, int c0, int c1) {
  asm volatile("cp.async.bulk.tensor.2d.global.shared::cta.bulk_group [%0, {%2, %3}], [%1];" :: "l"(tm), "r"(src), "r"(c0), "r"(c1) : "memory");
}
__device__ __forceinline__ void bulk_load(uint32_t dst, const void* src, uint32_t bytes, uint32_t bar) {
  asm volatile("cp.async.bulk.shared::cluster.global.mbarrier::complete_tx::bytes [%0], [%1], %2, [%3];" :: "r"(dst), "l"(src), "r"(bytes), "r"(bar) : "memory");
}
__device__ __forceinline__ void bulk_commit() { asm volatile("cp.async.bulk.commit_group;" ::: "memory"); }
__device__ __forceinline__ void bulk_wait_all() { asm volatile("cp.async.bulk.wait_group 0;" ::: "memory"); }
__device__ __forceinline__ void fence_async_smem() { asm volatile("fence.proxy.async.shared::cta;" ::: "memory"); }
__device__ __forceinline__ void wgmma_fence() { asm volatile("wgmma.fence.sync.aligned;" ::: "memory"); }
__device__ __forceinline__ void wgmma_commit() { asm volatile("wgmma.commit_group.sync.aligned;" ::: "memory"); }
__device__ __forceinline__ void wgmma_wait0() { asm volatile("wgmma.wait_group.sync.aligned 0;" ::: "memory"); }
__device__ __forceinline__ void bar_sync(int id, int n) { asm volatile("bar.sync %0, %1;" :: "r"(id), "r"(n) : "memory"); }
__device__ __forceinline__ void bar_arrive(int id, int n) { asm volatile("bar.arrive %0, %1;" :: "r"(id), "r"(n) : "memory"); }
template<int R> __device__ __forceinline__ void reg_inc() { asm volatile("setmaxnreg.inc.sync.aligned.u32 %0;" :: "n"(R)); }
template<int R> __device__ __forceinline__ void reg_dec() { asm volatile("setmaxnreg.dec.sync.aligned.u32 %0;" :: "n"(R)); }
__device__ __forceinline__ bool elect_one() {
  uint32_t p;
  asm volatile("{\n.reg .pred q;\nelect.sync _|q, 0xffffffff;\nselp.u32 %0, 1, 0, q;\n}\n" : "=r"(p));
  return p != 0;
}
__device__ __forceinline__ uint32_t mapa(uint32_t addr, uint32_t cta) { uint32_t r; asm volatile("mapa.shared::cluster.u32 %0, %1, %2;" : "=r"(r) : "r"(addr), "r"(cta)); return r; }
__device__ __forceinline__ void st_async_v4(uint32_t addr, uint32_t bar, uint32_t a, uint32_t b, uint32_t c, uint32_t d) {
  asm volatile("st.async.weak.shared::cluster.mbarrier::complete_tx::bytes.v4.b32 [%0], {%2, %3, %4, %5}, [%1];" :: "r"(addr), "r"(bar), "r"(a), "r"(b), "r"(c), "r"(d) : "memory");
}
__device__ __forceinline__ void stsm_x4(uint32_t addr, uint32_t a, uint32_t b, uint32_t c, uint32_t d) {
  asm volatile("stmatrix.sync.aligned.m8n8.x4.shared.b16 [%0], {%1, %2, %3, %4};" :: "r"(addr), "r"(a), "r"(b), "r"(c), "r"(d));
}
__device__ __forceinline__ uint4 lds128_v(uint32_t addr) { uint4 v; asm volatile("ld.shared.v4.b32 {%0, %1, %2, %3}, [%4];" : "=r"(v.x), "=r"(v.y), "=r"(v.z), "=r"(v.w) : "r"(addr)); return v; }
extern __shared__ __align__(1024) uint8_t smem_raw[];
template<class T> __device__ __forceinline__ T& smem_at(uint32_t addr) { return *reinterpret_cast<T*>(__cvta_shared_to_generic(addr)); }
#define SM_(T, off) smem_at<T>(sb + (off))
__device__ __forceinline__ uint4 ldg_nc128(const void* p) { uint4 v; asm volatile("ld.global.nc.v4.b32 {%0, %1, %2, %3}, [%4];" : "=r"(v.x), "=r"(v.y), "=r"(v.z), "=r"(v.w) : "l"(p)); return v; }
__device__ __forceinline__ void pkt_st128(void* p, uint32_t a, uint32_t b, uint32_t c, uint32_t d) {
  asm volatile("{\n.reg .b128 v;\n.reg .b64 lo, hi;\nmov.b64 lo, {%1, %2};\nmov.b64 hi, {%3, %4};\nmov.b128 v, {lo, hi};\nst.relaxed.gpu.global.b128 [%0], v;\n}\n"
    :: "l"(p), "r"(a), "r"(b), "r"(c), "r"(d) : "memory");
}
__device__ __forceinline__ uint4 pkt_ld128(const void* p) {
  uint4 r;
  asm volatile("{\n.reg .b128 v;\n.reg .b64 lo, hi;\nld.relaxed.gpu.global.b128 v, [%4];\nmov.b128 {lo, hi}, v;\nmov.b64 {%0, %1}, lo;\nmov.b64 {%2, %3}, hi;\n}\n"
    : "=r"(r.x), "=r"(r.y), "=r"(r.z), "=r"(r.w) : "l"(p) : "memory");
  return r;
}
__device__ __forceinline__ void pkt_ld128_if(uint4& r, const void* p, bool cond) {
  asm volatile("{\n.reg .pred q;\nsetp.ne.b32 q, %5, 0;\n@q ld.relaxed.gpu.global.v4.b32 {%0, %1, %2, %3}, [%4];\n}\n"
    : "+r"(r.x), "+r"(r.y), "+r"(r.z), "+r"(r.w) : "l"(p), "r"((uint32_t)cond) : "memory");
}
__device__ __forceinline__ void pkt_st64(void* p, uint32_t a, uint32_t b) {
  asm volatile("{\n.reg .b64 v;\nmov.b64 v, {%1, %2};\nst.relaxed.gpu.global.b64 [%0], v;\n}\n" :: "l"(p), "r"(a), "r"(b) : "memory");
}
__device__ __forceinline__ uint2 pkt_ld64(const void* p) {
  uint2 r;
  asm volatile("{\n.reg .b64 v;\nld.relaxed.gpu.global.b64 v, [%2];\nmov.b64 {%0, %1}, v;\n}\n" : "=r"(r.x), "=r"(r.y) : "l"(p) : "memory");
  return r;
}
__device__ __forceinline__ uint32_t ld_relaxed32(const void* p) { uint32_t v; asm volatile("ld.relaxed.gpu.global.b32 %0, [%1];" : "=r"(v) : "l"(p) : "memory"); return v; }
__device__ __forceinline__ void st_relaxed32(void* p, uint32_t v) { asm volatile("st.relaxed.gpu.global.b32 [%0], %1;" :: "l"(p), "r"(v) : "memory"); }
__device__ __forceinline__ void backoff() { if (BACKOFF_NS) __nanosleep(BACKOFF_NS); }
__device__ __forceinline__ uint32_t code_of(uint32_t tag) { return tag % 3u + 1u; }
__device__ __forceinline__ uint32_t with_bit(float v, uint32_t bit) { return (__float_as_uint(v) & ~1u) | (bit & 1u); }
__device__ __forceinline__ uint32_t pair_code(uint32_t a, uint32_t b) { return (a & 1u) | ((b & 1u) << 1); }
__device__ __forceinline__ uint32_t pack_bf16(float lo, float hi) { uint32_t r; asm("cvt.rn.bf16x2.f32 %0, %1, %2;" : "=r"(r) : "f"(hi), "f"(lo)); return r; }
__device__ __forceinline__ float bf_lo(uint32_t v) { return __uint_as_float(v << 16); }
__device__ __forceinline__ float bf_hi(uint32_t v) { return __uint_as_float(v & 0xFFFF0000u); }
__device__ __forceinline__ float bf16r(float x) { return __uint_as_float(pack_bf16(0.f, x)); }
__device__ __forceinline__ uint32_t badd2(uint32_t a, uint32_t b) { uint32_t r; asm("add.rn.bf16x2 %0, %1, %2;" : "=r"(r) : "r"(a), "r"(b)); return r; }
__device__ __forceinline__ uint32_t bmul2(uint32_t a, uint32_t b) { uint32_t r; asm("mul.rn.bf16x2 %0, %1, %2;" : "=r"(r) : "r"(a), "r"(b)); return r; }
__device__ __forceinline__ float warp_sum(float v) {
#pragma unroll
  for (int o = 16; o > 0; o >>= 1) v += __shfl_xor_sync(0xffffffffu, v, o);
  return v;
}
__device__ __forceinline__ uint64_t make_desc(uint32_t addr) {
  return (uint64_t)((addr & 0x3FFFF) >> 4) | ((uint64_t)1 << 16) | ((uint64_t)64 << 32) | ((uint64_t)1 << 62);
}
__device__ __forceinline__ uint64_t make_desc_noswz(uint32_t addr) {
  return (uint64_t)((addr & 0x3FFFF) >> 4) | ((uint64_t)8 << 16) | ((uint64_t)16 << 32);
}
__device__ __forceinline__ void wgmma_n256(float (&d)[128], uint64_t da, uint64_t db, int scale_d) {
  asm volatile("{\n.reg .pred p;\nsetp.ne.b32 p, %130, 0;\n"
    "wgmma.mma_async.sync.aligned.m64n256k16.f32.bf16.bf16 "
    "{%0, %1, %2, %3, %4, %5, %6, %7, %8, %9, %10, %11, %12, %13, %14, %15, %16, %17, %18, %19, %20, %21, %22, %23, %24, %25, %26, %27, %28, %29, %30, %31, "
    "%32, %33, %34, %35, %36, %37, %38, %39, %40, %41, %42, %43, %44, %45, %46, %47, %48, %49, %50, %51, %52, %53, %54, %55, %56, %57, %58, %59, %60, %61, %62, %63, "
    "%64, %65, %66, %67, %68, %69, %70, %71, %72, %73, %74, %75, %76, %77, %78, %79, %80, %81, %82, %83, %84, %85, %86, %87, %88, %89, %90, %91, %92, %93, %94, %95, "
    "%96, %97, %98, %99, %100, %101, %102, %103, %104, %105, %106, %107, %108, %109, %110, %111, %112, %113, %114, %115, %116, %117, %118, %119, %120, %121, %122, %123, %124, %125, %126, %127}, "
    "%128, %129, p, 1, 1, 0, 0;\n}\n"
    : "+f"(d[0]), "+f"(d[1]), "+f"(d[2]), "+f"(d[3]), "+f"(d[4]), "+f"(d[5]), "+f"(d[6]), "+f"(d[7]),
      "+f"(d[8]), "+f"(d[9]), "+f"(d[10]), "+f"(d[11]), "+f"(d[12]), "+f"(d[13]), "+f"(d[14]), "+f"(d[15]),
      "+f"(d[16]), "+f"(d[17]), "+f"(d[18]), "+f"(d[19]), "+f"(d[20]), "+f"(d[21]), "+f"(d[22]), "+f"(d[23]),
      "+f"(d[24]), "+f"(d[25]), "+f"(d[26]), "+f"(d[27]), "+f"(d[28]), "+f"(d[29]), "+f"(d[30]), "+f"(d[31]),
      "+f"(d[32]), "+f"(d[33]), "+f"(d[34]), "+f"(d[35]), "+f"(d[36]), "+f"(d[37]), "+f"(d[38]), "+f"(d[39]),
      "+f"(d[40]), "+f"(d[41]), "+f"(d[42]), "+f"(d[43]), "+f"(d[44]), "+f"(d[45]), "+f"(d[46]), "+f"(d[47]),
      "+f"(d[48]), "+f"(d[49]), "+f"(d[50]), "+f"(d[51]), "+f"(d[52]), "+f"(d[53]), "+f"(d[54]), "+f"(d[55]),
      "+f"(d[56]), "+f"(d[57]), "+f"(d[58]), "+f"(d[59]), "+f"(d[60]), "+f"(d[61]), "+f"(d[62]), "+f"(d[63]),
      "+f"(d[64]), "+f"(d[65]), "+f"(d[66]), "+f"(d[67]), "+f"(d[68]), "+f"(d[69]), "+f"(d[70]), "+f"(d[71]),
      "+f"(d[72]), "+f"(d[73]), "+f"(d[74]), "+f"(d[75]), "+f"(d[76]), "+f"(d[77]), "+f"(d[78]), "+f"(d[79]),
      "+f"(d[80]), "+f"(d[81]), "+f"(d[82]), "+f"(d[83]), "+f"(d[84]), "+f"(d[85]), "+f"(d[86]), "+f"(d[87]),
      "+f"(d[88]), "+f"(d[89]), "+f"(d[90]), "+f"(d[91]), "+f"(d[92]), "+f"(d[93]), "+f"(d[94]), "+f"(d[95]),
      "+f"(d[96]), "+f"(d[97]), "+f"(d[98]), "+f"(d[99]), "+f"(d[100]), "+f"(d[101]), "+f"(d[102]), "+f"(d[103]),
      "+f"(d[104]), "+f"(d[105]), "+f"(d[106]), "+f"(d[107]), "+f"(d[108]), "+f"(d[109]), "+f"(d[110]), "+f"(d[111]),
      "+f"(d[112]), "+f"(d[113]), "+f"(d[114]), "+f"(d[115]), "+f"(d[116]), "+f"(d[117]), "+f"(d[118]), "+f"(d[119]),
      "+f"(d[120]), "+f"(d[121]), "+f"(d[122]), "+f"(d[123]), "+f"(d[124]), "+f"(d[125]), "+f"(d[126]), "+f"(d[127])
    : "l"(da), "l"(db), "r"(scale_d));
}
__device__ __forceinline__ void wgmma_n256_rs(float (&d)[128], uint32_t a0, uint32_t a1, uint32_t a2, uint32_t a3, uint64_t db, int scale_d) {
  asm volatile("{\n.reg .pred p;\nsetp.ne.b32 p, %133, 0;\n"
    "wgmma.mma_async.sync.aligned.m64n256k16.f32.bf16.bf16 "
    "{%0, %1, %2, %3, %4, %5, %6, %7, %8, %9, %10, %11, %12, %13, %14, %15, %16, %17, %18, %19, %20, %21, %22, %23, %24, %25, %26, %27, %28, %29, %30, %31, "
    "%32, %33, %34, %35, %36, %37, %38, %39, %40, %41, %42, %43, %44, %45, %46, %47, %48, %49, %50, %51, %52, %53, %54, %55, %56, %57, %58, %59, %60, %61, %62, %63, "
    "%64, %65, %66, %67, %68, %69, %70, %71, %72, %73, %74, %75, %76, %77, %78, %79, %80, %81, %82, %83, %84, %85, %86, %87, %88, %89, %90, %91, %92, %93, %94, %95, "
    "%96, %97, %98, %99, %100, %101, %102, %103, %104, %105, %106, %107, %108, %109, %110, %111, %112, %113, %114, %115, %116, %117, %118, %119, %120, %121, %122, %123, %124, %125, %126, %127}, "
    "{%128, %129, %130, %131}, %132, p, 1, 1, 0;\n}\n"
    : "+f"(d[0]), "+f"(d[1]), "+f"(d[2]), "+f"(d[3]), "+f"(d[4]), "+f"(d[5]), "+f"(d[6]), "+f"(d[7]),
      "+f"(d[8]), "+f"(d[9]), "+f"(d[10]), "+f"(d[11]), "+f"(d[12]), "+f"(d[13]), "+f"(d[14]), "+f"(d[15]),
      "+f"(d[16]), "+f"(d[17]), "+f"(d[18]), "+f"(d[19]), "+f"(d[20]), "+f"(d[21]), "+f"(d[22]), "+f"(d[23]),
      "+f"(d[24]), "+f"(d[25]), "+f"(d[26]), "+f"(d[27]), "+f"(d[28]), "+f"(d[29]), "+f"(d[30]), "+f"(d[31]),
      "+f"(d[32]), "+f"(d[33]), "+f"(d[34]), "+f"(d[35]), "+f"(d[36]), "+f"(d[37]), "+f"(d[38]), "+f"(d[39]),
      "+f"(d[40]), "+f"(d[41]), "+f"(d[42]), "+f"(d[43]), "+f"(d[44]), "+f"(d[45]), "+f"(d[46]), "+f"(d[47]),
      "+f"(d[48]), "+f"(d[49]), "+f"(d[50]), "+f"(d[51]), "+f"(d[52]), "+f"(d[53]), "+f"(d[54]), "+f"(d[55]),
      "+f"(d[56]), "+f"(d[57]), "+f"(d[58]), "+f"(d[59]), "+f"(d[60]), "+f"(d[61]), "+f"(d[62]), "+f"(d[63]),
      "+f"(d[64]), "+f"(d[65]), "+f"(d[66]), "+f"(d[67]), "+f"(d[68]), "+f"(d[69]), "+f"(d[70]), "+f"(d[71]),
      "+f"(d[72]), "+f"(d[73]), "+f"(d[74]), "+f"(d[75]), "+f"(d[76]), "+f"(d[77]), "+f"(d[78]), "+f"(d[79]),
      "+f"(d[80]), "+f"(d[81]), "+f"(d[82]), "+f"(d[83]), "+f"(d[84]), "+f"(d[85]), "+f"(d[86]), "+f"(d[87]),
      "+f"(d[88]), "+f"(d[89]), "+f"(d[90]), "+f"(d[91]), "+f"(d[92]), "+f"(d[93]), "+f"(d[94]), "+f"(d[95]),
      "+f"(d[96]), "+f"(d[97]), "+f"(d[98]), "+f"(d[99]), "+f"(d[100]), "+f"(d[101]), "+f"(d[102]), "+f"(d[103]),
      "+f"(d[104]), "+f"(d[105]), "+f"(d[106]), "+f"(d[107]), "+f"(d[108]), "+f"(d[109]), "+f"(d[110]), "+f"(d[111]),
      "+f"(d[112]), "+f"(d[113]), "+f"(d[114]), "+f"(d[115]), "+f"(d[116]), "+f"(d[117]), "+f"(d[118]), "+f"(d[119]),
      "+f"(d[120]), "+f"(d[121]), "+f"(d[122]), "+f"(d[123]), "+f"(d[124]), "+f"(d[125]), "+f"(d[126]), "+f"(d[127])
    : "r"(a0), "r"(a1), "r"(a2), "r"(a3), "l"(db), "r"(scale_d));
}
__device__ __forceinline__ void wgmma_n128(float (&d)[64], uint64_t da, uint64_t db) {
  asm volatile("{\n.reg .pred p;\nsetp.ne.b32 p, 1, 0;\n"
    "wgmma.mma_async.sync.aligned.m64n128k16.f32.bf16.bf16 "
    "{%0, %1, %2, %3, %4, %5, %6, %7, %8, %9, %10, %11, %12, %13, %14, %15, %16, %17, %18, %19, %20, %21, %22, %23, %24, %25, %26, %27, %28, %29, %30, %31, %32, %33, %34, %35, %36, %37, %38, %39, %40, %41, %42, %43, %44, %45, %46, %47, %48, %49, %50, %51, %52, %53, %54, %55, %56, %57, %58, %59, %60, %61, %62, %63}, "
    "%64, %65, p, 1, 1, 0, 0;\n}\n"
    : "+f"(d[0]), "+f"(d[1]), "+f"(d[2]), "+f"(d[3]), "+f"(d[4]), "+f"(d[5]), "+f"(d[6]), "+f"(d[7]), "+f"(d[8]), "+f"(d[9]), "+f"(d[10]), "+f"(d[11]), "+f"(d[12]), "+f"(d[13]), "+f"(d[14]), "+f"(d[15]), "+f"(d[16]), "+f"(d[17]), "+f"(d[18]), "+f"(d[19]), "+f"(d[20]), "+f"(d[21]), "+f"(d[22]), "+f"(d[23]), "+f"(d[24]), "+f"(d[25]), "+f"(d[26]), "+f"(d[27]), "+f"(d[28]), "+f"(d[29]), "+f"(d[30]), "+f"(d[31]), "+f"(d[32]), "+f"(d[33]), "+f"(d[34]), "+f"(d[35]), "+f"(d[36]), "+f"(d[37]), "+f"(d[38]), "+f"(d[39]), "+f"(d[40]), "+f"(d[41]), "+f"(d[42]), "+f"(d[43]), "+f"(d[44]), "+f"(d[45]), "+f"(d[46]), "+f"(d[47]), "+f"(d[48]), "+f"(d[49]), "+f"(d[50]), "+f"(d[51]), "+f"(d[52]), "+f"(d[53]), "+f"(d[54]), "+f"(d[55]), "+f"(d[56]), "+f"(d[57]), "+f"(d[58]), "+f"(d[59]), "+f"(d[60]), "+f"(d[61]), "+f"(d[62]), "+f"(d[63])
    : "l"(da), "l"(db));
}
__device__ __forceinline__ void fence_acc64(float (&d)[64]) {
#pragma unroll
  for (int i = 0; i < 64; i++) asm volatile("" : "+f"(d[i]) :: "memory");
}
__device__ __forceinline__ void fence_acc(float (&d)[128]) {
#pragma unroll
  for (int i = 0; i < 128; i++) asm volatile("" : "+f"(d[i]) :: "memory");
}

template<int N, int I = 0, class F> __device__ __forceinline__ void static_for(F&& f) {
  if constexpr (I < N) { f(std::integral_constant<int, I>()); static_for<N, I + 1>(f); }
}

__device__ __forceinline__ void ldsm_x4_t(uint32_t addr, uint32_t& a, uint32_t& b, uint32_t& c, uint32_t& d) {
  asm volatile("ldmatrix.sync.aligned.m8n8.x4.trans.shared.b16 {%0, %1, %2, %3}, [%4];" : "=r"(a), "=r"(b), "=r"(c), "=r"(d) : "r"(addr));
}
__device__ __forceinline__ void sts128(uint32_t addr, uint32_t a, uint32_t b, uint32_t c, uint32_t d) {
  asm volatile("st.shared.v4.b32 [%0], {%1, %2, %3, %4};" :: "r"(addr), "r"(a), "r"(b), "r"(c), "r"(d));
}
__device__ __forceinline__ void mma16816(float (&c)[4], uint32_t a0, uint32_t a1, uint32_t a2, uint32_t a3, uint32_t b0, uint32_t b1) {
  asm volatile("mma.sync.aligned.m16n8k16.row.col.f32.bf16.bf16.f32 {%0, %1, %2, %3}, {%4, %5, %6, %7}, {%8, %9}, {%0, %1, %2, %3};"
      : "+f"(c[0]), "+f"(c[1]), "+f"(c[2]), "+f"(c[3]) : "r"(a0), "r"(a1), "r"(a2), "r"(a3), "r"(b0), "r"(b1));
}
__device__ __forceinline__ void mma1688(float (&c)[4], uint32_t a0, uint32_t a1, uint32_t b0) {
  asm volatile("mma.sync.aligned.m16n8k8.row.col.f32.bf16.bf16.f32 {%0, %1, %2, %3}, {%4, %5}, {%6}, {%0, %1, %2, %3};"
      : "+f"(c[0]), "+f"(c[1]), "+f"(c[2]), "+f"(c[3]) : "r"(a0), "r"(a1), "r"(b0));
}
template<class T> __device__ __forceinline__ void pin(T*& v) { asm volatile("" : "+l"(v)); }
__device__ __forceinline__ void pin(uint32_t& v) { asm volatile("" : "+r"(v)); }
__device__ __forceinline__ uint32_t bfma2(uint32_t a, uint32_t b, uint32_t c) { uint32_t r; asm("fma.rn.bf16x2 %0, %1, %2, %3;" : "=r"(r) : "r"(a), "r"(b), "r"(c)); return r; }
__device__ __forceinline__ void tma_store_5d(const CUtensorMap* tm, uint32_t src, int c0, int c3, int c4) {
  asm volatile("cp.async.bulk.tensor.5d.global.shared::cta.bulk_group [%0, {%2, %3, %3, %4, %5}], [%1];" :: "l"(tm), "r"(src), "r"(c0), "r"(0), "r"(c3), "r"(c4) : "memory");
}
__device__ __forceinline__ float rcp_fast(float x) { float r; asm("rcp.approx.ftz.f32 %0, %1;" : "=f"(r) : "f"(x)); return r; }
__device__ __forceinline__ float sqrt_fast(float x) { float r; asm("sqrt.approx.ftz.f32 %0, %1;" : "=f"(r) : "f"(x)); return r; }
__device__ __forceinline__ float ln_sd(float var) { return bf16r(sqrt_fast(bf16r(bf16r(fmaxf(var, 0.f)) + 1e-5f))); }
__device__ __forceinline__ uint32_t norm2(uint32_t h, uint32_t neg_mean2, float inv_sd) {
  const uint32_t d = badd2(h, neg_mean2);
  return pack_bf16(bf_lo(d) * inv_sd, bf_hi(d) * inv_sd);
}
template<int N> __device__ __forceinline__ void delay_clk() {
  if constexpr (N > 0) { const uint32_t t0 = clock(); while ((uint32_t)clock() - t0 < N) {} }
}
template<int V> using IC = std::integral_constant<int, V>;

#define CT(slot) do {} while (0)
#define PT(slot) do {} while (0)

template<int MAP>
__global__ void __cluster_dims__(2, 1, 1) __launch_bounds__(384, 1)
fnet_moe_kernel(const __grid_constant__ Params p) {
  uint32_t sb;
  asm volatile("mov.u32 %0, %1;" : "=r"(sb) : "r"(smem_u32(smem_raw)));
  const int warp = __shfl_sync(0xffffffffu, threadIdx.x >> 5, 0);
  const int tid = __shfl_sync(0xffffffffu, threadIdx.x, threadIdx.x & 31), lane = tid & 31;
  const int m = blockIdx.x & 1;
  int tau, eps;
  if (MAP == 0) {
    uint32_t smid;
    asm volatile("mov.u32 %0, %%smid;" : "=r"(smid));
    const int c = smid >> 1, e7 = ((c - 32) * 37) >> 8;
    if (c == 60 || c == 61) {
      const uint32_t tg = ld_relaxed32(&p.s->epoch) + 1;
      uint32_t n = 0;
      do { __nanosleep(1000); } while (!__all_sync(0xffffffffu, pkt_ld64(&p.s->xstat[(tid & 127) * 16]).y == tg) && ++n < 4096);
      return;
    }
    tau = c < 32 ? (c & 7) : (c < 60 ? c - 31 - 7 * e7 : 0);
    eps = c < 32 ? (c >> 3) : (c < 60 ? 4 + e7 : c - 58);
  } else {
    tau = (blockIdx.x >> 1) & 7; eps = blockIdx.x >> 4;
  }
  const int cid = tau * 16 + eps * 2 + m;
  const bool moe = tau > 0;
  auto BAR = [&](int i) { return sb + OFF_BAR + 8 * i; };
  const CUtensorMap* tmD = m ? &p.tmD1 : &p.tmD0;

  const uint64_t pol_ef = policy_evict_first();
#define LOAD_STREAM(d, tm, bar, c0, c1) tma_load_2d_hint(d, tm, bar, c0, c1, pol_ef)
  if (__builtin_expect(warp == 0, 1)) {
    if (elect_one()) {
      mbar_init(BAR(B_FULL), 1);
      asm volatile("fence.mbarrier_init.release.cluster;" ::: "memory");
      mbar_expect_tx(BAR(B_FULL), ST_BYTES);
      tma_load_2d(sb + A_BYTES, &p.tmX, BAR(B_FULL), 0, tau * 256);
      tma_load_2d(sb, tmD, BAR(B_FULL), 0, eps * 128);
#pragma unroll 1
      for (int k = 1; k < 4; k++) {
        mbar_init(BAR(B_FULL + k), 1);
        asm volatile("fence.mbarrier_init.release.cluster;" ::: "memory");
        mbar_expect_tx(BAR(B_FULL + k), ST_BYTES);
        LOAD_STREAM(sb + k * ST_BYTES, tmD, BAR(B_FULL + k), k * 64, eps * 128);
        tma_load_2d(sb + k * ST_BYTES + A_BYTES, &p.tmX, BAR(B_FULL + k), k * 64, tau * 256);
      }
    }
    PT(0);
  }
  if (warp == 8) {
    if (elect_one()) {
#pragma unroll
      for (int b = B_EMPTY; b < B_COUNT; b++)
        mbar_init(BAR(b), b < B_EPI ? 2 : (b == B_EPI || b == B_EPI0B) ? 4 : (b < B_STD || b == B_OUT) ? 8 : (b == B_STAT || b == B_XS) ? 3 : 1);
      asm volatile("fence.mbarrier_init.release.cluster;" ::: "memory");
      mbar_expect_tx(BAR(B_XCH), 32768);
      SM_(uint32_t, OFF_SEEN) = 0;
    }
  }
  __syncthreads();

  if (warp >= 8) {
    reg_dec<REG_P>();
    asm volatile("barrier.cluster.arrive.relaxed.aligned;" ::: "memory");
    const int abrow = m * 1024 + eps * 128;
    const int f0 = (cid - 16) * 32;
    if (warp == 8) {
      const CUtensorMap* tmW = m ? &p.tmW1 : &p.tmW0;
      const int tA = tau * 256 + m * 128, tB = tau * 256 + (1 - m) * 128;
      uint32_t seen = 0;
#pragma unroll 1
      for (int k = 4; k < 48; k++) {
        const int s = slot_of(k);
        const uint32_t sa = sb + s * ST_BYTES, sbb = sa + A_BYTES;
        const int kb = kblock(tau, k - 16);
        mbar_wait(BAR(B_EMPTY + s), (use_of(k) & 1) ^ 1);
        PT(64 + k);
        if (elect_one()) {
          mbar_expect_tx(BAR(B_FULL + s), (k >> 1) == 9 ? B_BYTES : k == 20 ? ST_BYTES - 8192 : ST_BYTES);
          if (k < 16) {
            LOAD_STREAM(sa, tmD, BAR(B_FULL + s), k * 64, eps * 128);
            tma_load_2d(sbb, &p.tmX, BAR(B_FULL + s), k * 64, tau * 256);
          } else {
            LOAD_STREAM(sbb, tmW, BAR(B_FULL + s), kb * 64, tA);
            LOAD_STREAM(sbb + 16384, tmW, BAR(B_FULL + s), kb * 64, tB);
            if (k < 18) {
              tma_load_2d(sa, &p.tmXr, BAR(B_FULL + s), eps * 128, tA + s * 64);
              tma_load_2d(sa + 8192, &p.tmXr, BAR(B_FULL + s), eps * 128 + 64, tA + s * 64);
            }
          }
        }
        if (k >= 24) {
          uint32_t n = 0;
          while (!((seen >> kb) & 1) && ++n < SPIN_LIMIT * 16) seen = *(volatile uint32_t*)&SM_(uint32_t, OFF_SEEN);
          if (elect_one()) tma_load_2d(sa, &p.tmAbL, BAR(B_FULL + s), kb * 64, abrow);
        }
        if (k == PUB_K1 && elect_one()) mbar_arrive(BAR(B_LATE));
        if (moe && k >= PF_K0 && !(k & 1)) {
          const int i = k < PF_K1 ? (k - PF_K0) >> 1 : PF_N0 + ((k - PF_K1) >> 1);
          if ((k >= PF_K1 || i < PF_N0) && elect_one()) {
            if (i < 8) asm volatile("cp.async.bulk.prefetch.tensor.2d.L2.global.tile [%0, {%1, %2}];" :: "l"(m ? &p.tmU : &p.tmG), "r"(f0), "r"(i * 128) : "memory");
            else if (i < 12) asm volatile("cp.async.bulk.prefetch.L2.global [%0], %1;" :: "l"(p.wdown + (size_t)f0 * 1024 + (i - 8) * 8192), "r"(16384) : "memory");
          }
        }
        if (moe && k >= MR_K0) {
          const int i = k - MR_K0, r6 = (i * 43) >> 8, u = i - 6 * r6, h = 2 * r6 + (u >> 1);
          if (u < 4 && h < NREG_H + 2) {
            if (h < 2) mbar_wait(BAR(B_STD + 2 + h), 0);
            if (elect_one()) {
              const uint32_t bar = BAR(h < NREG_H ? B_MR + (h & 1) : B_GU);
              if (!(u & 1) && h <= NREG_H) mbar_expect_tx(bar, h < NREG_H ? 16384 : (8 - NREG_H) * 16384);
              LOAD_STREAM(sb + OFF_XCH + u * 8192, (u & 1) ? &p.tmU : &p.tmG, bar, f0, h * 128);
            }
          }
        }
      }
      if (moe) {
        mbar_wait(BAR(B_EMPTY + 0), 1);
        if (elect_one()) mbar_expect_tx(BAR(B_DN), 65536);
#pragma unroll 1
        for (int i = 0; i < 10 - NREG_H; i++) {
          if (i == 3) mbar_wait(BAR(B_EMPTY + 1), 1);
          if (i == 4) {
            mbar_wait(BAR(B_EMPTY + 2), 1);
            mbar_wait(BAR(B_XCH), 0);
          }
          const uint32_t dst = sb + late_off(i);
          if (elect_one()) {
            if (i < 6 - NREG_H) {
              LOAD_STREAM(dst, &p.tmG, BAR(B_GU), f0, (NREG_H + 2 + i) * 128);
              LOAD_STREAM(dst + 8192, &p.tmU, BAR(B_GU), f0, (NREG_H + 2 + i) * 128);
            } else {
#pragma unroll
              for (int b = 0; b < 4; b++) LOAD_STREAM(dst + b * 4096, &p.tmDn, BAR(B_DN), (4 * (i - 6 + NREG_H) + b) * 64, f0);
            }
          }
          const long long t0 = clock64();
          while (i < 9 - NREG_H && clock64() - t0 < MOE_PACE_CLK) {}
        }
      }
    } else {
      const int a = warp - 9;
      const long long t_aux = clock64() - PROLOGUE_CLK;
      auto stage = [&](const bf16* src, int g) {
        if (elect_one()) {
          mbar_expect_tx(BAR(B_AUX + g), 16384);
          bulk_load(sb + OFF_XCH + g * 16384, src + g * 8192, 16384, BAR(B_AUX + g));
        }
      };
      const uint32_t tag = ld_relaxed32(&p.s->epoch) + 1;
      if (a == 2) {
        float s = 0.f;
#pragma unroll
        for (int q = 0; q < 4; q++) {
          const uint4 v = ldg_nc128(p.wr + (q * 32 + lane) * 8);
          s += ((bf_lo(v.x) + bf_hi(v.x)) + (bf_lo(v.y) + bf_hi(v.y))) + ((bf_lo(v.z) + bf_hi(v.z)) + (bf_lo(v.w) + bf_hi(v.w)));
          const int ch = q * 32 + lane - eps * 16;
          if (ch >= 0 && ch < 16) {
            SM_(uint32_t, OFF_WR + ch * 4) = v.x; SM_(uint32_t, OFF_WR + 80 + ch * 4) = v.y;
            SM_(uint32_t, OFF_WR + 160 + ch * 4) = v.z; SM_(uint32_t, OFF_WR + 240 + ch * 4) = v.w;
          }
        }
        s = warp_sum(s);
        if (lane == 0) { SM_(float, OFF_WSUM) = s; SM_(uint32_t, OFF_TAG) = tag; }
      }
      if (a < 2) {
        mbar_wait(BAR(B_FULL + 0), 0);
        if (a == 0) PT(1);
        stage(p.x + (size_t)cid * 16 * 1024, a);
      }
#pragma unroll 1
      for (int it = 0; it < 4; it++) {
        const int g = it & 1;
        mbar_wait(BAR(B_AUX + g), it >> 1);
        if (a == 0) PT(2 + it);
        const uint32_t ad = sb + OFF_XCH + g * 16384 + (lane >> 2) * 2048;
        float s0 = 0.f, s1 = 0.f, q0 = 0.f, q1 = 0.f;
        auto row = [&](auto sq) {
#pragma unroll
          for (int i = 0; i < 11; i++) {
            if (i == 10 && a == 2) break;
            const uint4 v = lds128_v(ad + (((a * 44 + 4 * i + lane) & 127) << 4));
            const uint32_t ww[4] = {v.x, v.y, v.z, v.w};
#pragma unroll
            for (int z = 0; z < 4; z++) {
              const float d0 = bf_lo(ww[z]), d1 = bf_hi(ww[z]);
              s0 += d0; s1 += d1;
              if (decltype(sq)::value) { q0 = fmaf(d0, d0, q0); q1 = fmaf(d1, d1, q1); }
            }
          }
        };
        if (it < 2) row(IC<1>()); else row(IC<0>());
        s0 += s1; q0 += q1;
#pragma unroll
        for (int o = 1; o < 4; o <<= 1) { s0 += __shfl_xor_sync(0xffffffffu, s0, o); q0 += __shfl_xor_sync(0xffffffffu, q0, o); }
        if ((lane & 3) == 0) SM_(float2, OFF_PUB + a * 256 + it * 64 + (lane >> 2) * 8) = make_float2(s0, q0);
        if (it != 2) bar_sync(NB_AUX, 96);
        if (it < 2 && a == 2) stage(cid < 64 ? p.Dre + (size_t)cid * 16 * 1024 : p.Dim + (size_t)(cid - 64) * 16 * 1024, g);
      }
      if (a == 1) {
        const float2 v0 = SM_(float2, OFF_PUB + lane * 8), v1 = SM_(float2, OFF_PUB + 256 + lane * 8), v2 = SM_(float2, OFF_PUB + 512 + lane * 8);
        const float s = v0.x + v1.x + v2.x, mean = s * (1.f / 1024.f);
        const float rs = rcp_fast(ln_sd((v0.y + v1.y + v2.y) * (1.f / 1024.f) - mean * mean));
        pkt_st64((lane < 16 ? p.s->xstat : p.s->dsum) + cid * 16 + (lane & 15), lane < 16 ? pack_bf16(rs, mean) : __float_as_uint(s), tag);
        PT(6);
      }
      auto prefetch = [&](int r) {
        const int l = r * 32 + lane;
        const bf16* ad = l < 1024 ? (((l >> 6) & 1) ? p.wup : p.wgate) + (size_t)((l >> 7) * 128 + m * 64 + (l & 63)) * 3584 + (f0 & ~63)
                                  : p.wdown + (size_t)f0 * 1024 + (l - 1024) * 64;
        if (moe) asm volatile("prefetch.global.L2 [%0];" :: "l"(ad));
      };
      __nanosleep(GATHER_NS);
      {
        const int i0 = a * 32 + lane;
        uint2 v[3], c0, c1; uint32_t n = 0;
        const uint2* dp = &p.s->dsum[abrow];
        while (true) {
#pragma unroll
          for (int q = 0; q < 3; q++) v[q] = pkt_ld64(&p.s->xstat[tau * 256 + min(i0 + 96 * q, 255)]);
          c0 = pkt_ld64(dp + i0); c1 = pkt_ld64(dp + min(i0 + 96, 127));
          if (__all_sync(0xffffffffu, v[0].y == tag && v[1].y == tag && v[2].y == tag && c0.y == tag && c1.y == tag) || ++n > SPIN_LIMIT) break;
          __nanosleep(200);
        }
#pragma unroll
        for (int q = 0; q < 3; q++) {
          const int col = min(i0 + 96 * q, 255);
          SM_(uint16_t, OFF_RS + ((col & 7) >> 1) * 144 + (col >> 3) * 4 + (col & 1) * 2) = (uint16_t)(v[q].x ^ (m << 15));
          const uint32_t nm = (v[q].x >> 16) ^ 0x8000u;
          SM_(uint4, OFF_EXB + (col >> 3) * 256 + (col & 7) * 16) = make_uint4(nm | (nm << 16), nm, 0, 0);
          SM_(uint4, OFF_EXB + (col >> 3) * 256 + 128 + (col & 7) * 16) = make_uint4(0, 0, 0, 0);
        }
#pragma unroll
        for (int q = 0; q < 2; q++) {
          const int e = min(i0 + 96 * q, 127);
          const float c = __uint_as_float(q ? c1.x : c0.x);
          const float hi = bf16r(c), mid = bf16r(c - hi), lo = bf16r((c - hi) - mid);
          SM_(uint4, OFF_EXA + (e >> 3) * 256 + (e & 7) * 16) = make_uint4((__float_as_uint(hi) >> 16) | (__float_as_uint(mid) & 0xFFFF0000u), __float_as_uint(lo) >> 16, 0, 0);
          SM_(uint4, OFF_EXA + (e >> 3) * 256 + 128 + (e & 7) * 16) = make_uint4(0, 0, 0, 0);
        }
        fence_async_smem();
      }
      __syncwarp();
      if (lane == 0) mbar_arrive(BAR(B_STAT));
      if (a == 0) PT(7);
      if (a == 0) {
        const uint32_t* flg = reinterpret_cast<const uint32_t*>(&p.s->abflag[((eps * 2 + m) * 8 + (lane >> 2)) * 2]) + (lane & 3);
        uint32_t seen = 0;
        auto poll = [&]() {
          seen = __ballot_sync(0xffffffffu, ld_relaxed32(flg) == tag);
          asm volatile("fence.proxy.async.global;" ::: "memory");
          *(volatile uint32_t*)&SM_(uint32_t, OFF_SEEN) = seen;
        };
        {
          const uint32_t* fa = reinterpret_cast<const uint32_t*>(&p.s->abflag[((eps * 2 + m) * 8 + ((tau + 1) & 7)) * 2 + 1]);
          mbar_wait(BAR(B_STDA), 0);
          uint32_t n = 0;
          while (!__all_sync(0xffffffffu, ld_relaxed32(fa) == tag) && ++n < SPIN_LIMIT) {}
          mbar_wait(BAR(B_EPI0B), 0);
          mbar_wait(BAR(B_FULL + 0), 0);
          PT(48);
          if (elect_one()) tma_load_2d(sb + OFF_XCH, &p.tmAbS, BAR(B_FULL + 0), ((tau + 1) & 7) * 256, abrow);
        }
        mbar_wait(BAR(B_STD + 0), 0);
#pragma unroll 1
        for (int s = 0; s < 4; s++) {
          const int kb = kblock(tau, 4 + s);
          uint32_t n = 0;
          while (!((seen >> kb) & 1) && ++n < SPIN_LIMIT) poll();
          if (s == 3) mbar_wait(BAR(B_STD + 1), 0);
          if (s) mbar_wait(BAR(B_FULL + s), 0);
          PT(16 + s);
          if (elect_one()) {
            if (s == 0) {
              mbar_expect_tx(BAR(B_A20), 8192);
              tma_load_2d(sb + OFF_XCH + 8192, &p.tmAbS, BAR(B_A20), kb * 64, abrow + 64);
            } else {
              tma_load_2d(sb + (s < 2 ? OFF_XCH + s * 16384 : s * ST_BYTES), &p.tmAbL, BAR(B_FULL + s), kb * 64, abrow);
            }
          }
        }
        uint32_t n = 0;
        while (seen != 0xFFFFFFFFu && ++n < SPIN_LIMIT) { poll(); __nanosleep(100); }
      } else if (a == 1) {
#pragma unroll 1
        for (int c = 0; c < 4; c++) {
          uint32_t* flag = reinterpret_cast<uint32_t*>(&p.s->abflag[((eps * 2 + m) * 8 + tau) * 2]) + c;
          mbar_wait(BAR(B_EPI + c), 0);
          if (c == 1) mbar_wait(BAR(B_LATE), 0);
          PT(8 + c);
          if (c >= 2) {
            bf16* dst = p.s->abT + (size_t)(abrow + (lane >> 3)) * 2048 + tau * 256 + c * 64;
#pragma unroll 4
            for (int i = 0; i < 32; i++) {
              const int row = 4 * i + (lane >> 3);
              const uint4 v = lds128_v(sb + chunk_off(c, 0) + i * 512 + lane * 16);
              asm volatile("st.global.v4.b32 [%0], {%1, %2, %3, %4};" :: "l"(dst + i * 4 * 2048 + (((lane & 7) ^ (row & 7)) << 3)), "r"(v.x), "r"(v.y), "r"(v.z), "r"(v.w));
            }
            __syncwarp();
            if (lane == 0) mbar_arrive(BAR(B_STD + c));
            if (c == 3) {
              asm volatile("fence.acq_rel.gpu;" ::: "memory");
              if (lane < 2) st_relaxed32(flag - lane, tag);
            }
            PT(12 + c);
            continue;
          }
          if (lane == 0) {
            tma_store_2d(&p.tmAbS, sb + chunk_off(c, 0), tau * 256 + c * 64, abrow);
            if (c == 0) {
              bulk_commit();
              bulk_wait_all();
              st_relaxed32(flag + 4, tag);
              mbar_arrive(BAR(B_STDA));
            }
          }
          mbar_wait(BAR(B_EPI0B), 0);
          if (lane == 0) {
            tma_store_2d(&p.tmAbS, sb + chunk_off(c, 1), tau * 256 + c * 64, abrow + 64);
            bulk_commit();
            bulk_wait_all();
            st_relaxed32(flag, tag);
            mbar_arrive(BAR(B_STD + c));
          }
          PT(12 + c);
        }
      } else {
      }
      {
        const uint4* kp = &p.s->key[(tau * 16 + (lane & 15)) * 2];
        const int i0 = a * 32 + lane;
        mbar_wait(BAR(B_KEY), 0);
        if (a == 0) PT(43);
        uint4 kq = pkt_ld128(kp), cv[3];
        uint32_t n = 0, kv;
        int gspec = -1;
        while (true) {
          const bool ok = kq.y == tag && kq.w == tag;
          kv = __reduce_max_sync(0xffffffffu, ok ? kq.x : 0u);
          const int gs = (0xFFFF - (int)(kv & 0xFFFFu)) >> 7;
          const bool cok = gs == gspec && cv[0].y == tag && cv[0].w == tag && cv[1].y == tag && cv[1].w == tag && cv[2].y == tag && cv[2].w == tag;
          if (__all_sync(0xffffffffu, ok && cok) || ++n > SPIN_LIMIT) break;
          if (!ok) kq = pkt_ld128(kp);
          const bool spec = __popc(__ballot_sync(0xffffffffu, ok)) >= 2 * SPEC_MIN;
          if (!cok && spec) {
#pragma unroll
            for (int i = 0; i < 3; i++) cv[i] = pkt_ld128(&p.s->cand[gs * 256 + min(i0 + 96 * i, 255)]);
          }
          if (spec) gspec = gs;
        }
        if (a == 0) PT(45);
        const uint32_t ms = __shfl_sync(0xffffffffu, kq.z, gspec);
        const uint32_t nm = ((ms & 0xFFFFu) ^ 0x8000u) * 0x10001u;
        const float is = rcp_fast(bf_hi(ms));
#pragma unroll
        for (int i = 0; i < 3; i++) {
          const int j = min(i0 + 96 * i, 255);
          SM_(uint2, OFF_XSEL + j * 8) = make_uint2(norm2(cv[i].x, nm, is), norm2(cv[i].z, nm, is));
          SM_(uint2, OFF_HSEL + j * 8) = make_uint2(cv[i].x, cv[i].z);
        }
        SM_(uint32_t, OFF_KV) = kv;
        __syncwarp();
        if (lane == 0) mbar_arrive(BAR(B_XS));
      }
    }
    if (warp == 8) {
      mbar_wait(BAR(B_OUT), 0);
      const uint32_t km = SM_(uint32_t, OFF_WKEY + (lane & 7) * 8);
      const uint32_t bk = __reduce_max_sync(0xffffffffu, km);
      const int ww = __ffs(__ballot_sync(0xffffffffu, km == bk)) - 1;
#pragma unroll 1
      for (int i = 1; i <= 8; i++) {
        const int W = (ww + i) & 7;
        if (i == 8) {
          mbar_wait(BAR(B_XS), 0);
          if (SM_(uint32_t, OFF_KV) == bk) {
#pragma unroll 2
            for (int j = lane; j < 256; j += 32) {
              const int rho = j >> 4, row = (tau * 2 + m) * 128 + 32 * (W >> 1) + 8 * ((rho & 7) >> 1) + 4 * (W & 1) + 2 * (rho >> 3) + (rho & 1);
              const uint4 v = lds128_v(sb + OFF_OUT + (j & 8) * 2048 + (16 * W + rho) * 128 + (((j ^ rho) & 7) << 4));
              if (row != 0xFFFF - (int)(bk & 0xFFFFu))
                asm volatile("st.global.v4.b32 [%0], {%1, %2, %3, %4};" :: "l"(p.out + (size_t)row * 1024 + eps * 128 + (j & 15) * 8), "r"(v.x), "r"(v.y), "r"(v.z), "r"(v.w));
            }
            break;
          }
        }
        if (lane == 0) {
          tma_store_5d(&p.tmOut, sb + OFF_OUT + W * 2048, eps * 128, 2 * (W & 1), tau * 8 + m * 4 + (W >> 1));
          tma_store_5d(&p.tmOut, sb + OFF_OUT + 16384 + W * 2048, eps * 128 + 64, 2 * (W & 1), tau * 8 + m * 4 + (W >> 1));
        }
        const long long t0 = clock64();
        while (i < 7 && clock64() - t0 < OUT_PACE_CLK) {}
      }
      if (lane == 0) { bulk_commit(); bulk_wait_all(); }
      PT(22);
    }
    asm volatile("barrier.cluster.wait.aligned;" ::: "memory");
  } else {
    reg_inc<REG_C>();
    const int w = warp >> 2, wi = warp & 3, t = tid & 127;
    const int g = lane >> 2, q = lane & 3;
    const int turn_me = NB_TURN0 + w, turn_other = NB_TURN1 - w;
    float acc[128];
#pragma unroll
    for (int i = 0; i < 128; i++) acc[i] = 0.f;
    if (w == 1) bar_arrive(NB_TURN0, 256);
    auto kstep = [&](int k, bool first, bool a_in_xch = false) {
      const int s = slot_of(k);
      mbar_wait(BAR(B_FULL + s), use_of(k) & 1);
      CT(64 + k);
      bar_sync(turn_me, 256);
      const uint64_t da = make_desc(sb + (a_in_xch ? OFF_XCH + s * 16384 : s * ST_BYTES) + w * 8192), db = make_desc(sb + s * ST_BYTES + A_BYTES);
      wgmma_fence();
      wgmma_n256(acc, da, db, !first);
#pragma unroll
      for (int kk = 1; kk < 4; kk++) wgmma_n256(acc, da + kk * 2, db + kk * 2, 1);
      wgmma_commit();
      bar_arrive(turn_other, 256);
    };
    auto release = [&](int s) { if (t == 0) mbar_arrive(BAR(B_EMPTY + s)); };
    auto kdone = [&](int k) { wgmma_wait0(); release(slot_of(k)); };
    auto wgmma_wait1 = [&]() { asm volatile("wgmma.wait_group.sync.aligned 1;" ::: "memory"); };

#pragma unroll 1
    for (int k = 0; k < 14; k++) {
      kstep(k, k == 0);
      if (k == 0) CT(0);
      if (k == 8 && warp == 2 && lane < 2) pkt_st128(&p.s->abflag[((eps * 2 + m) * 8 + tau) * 2 + lane], 0, 0, 0, 0);
      kdone(k);
    }
    uint32_t R[64];
    uint32_t tag;
    {
      const uint32_t rsa = sb + OFF_RS + q * 144;
      const uint64_t da2 = make_desc(sb + 2 * ST_BYTES + w * 8192), db2 = make_desc(sb + 2 * ST_BYTES + A_BYTES);
      const uint64_t da3 = make_desc(sb + 3 * ST_BYTES + w * 8192), db3 = make_desc(sb + 3 * ST_BYTES + A_BYTES);
      mbar_wait(BAR(B_FULL + 2), 1);
      CT(64 + 14);
      bar_sync(turn_me, 256);
      wgmma_fence();
#pragma unroll
      for (int kk = 0; kk < 4; kk++) wgmma_n256(acc, da2 + kk * 2, db2 + kk * 2, 1);
      wgmma_commit();
      mbar_wait(BAR(B_FULL + 3), 1);
      CT(64 + 15);
      wgmma_fence();
      wgmma_n256(acc, da3, db3, 1);
      wgmma_n256(acc, da3 + 2, db3 + 2, 1);
      wgmma_commit();
      mbar_wait(BAR(B_STAT), 0);
      tag = SM_(uint32_t, OFF_TAG);
#pragma unroll
      for (int i = 0; i < 8; i++) { const uint4 v = lds128_v(rsa + i * 16); R[8 * i] = v.x; R[8 * i + 2] = v.y; R[8 * i + 4] = v.z; R[8 * i + 6] = v.w; }
      wgmma_wait1();
      release(2);
      wgmma_fence();
      wgmma_n256(acc, da3 + 4, db3 + 4, 1);
      wgmma_n256(acc, da3 + 6, db3 + 6, 1);
      wgmma_n256(acc, make_desc_noswz(sb + OFF_EXA + w * 2048), make_desc_noswz(sb + OFF_EXB), 1);
      wgmma_commit();
      bar_arrive(turn_other, 256);
      kdone(15);
      mbar_wait(BAR(B_STAT), 0);
    }
    fence_acc(acc);
    CT(1);
    auto pack = [&](auto cc) {
      constexpr int c = decltype(cc)::value;
#pragma unroll
      for (int j = 8 * c; j < 8 * c + 8; j++) {
        const uint32_t rs = R[2 * j];
        const float* ac = &acc[4 * j];
        R[2 * j] = bmul2(pack_bf16(ac[0], ac[1]), rs);
        R[2 * j + 1] = bmul2(pack_bf16(ac[2], ac[3]), rs);
      }
    };
    auto put_chunk = [&](auto cc) {
      constexpr int c = decltype(cc)::value;
      const int rho = 16 * wi + (lane & 15);
#pragma unroll
      for (int j = 8 * c; j < 8 * c + 8; j += 2) {
        const int chunk = (j & 7) + (lane >> 4);
        stsm_x4(sb + chunk_off(c, w) + rho * 128 + ((chunk ^ (lane & 7)) << 4), R[2 * j], R[2 * j + 1], R[2 * j + 2], R[2 * j + 3]);
      }
    };
    auto staged = [&](int bar) {
      fence_async_smem();
      __syncwarp();
      if (lane == 0) mbar_arrive(BAR(bar));
    };
    auto mma_rs = [&](auto cc, auto k0, auto k1) {
      constexpr int c = decltype(cc)::value;
      const uint64_t db = make_desc(sb + c * ST_BYTES + A_BYTES);
#pragma unroll
      for (int kk = decltype(k0)::value; kk < decltype(k1)::value; kk++)
        wgmma_n256_rs(acc, R[16 * c + 4 * kk], R[16 * c + 4 * kk + 1], R[16 * c + 4 * kk + 2], R[16 * c + 4 * kk + 3], db + kk * 2, c + kk > 0);
      wgmma_commit();
    };
    auto kdone_x = [&](int k, auto ic) {
      constexpr int i = decltype(ic)::value;
      uint32_t r[8];
#pragma unroll
      for (int z = 0; z < 2; z++) {
        const int tr = 32 * (i & 1) + 16 * z + 8 * (lane >> 4) + (lane & 7), chunk = 2 * wi + ((lane >> 3) & 1);
        ldsm_x4_t(sb + (i >> 1) * ST_BYTES + w * 8192 + tr * 128 + ((chunk ^ (lane & 7)) << 4), r[4 * z], r[4 * z + 1], r[4 * z + 2], r[4 * z + 3]);
      }
      float f[16];
#pragma unroll
      for (int z = 0; z < 8; z++) { f[2 * z] = bf_lo(r[z]); f[2 * z + 1] = bf_hi(r[z]); }
#pragma unroll
      for (int z = 0; z < 16; z++) asm volatile("" : "+f"(f[z]));
      kdone(k);
#pragma unroll
      for (int z = 0; z < 16; z++) asm volatile("add.f32 %0, %0, %1;" : "+f"(acc[16 * i + z]) : "f"(f[z]));
    };
    pack(IC<0>());
    put_chunk(IC<0>());
    staged(w ? B_EPI0B : B_EPI);
    mbar_wait(BAR(B_STAT), 0);
    CT(21);
    pack(IC<1>());
    pack(IC<2>());
    pack(IC<3>());
#pragma unroll
    for (int i = 16; i < 64; i++) asm volatile("" : "+r"(R[i]));
    mbar_wait(BAR(B_FULL + 0), 0);
    CT(2);
    CT(64 + 16);
    bar_sync(turn_me, 256);
    wgmma_fence();
    mma_rs(IC<0>(), IC<0>(), IC<4>());
    mbar_wait(BAR(B_FULL + 1), 0);
    CT(64 + 17);
    wgmma_fence();
    mma_rs(IC<1>(), IC<0>(), IC<2>());
    wgmma_wait1();
    release(0);
    mma_rs(IC<1>(), IC<2>(), IC<4>());
    bar_arrive(turn_other, 256);
    kdone_x(17, IC<0>());
    static_for<2>([&](auto ic) {
      constexpr int c = 2 + decltype(ic)::value;
      mbar_wait(BAR(B_FULL + c), 0);
      CT(64 + 16 + c);
      bar_sync(turn_me, 256);
      wgmma_fence();
      mma_rs(IC<c>(), IC<0>(), IC<4>());
      bar_arrive(turn_other, 256);
      if (c == 2) { put_chunk(IC<1>()); staged(B_EPI + 1); }
      kdone_x(16 + c, IC<c - 1>());
    });
#pragma unroll 1
    for (int k = 20; k < 23; k++) {
      if (w == 1) mbar_wait(BAR(B_A20), 0);
      kstep(k, false, k < 22);
      if (k == 20) {
        kdone_x(k, IC<3>());
      } else {
        if (k == 21) put_chunk(IC<2>()); else put_chunk(IC<3>());
        __syncwarp();
        if (lane == 0) mbar_arrive(BAR(B_EPI + k - 19));
        kdone(k);
      }
    }
    uint32_t wf[32][4];
    auto load_wf = [&](auto hc) {
      constexpr int h = decltype(hc)::value;
      const int d = w * 64 + (lane >> 4) * 8 + (lane & 7);
      const uint32_t ad = sb + round_off(h) + (lane & 8) * 1024 + d * 64 + ((wi ^ ((lane >> 1) & 3)) << 4);
#pragma unroll
      for (int i = 0; i < 4; i++) ldsm_x4_t(ad + i * 1024, wf[4 * h + i][0], wf[4 * h + i][1], wf[4 * h + i][2], wf[4 * h + i][3]);
    };
    auto load_wf_rest = [&]() { static_for<8 - NREG_H>([&](auto ic) { load_wf(IC<NREG_H + decltype(ic)::value>()); }); };
#pragma unroll
    for (int i = 0; i < 4 * NREG_H; i++) { wf[i][0] = 0; wf[i][1] = 0; wf[i][2] = 0; wf[i][3] = 0; }
    const int grp = tau * 2 + m;
#pragma unroll 1
    for (int k = 23; k < 46; k++) {
      kstep(k, false);
      if (moe) {
        static_for<NREG_H>([&](auto hc) {
          constexpr int h = decltype(hc)::value;
          if (k == mr_k(h) + 1) { mbar_wait(BAR(B_MR + (h & 1)), (h >> 1) & 1); load_wf(hc); }
        });
      }
      if (k == 43) {
        if (moe) pkt_st128(&p.s->ypart[cid * 256 + tid], 0, 0, 0, 0);
        if (w == 1) pkt_st128(&p.s->hstat[(grp * 8 + eps) * 128 + t], 0, 0, 0, 0);
        if (warp == 0) pkt_st128(&p.s->cand[grp * 256 + eps * 32 + lane], 0, 0, 0, 0);
        if (eps == 0 && warp == 1 && lane < 16) pkt_st128(&p.s->key[((lane >> 1) * 16 + grp) * 2 + (lane & 1)], 0, 0, 0, 0);
      }
      kdone(k);
    }
    asm volatile("barrier.cluster.arrive.relaxed.aligned;" ::: "memory");
    uint32_t wa[16][2];
    uint32_t cd = code_of(tag);
    uint4* hp_pub = &p.s->hstat[(grp * 8 + eps) * 128 + warp * 16 + g];
    const uint4* hp_poll = &p.s->hstat[(grp * 8 + 2 * q) * 128 + warp * 16 + g];
    const uint32_t vec_off = (2 * wi) * 512 + q * 128 + ((g ^ (2 * q)) << 4);
    {
      float as[64], ak[64];
      fence_acc(acc);
#pragma unroll
      for (int i = 0; i < 64; i++) asm volatile("mov.b32 %0, %1;" : "=f"(as[i]) : "f"(acc[64 + i]));
#pragma unroll
      for (int i = 0; i < 64; i++) asm volatile("mov.b32 %0, %1;" : "=f"(ak[i]) : "f"(acc[i]));
      const uint64_t da1 = make_desc(sb + 2 * ST_BYTES + w * 8192), db1 = make_desc(sb + 2 * ST_BYTES + A_BYTES);
      const uint64_t da2 = make_desc(sb + 3 * ST_BYTES + w * 8192), db2 = make_desc(sb + 3 * ST_BYTES + A_BYTES);
      mbar_wait(BAR(B_FULL + 2), 1);
      CT(64 + 46);
      mbar_wait(BAR(B_FULL + 3), 1);
      CT(64 + 47);
      bar_sync(turn_me, 256);
      wgmma_fence();
#pragma unroll
      for (int kk = 0; kk < 4; kk++) wgmma_n128(as, da1 + kk * 2, db1 + 1024 + kk * 2);
#pragma unroll
      for (int kk = 0; kk < 4; kk++) wgmma_n128(as, da2 + kk * 2, db2 + 1024 + kk * 2);
      wgmma_commit();
      bar_arrive(turn_other, 256);
      const uint32_t rx = mapa(sb + OFF_PEER + w * 4096 + vec_off, 1 - m), rb = mapa(BAR(B_XCH), 1 - m);
      asm volatile("barrier.cluster.wait.aligned;" ::: "memory");
      wgmma_wait0();
      fence_acc64(as);
      auto keep = [&]() {
        bar_sync(turn_me, 256);
        wgmma_fence();
#pragma unroll
        for (int kk = 0; kk < 4; kk++) wgmma_n128(ak, da1 + kk * 2, db1 + kk * 2);
        wgmma_commit();
#pragma unroll
        for (int kk = 0; kk < 4; kk++) wgmma_n128(ak, da2 + kk * 2, db2 + kk * 2);
        wgmma_commit();
        if (w == 0) bar_arrive(turn_other, 256);
      };
      keep();
#pragma unroll
      for (int i = 0; i < 8; i++) {
        const float* ac = &as[16 * (i >> 1) + 2 * (i & 1)];
        st_async_v4(rx + (i >> 1) * 8192 + (i & 1) * 512, rb, pack_bf16(ac[0], ac[1]), pack_bf16(ac[4], ac[5]), pack_bf16(ac[8], ac[9]), pack_bf16(ac[12], ac[13]));
      }
#pragma unroll
      for (int i = 0; i < 4; i++) {
        const uint4 v = lds128_v(sb + OFF_WR + q * 80 + i * 16);
        const uint32_t vv[4] = {v.x, v.y, v.z, v.w};
#pragma unroll
        for (int z = 0; z < 4; z++) {
          asm volatile("{\n.reg .pred p;\nsetp.ne.b32 p, %2, 0;\nselp.b32 %0, %1, 0x3F803F80, p;\n}" : "=r"(wa[4 * i + z][0]) : "r"(vv[z]), "r"(g & 1));
          asm volatile("{\n.reg .pred p;\nsetp.ne.b32 p, %2, 0;\nselp.b32 %0, %1, 0x3F803F80, p;\n}" : "=r"(wa[4 * i + z][1]) : "r"(vv[z]), "r"(g & 1));
        }
      }
      pin(cd); pin(hp_pub); pin(hp_poll);
      wgmma_wait1();
      release(2);
      wgmma_wait0();
      fence_acc64(ak);
      CT(3);
#pragma unroll
      for (int i = 0; i < 8; i++) {
        const float* ac = &ak[16 * (i >> 1) + 2 * (i & 1)];
        sts128(sb + (2 + (i >> 2)) * ST_BYTES + w * 8192 + ((i >> 1) & 1) * 4096 + (i & 1) * 512 + vec_off,
               pack_bf16(ac[0], ac[1]), pack_bf16(ac[4], ac[5]), pack_bf16(ac[8], ac[9]), pack_bf16(ac[12], ac[13]));
      }
    }
    uint32_t h[8][4];
    {
      const int qq = 2 * (warp & 1) + ((lane >> 3) & 1);
      const uint32_t lo = (lane >> 4) * 512 + qq * 128 + (((lane & 7) ^ (2 * qq)) << 4);
      bar_sync(NB_BOTH, 256);
#pragma unroll
      for (int ks = 0; ks < 8; ks++)
        ldsm_x4_t(sb + (2 + w) * ST_BYTES + (ks >> 2) * 8192 + (wi >> 1) * 4096 + (ks & 3) * 1024 + lo, h[ks][0], h[ks][1], h[ks][2], h[ks][3]);
      mbar_wait_cluster(BAR(B_XCH), 0);
      CT(4);
      uint32_t r[8][4];
#pragma unroll
      for (int ks = 0; ks < 8; ks++) ldsm_x4_t(sb + OFF_PEER + (warp >> 1) * 8192 + ks * 1024 + lo, r[ks][0], r[ks][1], r[ks][2], r[ks][3]);
      float d[4][4] = {};
#pragma unroll
      for (int ks = 0; ks < 8; ks++) {
#pragma unroll
        for (int i = 0; i < 4; i++) {
          h[ks][i] = badd2(h[ks][i], r[ks][i]);
          mma1688(d[i], h[ks][i], wa[2 * ks + (i >> 1)][i & 1], h[ks][i]);
        }
      }
#pragma unroll
      for (int i = 0; i < 2; i++) {
        const float sq = (g & 1) ? d[i][1] + d[i + 2][1] : d[i][0] + d[i + 2][0];
        const float e0 = d[i][2] + d[i + 2][2], e1 = d[i][3] + d[i + 2][3];
        const float other = __shfl_xor_sync(0xffffffffu, (g & 1) ? e0 : e1, 4);
        if (q == (g >> 1)) pkt_st128(hp_pub + 8 * i, with_bit((g & 1) ? other : e0, cd), with_bit(sq, cd >> 1), __float_as_uint((g & 1) ? e1 : other), tag);
      }
    }
    CT(5);
    if (tid == 0) mbar_arrive(BAR(B_KEY));
    delay_clk<HOP1_DELAY>();
    float m_bf, sd, inv_sd, r_bf;
    uint4* key_pub = &p.s->key[((lane & 7) * 16 + grp) * 2];
    uint4* cand_pub = &p.s->cand[grp * 256 + eps * 32 + q];
    uint32_t trow_inv = 0xFFFFu - (uint32_t)(grp * 128 + 32 * (warp >> 1) + 8 * (g >> 1) + 4 * (warp & 1) + (q & 2) + (g & 1));
    {
      uint4 u[4];
#pragma unroll
      for (int i = 0; i < 4; i++) u[i] = pkt_ld128(hp_poll + (i & 1) * 128 + (i >> 1) * 8);
      const float wsum = SM_(float, OFF_WSUM);
      pin(key_pub); pin(cand_pub); pin(trow_inv);
      uint32_t n = 0;
      while (true) {
        bool ok[4];
#pragma unroll
        for (int i = 0; i < 4; i++) ok[i] = u[i].w == tag && pair_code(u[i].x, u[i].y) == cd;
        const bool all = __all_sync(0xffffffffu, ok[0] && ok[1] && ok[2] && ok[3]);
        if (all || ++n > SPIN_LIMIT) break;
#pragma unroll
        for (int i = 0; i < 4; i++) pkt_ld128_if(u[i], hp_poll + (i & 1) * 128 + (i >> 1) * 8, !ok[i]);
      }
      CT(6);
      float a[3], b[3];
      a[0] = __uint_as_float(u[0].x & ~1u) + __uint_as_float(u[1].x & ~1u); b[0] = __uint_as_float(u[2].x & ~1u) + __uint_as_float(u[3].x & ~1u);
      a[1] = __uint_as_float(u[0].y & ~1u) + __uint_as_float(u[1].y & ~1u); b[1] = __uint_as_float(u[2].y & ~1u) + __uint_as_float(u[3].y & ~1u);
      a[2] = __uint_as_float(u[0].z) + __uint_as_float(u[1].z); b[2] = __uint_as_float(u[2].z) + __uint_as_float(u[3].z);
#pragma unroll
      for (int i = 0; i < 3; i++) {
        a[i] = ((q & 2) ? b[i] : a[i]) + __shfl_xor_sync(0xffffffffu, (q & 2) ? a[i] : b[i], 2);
        a[i] += __shfl_xor_sync(0xffffffffu, a[i], 1);
      }
      const float mu = a[0] * (1.f / 1024.f);
      m_bf = bf16r(mu);
      sd = ln_sd(a[1] * (1.f / 1024.f) - mu * mu);
      inv_sd = rcp_fast(sd);
      r_bf = bf16r((a[2] - m_bf * wsum) * inv_sd);
    }
    {
      const uint32_t u = __float_as_uint(r_bf);
      const uint32_t ord = (u & 0x80000000u) ? ~u : (u | 0x80000000u);
      const uint32_t key = (ord & 0xFFFF0000u) | trow_inv;
      const uint32_t wk = __reduce_max_sync(0xffffffffu, key);
      if (key == wk) SM_(uint2, OFF_WKEY + warp * 8) = make_uint2(wk, (__float_as_uint(m_bf) >> 16) | __float_as_uint(sd));
      const uint32_t wmask = __ballot_sync(0xffffffffu, key == wk);
      const bool hi = (wmask & 0xCCCCCCCCu) != 0;
      uint32_t c[16];
#pragma unroll
      for (int ks = 0; ks < 8; ks++) { c[2 * ks] = hi ? h[ks][1] : h[ks][0]; c[2 * ks + 1] = hi ? h[ks][3] : h[ks][2]; }
      bar_sync(NB_BOTH, 256);
      const uint2 km = SM_(uint2, OFF_WKEY + (lane & 7) * 8);
      const uint32_t bk = __reduce_max_sync(0xffffffffu, km.x);
      if (wk == bk) {
        if ((wmask >> (lane & 28)) & 15) {
#pragma unroll
          for (int ks = 0; ks < 8; ks++) pkt_st128(cand_pub + ks * 4, c[2 * ks], tag, c[2 * ks + 1], tag);
        }
      } else if (eps == 0) {
        const uint32_t kx = __shfl_sync(0xffffffffu, km.x, warp ^ 1), ms = __shfl_sync(0xffffffffu, km.y, warp ^ 1);
        if (kx == bk && lane < 8) pkt_st128(key_pub, bk, tag, ms, tag);
      }
      CT(7);
    }
    {
      const float ih = bf16r(inv_sd);
      const uint32_t nm = pack_bf16(-m_bf, -m_bf), iv = pack_bf16(ih, inv_sd - ih);
      const uint32_t nm_o = __shfl_xor_sync(0xffffffffu, nm, 2), iv_o = __shfl_xor_sync(0xffffffffu, iv, 2);
      const uint32_t nm2[2] = {(q & 2) ? nm_o : nm, (q & 2) ? nm : nm_o}, iv2[2] = {(q & 2) ? iv_o : iv, (q & 2) ? iv : iv_o};
      const uint32_t hi2[2] = {__byte_perm(iv2[0], 0, 0x1010), __byte_perm(iv2[1], 0, 0x1010)}, lo2[2] = {__byte_perm(iv2[0], 0, 0x3232), __byte_perm(iv2[1], 0, 0x3232)};
      const uint32_t oa = sb + OFF_OUT + (warp * 16 + (lane & 15)) * 128;
#pragma unroll
      for (int ks = 0; ks < 8; ks++) {
        uint32_t o[4];
#pragma unroll
        for (int i = 0; i < 4; i++) {
          const uint32_t dd = badd2(h[ks][i], nm2[i & 1]);
          o[i] = badd2(h[ks][i], bfma2(dd, hi2[i & 1], bmul2(dd, lo2[i & 1])));
        }
        stsm_x4(oa + (ks >> 2) * 16384 + (((2 * (ks & 3) + (lane >> 4)) ^ (lane & 7)) << 4), o[0], o[1], o[2], o[3]);
      }
      staged(B_OUT);
    }
    CT(8);
    uint32_t df[16][4];
    auto load_df = [&]() {
      const int frow = (lane & 7) + ((lane >> 4) << 3), hi = (lane >> 3) & 1;
      const uint32_t base = sb + down_off(warp >> 1) + (warp & 1) * 8192 + frow * 128;
#pragma unroll
      for (int mt = 0; mt < 8; mt++) {
#pragma unroll
        for (int ks = 0; ks < 2; ks++)
          ldsm_x4_t(base + (mt >> 2) * 4096 + ks * 2048 + (((2 * (mt & 3) + hi) ^ (lane & 7)) << 4),
                    df[2 * mt + ks][0], df[2 * mt + ks][1], df[2 * mt + ks][2], df[2 * mt + ks][3]);
      }
    };
    if (moe) {
      mbar_wait(BAR(B_GU), 0);
      load_wf_rest();
      mbar_wait(BAR(B_DN), 0);
      load_df();
    }
    mbar_wait(BAR(B_XS), 0);
    CT(9);
    if (moe) {
      float gd[8][4] = {};
      uint2 bx[4];
#pragma unroll
      for (int r = 0; r < 4; r++) bx[r] = SM_(uint2, OFF_XSEL + (16 * r + 8 * (g >> 2) + 4 * w + (g & 3)) * 32 + q * 8);
#pragma unroll
      for (int r = 0; r < 4; r++) {
#pragma unroll
        for (int i = 0; i < 8; i++) mma16816(gd[i], wf[8 * r + i][0], wf[8 * r + i][1], wf[8 * r + i][2], wf[8 * r + i][3], bx[r].x, bx[r].y);
      }
      float gs = q == 0 ? gd[0][0] + gd[1][1] : q == 1 ? gd[2][0] + gd[3][1] : q == 2 ? gd[4][0] + gd[5][1] : gd[6][0] + gd[7][1];
      float us = q == 0 ? gd[0][2] + gd[1][3] : q == 1 ? gd[2][2] + gd[3][3] : q == 2 ? gd[4][2] + gd[5][3] : gd[6][2] + gd[7][3];
      float v = ((q & 2) ? us : gs) + __shfl_xor_sync(0xffffffffu, (q & 2) ? gs : us, 2);
      SM_(float, OFF_GP + (wi * 8 + g) * 32 + w * 16 + q * 4) = v;
      CT(10);
      bar_sync(NB_BOTH, 256);
      uint32_t bq[4];
      {
        const float4 p0 = SM_(float4, OFF_GP + lane * 32), p1 = SM_(float4, OFF_GP + lane * 32 + 16);
        const float gt = bf16r((p0.x + p0.y) + (p1.x + p1.y)), up = bf16r((p0.z + p0.w) + (p1.z + p1.w));
        const float act = bf16r(__fdividef(gt, 1.f + __expf(-gt))) * up;
        const uint32_t pr = pack_bf16(act, __shfl_down_sync(0xffffffffu, act, 1));
#pragma unroll
        for (int i = 0; i < 4; i++) bq[i] = __shfl_sync(0xffffffffu, pr, 8 * i + 2 * q);
      }
      CT(11);
      float yd[8][4] = {};
#pragma unroll
      for (int ks = 0; ks < 2; ks++) {
#pragma unroll
        for (int mt = 0; mt < 8; mt++) mma16816(yd[mt], df[2 * mt + ks][0], df[2 * mt + ks][1], df[2 * mt + ks][2], df[2 * mt + ks][3], bq[2 * ks], bq[2 * ks + 1]);
      }
      const float y0 = q == 0 ? yd[0][0] : q == 1 ? yd[2][0] : q == 2 ? yd[4][0] : yd[6][0];
      const float y1 = q == 0 ? yd[0][2] : q == 1 ? yd[2][2] : q == 2 ? yd[4][2] : yd[6][2];
      const float y2 = q == 0 ? yd[1][0] : q == 1 ? yd[3][0] : q == 2 ? yd[5][0] : yd[7][0];
      const float y3 = q == 0 ? yd[1][2] : q == 1 ? yd[3][2] : q == 2 ? yd[5][2] : yd[7][2];
      pkt_st128(&p.s->ypart[cid * 256 + tid], with_bit(y0, cd), with_bit(y1, cd >> 1), with_bit(y2, cd), with_bit(y3, cd >> 1));
    } else {
      const long long tw = clock64();
      while (clock64() - tw < IDLE_WAIT_CLK) __nanosleep(100);
    }
    CT(12);
    const uint32_t kv = SM_(uint32_t, OFF_KV);
    const int tsel = 0xFFFF - (int)(kv & 0xFFFFu);
    const float r_sel = __uint_as_float((kv & 0x80000000u) ? (kv & 0x7FFF0000u) : (~kv & 0xFFFF0000u));
    const float sig = bf16r(__fdividef(1.f, 1.f + __expf(-r_sel)));
    const int pfin = 2 * cid + (tid & 1);
    const int col_fin = (pfin >> 5) * 128 + (pfin & 3) * 32 + ((pfin & 31) >> 2) + 8 * ((tid >> 1) & 3);
    const int sel_off = (col_fin >> 4) * 32 + ((col_fin & 7) >> 1) * 8 + ((col_fin >> 3) & 1) * 4 + (col_fin & 1) * 2;
    const float hn_fin = __uint_as_float((uint32_t)SM_(uint16_t, OFF_XSEL + sel_off) << 16), h_fin = __uint_as_float((uint32_t)SM_(uint16_t, OFF_HSEL + sel_off) << 16);
    {
      const uint4* src = &p.s->ypart[(16 + (tid >> 1)) * 256 + pfin];
      uint4 v = make_uint4(0, 0, 0, 0);
      if (warp < 7) {
        delay_clk<HOP3_DELAY>();
        uint32_t n = 0;
        bool ok = false;
        do {
          pkt_ld128_if(v, src, !ok);
          ok = pair_code(v.x, v.y) == cd && pair_code(v.z, v.w) == cd;
        } while (!__all_sync(0xffffffffu, ok) && ++n < SPIN_LIMIT);
      }
      CT(13);
      const float y0 = __uint_as_float(v.x & ~1u), y1 = __uint_as_float(v.y & ~1u), y2 = __uint_as_float(v.z & ~1u), y3 = __uint_as_float(v.w & ~1u);
      const float a0 = ((lane & 2) ? y1 : y0) + __shfl_xor_sync(0xffffffffu, (lane & 2) ? y0 : y1, 2);
      const float a1 = ((lane & 2) ? y3 : y2) + __shfl_xor_sync(0xffffffffu, (lane & 2) ? y2 : y3, 2);
      float b = ((lane & 4) ? a1 : a0) + __shfl_xor_sync(0xffffffffu, (lane & 4) ? a0 : a1, 4);
      b += __shfl_xor_sync(0xffffffffu, b, 8);
      b += __shfl_xor_sync(0xffffffffu, b, 16);
      if (lane < 8) SM_(float, OFF_FIN + warp * 32 + lane * 4) = b;
    }
    bar_sync(NB_BOTH, 256);
    if (tid < 8) {
      float y = 0.f;
#pragma unroll
      for (int i = 0; i < 7; i++) y += SM_(float, OFF_FIN + i * 32 + tid * 4);
      p.out[(size_t)tsel * 1024 + col_fin] = __float2bfloat16_rn(h_fin + bf16r(hn_fin + bf16r(bf16r(y) * sig)));
      if (cid == 0 && tid == 0) st_relaxed32(&p.s->epoch, tag);
    }
    CT(14);
  }
}

__global__ void __launch_bounds__(384, 1) occupancy_probe_kernel() {}

typedef CUresult (*EncodeFn)(CUtensorMap*, CUtensorMapDataType, cuuint32_t, void*, const cuuint64_t*, const cuuint64_t*, const cuuint32_t*, const cuuint32_t*,
                             CUtensorMapInterleave, CUtensorMapSwizzle, CUtensorMapL2promotion, CUtensorMapFloatOOBfill);

static void make_tm(EncodeFn enc, CUtensorMap* tm, const void* ptr, uint64_t rows, uint64_t cols, uint32_t brows, uint32_t bcols, CUtensorMapSwizzle sw,
                    CUtensorMapL2promotion promo = CU_TENSOR_MAP_L2_PROMOTION_L2_256B) {
  cuuint64_t dims[2] = {cols, rows};
  cuuint64_t strides[1] = {cols * 2};
  cuuint32_t box[2] = {bcols, brows};
  cuuint32_t es[2] = {1, 1};
  enc(tm, CU_TENSOR_MAP_DATA_TYPE_BFLOAT16, 2, const_cast<void*>(ptr), dims, strides, box, es, CU_TENSOR_MAP_INTERLEAVE_NONE, sw,
      promo, CU_TENSOR_MAP_FLOAT_OOB_FILL_NONE);
}

extern "C" void kernel_launch(void* const* d_in, const int* in_sizes, int n_in, void* d_out, int out_size) {
  (void)in_sizes; (void)n_in; (void)out_size;
  static EncodeFn enc = nullptr;
  static void* abT = nullptr;
  static int map = 0;
  if (!enc) {
    void* fn = nullptr; cudaDriverEntryPointQueryResult st;
    cudaGetDriverEntryPoint("cuTensorMapEncodeTiled", &fn, cudaEnableDefault, &st);
    enc = (EncodeFn)fn;
    cudaGetSymbolAddress(&abT, g_scratch);
    cudaFuncSetAttribute(fnet_moe_kernel<0>, cudaFuncAttributeMaxDynamicSharedMemorySize, SMEM_TOTAL);
    cudaFuncSetAttribute(fnet_moe_kernel<1>, cudaFuncAttributeMaxDynamicSharedMemorySize, SMEM_TOTAL);
    cudaFuncSetAttribute(occupancy_probe_kernel, cudaFuncAttributeMaxDynamicSharedMemorySize, SMEM_TOTAL);
    cudaFuncSetAttribute(occupancy_probe_kernel, cudaFuncAttributeNonPortableClusterSizeAllowed, 1);
    auto max_clusters = [&](int size) {
      cudaLaunchConfig_t cfg = {};
      cfg.gridDim = dim3(128); cfg.blockDim = dim3(384); cfg.dynamicSmemBytes = SMEM_TOTAL;
      cudaLaunchAttribute at[1];
      at[0].id = cudaLaunchAttributeClusterDimension; at[0].val.clusterDim.x = size; at[0].val.clusterDim.y = 1; at[0].val.clusterDim.z = 1;
      cfg.attrs = at; cfg.numAttrs = 1;
      int ncl = 0;
      return cudaOccupancyMaxActiveClusters(&ncl, occupancy_probe_kernel, &cfg) == cudaSuccess ? ncl : 0;
    };
    int dev = 0, sms = 0;
    cudaGetDevice(&dev);
    cudaDeviceGetAttribute(&sms, cudaDevAttrMultiProcessorCount, dev);
    map = (!getenv("MAP1") && sms == 132 && max_clusters(2) == 66 && max_clusters(16) == 7) ? 0 : 1;
    (void)cudaGetLastError();
  }
  Params p;
  const bf16* x = (const bf16*)d_in[0];
  make_tm(enc, &p.tmD0, d_in[3], 1024, 1024, 128, 64, CU_TENSOR_MAP_SWIZZLE_128B);
  make_tm(enc, &p.tmD1, d_in[4], 1024, 1024, 128, 64, CU_TENSOR_MAP_SWIZZLE_128B);
  make_tm(enc, &p.tmX, x, 2048, 1024, 256, 64, CU_TENSOR_MAP_SWIZZLE_128B);
  make_tm(enc, &p.tmXr, x, 2048, 1024, 64, 64, CU_TENSOR_MAP_SWIZZLE_128B);
  make_tm(enc, &p.tmAbS, abT, 2048, 2048, 64, 64, CU_TENSOR_MAP_SWIZZLE_128B);
  make_tm(enc, &p.tmAbL, abT, 2048, 2048, 128, 64, CU_TENSOR_MAP_SWIZZLE_128B);
  make_tm(enc, &p.tmW0, d_in[1], 2048, 2048, 128, 64, CU_TENSOR_MAP_SWIZZLE_128B, W_PROMO);
  make_tm(enc, &p.tmW1, d_in[2], 2048, 2048, 128, 64, CU_TENSOR_MAP_SWIZZLE_128B, W_PROMO);
  {
    cuuint64_t dims[5] = {1024, 2, 4, 4, 64};
    cuuint64_t strides[4] = {2048, 8 * 2048, 2 * 2048, 32 * 2048};
    cuuint32_t box[5] = {64, 2, 4, 2, 1};
    cuuint32_t es[5] = {1, 1, 1, 1, 1};
    enc(&p.tmOut, CU_TENSOR_MAP_DATA_TYPE_BFLOAT16, 5, d_out, dims, strides, box, es, CU_TENSOR_MAP_INTERLEAVE_NONE, CU_TENSOR_MAP_SWIZZLE_128B,
        CU_TENSOR_MAP_L2_PROMOTION_NONE, CU_TENSOR_MAP_FLOAT_OOB_FILL_NONE);
  }
  make_tm(enc, &p.tmG, d_in[7], 1024, 3584, 128, 32, CU_TENSOR_MAP_SWIZZLE_64B, CU_TENSOR_MAP_L2_PROMOTION_L2_128B);
  make_tm(enc, &p.tmU, d_in[8], 1024, 3584, 128, 32, CU_TENSOR_MAP_SWIZZLE_64B, CU_TENSOR_MAP_L2_PROMOTION_L2_128B);
  make_tm(enc, &p.tmDn, d_in[9], 3584, 1024, 32, 64, CU_TENSOR_MAP_SWIZZLE_128B);
  p.x = x; p.Dre = (const bf16*)d_in[3]; p.Dim = (const bf16*)d_in[4];
  p.wr = (const bf16*)d_in[6]; p.wdown = (const bf16*)d_in[9]; p.wgate = (const bf16*)d_in[7]; p.wup = (const bf16*)d_in[8];
  p.out = (bf16*)d_out; p.s = (Scratch*)abT;
  if (map == 1) fnet_moe_kernel<1><<<128, 384, SMEM_TOTAL>>>(p);
  else fnet_moe_kernel<0><<<132, 384, SMEM_TOTAL>>>(p);
}
```

```cpp
#include <cuda.h>
#include <cuda_runtime.h>
#include <cuda_bf16.h>
#include <stdint.h>
#include <stdlib.h>
#include <type_traits>

typedef __nv_bfloat16 bf16;

#define REG_C 232
#define REG_P 40
__device__ __forceinline__ int kblock(int tau, int j) {
  const int i = j - 4, c = (i * 37) >> 8;
  return j < 4 ? tau * 4 + j : ((tau + 1 + i - 7 * c) & 7) * 4 + c;
}
#define HOP1_DELAY 150
#define HOP3_DELAY 300
#define BACKOFF_NS 0
#define SPEC_MIN 10
#define PF_K0 10
#define PF_N0 4
#define PF_K1 26
#define OUT_PACE_CLK 100
#define PUB_K1 22
#define NREG_H 5
#define MR_K0 28
__host__ __device__ constexpr int mr_k(int h) { return MR_K0 + 6 * (h >> 1) + 2 * (h & 1); }
constexpr int A_BYTES = 128 * 64 * 2;
constexpr int B_BYTES = 256 * 64 * 2;
constexpr int ST_BYTES = A_BYTES + B_BYTES;
constexpr int OFF_XCH = 4 * ST_BYTES;
constexpr int OFF_BAR = OFF_XCH + 32768;
constexpr int OFF_WR = OFF_BAR + 384;
constexpr int OFF_RS = OFF_WR + 384;
constexpr int OFF_PUB = OFF_RS + 640;
constexpr int OFF_MISC = OFF_PUB + 768;
constexpr int SMEM_TOTAL = OFF_MISC + 256;
constexpr int OFF_WSUM = OFF_MISC, OFF_TAG = OFF_MISC + 4;
constexpr int OFF_SEEN = OFF_MISC + 8;
constexpr int OFF_KV = OFF_MISC + 12;
constexpr int OFF_WKEY = OFF_MISC + 32;
constexpr int OFF_EXA = OFF_XCH;
constexpr int OFF_EXB = OFF_XCH + 4096;
__host__ __device__ constexpr int chunk_off(int c, int w) { return (c < 2 ? (c + 2) * ST_BYTES : OFF_XCH + (c - 2) * 16384) + w * 8192; }
__host__ __device__ constexpr int late_off(int i) { return i < 4 ? i * 16384 : 2 * ST_BYTES + A_BYTES + (i - 4) * 16384; }
__host__ __device__ constexpr int round_off(int h) { return h < NREG_H + 2 ? OFF_XCH + (h & 1) * 16384 : late_off(h - NREG_H - 2); }
__host__ __device__ constexpr int down_off(int i) { return late_off(6 - NREG_H + i); }
constexpr int OFF_PEER = ST_BYTES + A_BYTES;
constexpr int OFF_OUT = 3 * ST_BYTES + A_BYTES;
constexpr int OFF_XSEL = OFF_PEER;
constexpr int OFF_HSEL = OFF_PEER + 4096;
constexpr int OFF_GP = OFF_PEER + 8192;
constexpr int OFF_FIN = OFF_PEER + 9216;
__device__ __forceinline__ int slot_of(int k) { return k & 3; }
__device__ __forceinline__ int use_of(int k) { return k >> 2; }
enum { B_FULL = 0, B_EMPTY = 4, B_EPI = 8, B_STD = 12, B_EPI0B = 16, B_LATE = 17, B_STAT = 18, B_XCH = 19, B_MR = 20  , B_GU = 22,
       B_DN = 23, B_AUX = 24  , B_OUT = 26, B_KEY = 27, B_XS = 28, B_A20 = 29, B_STDA = 30, B_COUNT = 31 };
enum { NB_TURN0 = 1, NB_TURN1 = 2, NB_BOTH = 5, NB_AUX = 6 };

struct Scratch {
  bf16 abT[2048 * 2048];
  uint2 xstat[2048];
  uint2 dsum[2048];
  uint4 abflag[16 * 8 * 2];
  uint4 hstat[16 * 8 * 128];
  uint4 cand[16 * 256];
  uint4 key[8 * 16 * 2];
  uint4 ypart[128 * 256];
  uint32_t epoch;
};
__device__ __align__(1024) Scratch g_scratch;

struct Params {
  Scratch* s; bf16* out;
  const bf16* x; const bf16* Dre; const bf16* Dim; const bf16* wr; const bf16* wdown; const bf16* wgate; const bf16* wup;
  CUtensorMap tmX, tmD0, tmD1, tmXr, tmAbS, tmAbL, tmW0, tmW1, tmOut, tmG, tmU, tmDn;
};

#define SPIN_LIMIT (1u << 14)
#define MBAR_LIMIT (1u << 10)
constexpr int PROLOGUE_CLK = 1800;
#define GATHER_NS 400
#define PF_R1 99
#define PF_START3_CLK 43000
#define W_PROMO CU_TENSOR_MAP_L2_PROMOTION_L2_128B
#define PF_R0 16
#define PF_STEP_CLK 300
#define PF_START2_CLK 26000
#define PF_STEP2_CLK 600
#define MOE_PACE_CLK 300
constexpr int IDLE_WAIT_CLK = 1200;
__device__ __forceinline__ uint32_t smem_u32(const void* p) { return (uint32_t)__cvta_generic_to_shared(p); }
__device__ __forceinline__ void mbar_init(uint32_t bar, uint32_t cnt) { asm volatile("mbarrier.init.shared::cta.b64 [%0], %1;" :: "r"(bar), "r"(cnt) : "memory"); }
__device__ __forceinline__ void mbar_expect_tx(uint32_t bar, uint32_t bytes) { asm volatile("mbarrier.arrive.expect_tx.shared::cta.b64 _, [%0], %1;" :: "r"(bar), "r"(bytes) : "memory"); }
__device__ __forceinline__ void mbar_arrive(uint32_t bar) { asm volatile("mbarrier.arrive.shared::cta.b64 _, [%0];" :: "r"(bar) : "memory"); }
__device__ __forceinline__ void mbar_wait(uint32_t bar, uint32_t parity) {
  uint32_t ok, n = 0;
  do {
    asm volatile("{\n.reg .pred p;\nmbarrier.try_wait.parity.shared::cta.b64 p, [%1], %2;\nselp.u32 %0, 1, 0, p;\n}\n" : "=r"(ok) : "r"(bar), "r"(parity) : "memory");
  } while (!ok && ++n < MBAR_LIMIT);
}
__device__ __forceinline__ bool mbar_test(uint32_t bar, uint32_t parity) {
  uint32_t ok;
  asm volatile("{\n.reg .pred p;\nmbarrier.test_wait.parity.shared::cta.b64 p, [%1], %2;\nselp.u32 %0, 1, 0, p;\n}\n" : "=r"(ok) : "r"(bar), "r"(parity) : "memory");
  return ok != 0;
}
__device__ __forceinline__ void mbar_wait_cluster(uint32_t bar, uint32_t parity) {
  uint32_t ok, n = 0;
  do {
    asm volatile("{\n.reg .pred p;\nmbarrier.try_wait.parity.acquire.cluster.shared::cta.b64 p, [%1], %2;\nselp.u32 %0, 1, 0, p;\n}\n" : "=r"(ok) : "r"(bar), "r"(parity) : "memory");
  } while (!ok && ++n < MBAR_LIMIT);
}
__device__ __forceinline__ void tma_load_2d(uint32_t dst, const CUtensorMap* tm, uint32_t bar, int c0, int c1) {
  asm volatile("cp.async.bulk.tensor.2d.shared::cluster.global.mbarrier::complete_tx::bytes [%0], [%1, {%3, %4}], [%2];"
    :: "r"(dst), "l"(tm), "r"(bar), "r"(c0), "r"(c1) : "memory");
}
__device__ __forceinline__ void tma_load_2d_hint(uint32_t dst, const CUtensorMap* tm, uint32_t bar, int c0, int c1, uint64_t pol) {
  asm volatile("cp.async.bulk.tensor.2d.shared::cluster.global.mbarrier::complete_tx::bytes.L2::cache_hint [%0], [%1, {%3, %4}], [%2], %5;"
    :: "r"(dst), "l"(tm), "r"(bar), "r"(c0), "r"(c1), "l"(pol) : "memory");
}
__device__ __forceinline__ uint64_t policy_evict_first() { uint64_t p; asm volatile("createpolicy.fractional.L2::evict_first.b64 %0, 1.0;" : "=l"(p)); return p; }
__device__ __forceinline__ void tma_store_2d(const CUtensorMap* tm, uint32_t src, int c0, int c1) {
  asm volatile("cp.async.bulk.tensor.2d.global.shared::cta.bulk_group [%0, {%2, %3}], [%1];" :: "l"(tm), "r"(src), "r"(c0), "r"(c1) : "memory");
}
__device__ __forceinline__ void bulk_load(uint32_t dst, const void* src, uint32_t bytes, uint32_t bar) {
  asm volatile("cp.async.bulk.shared::cluster.global.mbarrier::complete_tx::bytes [%0], [%1], %2, [%3];" :: "r"(dst), "l"(src), "r"(bytes), "r"(bar) : "memory");
}
__device__ __forceinline__ void bulk_commit() { asm volatile("cp.async.bulk.commit_group;" ::: "memory"); }
__device__ __forceinline__ void bulk_wait_all() { asm volatile("cp.async.bulk.wait_group 0;" ::: "memory"); }
__device__ __forceinline__ void fence_async_smem() { asm volatile("fence.proxy.async.shared::cta;" ::: "memory"); }
__device__ __forceinline__ void wgmma_fence() { asm volatile("wgmma.fence.sync.aligned;" ::: "memory"); }
__device__ __forceinline__ void wgmma_commit() { asm volatile("wgmma.commit_group.sync.aligned;" ::: "memory"); }
__device__ __forceinline__ void wgmma_wait0() { asm volatile("wgmma.wait_group.sync.aligned 0;" ::: "memory"); }
__device__ __forceinline__ void bar_sync(int id, int n) { asm volatile("bar.sync %0, %1;" :: "r"(id), "r"(n) : "memory"); }
__device__ __forceinline__ void bar_arrive(int id, int n) { asm volatile("bar.arrive %0, %1;" :: "r"(id), "r"(n) : "memory"); }
template<int R> __device__ __forceinline__ void reg_inc() { asm volatile("setmaxnreg.inc.sync.aligned.u32 %0;" :: "n"(R)); }
template<int R> __device__ __forceinline__ void reg_dec() { asm volatile("setmaxnreg.dec.sync.aligned.u32 %0;" :: "n"(R)); }
__device__ __forceinline__ bool elect_one() {
  uint32_t p;
  asm volatile("{\n.reg .pred q;\nelect.sync _|q, 0xffffffff;\nselp.u32 %0, 1, 0, q;\n}\n" : "=r"(p));
  return p != 0;
}
__device__ __forceinline__ uint32_t mapa(uint32_t addr, uint32_t cta) { uint32_t r; asm volatile("mapa.shared::cluster.u32 %0, %1, %2;" : "=r"(r) : "r"(addr), "r"(cta)); return r; }
__device__ __forceinline__ void st_async_v4(uint32_t addr, uint32_t bar, uint32_t a, uint32_t b, uint32_t c, uint32_t d) {
  asm volatile("st.async.weak.shared::cluster.mbarrier::complete_tx::bytes.v4.b32 [%0], {%2, %3, %4, %5}, [%1];" :: "r"(addr), "r"(bar), "r"(a), "r"(b), "r"(c), "r"(d) : "memory");
}
__device__ __forceinline__ void stsm_x4(uint32_t addr, uint32_t a, uint32_t b, uint32_t c, uint32_t d) {
  asm volatile("stmatrix.sync.aligned.m8n8.x4.shared.b16 [%0], {%1, %2, %3, %4};" :: "r"(addr), "r"(a), "r"(b), "r"(c), "r"(d));
}
__device__ __forceinline__ uint4 lds128_v(uint32_t addr) { uint4 v; asm volatile("ld.shared.v4.b32 {%0, %1, %2, %3}, [%4];" : "=r"(v.x), "=r"(v.y), "=r"(v.z), "=r"(v.w) : "r"(addr)); return v; }
extern __shared__ __align__(1024) uint8_t smem_raw[];
template<class T> __device__ __forceinline__ T& smem_at(uint32_t addr) { return *reinterpret_cast<T*>(__cvta_shared_to_generic(addr)); }
#define SM_(T, off) smem_at<T>(sb + (off))
__device__ __forceinline__ uint4 ldg_nc128(const void* p) { uint4 v; asm volatile("ld.global.nc.v4.b32 {%0, %1, %2, %3}, [%4];" : "=r"(v.x), "=r"(v.y), "=r"(v.z), "=r"(v.w) : "l"(p)); return v; }
__device__ __forceinline__ void pkt_st128(void* p, uint32_t a, uint32_t b, uint32_t c, uint32_t d) {
  asm volatile("{\n.reg .b128 v;\n.reg .b64 lo, hi;\nmov.b64 lo, {%1, %2};\nmov.b64 hi, {%3, %4};\nmov.b128 v, {lo, hi};\nst.relaxed.gpu.global.b128 [%0], v;\n}\n"
    :: "l"(p), "r"(a), "r"(b), "r"(c), "r"(d) : "memory");
}
__device__ __forceinline__ uint4 pkt_ld128(const void* p) {
  uint4 r;
  asm volatile("{\n.reg .b128 v;\n.reg .b64 lo, hi;\nld.relaxed.gpu.global.b128 v, [%4];\nmov.b128 {lo, hi}, v;\nmov.b64 {%0, %1}, lo;\nmov.b64 {%2, %3}, hi;\n}\n"
    : "=r"(r.x), "=r"(r.y), "=r"(r.z), "=r"(r.w) : "l"(p) : "memory");
  return r;
}
__device__ __forceinline__ void pkt_ld128_if(uint4& r, const void* p, bool cond) {
  asm volatile("{\n.reg .pred q;\nsetp.ne.b32 q, %5, 0;\n@q ld.relaxed.gpu.global.v4.b32 {%0, %1, %2, %3}, [%4];\n}\n"
    : "+r"(r.x), "+r"(r.y), "+r"(r.z), "+r"(r.w) : "l"(p), "r"((uint32_t)cond) : "memory");
}
__device__ __forceinline__ void pkt_st64(void* p, uint32_t a, uint32_t b) {
  asm volatile("{\n.reg .b64 v;\nmov.b64 v, {%1, %2};\nst.relaxed.gpu.global.b64 [%0], v;\n}\n" :: "l"(p), "r"(a), "r"(b) : "memory");
}
__device__ __forceinline__ uint2 pkt_ld64(const void* p) {
  uint2 r;
  asm volatile("{\n.reg .b64 v;\nld.relaxed.gpu.global.b64 v, [%2];\nmov.b64 {%0, %1}, v;\n}\n" : "=r"(r.x), "=r"(r.y) : "l"(p) : "memory");
  return r;
}
__device__ __forceinline__ uint32_t ld_relaxed32(const void* p) { uint32_t v; asm volatile("ld.relaxed.gpu.global.b32 %0, [%1];" : "=r"(v) : "l"(p) : "memory"); return v; }
__device__ __forceinline__ void st_relaxed32(void* p, uint32_t v) { asm volatile("st.relaxed.gpu.global.b32 [%0], %1;" :: "l"(p), "r"(v) : "memory"); }
__device__ __forceinline__ void backoff() { if (BACKOFF_NS) __nanosleep(BACKOFF_NS); }
__device__ __forceinline__ uint32_t code_of(uint32_t tag) { return tag % 3u + 1u; }
__device__ __forceinline__ uint32_t with_bit(float v, uint32_t bit) { return (__float_as_uint(v) & ~1u) | (bit & 1u); }
__device__ __forceinline__ uint32_t pair_code(uint32_t a, uint32_t b) { return (a & 1u) | ((b & 1u) << 1); }
__device__ __forceinline__ uint32_t pack_bf16(float lo, float hi) { uint32_t r; asm("cvt.rn.bf16x2.f32 %0, %1, %2;" : "=r"(r) : "f"(hi), "f"(lo)); return r; }
__device__ __forceinline__ float bf_lo(uint32_t v) { return __uint_as_float(v << 16); }
__device__ __forceinline__ float bf_hi(uint32_t v) { return __uint_as_float(v & 0xFFFF0000u); }
__device__ __forceinline__ float bf16r(float x) { return __uint_as_float(pack_bf16(0.f, x)); }
__device__ __forceinline__ uint32_t badd2(uint32_t a, uint32_t b) { uint32_t r; asm("add.rn.bf16x2 %0, %1, %2;" : "=r"(r) : "r"(a), "r"(b)); return r; }
__device__ __forceinline__ uint32_t bmul2(uint32_t a, uint32_t b) { uint32_t r; asm("mul.rn.bf16x2 %0, %1, %2;" : "=r"(r) : "r"(a), "r"(b)); return r; }
__device__ __forceinline__ float warp_sum(float v) {
#pragma unroll
  for (int o = 16; o > 0; o >>= 1) v += __shfl_xor_sync(0xffffffffu, v, o);
  return v;
}
__device__ __forceinline__ uint64_t make_desc(uint32_t addr) {
  return (uint64_t)((addr & 0x3FFFF) >> 4) | ((uint64_t)1 << 16) | ((uint64_t)64 << 32) | ((uint64_t)1 << 62);
}
__device__ __forceinline__ uint64_t make_desc_noswz(uint32_t addr) {
  return (uint64_t)((addr & 0x3FFFF) >> 4) | ((uint64_t)8 << 16) | ((uint64_t)16 << 32);
}
__device__ __forceinline__ void wgmma_n256(float (&d)[128], uint64_t da, uint64_t db, int scale_d) {
  asm volatile("{\n.reg .pred p;\nsetp.ne.b32 p, %130, 0;\n"
    "wgmma.mma_async.sync.aligned.m64n256k16.f32.bf16.bf16 "
    "{%0, %1, %2, %3, %4, %5, %6, %7, %8, %9, %10, %11, %12, %13, %14, %15, %16, %17, %18, %19, %20, %21, %22, %23, %24, %25, %26, %27, %28, %29, %30, %31, "
    "%32, %33, %34, %35, %36, %37, %38, %39, %40, %41, %42, %43, %44, %45, %46, %47, %48, %49, %50, %51, %52, %53, %54, %55, %56, %57, %58, %59, %60, %61, %62, %63, "
    "%64, %65, %66, %67, %68, %69, %70, %71, %72, %73, %74, %75, %76, %77, %78, %79, %80, %81, %82, %83, %84, %85, %86, %87, %88, %89, %90, %91, %92, %93, %94, %95, "
    "%96, %97, %98, %99, %100, %101, %102, %103, %104, %105, %106, %107, %108, %109, %110, %111, %112, %113, %114, %115, %116, %117, %118, %119, %120, %121, %122, %123, %124, %125, %126, %127}, "
    "%128, %129, p, 1, 1, 0, 0;\n}\n"
    : "+f"(d[0]), "+f"(d[1]), "+f"(d[2]), "+f"(d[3]), "+f"(d[4]), "+f"(d[5]), "+f"(d[6]), "+f"(d[7]),
      "+f"(d[8]), "+f"(d[9]), "+f"(d[10]), "+f"(d[11]), "+f"(d[12]), "+f"(d[13]), "+f"(d[14]), "+f"(d[15]),
      "+f"(d[16]), "+f"(d[17]), "+f"(d[18]), "+f"(d[19]), "+f"(d[20]), "+f"(d[21]), "+f"(d[22]), "+f"(d[23]),
      "+f"(d[24]), "+f"(d[25]), "+f"(d[26]), "+f"(d[27]), "+f"(d[28]), "+f"(d[29]), "+f"(d[30]), "+f"(d[31]),
      "+f"(d[32]), "+f"(d[33]), "+f"(d[34]), "+f"(d[35]), "+f"(d[36]), "+f"(d[37]), "+f"(d[38]), "+f"(d[39]),
      "+f"(d[40]), "+f"(d[41]), "+f"(d[42]), "+f"(d[43]), "+f"(d[44]), "+f"(d[45]), "+f"(d[46]), "+f"(d[47]),
      "+f"(d[48]), "+f"(d[49]), "+f"(d[50]), "+f"(d[51]), "+f"(d[52]), "+f"(d[53]), "+f"(d[54]), "+f"(d[55]),
      "+f"(d[56]), "+f"(d[57]), "+f"(d[58]), "+f"(d[59]), "+f"(d[60]), "+f"(d[61]), "+f"(d[62]), "+f"(d[63]),
      "+f"(d[64]), "+f"(d[65]), "+f"(d[66]), "+f"(d[67]), "+f"(d[68]), "+f"(d[69]), "+f"(d[70]), "+f"(d[71]),
      "+f"(d[72]), "+f"(d[73]), "+f"(d[74]), "+f"(d[75]), "+f"(d[76]), "+f"(d[77]), "+f"(d[78]), "+f"(d[79]),
      "+f"(d[80]), "+f"(d[81]), "+f"(d[82]), "+f"(d[83]), "+f"(d[84]), "+f"(d[85]), "+f"(d[86]), "+f"(d[87]),
      "+f"(d[88]), "+f"(d[89]), "+f"(d[90]), "+f"(d[91]), "+f"(d[92]), "+f"(d[93]), "+f"(d[94]), "+f"(d[95]),
      "+f"(d[96]), "+f"(d[97]), "+f"(d[98]), "+f"(d[99]), "+f"(d[100]), "+f"(d[101]), "+f"(d[102]), "+f"(d[103]),
      "+f"(d[104]), "+f"(d[105]), "+f"(d[106]), "+f"(d[107]), "+f"(d[108]), "+f"(d[109]), "+f"(d[110]), "+f"(d[111]),
      "+f"(d[112]), "+f"(d[113]), "+f"(d[114]), "+f"(d[115]), "+f"(d[116]), "+f"(d[117]), "+f"(d[118]), "+f"(d[119]),
      "+f"(d[120]), "+f"(d[121]), "+f"(d[122]), "+f"(d[123]), "+f"(d[124]), "+f"(d[125]), "+f"(d[126]), "+f"(d[127])
    : "l"(da), "l"(db), "r"(scale_d));
}
__device__ __forceinline__ void wgmma_n256_rs(float (&d)[128], uint32_t a0, uint32_t a1, uint32_t a2, uint32_t a3, uint64_t db, int scale_d) {
  asm volatile("{\n.reg .pred p;\nsetp.ne.b32 p, %133, 0;\n"
    "wgmma.mma_async.sync.aligned.m64n256k16.f32.bf16.bf16 "
    "{%0, %1, %2, %3, %4, %5, %6, %7, %8, %9, %10, %11, %12, %13, %14, %15, %16, %17, %18, %19, %20, %21, %22, %23, %24, %25, %26, %27, %28, %29, %30, %31, "
    "%32, %33, %34, %35, %36, %37, %38, %39, %40, %41, %42, %43, %44, %45, %46, %47, %48, %49, %50, %51, %52, %53, %54, %55, %56, %57, %58, %59, %60, %61, %62, %63, "
    "%64, %65, %66, %67, %68, %69, %70, %71, %72, %73, %74, %75, %76, %77, %78, %79, %80, %81, %82, %83, %84, %85, %86, %87, %88, %89, %90, %91, %92, %93, %94, %95, "
    "%96, %97, %98, %99, %100, %101, %102, %103, %104, %105, %106, %107, %108, %109, %110, %111, %112, %113, %114, %115, %116, %117, %118, %119, %120, %121, %122, %123, %124, %125, %126, %127}, "
    "{%128, %129, %130, %131}, %132, p, 1, 1, 0;\n}\n"
    : "+f"(d[0]), "+f"(d[1]), "+f"(d[2]), "+f"(d[3]), "+f"(d[4]), "+f"(d[5]), "+f"(d[6]), "+f"(d[7]),
      "+f"(d[8]), "+f"(d[9]), "+f"(d[10]), "+f"(d[11]), "+f"(d[12]), "+f"(d[13]), "+f"(d[14]), "+f"(d[15]),
      "+f"(d[16]), "+f"(d[17]), "+f"(d[18]), "+f"(d[19]), "+f"(d[20]), "+f"(d[21]), "+f"(d[22]), "+f"(d[23]),
      "+f"(d[24]), "+f"(d[25]), "+f"(d[26]), "+f"(d[27]), "+f"(d[28]), "+f"(d[29]), "+f"(d[30]), "+f"(d[31]),
      "+f"(d[32]), "+f"(d[33]), "+f"(d[34]), "+f"(d[35]), "+f"(d[36]), "+f"(d[37]), "+f"(d[38]), "+f"(d[39]),
      "+f"(d[40]), "+f"(d[41]), "+f"(d[42]), "+f"(d[43]), "+f"(d[44]), "+f"(d[45]), "+f"(d[46]), "+f"(d[47]),
      "+f"(d[48]), "+f"(d[49]), "+f"(d[50]), "+f"(d[51]), "+f"(d[52]), "+f"(d[53]), "+f"(d[54]), "+f"(d[55]),
      "+f"(d[56]), "+f"(d[57]), "+f"(d[58]), "+f"(d[59]), "+f"(d[60]), "+f"(d[61]), "+f"(d[62]), "+f"(d[63]),
      "+f"(d[64]), "+f"(d[65]), "+f"(d[66]), "+f"(d[67]), "+f"(d[68]), "+f"(d[69]), "+f"(d[70]), "+f"(d[71]),
      "+f"(d[72]), "+f"(d[73]), "+f"(d[74]), "+f"(d[75]), "+f"(d[76]), "+f"(d[77]), "+f"(d[78]), "+f"(d[79]),
      "+f"(d[80]), "+f"(d[81]), "+f"(d[82]), "+f"(d[83]), "+f"(d[84]), "+f"(d[85]), "+f"(d[86]), "+f"(d[87]),
      "+f"(d[88]), "+f"(d[89]), "+f"(d[90]), "+f"(d[91]), "+f"(d[92]), "+f"(d[93]), "+f"(d[94]), "+f"(d[95]),
      "+f"(d[96]), "+f"(d[97]), "+f"(d[98]), "+f"(d[99]), "+f"(d[100]), "+f"(d[101]), "+f"(d[102]), "+f"(d[103]),
      "+f"(d[104]), "+f"(d[105]), "+f"(d[106]), "+f"(d[107]), "+f"(d[108]), "+f"(d[109]), "+f"(d[110]), "+f"(d[111]),
      "+f"(d[112]), "+f"(d[113]), "+f"(d[114]), "+f"(d[115]), "+f"(d[116]), "+f"(d[117]), "+f"(d[118]), "+f"(d[119]),
      "+f"(d[120]), "+f"(d[121]), "+f"(d[122]), "+f"(d[123]), "+f"(d[124]), "+f"(d[125]), "+f"(d[126]), "+f"(d[127])
    : "r"(a0), "r"(a1), "r"(a2), "r"(a3), "l"(db), "r"(scale_d));
}
__device__ __forceinline__ void wgmma_n128(float (&d)[64], uint64_t da, uint64_t db) {
  asm volatile("{\n.reg .pred p;\nsetp.ne.b32 p, 1, 0;\n"
    "wgmma.mma_async.sync.aligned.m64n128k16.f32.bf16.bf16 "
    "{%0, %1, %2, %3, %4, %5, %6, %7, %8, %9, %10, %11, %12, %13, %14, %15, %16, %17, %18, %19, %20, %21, %22, %23, %24, %25, %26, %27, %28, %29, %30, %31, %32, %33, %34, %35, %36, %37, %38, %39, %40, %41, %42, %43, %44, %45, %46, %47, %48, %49, %50, %51, %52, %53, %54, %55, %56, %57, %58, %59, %60, %61, %62, %63}, "
    "%64, %65, p, 1, 1, 0, 0;\n}\n"
    : "+f"(d[0]), "+f"(d[1]), "+f"(d[2]), "+f"(d[3]), "+f"(d[4]), "+f"(d[5]), "+f"(d[6]), "+f"(d[7]), "+f"(d[8]), "+f"(d[9]), "+f"(d[10]), "+f"(d[11]), "+f"(d[12]), "+f"(d[13]), "+f"(d[14]), "+f"(d[15]), "+f"(d[16]), "+f"(d[17]), "+f"(d[18]), "+f"(d[19]), "+f"(d[20]), "+f"(d[21]), "+f"(d[22]), "+f"(d[23]), "+f"(d[24]), "+f"(d[25]), "+f"(d[26]), "+f"(d[27]), "+f"(d[28]), "+f"(d[29]), "+f"(d[30]), "+f"(d[31]), "+f"(d[32]), "+f"(d[33]), "+f"(d[34]), "+f"(d[35]), "+f"(d[36]), "+f"(d[37]), "+f"(d[38]), "+f"(d[39]), "+f"(d[40]), "+f"(d[41]), "+f"(d[42]), "+f"(d[43]), "+f"(d[44]), "+f"(d[45]), "+f"(d[46]), "+f"(d[47]), "+f"(d[48]), "+f"(d[49]), "+f"(d[50]), "+f"(d[51]), "+f"(d[52]), "+f"(d[53]), "+f"(d[54]), "+f"(d[55]), "+f"(d[56]), "+f"(d[57]), "+f"(d[58]), "+f"(d[59]), "+f"(d[60]), "+f"(d[61]), "+f"(d[62]), "+f"(d[63])
    : "l"(da), "l"(db));
}
__device__ __forceinline__ void fence_acc64(float (&d)[64]) {
#pragma unroll
  for (int i = 0; i < 64; i++) asm volatile("" : "+f"(d[i]) :: "memory");
}
__device__ __forceinline__ void fence_acc(float (&d)[128]) {
#pragma unroll
  for (int i = 0; i < 128; i++) asm volatile("" : "+f"(d[i]) :: "memory");
}

template<int N, int I = 0, class F> __device__ __forceinline__ void static_for(F&& f) {
  if constexpr (I < N) { f(std::integral_constant<int, I>()); static_for<N, I + 1>(f); }
}

__device__ __forceinline__ void ldsm_x4_t(uint32_t addr, uint32_t& a, uint32_t& b, uint32_t& c, uint32_t& d) {
  asm volatile("ldmatrix.sync.aligned.m8n8.x4.trans.shared.b16 {%0, %1, %2, %3}, [%4];" : "=r"(a), "=r"(b), "=r"(c), "=r"(d) : "r"(addr));
}
__device__ __forceinline__ void sts128(uint32_t addr, uint32_t a, uint32_t b, uint32_t c, uint32_t d) {
  asm volatile("st.shared.v4.b32 [%0], {%1, %2, %3, %4};" :: "r"(addr), "r"(a), "r"(b), "r"(c), "r"(d));
}
__device__ __forceinline__ void mma16816(float (&c)[4], uint32_t a0, uint32_t a1, uint32_t a2, uint32_t a3, uint32_t b0, uint32_t b1) {
  asm volatile("mma.sync.aligned.m16n8k16.row.col.f32.bf16.bf16.f32 {%0, %1, %2, %3}, {%4, %5, %6, %7}, {%8, %9}, {%0, %1, %2, %3};"
      : "+f"(c[0]), "+f"(c[1]), "+f"(c[2]), "+f"(c[3]) : "r"(a0), "r"(a1), "r"(a2), "r"(a3), "r"(b0), "r"(b1));
}
__device__ __forceinline__ void mma1688(float (&c)[4], uint32_t a0, uint32_t a1, uint32_t b0) {
  asm volatile("mma.sync.aligned.m16n8k8.row.col.f32.bf16.bf16.f32 {%0, %1, %2, %3}, {%4, %5}, {%6}, {%0, %1, %2, %3};"
      : "+f"(c[0]), "+f"(c[1]), "+f"(c[2]), "+f"(c[3]) : "r"(a0), "r"(a1), "r"(b0));
}
template<class T> __device__ __forceinline__ void pin(T*& v) { asm volatile("" : "+l"(v)); }
__device__ __forceinline__ void pin(uint32_t& v) { asm volatile("" : "+r"(v)); }
__device__ __forceinline__ uint32_t bfma2(uint32_t a, uint32_t b, uint32_t c) { uint32_t r; asm("fma.rn.bf16x2 %0, %1, %2, %3;" : "=r"(r) : "r"(a), "r"(b), "r"(c)); return r; }
__device__ __forceinline__ void tma_store_5d(const CUtensorMap* tm, uint32_t src, int c0, int c3, int c4) {
  asm volatile("cp.async.bulk.tensor.5d.global.shared::cta.bulk_group [%0, {%2, %3, %3, %4, %5}], [%1];" :: "l"(tm), "r"(src), "r"(c0), "r"(0), "r"(c3), "r"(c4) : "memory");
}
__device__ __forceinline__ float rcp_fast(float x) { float r; asm("rcp.approx.ftz.f32 %0, %1;" : "=f"(r) : "f"(x)); return r; }
__device__ __forceinline__ float sqrt_fast(float x) { float r; asm("sqrt.approx.ftz.f32 %0, %1;" : "=f"(r) : "f"(x)); return r; }
__device__ __forceinline__ float ln_sd(float var) { return bf16r(sqrt_fast(bf16r(bf16r(fmaxf(var, 0.f)) + 1e-5f))); }
__device__ __forceinline__ uint32_t norm2(uint32_t h, uint32_t neg_mean2, float inv_sd) {
  const uint32_t d = badd2(h, neg_mean2);
  return pack_bf16(bf_lo(d) * inv_sd, bf_hi(d) * inv_sd);
}
template<int N> __device__ __forceinline__ void delay_clk() {
  if constexpr (N > 0) { const uint32_t t0 = clock(); while ((uint32_t)clock() - t0 < N) {} }
}
template<int V> using IC = std::integral_constant<int, V>;

#define CT(slot) do {} while (0)
#define PT(slot) do {} while (0)

template<int MAP>
__global__ void __cluster_dims__(2, 1, 1) __launch_bounds__(384, 1)
fnet_moe_kernel(const __grid_constant__ Params p) {
  uint32_t sb;
  asm volatile("mov.u32 %0, %1;" : "=r"(sb) : "r"(smem_u32(smem_raw)));
  const int m = blockIdx.x & 1;
  int tau, eps;
  bool idle = false;
  if (MAP == 0) {
    uint32_t smid;
    asm volatile("mov.u32 %0, %%smid;" : "=r"(smid));
    const int c = smid >> 1, e7 = ((c - 32) * 37) >> 8;
    idle = c == 60 || c == 61;
    tau = c < 32 ? (c & 7) : (c < 60 ? c - 31 - 7 * e7 : 0);
    eps = c < 32 ? (c >> 3) : (c < 60 ? 4 + e7 : c - 58);
  } else {
    tau = (blockIdx.x >> 1) & 7; eps = blockIdx.x >> 4;
  }
  const int cid = tau * 16 + eps * 2 + m;
  const bool moe = tau > 0;
  auto BAR = [&](int i) { return sb + OFF_BAR + 8 * i; };
  const CUtensorMap* tmD = m ? &p.tmD1 : &p.tmD0;
  const uint64_t pol_ef = policy_evict_first();
#define LOAD_STREAM(d, tm, bar, c0, c1) tma_load_2d_hint(d, tm, bar, c0, c1, pol_ef)
  if (threadIdx.x < 32 && !idle) {
    if (elect_one()) {
#pragma unroll
      for (int k = 0; k < 4; k++) mbar_init(BAR(B_FULL + k), 1);
      asm volatile("fence.mbarrier_init.release.cluster;" ::: "memory");
#pragma unroll
      for (int k = 0; k < 4; k++) mbar_expect_tx(BAR(B_FULL + k), ST_BYTES);
    }
    PT(50);
    if (elect_one()) {
      tma_load_2d(sb + A_BYTES, &p.tmX, BAR(B_FULL), 0, tau * 256);
      LOAD_STREAM(sb, tmD, BAR(B_FULL), 0, eps * 128);
    }
    PT(52);
    if (elect_one()) {
#pragma unroll
      for (int k = 1; k < 4; k++) {
        tma_load_2d(sb + k * ST_BYTES + A_BYTES, &p.tmX, BAR(B_FULL + k), k * 64, tau * 256);
        LOAD_STREAM(sb + k * ST_BYTES, tmD, BAR(B_FULL + k), k * 64, eps * 128);
      }
    }
    PT(0);
  }
  __syncwarp();
  const int warp = __shfl_sync(0xffffffffu, threadIdx.x >> 5, 0);
  const int tid = __shfl_sync(0xffffffffu, threadIdx.x, threadIdx.x & 31), lane = tid & 31;
  if (idle) {
    __nanosleep(4000);
    const uint32_t tg = ld_relaxed32(&p.s->epoch) + 1;
    uint32_t n = 0;
    do { __nanosleep(1000); } while (!__all_sync(0xffffffffu, pkt_ld64(&p.s->xstat[(tid & 127) * 16]).y == tg) && ++n < 4096);
    return;
  }
  if (warp == 8) {
    if (elect_one()) {
#pragma unroll
      for (int b = B_EMPTY; b < B_COUNT; b++)
        mbar_init(BAR(b), b < B_EPI ? 2 : (b == B_EPI || b == B_EPI0B) ? 4 : (b < B_STD || b == B_OUT) ? 8 : (b == B_STAT || b == B_XS) ? 3 : 1);
      asm volatile("fence.mbarrier_init.release.cluster;" ::: "memory");
      mbar_expect_tx(BAR(B_XCH), 32768);
      SM_(uint32_t, OFF_SEEN) = 0;
    }
  }
  __syncthreads();

  if (warp >= 8) {
    reg_dec<REG_P>();
    asm volatile("barrier.cluster.arrive.relaxed.aligned;" ::: "memory");
    const int abrow = m * 1024 + eps * 128;
    const int f0 = (cid - 16) * 32;
    if (warp == 8) {
      const CUtensorMap* tmW = m ? &p.tmW1 : &p.tmW0;
      const int tA = tau * 256 + m * 128, tB = tau * 256 + (1 - m) * 128;
      uint32_t seen = 0;
#pragma unroll 1
      for (int k = 4; k < 48; k++) {
        const int s = slot_of(k);
        const uint32_t sa = sb + s * ST_BYTES, sbb = sa + A_BYTES;
        const int kb = kblock(tau, k - 16);
        mbar_wait(BAR(B_EMPTY + s), (use_of(k) & 1) ^ 1);
        PT(64 + k);
        if (elect_one()) {
          mbar_expect_tx(BAR(B_FULL + s), (k >> 1) == 9 ? B_BYTES : k == 20 ? ST_BYTES - 8192 : ST_BYTES);
          if (k < 16) {
            LOAD_STREAM(sa, tmD, BAR(B_FULL + s), k * 64, eps * 128);
            tma_load_2d(sbb, &p.tmX, BAR(B_FULL + s), k * 64, tau * 256);
          } else {
            LOAD_STREAM(sbb, tmW, BAR(B_FULL + s), kb * 64, tA);
            LOAD_STREAM(sbb + 16384, tmW, BAR(B_FULL + s), kb * 64, tB);
            if (k < 18) {
              tma_load_2d(sa, &p.tmXr, BAR(B_FULL + s), eps * 128, tA + s * 64);
              tma_load_2d(sa + 8192, &p.tmXr, BAR(B_FULL + s), eps * 128 + 64, tA + s * 64);
            }
          }
        }
        if (k >= 24) {
          uint32_t n = 0;
          while (!((seen >> kb) & 1) && ++n < SPIN_LIMIT * 16) seen = *(volatile uint32_t*)&SM_(uint32_t, OFF_SEEN);
          if (elect_one()) tma_load_2d(sa, &p.tmAbL, BAR(B_FULL + s), kb * 64, abrow);
        }
        if (k == PUB_K1 && elect_one()) mbar_arrive(BAR(B_LATE));
        if (moe && k >= PF_K0 && !(k & 1)) {
          const int i = k < PF_K1 ? (k - PF_K0) >> 1 : PF_N0 + ((k - PF_K1) >> 1);
          if ((k >= PF_K1 || i < PF_N0) && elect_one()) {
            if (i < 8) asm volatile("cp.async.bulk.prefetch.tensor.2d.L2.global.tile [%0, {%1, %2}];" :: "l"(m ? &p.tmU : &p.tmG), "r"(f0), "r"(i * 128) : "memory");
            else if (i < 12) asm volatile("cp.async.bulk.prefetch.L2.global [%0], %1;" :: "l"(p.wdown + (size_t)f0 * 1024 + (i - 8) * 8192), "r"(16384) : "memory");
          }
        }
        if (moe && k >= MR_K0) {
          const int i = k - MR_K0, r6 = (i * 43) >> 8, u = i - 6 * r6, h = 2 * r6 + (u >> 1);
          if (u < 4 && h < NREG_H + 2) {
            if (h < 2) mbar_wait(BAR(B_STD + 2 + h), 0);
            if (elect_one()) {
              const uint32_t bar = BAR(h < NREG_H ? B_MR + (h & 1) : B_GU);
              if (!(u & 1) && h <= NREG_H) mbar_expect_tx(bar, h < NREG_H ? 16384 : (8 - NREG_H) * 16384);
              LOAD_STREAM(sb + OFF_XCH + u * 8192, (u & 1) ? &p.tmU : &p.tmG, bar, f0, h * 128);
            }
          }
        }
      }
      if (moe) {
        mbar_wait(BAR(B_EMPTY + 0), 1);
        if (elect_one()) mbar_expect_tx(BAR(B_DN), 65536);
#pragma unroll 1
        for (int i = 0; i < 10 - NREG_H; i++) {
          if (i == 3) mbar_wait(BAR(B_EMPTY + 1), 1);
          if (i == 4) {
            mbar_wait(BAR(B_EMPTY + 2), 1);
            mbar_wait(BAR(B_XCH), 0);
          }
          const uint32_t dst = sb + late_off(i);
          if (elect_one()) {
            if (i < 6 - NREG_H) {
              LOAD_STREAM(dst, &p.tmG, BAR(B_GU), f0, (NREG_H + 2 + i) * 128);
              LOAD_STREAM(dst + 8192, &p.tmU, BAR(B_GU), f0, (NREG_H + 2 + i) * 128);
            } else {
#pragma unroll
              for (int b = 0; b < 4; b++) LOAD_STREAM(dst + b * 4096, &p.tmDn, BAR(B_DN), (4 * (i - 6 + NREG_H) + b) * 64, f0);
            }
          }
          const long long t0 = clock64();
          while (i < 9 - NREG_H && clock64() - t0 < MOE_PACE_CLK) {}
        }
      }
    } else {
      const int a = warp - 9;
      const long long t_aux = clock64() - PROLOGUE_CLK;
      auto stage = [&](const bf16* src, int g) {
        if (elect_one()) {
          mbar_expect_tx(BAR(B_AUX + g), 16384);
          bulk_load(sb + OFF_XCH + g * 16384, src + g * 8192, 16384, BAR(B_AUX + g));
        }
      };
      mbar_wait(BAR(B_FULL + 0), 0);
      if (a == 0) PT(1);
      if (a < 2) stage(p.x + (size_t)cid * 16 * 1024, a);
      const uint32_t tag = ld_relaxed32(&p.s->epoch) + 1;
      if (a == 2) {
        float s = 0.f;
#pragma unroll
        for (int q = 0; q < 4; q++) {
          const uint4 v = ldg_nc128(p.wr + (q * 32 + lane) * 8);
          s += ((bf_lo(v.x) + bf_hi(v.x)) + (bf_lo(v.y) + bf_hi(v.y))) + ((bf_lo(v.z) + bf_hi(v.z)) + (bf_lo(v.w) + bf_hi(v.w)));
          const int ch = q * 32 + lane - eps * 16;
          if (ch >= 0 && ch < 16) {
            SM_(uint32_t, OFF_WR + ch * 4) = v.x; SM_(uint32_t, OFF_WR + 80 + ch * 4) = v.y;
            SM_(uint32_t, OFF_WR + 160 + ch * 4) = v.z; SM_(uint32_t, OFF_WR + 240 + ch * 4) = v.w;
          }
        }
        s = warp_sum(s);
        if (lane == 0) { SM_(float, OFF_WSUM) = s; SM_(uint32_t, OFF_TAG) = tag; }
      }
#pragma unroll 1
      for (int it = 0; it < 4; it++) {
        const int g = it & 1;
        mbar_wait(BAR(B_AUX + g), it >> 1);
        if (a == 0) PT(2 + it);
        const uint32_t ad = sb + OFF_XCH + g * 16384 + (lane >> 2) * 2048;
        float s0 = 0.f, s1 = 0.f, q0 = 0.f, q1 = 0.f;
        auto row = [&](auto sq) {
#pragma unroll
          for (int i = 0; i < 11; i++) {
            if (i == 10 && a == 2) break;
            const uint4 v = lds128_v(ad + (((a * 44 + 4 * i + lane) & 127) << 4));
            const uint32_t ww[4] = {v.x, v.y, v.z, v.w};
#pragma unroll
            for (int z = 0; z < 4; z++) {
              const float d0 = bf_lo(ww[z]), d1 = bf_hi(ww[z]);
              s0 += d0; s1 += d1;
              if (decltype(sq)::value) { q0 = fmaf(d0, d0, q0); q1 = fmaf(d1, d1, q1); }
            }
          }
        };
        if (it < 2) row(IC<1>()); else row(IC<0>());
        s0 += s1; q0 += q1;
#pragma unroll
        for (int o = 1; o < 4; o <<= 1) { s0 += __shfl_xor_sync(0xffffffffu, s0, o); q0 += __shfl_xor_sync(0xffffffffu, q0, o); }
        if ((lane & 3) == 0) SM_(float2, OFF_PUB + a * 256 + it * 64 + (lane >> 2) * 8) = make_float2(s0, q0);
        if (it != 2) bar_sync(NB_AUX, 96);
        if (it < 2 && a == 2) stage(cid < 64 ? p.Dre + (size_t)cid * 16 * 1024 : p.Dim + (size_t)(cid - 64) * 16 * 1024, g);
      }
      if (a == 1) {
        const float2 v0 = SM_(float2, OFF_PUB + lane * 8), v1 = SM_(float2, OFF_PUB + 256 + lane * 8), v2 = SM_(float2, OFF_PUB + 512 + lane * 8);
        const float s = v0.x + v1.x + v2.x, mean = s * (1.f / 1024.f);
        const float rs = rcp_fast(ln_sd((v0.y + v1.y + v2.y) * (1.f / 1024.f) - mean * mean));
        pkt_st64((lane < 16 ? p.s->xstat : p.s->dsum) + cid * 16 + (lane & 15), lane < 16 ? pack_bf16(rs, mean) : __float_as_uint(s), tag);
        PT(6);
      }
      auto prefetch = [&](int r) {
        const int l = r * 32 + lane;
        const bf16* ad = l < 1024 ? (((l >> 6) & 1) ? p.wup : p.wgate) + (size_t)((l >> 7) * 128 + m * 64 + (l & 63)) * 3584 + (f0 & ~63)
                                  : p.wdown + (size_t)f0 * 1024 + (l - 1024) * 64;
        if (moe) asm volatile("prefetch.global.L2 [%0];" :: "l"(ad));
      };
      __nanosleep(GATHER_NS);
      {
        const int i0 = a * 32 + lane;
        uint2 v[3], c0, c1; uint32_t n = 0;
        const uint2* dp = &p.s->dsum[abrow];
        while (true) {
#pragma unroll
          for (int q = 0; q < 3; q++) v[q] = pkt_ld64(&p.s->xstat[tau * 256 + min(i0 + 96 * q, 255)]);
          c0 = pkt_ld64(dp + i0); c1 = pkt_ld64(dp + min(i0 + 96, 127));
          if (__all_sync(0xffffffffu, v[0].y == tag && v[1].y == tag && v[2].y == tag && c0.y == tag && c1.y == tag) || ++n > SPIN_LIMIT) break;
          __nanosleep(200);
        }
#pragma unroll
        for (int q = 0; q < 3; q++) {
          const int col = min(i0 + 96 * q, 255);
          SM_(uint16_t, OFF_RS + ((col & 7) >> 1) * 144 + (col >> 3) * 4 + (col & 1) * 2) = (uint16_t)(v[q].x ^ (m << 15));
          const uint32_t nm = (v[q].x >> 16) ^ 0x8000u;
          SM_(uint4, OFF_EXB + (col >> 3) * 256 + (col & 7) * 16) = make_uint4(nm | (nm << 16), nm, 0, 0);
          SM_(uint4, OFF_EXB + (col >> 3) * 256 + 128 + (col & 7) * 16) = make_uint4(0, 0, 0, 0);
        }
#pragma unroll
        for (int q = 0; q < 2; q++) {
          const int e = min(i0 + 96 * q, 127);
          const float c = __uint_as_float(q ? c1.x : c0.x);
          const float hi = bf16r(c), mid = bf16r(c - hi), lo = bf16r((c - hi) - mid);
          SM_(uint4, OFF_EXA + (e >> 3) * 256 + (e & 7) * 16) = make_uint4((__float_as_uint(hi) >> 16) | (__float_as_uint(mid) & 0xFFFF0000u), __float_as_uint(lo) >> 16, 0, 0);
          SM_(uint4, OFF_EXA + (e >> 3) * 256 + 128 + (e & 7) * 16) = make_uint4(0, 0, 0, 0);
        }
        fence_async_smem();
      }
      __syncwarp();
      if (lane == 0) mbar_arrive(BAR(B_STAT));
      if (a == 0) PT(7);
      if (a == 0) {
        const uint32_t* flg = reinterpret_cast<const uint32_t*>(&p.s->abflag[((eps * 2 + m) * 8 + (lane >> 2)) * 2]) + (lane & 3);
        uint32_t seen = 0;
        auto poll = [&]() {
          seen = __ballot_sync(0xffffffffu, ld_relaxed32(flg) == tag);
          asm volatile("fence.proxy.async.global;" ::: "memory");
          *(volatile uint32_t*)&SM_(uint32_t, OFF_SEEN) = seen;
        };
        {
          const uint32_t* fa = reinterpret_cast<const uint32_t*>(&p.s->abflag[((eps * 2 + m) * 8 + ((tau + 1) & 7)) * 2 + 1]);
          mbar_wait(BAR(B_STDA), 0);
          uint32_t n = 0;
          while (!__all_sync(0xffffffffu, ld_relaxed32(fa) == tag) && ++n < SPIN_LIMIT) {}
          mbar_wait(BAR(B_EPI0B), 0);
          mbar_wait(BAR(B_FULL + 0), 0);
          PT(48);
          if (elect_one()) tma_load_2d(sb + OFF_XCH, &p.tmAbS, BAR(B_FULL + 0), ((tau + 1) & 7) * 256, abrow);
        }
        mbar_wait(BAR(B_STD + 0), 0);
#pragma unroll 1
        for (int s = 0; s < 4; s++) {
          const int kb = kblock(tau, 4 + s);
          uint32_t n = 0;
          while (!((seen >> kb) & 1) && ++n < SPIN_LIMIT) poll();
          if (s == 3) mbar_wait(BAR(B_STD + 1), 0);
          if (s) mbar_wait(BAR(B_FULL + s), 0);
          PT(16 + s);
          if (elect_one()) {
            if (s == 0) {
              mbar_expect_tx(BAR(B_A20), 8192);
              tma_load_2d(sb + OFF_XCH + 8192, &p.tmAbS, BAR(B_A20), kb * 64, abrow + 64);
            } else {
              tma_load_2d(sb + (s < 2 ? OFF_XCH + s * 16384 : s * ST_BYTES), &p.tmAbL, BAR(B_FULL + s), kb * 64, abrow);
            }
          }
        }
        uint32_t n = 0;
        while (seen != 0xFFFFFFFFu && ++n < SPIN_LIMIT) { poll(); __nanosleep(100); }
      } else if (a == 1) {
#pragma unroll 1
        for (int c = 0; c < 4; c++) {
          uint32_t* flag = reinterpret_cast<uint32_t*>(&p.s->abflag[((eps * 2 + m) * 8 + tau) * 2]) + c;
          mbar_wait(BAR(B_EPI + c), 0);
          if (c == 1) mbar_wait(BAR(B_LATE), 0);
          PT(8 + c);
          if (c >= 2) {
            bf16* dst = p.s->abT + (size_t)(abrow + (lane >> 3)) * 2048 + tau * 256 + c * 64;
#pragma unroll 4
            for (int i = 0; i < 32; i++) {
              const int row = 4 * i + (lane >> 3);
              const uint4 v = lds128_v(sb + chunk_off(c, 0) + i * 512 + lane * 16);
              asm volatile("st.global.v4.b32 [%0], {%1, %2, %3, %4};" :: "l"(dst + i * 4 * 2048 + (((lane & 7) ^ (row & 7)) << 3)), "r"(v.x), "r"(v.y), "r"(v.z), "r"(v.w));
            }
            __syncwarp();
            if (lane == 0) mbar_arrive(BAR(B_STD + c));
            if (c == 3) {
              asm volatile("fence.acq_rel.gpu;" ::: "memory");
              if (lane < 2) st_relaxed32(flag - lane, tag);
            }
            PT(12 + c);
            continue;
          }
          if (lane == 0) {
            tma_store_2d(&p.tmAbS, sb + chunk_off(c, 0), tau * 256 + c * 64, abrow);
            if (c == 0) {
              bulk_commit();
              bulk_wait_all();
              st_relaxed32(flag + 4, tag);
              mbar_arrive(BAR(B_STDA));
            }
          }
          mbar_wait(BAR(B_EPI0B), 0);
          if (lane == 0) {
            tma_store_2d(&p.tmAbS, sb + chunk_off(c, 1), tau * 256 + c * 64, abrow + 64);
            bulk_commit();
            bulk_wait_all();
            st_relaxed32(flag, tag);
            mbar_arrive(BAR(B_STD + c));
          }
          PT(12 + c);
        }
      } else {
      }
      {
        const uint4* kp = &p.s->key[(tau * 16 + (lane & 15)) * 2];
        const int i0 = a * 32 + lane;
        mbar_wait(BAR(B_KEY), 0);
        if (a == 0) PT(43);
        uint4 kq = pkt_ld128(kp), cv[3];
        uint32_t n = 0, kv;
        int gspec = -1;
        while (true) {
          const bool ok = kq.y == tag && kq.w == tag;
          kv = __reduce_max_sync(0xffffffffu, ok ? kq.x : 0u);
          const int gs = (0xFFFF - (int)(kv & 0xFFFFu)) >> 7;
          const bool cok = gs == gspec && cv[0].y == tag && cv[0].w == tag && cv[1].y == tag && cv[1].w == tag && cv[2].y == tag && cv[2].w == tag;
          if (__all_sync(0xffffffffu, ok && cok) || ++n > SPIN_LIMIT) break;
          if (!ok) kq = pkt_ld128(kp);
          const bool spec = __popc(__ballot_sync(0xffffffffu, ok)) >= 2 * SPEC_MIN;
          if (!cok && spec) {
#pragma unroll
            for (int i = 0; i < 3; i++) cv[i] = pkt_ld128(&p.s->cand[gs * 256 + min(i0 + 96 * i, 255)]);
          }
          if (spec) gspec = gs;
        }
        if (a == 0) PT(45);
        const uint32_t ms = __shfl_sync(0xffffffffu, kq.z, gspec);
        const uint32_t nm = ((ms & 0xFFFFu) ^ 0x8000u) * 0x10001u;
        const float is = rcp_fast(bf_hi(ms));
#pragma unroll
        for (int i = 0; i < 3; i++) {
          const int j = min(i0 + 96 * i, 255);
          SM_(uint2, OFF_XSEL + j * 8) = make_uint2(norm2(cv[i].x, nm, is), norm2(cv[i].z, nm, is));
          SM_(uint2, OFF_HSEL + j * 8) = make_uint2(cv[i].x, cv[i].z);
        }
        SM_(uint32_t, OFF_KV) = kv;
        __syncwarp();
        if (lane == 0) mbar_arrive(BAR(B_XS));
      }
    }
    if (warp == 8) {
      const int lane = threadIdx.x & 31;
      mbar_wait(BAR(B_OUT), 0);
      const uint32_t km = SM_(uint32_t, OFF_WKEY + (lane & 7) * 8);
      const uint32_t bk = __reduce_max_sync(0xffffffffu, km);
      const int ww = __ffs(__ballot_sync(0xffffffffu, km == bk)) - 1;
#pragma unroll 1
      for (int i = 1; i <= 8; i++) {
        const int W = (ww + i) & 7;
        if (i == 8) {
          mbar_wait(BAR(B_XS), 0);
          if (SM_(uint32_t, OFF_KV) == bk) {
#pragma unroll 2
            for (int j = lane; j < 256; j += 32) {
              const int rho = j >> 4, row = (tau * 2 + m) * 128 + 32 * (W >> 1) + 8 * ((rho & 7) >> 1) + 4 * (W & 1) + 2 * (rho >> 3) + (rho & 1);
              const uint4 v = lds128_v(sb + OFF_OUT + (j & 8) * 2048 + (16 * W + rho) * 128 + (((j ^ rho) & 7) << 4));
              if (row != 0xFFFF - (int)(bk & 0xFFFFu))
                asm volatile("st.global.v4.b32 [%0], {%1, %2, %3, %4};" :: "l"(p.out + (size_t)row * 1024 + eps * 128 + (j & 15) * 8), "r"(v.x), "r"(v.y), "r"(v.z), "r"(v.w));
            }
            break;
          }
        }
        if (lane == 0) {
          tma_store_5d(&p.tmOut, sb + OFF_OUT + W * 2048, eps * 128, 2 * (W & 1), tau * 8 + m * 4 + (W >> 1));
          tma_store_5d(&p.tmOut, sb + OFF_OUT + 16384 + W * 2048, eps * 128 + 64, 2 * (W & 1), tau * 8 + m * 4 + (W >> 1));
        }
        const long long t0 = clock64();
        while (i < 7 && clock64() - t0 < OUT_PACE_CLK) {}
      }
      if (lane == 0) { bulk_commit(); bulk_wait_all(); }
      PT(22);
    }
    asm volatile("barrier.cluster.wait.aligned;" ::: "memory");
  } else {
    reg_inc<REG_C>();
    const int w = warp >> 2, wi = warp & 3, t = tid & 127;
    const int g = lane >> 2, q = lane & 3;
    const int turn_me = NB_TURN0 + w, turn_other = NB_TURN1 - w;
    float acc[128];
#pragma unroll
    for (int i = 0; i < 128; i++) acc[i] = 0.f;
    if (w == 1) bar_arrive(NB_TURN0, 256);
    auto kstep = [&](int k, bool first, bool a_in_xch = false) {
      const int s = slot_of(k);
      mbar_wait(BAR(B_FULL + s), use_of(k) & 1);
      CT(64 + k);
      bar_sync(turn_me, 256);
      const uint64_t da = make_desc(sb + (a_in_xch ? OFF_XCH + s * 16384 : s * ST_BYTES) + w * 8192), db = make_desc(sb + s * ST_BYTES + A_BYTES);
      wgmma_fence();
      wgmma_n256(acc, da, db, !first);
#pragma unroll
      for (int kk = 1; kk < 4; kk++) wgmma_n256(acc, da + kk * 2, db + kk * 2, 1);
      wgmma_commit();
      bar_arrive(turn_other, 256);
    };
    auto release = [&](int s) { if (t == 0) mbar_arrive(BAR(B_EMPTY + s)); };
    auto kdone = [&](int k) { wgmma_wait0(); release(slot_of(k)); };
    auto wgmma_wait1 = [&]() { asm volatile("wgmma.wait_group.sync.aligned 1;" ::: "memory"); };

#pragma unroll 1
    for (int k = 0; k < 14; k++) {
      kstep(k, k == 0);
      if (k == 0) CT(0);
      if (k == 8 && warp == 2 && lane < 2) pkt_st128(&p.s->abflag[((eps * 2 + m) * 8 + tau) * 2 + lane], 0, 0, 0, 0);
      kdone(k);
    }
    uint32_t R[64];
    uint32_t tag;
    {
      const uint32_t rsa = sb + OFF_RS + q * 144;
      const uint64_t da2 = make_desc(sb + 2 * ST_BYTES + w * 8192), db2 = make_desc(sb + 2 * ST_BYTES + A_BYTES);
      const uint64_t da3 = make_desc(sb + 3 * ST_BYTES + w * 8192), db3 = make_desc(sb + 3 * ST_BYTES + A_BYTES);
      mbar_wait(BAR(B_FULL + 2), 1);
      CT(64 + 14);
      bar_sync(turn_me, 256);
      wgmma_fence();
#pragma unroll
      for (int kk = 0; kk < 4; kk++) wgmma_n256(acc, da2 + kk * 2, db2 + kk * 2, 1);
      wgmma_commit();
      mbar_wait(BAR(B_FULL + 3), 1);
      CT(64 + 15);
      wgmma_fence();
      wgmma_n256(acc, da3, db3, 1);
      wgmma_n256(acc, da3 + 2, db3 + 2, 1);
      wgmma_commit();
      mbar_wait(BAR(B_STAT), 0);
      tag = SM_(uint32_t, OFF_TAG);
#pragma unroll
      for (int i = 0; i < 8; i++) { const uint4 v = lds128_v(rsa + i * 16); R[8 * i] = v.x; R[8 * i + 2] = v.y; R[8 * i + 4] = v.z; R[8 * i + 6] = v.w; }
      wgmma_wait1();
      release(2);
      wgmma_fence();
      wgmma_n256(acc, da3 + 4, db3 + 4, 1);
      wgmma_n256(acc, da3 + 6, db3 + 6, 1);
      wgmma_n256(acc, make_desc_noswz(sb + OFF_EXA + w * 2048), make_desc_noswz(sb + OFF_EXB), 1);
      wgmma_commit();
      bar_arrive(turn_other, 256);
      kdone(15);
      mbar_wait(BAR(B_STAT), 0);
    }
    fence_acc(acc);
    CT(1);
    auto pack = [&](auto cc) {
      constexpr int c = decltype(cc)::value;
#pragma unroll
      for (int j = 8 * c; j < 8 * c + 8; j++) {
        const uint32_t rs = R[2 * j];
        const float* ac = &acc[4 * j];
        R[2 * j] = bmul2(pack_bf16(ac[0], ac[1]), rs);
        R[2 * j + 1] = bmul2(pack_bf16(ac[2], ac[3]), rs);
      }
    };
    auto put_chunk = [&](auto cc) {
      constexpr int c = decltype(cc)::value;
      const int rho = 16 * wi + (lane & 15);
#pragma unroll
      for (int j = 8 * c; j < 8 * c + 8; j += 2) {
        const int chunk = (j & 7) + (lane >> 4);
        stsm_x4(sb + chunk_off(c, w) + rho * 128 + ((chunk ^ (lane & 7)) << 4), R[2 * j], R[2 * j + 1], R[2 * j + 2], R[2 * j + 3]);
      }
    };
    auto staged = [&](int bar) {
      fence_async_smem();
      __syncwarp();
      if (lane == 0) mbar_arrive(BAR(bar));
    };
    auto mma_rs = [&](auto cc, auto k0, auto k1) {
      constexpr int c = decltype(cc)::value;
      const uint64_t db = make_desc(sb + c * ST_BYTES + A_BYTES);
#pragma unroll
      for (int kk = decltype(k0)::value; kk < decltype(k1)::value; kk++)
        wgmma_n256_rs(acc, R[16 * c + 4 * kk], R[16 * c + 4 * kk + 1], R[16 * c + 4 * kk + 2], R[16 * c + 4 * kk + 3], db + kk * 2, c + kk > 0);
      wgmma_commit();
    };
    auto kdone_x = [&](int k, auto ic) {
      constexpr int i = decltype(ic)::value;
      uint32_t r[8];
#pragma unroll
      for (int z = 0; z < 2; z++) {
        const int tr = 32 * (i & 1) + 16 * z + 8 * (lane >> 4) + (lane & 7), chunk = 2 * wi + ((lane >> 3) & 1);
        ldsm_x4_t(sb + (i >> 1) * ST_BYTES + w * 8192 + tr * 128 + ((chunk ^ (lane & 7)) << 4), r[4 * z], r[4 * z + 1], r[4 * z + 2], r[4 * z + 3]);
      }
      float f[16];
#pragma unroll
      for (int z = 0; z < 8; z++) { f[2 * z] = bf_lo(r[z]); f[2 * z + 1] = bf_hi(r[z]); }
#pragma unroll
      for (int z = 0; z < 16; z++) asm volatile("" : "+f"(f[z]));
      kdone(k);
#pragma unroll
      for (int z = 0; z < 16; z++) asm volatile("add.f32 %0, %0, %1;" : "+f"(acc[16 * i + z]) : "f"(f[z]));
    };
    pack(IC<0>());
    put_chunk(IC<0>());
    staged(w ? B_EPI0B : B_EPI);
    mbar_wait(BAR(B_STAT), 0);
    CT(21);
    pack(IC<1>());
    pack(IC<2>());
    pack(IC<3>());
#pragma unroll
    for (int i = 16; i < 64; i++) asm volatile("" : "+r"(R[i]));
    mbar_wait(BAR(B_FULL + 0), 0);
    CT(2);
    CT(64 + 16);
    bar_sync(turn_me, 256);
    wgmma_fence();
    mma_rs(IC<0>(), IC<0>(), IC<4>());
    mbar_wait(BAR(B_FULL + 1), 0);
    CT(64 + 17);
    wgmma_fence();
    mma_rs(IC<1>(), IC<0>(), IC<2>());
    wgmma_wait1();
    release(0);
    mma_rs(IC<1>(), IC<2>(), IC<4>());
    bar_arrive(turn_other, 256);
    kdone_x(17, IC<0>());
    static_for<2>([&](auto ic) {
      constexpr int c = 2 + decltype(ic)::value;
      mbar_wait(BAR(B_FULL + c), 0);
      CT(64 + 16 + c);
      bar_sync(turn_me, 256);
      wgmma_fence();
      mma_rs(IC<c>(), IC<0>(), IC<4>());
      bar_arrive(turn_other, 256);
      if (c == 2) { put_chunk(IC<1>()); staged(B_EPI + 1); }
      kdone_x(16 + c, IC<c - 1>());
    });
#pragma unroll 1
    for (int k = 20; k < 23; k++) {
      if (w == 1) mbar_wait(BAR(B_A20), 0);
      kstep(k, false, k < 22);
      if (k == 20) {
        kdone_x(k, IC<3>());
      } else {
        if (k == 21) put_chunk(IC<2>()); else put_chunk(IC<3>());
        __syncwarp();
        if (lane == 0) mbar_arrive(BAR(B_EPI + k - 19));
        kdone(k);
      }
    }
    uint32_t wf[32][4];
    auto load_wf = [&](auto hc) {
      constexpr int h = decltype(hc)::value;
      const int d = w * 64 + (lane >> 4) * 8 + (lane & 7);
      const uint32_t ad = sb + round_off(h) + (lane & 8) * 1024 + d * 64 + ((wi ^ ((lane >> 1) & 3)) << 4);
#pragma unroll
      for (int i = 0; i < 4; i++) ldsm_x4_t(ad + i * 1024, wf[4 * h + i][0], wf[4 * h + i][1], wf[4 * h + i][2], wf[4 * h + i][3]);
    };
    auto load_wf_rest = [&]() { static_for<8 - NREG_H>([&](auto ic) { load_wf(IC<NREG_H + decltype(ic)::value>()); }); };
#pragma unroll
    for (int i = 0; i < 4 * NREG_H; i++) { wf[i][0] = 0; wf[i][1] = 0; wf[i][2] = 0; wf[i][3] = 0; }
    const int grp = tau * 2 + m;
#pragma unroll 1
    for (int k = 23; k < 46; k++) {
      kstep(k, false);
      if (moe) {
        static_for<NREG_H>([&](auto hc) {
          constexpr int h = decltype(hc)::value;
          if (k == mr_k(h) + 1) { mbar_wait(BAR(B_MR + (h & 1)), (h >> 1) & 1); load_wf(hc); }
        });
      }
      if (k == 43) {
        if (moe) pkt_st128(&p.s->ypart[cid * 256 + tid], 0, 0, 0, 0);
        if (w == 1) pkt_st128(&p.s->hstat[(grp * 8 + eps) * 128 + t], 0, 0, 0, 0);
        if (warp == 0) pkt_st128(&p.s->cand[grp * 256 + eps * 32 + lane], 0, 0, 0, 0);
        if (eps == 0 && warp == 1 && lane < 16) pkt_st128(&p.s->key[((lane >> 1) * 16 + grp) * 2 + (lane & 1)], 0, 0, 0, 0);
      }
      kdone(k);
    }
    asm volatile("barrier.cluster.arrive.relaxed.aligned;" ::: "memory");
    uint32_t wa[16][2];
    uint32_t cd = code_of(tag);
    uint4* hp_pub = &p.s->hstat[(grp * 8 + eps) * 128 + warp * 16 + g];
    const uint4* hp_poll = &p.s->hstat[(grp * 8 + 2 * q) * 128 + warp * 16 + g];
    const uint32_t vec_off = (2 * wi) * 512 + q * 128 + ((g ^ (2 * q)) << 4);
    {
      float as[64], ak[64];
      fence_acc(acc);
#pragma unroll
      for (int i = 0; i < 64; i++) asm volatile("mov.b32 %0, %1;" : "=f"(as[i]) : "f"(acc[64 + i]));
#pragma unroll
      for (int i = 0; i < 64; i++) asm volatile("mov.b32 %0, %1;" : "=f"(ak[i]) : "f"(acc[i]));
      const uint64_t da1 = make_desc(sb + 2 * ST_BYTES + w * 8192), db1 = make_desc(sb + 2 * ST_BYTES + A_BYTES);
      const uint64_t da2 = make_desc(sb + 3 * ST_BYTES + w * 8192), db2 = make_desc(sb + 3 * ST_BYTES + A_BYTES);
      mbar_wait(BAR(B_FULL + 2), 1);
      CT(64 + 46);
      mbar_wait(BAR(B_FULL + 3), 1);
      CT(64 + 47);
      bar_sync(turn_me, 256);
      wgmma_fence();
#pragma unroll
      for (int kk = 0; kk < 4; kk++) wgmma_n128(as, da1 + kk * 2, db1 + 1024 + kk * 2);
#pragma unroll
      for (int kk = 0; kk < 4; kk++) wgmma_n128(as, da2 + kk * 2, db2 + 1024 + kk * 2);
      wgmma_commit();
      bar_arrive(turn_other, 256);
      const uint32_t rx = mapa(sb + OFF_PEER + w * 4096 + vec_off, 1 - m), rb = mapa(BAR(B_XCH), 1 - m);
      asm volatile("barrier.cluster.wait.aligned;" ::: "memory");
      wgmma_wait0();
      fence_acc64(as);
      auto keep = [&]() {
        bar_sync(turn_me, 256);
        wgmma_fence();
#pragma unroll
        for (int kk = 0; kk < 4; kk++) wgmma_n128(ak, da1 + kk * 2, db1 + kk * 2);
        wgmma_commit();
#pragma unroll
        for (int kk = 0; kk < 4; kk++) wgmma_n128(ak, da2 + kk * 2, db2 + kk * 2);
        wgmma_commit();
        if (w == 0) bar_arrive(turn_other, 256);
      };
      keep();
#pragma unroll
      for (int i = 0; i < 8; i++) {
        const float* ac = &as[16 * (i >> 1) + 2 * (i & 1)];
        st_async_v4(rx + (i >> 1) * 8192 + (i & 1) * 512, rb, pack_bf16(ac[0], ac[1]), pack_bf16(ac[4], ac[5]), pack_bf16(ac[8], ac[9]), pack_bf16(ac[12], ac[13]));
      }
#pragma unroll
      for (int i = 0; i < 4; i++) {
        const uint4 v = lds128_v(sb + OFF_WR + q * 80 + i * 16);
        const uint32_t vv[4] = {v.x, v.y, v.z, v.w};
#pragma unroll
        for (int z = 0; z < 4; z++) {
          asm volatile("{\n.reg .pred p;\nsetp.ne.b32 p, %2, 0;\nselp.b32 %0, %1, 0x3F803F80, p;\n}" : "=r"(wa[4 * i + z][0]) : "r"(vv[z]), "r"(g & 1));
          asm volatile("{\n.reg .pred p;\nsetp.ne.b32 p, %2, 0;\nselp.b32 %0, %1, 0x3F803F80, p;\n}" : "=r"(wa[4 * i + z][1]) : "r"(vv[z]), "r"(g & 1));
        }
      }
      pin(cd); pin(hp_pub); pin(hp_poll);
      wgmma_wait1();
      release(2);
      wgmma_wait0();
      fence_acc64(ak);
      CT(3);
#pragma unroll
      for (int i = 0; i < 8; i++) {
        const float* ac = &ak[16 * (i >> 1) + 2 * (i & 1)];
        sts128(sb + (2 + (i >> 2)) * ST_BYTES + w * 8192 + ((i >> 1) & 1) * 4096 + (i & 1) * 512 + vec_off,
               pack_bf16(ac[0], ac[1]), pack_bf16(ac[4], ac[5]), pack_bf16(ac[8], ac[9]), pack_bf16(ac[12], ac[13]));
      }
    }
    uint32_t h[8][4];
    {
      const int qq = 2 * (warp & 1) + ((lane >> 3) & 1);
      const uint32_t lo = (lane >> 4) * 512 + qq * 128 + (((lane & 7) ^ (2 * qq)) << 4);
      bar_sync(NB_BOTH, 256);
#pragma unroll
      for (int ks = 0; ks < 8; ks++)
        ldsm_x4_t(sb + (2 + w) * ST_BYTES + (ks >> 2) * 8192 + (wi >> 1) * 4096 + (ks & 3) * 1024 + lo, h[ks][0], h[ks][1], h[ks][2], h[ks][3]);
      mbar_wait_cluster(BAR(B_XCH), 0);
      CT(4);
      uint32_t r[8][4];
#pragma unroll
      for (int ks = 0; ks < 8; ks++) ldsm_x4_t(sb + OFF_PEER + (warp >> 1) * 8192 + ks * 1024 + lo, r[ks][0], r[ks][1], r[ks][2], r[ks][3]);
      float d[4][4] = {};
#pragma unroll
      for (int ks = 0; ks < 8; ks++) {
#pragma unroll
        for (int i = 0; i < 4; i++) {
          h[ks][i] = badd2(h[ks][i], r[ks][i]);
          mma1688(d[i], h[ks][i], wa[2 * ks + (i >> 1)][i & 1], h[ks][i]);
        }
      }
#pragma unroll
      for (int i = 0; i < 2; i++) {
        const float sq = (g & 1) ? d[i][1] + d[i + 2][1] : d[i][0] + d[i + 2][0];
        const float e0 = d[i][2] + d[i + 2][2], e1 = d[i][3] + d[i + 2][3];
        const float other = __shfl_xor_sync(0xffffffffu, (g & 1) ? e0 : e1, 4);
        if (q == (g >> 1)) pkt_st128(hp_pub + 8 * i, with_bit((g & 1) ? other : e0, cd), with_bit(sq, cd >> 1), __float_as_uint((g & 1) ? e1 : other), tag);
      }
    }
    CT(5);
    if (tid == 0) mbar_arrive(BAR(B_KEY));
    delay_clk<HOP1_DELAY>();
    float m_bf, sd, inv_sd, r_bf;
    uint4* key_pub = &p.s->key[((lane & 7) * 16 + grp) * 2];
    uint4* cand_pub = &p.s->cand[grp * 256 + eps * 32 + q];
    uint32_t trow_inv = 0xFFFFu - (uint32_t)(grp * 128 + 32 * (warp >> 1) + 8 * (g >> 1) + 4 * (warp & 1) + (q & 2) + (g & 1));
    {
      uint4 u[4];
#pragma unroll
      for (int i = 0; i < 4; i++) u[i] = pkt_ld128(hp_poll + (i & 1) * 128 + (i >> 1) * 8);
      const float wsum = SM_(float, OFF_WSUM);
      pin(key_pub); pin(cand_pub); pin(trow_inv);
      uint32_t n = 0;
      while (true) {
        bool ok[4];
#pragma unroll
        for (int i = 0; i < 4; i++) ok[i] = u[i].w == tag && pair_code(u[i].x, u[i].y) == cd;
        const bool all = __all_sync(0xffffffffu, ok[0] && ok[1] && ok[2] && ok[3]);
        if (all || ++n > SPIN_LIMIT) break;
#pragma unroll
        for (int i = 0; i < 4; i++) pkt_ld128_if(u[i], hp_poll + (i & 1) * 128 + (i >> 1) * 8, !ok[i]);
      }
      CT(6);
      float a[3], b[3];
      a[0] = __uint_as_float(u[0].x & ~1u) + __uint_as_float(u[1].x & ~1u); b[0] = __uint_as_float(u[2].x & ~1u) + __uint_as_float(u[3].x & ~1u);
      a[1] = __uint_as_float(u[0].y & ~1u) + __uint_as_float(u[1].y & ~1u); b[1] = __uint_as_float(u[2].y & ~1u) + __uint_as_float(u[3].y & ~1u);
      a[2] = __uint_as_float(u[0].z) + __uint_as_float(u[1].z); b[2] = __uint_as_float(u[2].z) + __uint_as_float(u[3].z);
#pragma unroll
      for (int i = 0; i < 3; i++) {
        a[i] = ((q & 2) ? b[i] : a[i]) + __shfl_xor_sync(0xffffffffu, (q & 2) ? a[i] : b[i], 2);
        a[i] += __shfl_xor_sync(0xffffffffu, a[i], 1);
      }
      const float mu = a[0] * (1.f / 1024.f);
      m_bf = bf16r(mu);
      sd = ln_sd(a[1] * (1.f / 1024.f) - mu * mu);
      inv_sd = rcp_fast(sd);
      r_bf = bf16r((a[2] - m_bf * wsum) * inv_sd);
    }
    {
      const uint32_t u = __float_as_uint(r_bf);
      const uint32_t ord = (u & 0x80000000u) ? ~u : (u | 0x80000000u);
      const uint32_t key = (ord & 0xFFFF0000u) | trow_inv;
      const uint32_t wk = __reduce_max_sync(0xffffffffu, key);
      if (key == wk) SM_(uint2, OFF_WKEY + warp * 8) = make_uint2(wk, (__float_as_uint(m_bf) >> 16) | __float_as_uint(sd));
      const uint32_t wmask = __ballot_sync(0xffffffffu, key == wk);
      const bool hi = (wmask & 0xCCCCCCCCu) != 0;
      uint32_t c[16];
#pragma unroll
      for (int ks = 0; ks < 8; ks++) { c[2 * ks] = hi ? h[ks][1] : h[ks][0]; c[2 * ks + 1] = hi ? h[ks][3] : h[ks][2]; }
      bar_sync(NB_BOTH, 256);
      const uint2 km = SM_(uint2, OFF_WKEY + (lane & 7) * 8);
      const uint32_t bk = __reduce_max_sync(0xffffffffu, km.x);
      if (wk == bk) {
        if ((wmask >> (lane & 28)) & 15) {
#pragma unroll
          for (int ks = 0; ks < 8; ks++) pkt_st128(cand_pub + ks * 4, c[2 * ks], tag, c[2 * ks + 1], tag);
        }
      } else if (eps == 0) {
        const uint32_t kx = __shfl_sync(0xffffffffu, km.x, warp ^ 1), ms = __shfl_sync(0xffffffffu, km.y, warp ^ 1);
        if (kx == bk && lane < 8) pkt_st128(key_pub, bk, tag, ms, tag);
      }
      CT(7);
    }
    {
      const float ih = bf16r(inv_sd);
      const uint32_t nm = pack_bf16(-m_bf, -m_bf), iv = pack_bf16(ih, inv_sd - ih);
      const uint32_t nm_o = __shfl_xor_sync(0xffffffffu, nm, 2), iv_o = __shfl_xor_sync(0xffffffffu, iv, 2);
      const uint32_t nm2[2] = {(q & 2) ? nm_o : nm, (q & 2) ? nm : nm_o}, iv2[2] = {(q & 2) ? iv_o : iv, (q & 2) ? iv : iv_o};
      const uint32_t hi2[2] = {__byte_perm(iv2[0], 0, 0x1010), __byte_perm(iv2[1], 0, 0x1010)}, lo2[2] = {__byte_perm(iv2[0], 0, 0x3232), __byte_perm(iv2[1], 0, 0x3232)};
      const uint32_t oa = sb + OFF_OUT + (warp * 16 + (lane & 15)) * 128;
#pragma unroll
      for (int ks = 0; ks < 8; ks++) {
        uint32_t o[4];
#pragma unroll
        for (int i = 0; i < 4; i++) {
          const uint32_t dd = badd2(h[ks][i], nm2[i & 1]);
          o[i] = badd2(h[ks][i], bfma2(dd, hi2[i & 1], bmul2(dd, lo2[i & 1])));
        }
        stsm_x4(oa + (ks >> 2) * 16384 + (((2 * (ks & 3) + (lane >> 4)) ^ (lane & 7)) << 4), o[0], o[1], o[2], o[3]);
      }
      staged(B_OUT);
    }
    CT(8);
    uint32_t df[16][4];
    auto load_df = [&]() {
      const int frow = (lane & 7) + ((lane >> 4) << 3), hi = (lane >> 3) & 1;
      const uint32_t base = sb + down_off(warp >> 1) + (warp & 1) * 8192 + frow * 128;
#pragma unroll
      for (int mt = 0; mt < 8; mt++) {
#pragma unroll
        for (int ks = 0; ks < 2; ks++)
          ldsm_x4_t(base + (mt >> 2) * 4096 + ks * 2048 + (((2 * (mt & 3) + hi) ^ (lane & 7)) << 4),
                    df[2 * mt + ks][0], df[2 * mt + ks][1], df[2 * mt + ks][2], df[2 * mt + ks][3]);
      }
    };
    if (moe) {
      mbar_wait(BAR(B_GU), 0);
      load_wf_rest();
      mbar_wait(BAR(B_DN), 0);
      load_df();
    }
    mbar_wait(BAR(B_XS), 0);
    CT(9);
    if (moe) {
      float gd[8][4] = {};
      uint2 bx[4];
#pragma unroll
      for (int r = 0; r < 4; r++) bx[r] = SM_(uint2, OFF_XSEL + (16 * r + 8 * (g >> 2) + 4 * w + (g & 3)) * 32 + q * 8);
#pragma unroll
      for (int r = 0; r < 4; r++) {
#pragma unroll
        for (int i = 0; i < 8; i++) mma16816(gd[i], wf[8 * r + i][0], wf[8 * r + i][1], wf[8 * r + i][2], wf[8 * r + i][3], bx[r].x, bx[r].y);
      }
      float gs = q == 0 ? gd[0][0] + gd[1][1] : q == 1 ? gd[2][0] + gd[3][1] : q == 2 ? gd[4][0] + gd[5][1] : gd[6][0] + gd[7][1];
      float us = q == 0 ? gd[0][2] + gd[1][3] : q == 1 ? gd[2][2] + gd[3][3] : q == 2 ? gd[4][2] + gd[5][3] : gd[6][2] + gd[7][3];
      float v = ((q & 2) ? us : gs) + __shfl_xor_sync(0xffffffffu, (q & 2) ? gs : us, 2);
      SM_(float, OFF_GP + (wi * 8 + g) * 32 + w * 16 + q * 4) = v;
      CT(10);
      bar_sync(NB_BOTH, 256);
      uint32_t bq[4];
      {
        const float4 p0 = SM_(float4, OFF_GP + lane * 32), p1 = SM_(float4, OFF_GP + lane * 32 + 16);
        const float gt = bf16r((p0.x + p0.y) + (p1.x + p1.y)), up = bf16r((p0.z + p0.w) + (p1.z + p1.w));
        const float act = bf16r(__fdividef(gt, 1.f + __expf(-gt))) * up;
        const uint32_t pr = pack_bf16(act, __shfl_down_sync(0xffffffffu, act, 1));
#pragma unroll
        for (int i = 0; i < 4; i++) bq[i] = __shfl_sync(0xffffffffu, pr, 8 * i + 2 * q);
      }
      CT(11);
      float yd[8][4] = {};
#pragma unroll
      for (int ks = 0; ks < 2; ks++) {
#pragma unroll
        for (int mt = 0; mt < 8; mt++) mma16816(yd[mt], df[2 * mt + ks][0], df[2 * mt + ks][1], df[2 * mt + ks][2], df[2 * mt + ks][3], bq[2 * ks], bq[2 * ks + 1]);
      }
      const float y0 = q == 0 ? yd[0][0] : q == 1 ? yd[2][0] : q == 2 ? yd[4][0] : yd[6][0];
      const float y1 = q == 0 ? yd[0][2] : q == 1 ? yd[2][2] : q == 2 ? yd[4][2] : yd[6][2];
      const float y2 = q == 0 ? yd[1][0] : q == 1 ? yd[3][0] : q == 2 ? yd[5][0] : yd[7][0];
      const float y3 = q == 0 ? yd[1][2] : q == 1 ? yd[3][2] : q == 2 ? yd[5][2] : yd[7][2];
      pkt_st128(&p.s->ypart[cid * 256 + tid], with_bit(y0, cd), with_bit(y1, cd >> 1), with_bit(y2, cd), with_bit(y3, cd >> 1));
    } else {
      const long long tw = clock64();
      while (clock64() - tw < IDLE_WAIT_CLK) __nanosleep(100);
    }
    CT(12);
    const uint32_t kv = SM_(uint32_t, OFF_KV);
    const int tsel = 0xFFFF - (int)(kv & 0xFFFFu);
    const float r_sel = __uint_as_float((kv & 0x80000000u) ? (kv & 0x7FFF0000u) : (~kv & 0xFFFF0000u));
    const float sig = bf16r(__fdividef(1.f, 1.f + __expf(-r_sel)));
    const int pfin = 2 * cid + (tid & 1);
    const int col_fin = (pfin >> 5) * 128 + (pfin & 3) * 32 + ((pfin & 31) >> 2) + 8 * ((tid >> 1) & 3);
    const int sel_off = (col_fin >> 4) * 32 + ((col_fin & 7) >> 1) * 8 + ((col_fin >> 3) & 1) * 4 + (col_fin & 1) * 2;
    const float hn_fin = __uint_as_float((uint32_t)SM_(uint16_t, OFF_XSEL + sel_off) << 16), h_fin = __uint_as_float((uint32_t)SM_(uint16_t, OFF_HSEL + sel_off) << 16);
    {
      const uint4* src = &p.s->ypart[(16 + (tid >> 1)) * 256 + pfin];
      uint4 v = make_uint4(0, 0, 0, 0);
      if (warp < 7) {
        delay_clk<HOP3_DELAY>();
        uint32_t n = 0;
        bool ok = false;
        do {
          pkt_ld128_if(v, src, !ok);
          ok = pair_code(v.x, v.y) == cd && pair_code(v.z, v.w) == cd;
        } while (!__all_sync(0xffffffffu, ok) && ++n < SPIN_LIMIT);
      }
      CT(13);
      const float y0 = __uint_as_float(v.x & ~1u), y1 = __uint_as_float(v.y & ~1u), y2 = __uint_as_float(v.z & ~1u), y3 = __uint_as_float(v.w & ~1u);
      const float a0 = ((lane & 2) ? y1 : y0) + __shfl_xor_sync(0xffffffffu, (lane & 2) ? y0 : y1, 2);
      const float a1 = ((lane & 2) ? y3 : y2) + __shfl_xor_sync(0xffffffffu, (lane & 2) ? y2 : y3, 2);
      float b = ((lane & 4) ? a1 : a0) + __shfl_xor_sync(0xffffffffu, (lane & 4) ? a0 : a1, 4);
      b += __shfl_xor_sync(0xffffffffu, b, 8);
      b += __shfl_xor_sync(0xffffffffu, b, 16);
      if (lane < 8) SM_(float, OFF_FIN + warp * 32 + lane * 4) = b;
    }
    bar_sync(NB_BOTH, 256);
    if (tid < 8) {
      float y = 0.f;
#pragma unroll
      for (int i = 0; i < 7; i++) y += SM_(float, OFF_FIN + i * 32 + tid * 4);
      p.out[(size_t)tsel * 1024 + col_fin] = __float2bfloat16_rn(h_fin + bf16r(hn_fin + bf16r(bf16r(y) * sig)));
      if (cid == 0 && tid == 0) st_relaxed32(&p.s->epoch, tag);
    }
    CT(14);
  }
}

__global__ void __launch_bounds__(384, 1) occupancy_probe_kernel() {}

typedef CUresult (*EncodeFn)(CUtensorMap*, CUtensorMapDataType, cuuint32_t, void*, const cuuint64_t*, const cuuint64_t*, const cuuint32_t*, const cuuint32_t*,
                             CUtensorMapInterleave, CUtensorMapSwizzle, CUtensorMapL2promotion, CUtensorMapFloatOOBfill);

static void make_tm(EncodeFn enc, CUtensorMap* tm, const void* ptr, uint64_t rows, uint64_t cols, uint32_t brows, uint32_t bcols, CUtensorMapSwizzle sw,
                    CUtensorMapL2promotion promo = CU_TENSOR_MAP_L2_PROMOTION_L2_256B) {
  cuuint64_t dims[2] = {cols, rows};
  cuuint64_t strides[1] = {cols * 2};
  cuuint32_t box[2] = {bcols, brows};
  cuuint32_t es[2] = {1, 1};
  enc(tm, CU_TENSOR_MAP_DATA_TYPE_BFLOAT16, 2, const_cast<void*>(ptr), dims, strides, box, es, CU_TENSOR_MAP_INTERLEAVE_NONE, sw,
      promo, CU_TENSOR_MAP_FLOAT_OOB_FILL_NONE);
}

extern "C" void kernel_launch(void* const* d_in, const int* in_sizes, int n_in, void* d_out, int out_size) {
  (void)in_sizes; (void)n_in; (void)out_size;
  static EncodeFn enc = nullptr;
  static void* abT = nullptr;
  static int map = 0;
  if (!enc) {
    void* fn = nullptr; cudaDriverEntryPointQueryResult st;
    cudaGetDriverEntryPoint("cuTensorMapEncodeTiled", &fn, cudaEnableDefault, &st);
    enc = (EncodeFn)fn;
    cudaGetSymbolAddress(&abT, g_scratch);
    cudaFuncSetAttribute(fnet_moe_kernel<0>, cudaFuncAttributeMaxDynamicSharedMemorySize, SMEM_TOTAL);
    cudaFuncSetAttribute(fnet_moe_kernel<1>, cudaFuncAttributeMaxDynamicSharedMemorySize, SMEM_TOTAL);
    cudaFuncSetAttribute(occupancy_probe_kernel, cudaFuncAttributeMaxDynamicSharedMemorySize, SMEM_TOTAL);
    cudaFuncSetAttribute(occupancy_probe_kernel, cudaFuncAttributeNonPortableClusterSizeAllowed, 1);
    auto max_clusters = [&](int size) {
      cudaLaunchConfig_t cfg = {};
      cfg.gridDim = dim3(128); cfg.blockDim = dim3(384); cfg.dynamicSmemBytes = SMEM_TOTAL;
      cudaLaunchAttribute at[1];
      at[0].id = cudaLaunchAttributeClusterDimension; at[0].val.clusterDim.x = size; at[0].val.clusterDim.y = 1; at[0].val.clusterDim.z = 1;
      cfg.attrs = at; cfg.numAttrs = 1;
      int ncl = 0;
      return cudaOccupancyMaxActiveClusters(&ncl, occupancy_probe_kernel, &cfg) == cudaSuccess ? ncl : 0;
    };
    int dev = 0, sms = 0;
    cudaGetDevice(&dev);
    cudaDeviceGetAttribute(&sms, cudaDevAttrMultiProcessorCount, dev);
    map = (!getenv("MAP1") && sms == 132 && max_clusters(2) == 66 && max_clusters(16) == 7) ? 0 : 1;
    (void)cudaGetLastError();
  }
  Params p;
  const bf16* x = (const bf16*)d_in[0];
  make_tm(enc, &p.tmD0, d_in[3], 1024, 1024, 128, 64, CU_TENSOR_MAP_SWIZZLE_128B);
  make_tm(enc, &p.tmD1, d_in[4], 1024, 1024, 128, 64, CU_TENSOR_MAP_SWIZZLE_128B);
  make_tm(enc, &p.tmX, x, 2048, 1024, 256, 64, CU_TENSOR_MAP_SWIZZLE_128B);
  make_tm(enc, &p.tmXr, x, 2048, 1024, 64, 64, CU_TENSOR_MAP_SWIZZLE_128B);
  make_tm(enc, &p.tmAbS, abT, 2048, 2048, 64, 64, CU_TENSOR_MAP_SWIZZLE_128B);
  make_tm(enc, &p.tmAbL, abT, 2048, 2048, 128, 64, CU_TENSOR_MAP_SWIZZLE_128B);
  make_tm(enc, &p.tmW0, d_in[1], 2048, 2048, 128, 64, CU_TENSOR_MAP_SWIZZLE_128B, W_PROMO);
  make_tm(enc, &p.tmW1, d_in[2], 2048, 2048, 128, 64, CU_TENSOR_MAP_SWIZZLE_128B, W_PROMO);
  {
    cuuint64_t dims[5] = {1024, 2, 4, 4, 64};
    cuuint64_t strides[4] = {2048, 8 * 2048, 2 * 2048, 32 * 2048};
    cuuint32_t box[5] = {64, 2, 4, 2, 1};
    cuuint32_t es[5] = {1, 1, 1, 1, 1};
    enc(&p.tmOut, CU_TENSOR_MAP_DATA_TYPE_BFLOAT16, 5, d_out, dims, strides, box, es, CU_TENSOR_MAP_INTERLEAVE_NONE, CU_TENSOR_MAP_SWIZZLE_128B,
        CU_TENSOR_MAP_L2_PROMOTION_NONE, CU_TENSOR_MAP_FLOAT_OOB_FILL_NONE);
  }
  make_tm(enc, &p.tmG, d_in[7], 1024, 3584, 128, 32, CU_TENSOR_MAP_SWIZZLE_64B, CU_TENSOR_MAP_L2_PROMOTION_L2_128B);
  make_tm(enc, &p.tmU, d_in[8], 1024, 3584, 128, 32, CU_TENSOR_MAP_SWIZZLE_64B, CU_TENSOR_MAP_L2_PROMOTION_L2_128B);
  make_tm(enc, &p.tmDn, d_in[9], 3584, 1024, 32, 64, CU_TENSOR_MAP_SWIZZLE_128B);
  p.x = x; p.Dre = (const bf16*)d_in[3]; p.Dim = (const bf16*)d_in[4];
  p.wr = (const bf16*)d_in[6]; p.wdown = (const bf16*)d_in[9]; p.wgate = (const bf16*)d_in[7]; p.wup = (const bf16*)d_in[8];
  p.out = (bf16*)d_out; p.s = (Scratch*)abT;
  if (map == 1) fnet_moe_kernel<1><<<128, 384, SMEM_TOTAL>>>(p);
  else fnet_moe_kernel<0><<<132, 384, SMEM_TOTAL>>>(p);
}
```

```cpp
#include <cuda.h>
#include <cuda_runtime.h>
#include <cuda_bf16.h>
#include <stdint.h>
#include <stdlib.h>
#include <type_traits>

typedef __nv_bfloat16 bf16;

#define REG_C 232
#define REG_P 40
__device__ __forceinline__ int kblock(int tau, int j) {
  const int i = j - 4, c = (i * 37) >> 8;
  return j < 4 ? tau * 4 + j : ((tau + 1 + i - 7 * c) & 7) * 4 + c;
}
#define HOP1_DELAY 150
#define HOP3_DELAY 300
#define BACKOFF_NS 0
#define SPEC_MIN 10
#define PF_K0 8
#define PF_N0 2
#define PF_K1 24
#define OUT_PACE_CLK 100
#define WPF_K0 12
#define WPF_J0 0
#define WPF_J1 32
#define PUB_K1 22
#define NREG_H 5
#define MR_K0 28
__host__ __device__ constexpr int mr_k(int h) { return MR_K0 + 6 * (h >> 1) + 2 * (h & 1); }
constexpr int A_BYTES = 128 * 64 * 2;
constexpr int B_BYTES = 256 * 64 * 2;
constexpr int ST_BYTES = A_BYTES + B_BYTES;
constexpr int OFF_XCH = 4 * ST_BYTES;
constexpr int OFF_BAR = OFF_XCH + 32768;
constexpr int OFF_WR = OFF_BAR + 384;
constexpr int OFF_RS = OFF_WR + 384;
constexpr int OFF_PUB = OFF_RS + 640;
constexpr int OFF_MISC = OFF_PUB + 768;
constexpr int SMEM_TOTAL = OFF_MISC + 256;
constexpr int OFF_WSUM = OFF_MISC, OFF_TAG = OFF_MISC + 4;
constexpr int OFF_SEEN = OFF_MISC + 8;
constexpr int OFF_KV = OFF_MISC + 12;
constexpr int OFF_WKEY = OFF_MISC + 32;
constexpr int OFF_EXA = OFF_XCH;
constexpr int OFF_EXB = OFF_XCH + 4096;
__host__ __device__ constexpr int chunk_off(int c, int w) { return (c < 2 ? (c + 2) * ST_BYTES : OFF_XCH + (c - 2) * 16384) + w * 8192; }
__host__ __device__ constexpr int late_off(int i) { return i < 4 ? i * 16384 : 2 * ST_BYTES + A_BYTES + (i - 4) * 16384; }
__host__ __device__ constexpr int round_off(int h) { return h < NREG_H + 2 ? OFF_XCH + (h & 1) * 16384 : late_off(h - NREG_H - 2); }
__host__ __device__ constexpr int down_off(int i) { return late_off(6 - NREG_H + i); }
constexpr int OFF_PEER = ST_BYTES + A_BYTES;
constexpr int OFF_OUT = 3 * ST_BYTES + A_BYTES;
constexpr int OFF_XSEL = OFF_PEER;
constexpr int OFF_HSEL = OFF_PEER + 4096;
constexpr int OFF_GP = OFF_PEER + 8192;
constexpr int OFF_FIN = OFF_PEER + 9216;
__device__ __forceinline__ int slot_of(int k) { return k & 3; }
__device__ __forceinline__ int use_of(int k) { return k >> 2; }
enum { B_FULL = 0, B_EMPTY = 4, B_EPI = 8, B_STD = 12, B_EPI0B = 16, B_LATE = 17, B_STAT = 18, B_XCH = 19, B_MR = 20  , B_GU = 22,
       B_DN = 23, B_AUX = 24  , B_OUT = 26, B_KEY = 27, B_XS = 28, B_A20 = 29, B_STDA = 30, B_COUNT = 31 };
enum { NB_TURN0 = 1, NB_TURN1 = 2, NB_BOTH = 5, NB_AUX = 6 };

struct Scratch {
  bf16 abT[2048 * 2048];
  uint2 xstat[2048];
  uint2 dsum[2048];
  uint4 abflag[16 * 8 * 2];
  uint4 hstat[16 * 8 * 128];
  uint4 cand[16 * 256];
  uint4 key[8 * 16 * 2];
  uint4 ypart[128 * 256];
  uint32_t epoch;
};
__device__ __align__(1024) Scratch g_scratch;

struct Params {
  Scratch* s; bf16* out;
  const bf16* x; const bf16* Dre; const bf16* Dim; const bf16* wr; const bf16* wdown; const bf16* wgate; const bf16* wup;
  CUtensorMap tmX, tmD0, tmD1, tmXr, tmAbS, tmAbL, tmW0, tmW1, tmOut, tmG, tmU, tmDn;
};

#define SPIN_LIMIT (1u << 14)
#define MBAR_LIMIT (1u << 10)
constexpr int PROLOGUE_CLK = 1800;
#define GATHER_NS 400
#define PF_R1 99
#define PF_START3_CLK 43000
#define W_PROMO CU_TENSOR_MAP_L2_PROMOTION_L2_128B
#define PF_R0 16
#define PF_STEP_CLK 300
#define PF_START2_CLK 26000
#define PF_STEP2_CLK 600
#define MOE_PACE_CLK 300
constexpr int IDLE_WAIT_CLK = 1200;
__device__ __forceinline__ uint32_t smem_u32(const void* p) { return (uint32_t)__cvta_generic_to_shared(p); }
__device__ __forceinline__ void mbar_init(uint32_t bar, uint32_t cnt) { asm volatile("mbarrier.init.shared::cta.b64 [%0], %1;" :: "r"(bar), "r"(cnt) : "memory"); }
__device__ __forceinline__ void mbar_expect_tx(uint32_t bar, uint32_t bytes) { asm volatile("mbarrier.arrive.expect_tx.shared::cta.b64 _, [%0], %1;" :: "r"(bar), "r"(bytes) : "memory"); }
__device__ __forceinline__ void mbar_arrive(uint32_t bar) { asm volatile("mbarrier.arrive.shared::cta.b64 _, [%0];" :: "r"(bar) : "memory"); }
__device__ __forceinline__ void mbar_wait(uint32_t bar, uint32_t parity) {
  uint32_t ok, n = 0;
  do {
    asm volatile("{\n.reg .pred p;\nmbarrier.try_wait.parity.shared::cta.b64 p, [%1], %2;\nselp.u32 %0, 1, 0, p;\n}\n" : "=r"(ok) : "r"(bar), "r"(parity) : "memory");
  } while (!ok && ++n < MBAR_LIMIT);
}
__device__ __forceinline__ bool mbar_test(uint32_t bar, uint32_t parity) {
  uint32_t ok;
  asm volatile("{\n.reg .pred p;\nmbarrier.test_wait.parity.shared::cta.b64 p, [%1], %2;\nselp.u32 %0, 1, 0, p;\n}\n" : "=r"(ok) : "r"(bar), "r"(parity) : "memory");
  return ok != 0;
}
__device__ __forceinline__ void mbar_wait_cluster(uint32_t bar, uint32_t parity) {
  uint32_t ok, n = 0;
  do {
    asm volatile("{\n.reg .pred p;\nmbarrier.try_wait.parity.acquire.cluster.shared::cta.b64 p, [%1], %2;\nselp.u32 %0, 1, 0, p;\n}\n" : "=r"(ok) : "r"(bar), "r"(parity) : "memory");
  } while (!ok && ++n < MBAR_LIMIT);
}
__device__ __forceinline__ void tma_load_2d(uint32_t dst, const CUtensorMap* tm, uint32_t bar, int c0, int c1) {
  asm volatile("cp.async.bulk.tensor.2d.shared::cluster.global.mbarrier::complete_tx::bytes [%0], [%1, {%3, %4}], [%2];"
    :: "r"(dst), "l"(tm), "r"(bar), "r"(c0), "r"(c1) : "memory");
}
__device__ __forceinline__ void tma_load_2d_hint(uint32_t dst, const CUtensorMap* tm, uint32_t bar, int c0, int c1, uint64_t pol) {
  asm volatile("cp.async.bulk.tensor.2d.shared::cluster.global.mbarrier::complete_tx::bytes.L2::cache_hint [%0], [%1, {%3, %4}], [%2], %5;"
    :: "r"(dst), "l"(tm), "r"(bar), "r"(c0), "r"(c1), "l"(pol) : "memory");
}
__device__ __forceinline__ uint64_t policy_evict_first() { uint64_t p; asm volatile("createpolicy.fractional.L2::evict_first.b64 %0, 1.0;" : "=l"(p)); return p; }
__device__ __forceinline__ void tma_store_2d(const CUtensorMap* tm, uint32_t src, int c0, int c1) {
  asm volatile("cp.async.bulk.tensor.2d.global.shared::cta.bulk_group [%0, {%2, %3}], [%1];" :: "l"(tm), "r"(src), "r"(c0), "r"(c1) : "memory");
}
__device__ __forceinline__ void bulk_load(uint32_t dst, const void* src, uint32_t bytes, uint32_t bar) {
  asm volatile("cp.async.bulk.shared::cluster.global.mbarrier::complete_tx::bytes [%0], [%1], %2, [%3];" :: "r"(dst), "l"(src), "r"(bytes), "r"(bar) : "memory");
}
__device__ __forceinline__ void bulk_commit() { asm volatile("cp.async.bulk.commit_group;" ::: "memory"); }
__device__ __forceinline__ void bulk_wait_all() { asm volatile("cp.async.bulk.wait_group 0;" ::: "memory"); }
__device__ __forceinline__ void fence_async_smem() { asm volatile("fence.proxy.async.shared::cta;" ::: "memory"); }
__device__ __forceinline__ void wgmma_fence() { asm volatile("wgmma.fence.sync.aligned;" ::: "memory"); }
__device__ __forceinline__ void wgmma_commit() { asm volatile("wgmma.commit_group.sync.aligned;" ::: "memory"); }
__device__ __forceinline__ void wgmma_wait0() { asm volatile("wgmma.wait_group.sync.aligned 0;" ::: "memory"); }
__device__ __forceinline__ void bar_sync(int id, int n) { asm volatile("bar.sync %0, %1;" :: "r"(id), "r"(n) : "memory"); }
__device__ __forceinline__ void bar_arrive(int id, int n) { asm volatile("bar.arrive %0, %1;" :: "r"(id), "r"(n) : "memory"); }
template<int R> __device__ __forceinline__ void reg_inc() { asm volatile("setmaxnreg.inc.sync.aligned.u32 %0;" :: "n"(R)); }
template<int R> __device__ __forceinline__ void reg_dec() { asm volatile("setmaxnreg.dec.sync.aligned.u32 %0;" :: "n"(R)); }
__device__ __forceinline__ bool elect_one() {
  uint32_t p;
  asm volatile("{\n.reg .pred q;\nelect.sync _|q, 0xffffffff;\nselp.u32 %0, 1, 0, q;\n}\n" : "=r"(p));
  return p != 0;
}
__device__ __forceinline__ uint32_t mapa(uint32_t addr, uint32_t cta) { uint32_t r; asm volatile("mapa.shared::cluster.u32 %0, %1, %2;" : "=r"(r) : "r"(addr), "r"(cta)); return r; }
__device__ __forceinline__ void st_async_v4(uint32_t addr, uint32_t bar, uint32_t a, uint32_t b, uint32_t c, uint32_t d) {
  asm volatile("st.async.weak.shared::cluster.mbarrier::complete_tx::bytes.v4.b32 [%0], {%2, %3, %4, %5}, [%1];" :: "r"(addr), "r"(bar), "r"(a), "r"(b), "r"(c), "r"(d) : "memory");
}
__device__ __forceinline__ void stsm_x4(uint32_t addr, uint32_t a, uint32_t b, uint32_t c, uint32_t d) {
  asm volatile("stmatrix.sync.aligned.m8n8.x4.shared.b16 [%0], {%1, %2, %3, %4};" :: "r"(addr), "r"(a), "r"(b), "r"(c), "r"(d));
}
__device__ __forceinline__ uint4 lds128_v(uint32_t addr) { uint4 v; asm volatile("ld.shared.v4.b32 {%0, %1, %2, %3}, [%4];" : "=r"(v.x), "=r"(v.y), "=r"(v.z), "=r"(v.w) : "r"(addr)); return v; }
extern __shared__ __align__(1024) uint8_t smem_raw[];
template<class T> __device__ __forceinline__ T& smem_at(uint32_t addr) { return *reinterpret_cast<T*>(__cvta_shared_to_generic(addr)); }
#define SM_(T, off) smem_at<T>(sb + (off))
__device__ __forceinline__ uint4 ldg_nc128(const void* p) { uint4 v; asm volatile("ld.global.nc.v4.b32 {%0, %1, %2, %3}, [%4];" : "=r"(v.x), "=r"(v.y), "=r"(v.z), "=r"(v.w) : "l"(p)); return v; }
__device__ __forceinline__ void pkt_st128(void* p, uint32_t a, uint32_t b, uint32_t c, uint32_t d) {
  asm volatile("{\n.reg .b128 v;\n.reg .b64 lo, hi;\nmov.b64 lo, {%1, %2};\nmov.b64 hi, {%3, %4};\nmov.b128 v, {lo, hi};\nst.relaxed.gpu.global.b128 [%0], v;\n}\n"
    :: "l"(p), "r"(a), "r"(b), "r"(c), "r"(d) : "memory");
}
__device__ __forceinline__ uint4 pkt_ld128(const void* p) {
  uint4 r;
  asm volatile("{\n.reg .b128 v;\n.reg .b64 lo, hi;\nld.relaxed.gpu.global.b128 v, [%4];\nmov.b128 {lo, hi}, v;\nmov.b64 {%0, %1}, lo;\nmov.b64 {%2, %3}, hi;\n}\n"
    : "=r"(r.x), "=r"(r.y), "=r"(r.z), "=r"(r.w) : "l"(p) : "memory");
  return r;
}
__device__ __forceinline__ void pkt_ld128_if(uint4& r, const void* p, bool cond) {
  asm volatile("{\n.reg .pred q;\nsetp.ne.b32 q, %5, 0;\n@q ld.relaxed.gpu.global.v4.b32 {%0, %1, %2, %3}, [%4];\n}\n"
    : "+r"(r.x), "+r"(r.y), "+r"(r.z), "+r"(r.w) : "l"(p), "r"((uint32_t)cond) : "memory");
}
__device__ __forceinline__ void pkt_st64(void* p, uint32_t a, uint32_t b) {
  asm volatile("{\n.reg .b64 v;\nmov.b64 v, {%1, %2};\nst.relaxed.gpu.global.b64 [%0], v;\n}\n" :: "l"(p), "r"(a), "r"(b) : "memory");
}
__device__ __forceinline__ uint2 pkt_ld64(const void* p) {
  uint2 r;
  asm volatile("{\n.reg .b64 v;\nld.relaxed.gpu.global.b64 v, [%2];\nmov.b64 {%0, %1}, v;\n}\n" : "=r"(r.x), "=r"(r.y) : "l"(p) : "memory");
  return r;
}
__device__ __forceinline__ uint32_t ld_relaxed32(const void* p) { uint32_t v; asm volatile("ld.relaxed.gpu.global.b32 %0, [%1];" : "=r"(v) : "l"(p) : "memory"); return v; }
__device__ __forceinline__ void st_relaxed32(void* p, uint32_t v) { asm volatile("st.relaxed.gpu.global.b32 [%0], %1;" :: "l"(p), "r"(v) : "memory"); }
__device__ __forceinline__ void backoff() { if (BACKOFF_NS) __nanosleep(BACKOFF_NS); }
__device__ __forceinline__ uint32_t code_of(uint32_t tag) { return tag % 3u + 1u; }
__device__ __forceinline__ uint32_t with_bit(float v, uint32_t bit) { return (__float_as_uint(v) & ~1u) | (bit & 1u); }
__device__ __forceinline__ uint32_t pair_code(uint32_t a, uint32_t b) { return (a & 1u) | ((b & 1u) << 1); }
__device__ __forceinline__ uint32_t pack_bf16(float lo, float hi) { uint32_t r; asm("cvt.rn.bf16x2.f32 %0, %1, %2;" : "=r"(r) : "f"(hi), "f"(lo)); return r; }
__device__ __forceinline__ float bf_lo(uint32_t v) { return __uint_as_float(v << 16); }
__device__ __forceinline__ float bf_hi(uint32_t v) { return __uint_as_float(v & 0xFFFF0000u); }
__device__ __forceinline__ float bf16r(float x) { return __uint_as_float(pack_bf16(0.f, x)); }
__device__ __forceinline__ uint32_t badd2(uint32_t a, uint32_t b) { uint32_t r; asm("add.rn.bf16x2 %0, %1, %2;" : "=r"(r) : "r"(a), "r"(b)); return r; }
__device__ __forceinline__ uint32_t bmul2(uint32_t a, uint32_t b) { uint32_t r; asm("mul.rn.bf16x2 %0, %1, %2;" : "=r"(r) : "r"(a), "r"(b)); return r; }
__device__ __forceinline__ float warp_sum(float v) {
#pragma unroll
  for (int o = 16; o > 0; o >>= 1) v += __shfl_xor_sync(0xffffffffu, v, o);
  return v;
}
__device__ __forceinline__ uint64_t make_desc(uint32_t addr) {
  return (uint64_t)((addr & 0x3FFFF) >> 4) | ((uint64_t)1 << 16) | ((uint64_t)64 << 32) | ((uint64_t)1 << 62);
}
__device__ __forceinline__ uint64_t make_desc_noswz(uint32_t addr) {
  return (uint64_t)((addr & 0x3FFFF) >> 4) | ((uint64_t)8 << 16) | ((uint64_t)16 << 32);
}
__device__ __forceinline__ void wgmma_n256(float (&d)[128], uint64_t da, uint64_t db, int scale_d) {
  asm volatile("{\n.reg .pred p;\nsetp.ne.b32 p, %130, 0;\n"
    "wgmma.mma_async.sync.aligned.m64n256k16.f32.bf16.bf16 "
    "{%0, %1, %2, %3, %4, %5, %6, %7, %8, %9, %10, %11, %12, %13, %14, %15, %16, %17, %18, %19, %20, %21, %22, %23, %24, %25, %26, %27, %28, %29, %30, %31, "
    "%32, %33, %34, %35, %36, %37, %38, %39, %40, %41, %42, %43, %44, %45, %46, %47, %48, %49, %50, %51, %52, %53, %54, %55, %56, %57, %58, %59, %60, %61, %62, %63, "
    "%64, %65, %66, %67, %68, %69, %70, %71, %72, %73, %74, %75, %76, %77, %78, %79, %80, %81, %82, %83, %84, %85, %86, %87, %88, %89, %90, %91, %92, %93, %94, %95, "
    "%96, %97, %98, %99, %100, %101, %102, %103, %104, %105, %106, %107, %108, %109, %110, %111, %112, %113, %114, %115, %116, %117, %118, %119, %120, %121, %122, %123, %124, %125, %126, %127}, "
    "%128, %129, p, 1, 1, 0, 0;\n}\n"
    : "+f"(d[0]), "+f"(d[1]), "+f"(d[2]), "+f"(d[3]), "+f"(d[4]), "+f"(d[5]), "+f"(d[6]), "+f"(d[7]),
      "+f"(d[8]), "+f"(d[9]), "+f"(d[10]), "+f"(d[11]), "+f"(d[12]), "+f"(d[13]), "+f"(d[14]), "+f"(d[15]),
      "+f"(d[16]), "+f"(d[17]), "+f"(d[18]), "+f"(d[19]), "+f"(d[20]), "+f"(d[21]), "+f"(d[22]), "+f"(d[23]),
      "+f"(d[24]), "+f"(d[25]), "+f"(d[26]), "+f"(d[27]), "+f"(d[28]), "+f"(d[29]), "+f"(d[30]), "+f"(d[31]),
      "+f"(d[32]), "+f"(d[33]), "+f"(d[34]), "+f"(d[35]), "+f"(d[36]), "+f"(d[37]), "+f"(d[38]), "+f"(d[39]),
      "+f"(d[40]), "+f"(d[41]), "+f"(d[42]), "+f"(d[43]), "+f"(d[44]), "+f"(d[45]), "+f"(d[46]), "+f"(d[47]),
      "+f"(d[48]), "+f"(d[49]), "+f"(d[50]), "+f"(d[51]), "+f"(d[52]), "+f"(d[53]), "+f"(d[54]), "+f"(d[55]),
      "+f"(d[56]), "+f"(d[57]), "+f"(d[58]), "+f"(d[59]), "+f"(d[60]), "+f"(d[61]), "+f"(d[62]), "+f"(d[63]),
      "+f"(d[64]), "+f"(d[65]), "+f"(d[66]), "+f"(d[67]), "+f"(d[68]), "+f"(d[69]), "+f"(d[70]), "+f"(d[71]),
      "+f"(d[72]), "+f"(d[73]), "+f"(d[74]), "+f"(d[75]), "+f"(d[76]), "+f"(d[77]), "+f"(d[78]), "+f"(d[79]),
      "+f"(d[80]), "+f"(d[81]), "+f"(d[82]), "+f"(d[83]), "+f"(d[84]), "+f"(d[85]), "+f"(d[86]), "+f"(d[87]),
      "+f"(d[88]), "+f"(d[89]), "+f"(d[90]), "+f"(d[91]), "+f"(d[92]), "+f"(d[93]), "+f"(d[94]), "+f"(d[95]),
      "+f"(d[96]), "+f"(d[97]), "+f"(d[98]), "+f"(d[99]), "+f"(d[100]), "+f"(d[101]), "+f"(d[102]), "+f"(d[103]),
      "+f"(d[104]), "+f"(d[105]), "+f"(d[106]), "+f"(d[107]), "+f"(d[108]), "+f"(d[109]), "+f"(d[110]), "+f"(d[111]),
      "+f"(d[112]), "+f"(d[113]), "+f"(d[114]), "+f"(d[115]), "+f"(d[116]), "+f"(d[117]), "+f"(d[118]), "+f"(d[119]),
      "+f"(d[120]), "+f"(d[121]), "+f"(d[122]), "+f"(d[123]), "+f"(d[124]), "+f"(d[125]), "+f"(d[126]), "+f"(d[127])
    : "l"(da), "l"(db), "r"(scale_d));
}
__device__ __forceinline__ void wgmma_n256_rs(float (&d)[128], uint32_t a0, uint32_t a1, uint32_t a2, uint32_t a3, uint64_t db, int scale_d) {
  asm volatile("{\n.reg .pred p;\nsetp.ne.b32 p, %133, 0;\n"
    "wgmma.mma_async.sync.aligned.m64n256k16.f32.bf16.bf16 "
    "{%0, %1, %2, %3, %4, %5, %6, %7, %8, %9, %10, %11, %12, %13, %14, %15, %16, %17, %18, %19, %20, %21, %22, %23, %24, %25, %26, %27, %28, %29, %30, %31, "
    "%32, %33, %34, %35, %36, %37, %38, %39, %40, %41, %42, %43, %44, %45, %46, %47, %48, %49, %50, %51, %52, %53, %54, %55, %56, %57, %58, %59, %60, %61, %62, %63, "
    "%64, %65, %66, %67, %68, %69, %70, %71, %72, %73, %74, %75, %76, %77, %78, %79, %80, %81, %82, %83, %84, %85, %86, %87, %88, %89, %90, %91, %92, %93, %94, %95, "
    "%96, %97, %98, %99, %100, %101, %102, %103, %104, %105, %106, %107, %108, %109, %110, %111, %112, %113, %114, %115, %116, %117, %118, %119, %120, %121, %122, %123, %124, %125, %126, %127}, "
    "{%128, %129, %130, %131}, %132, p, 1, 1, 0;\n}\n"
    : "+f"(d[0]), "+f"(d[1]), "+f"(d[2]), "+f"(d[3]), "+f"(d[4]), "+f"(d[5]), "+f"(d[6]), "+f"(d[7]),
      "+f"(d[8]), "+f"(d[9]), "+f"(d[10]), "+f"(d[11]), "+f"(d[12]), "+f"(d[13]), "+f"(d[14]), "+f"(d[15]),
      "+f"(d[16]), "+f"(d[17]), "+f"(d[18]), "+f"(d[19]), "+f"(d[20]), "+f"(d[21]), "+f"(d[22]), "+f"(d[23]),
      "+f"(d[24]), "+f"(d[25]), "+f"(d[26]), "+f"(d[27]), "+f"(d[28]), "+f"(d[29]), "+f"(d[30]), "+f"(d[31]),
      "+f"(d[32]), "+f"(d[33]), "+f"(d[34]), "+f"(d[35]), "+f"(d[36]), "+f"(d[37]), "+f"(d[38]), "+f"(d[39]),
      "+f"(d[40]), "+f"(d[41]), "+f"(d[42]), "+f"(d[43]), "+f"(d[44]), "+f"(d[45]), "+f"(d[46]), "+f"(d[47]),
      "+f"(d[48]), "+f"(d[49]), "+f"(d[50]), "+f"(d[51]), "+f"(d[52]), "+f"(d[53]), "+f"(d[54]), "+f"(d[55]),
      "+f"(d[56]), "+f"(d[57]), "+f"(d[58]), "+f"(d[59]), "+f"(d[60]), "+f"(d[61]), "+f"(d[62]), "+f"(d[63]),
      "+f"(d[64]), "+f"(d[65]), "+f"(d[66]), "+f"(d[67]), "+f"(d[68]), "+f"(d[69]), "+f"(d[70]), "+f"(d[71]),
      "+f"(d[72]), "+f"(d[73]), "+f"(d[74]), "+f"(d[75]), "+f"(d[76]), "+f"(d[77]), "+f"(d[78]), "+f"(d[79]),
      "+f"(d[80]), "+f"(d[81]), "+f"(d[82]), "+f"(d[83]), "+f"(d[84]), "+f"(d[85]), "+f"(d[86]), "+f"(d[87]),
      "+f"(d[88]), "+f"(d[89]), "+f"(d[90]), "+f"(d[91]), "+f"(d[92]), "+f"(d[93]), "+f"(d[94]), "+f"(d[95]),
      "+f"(d[96]), "+f"(d[97]), "+f"(d[98]), "+f"(d[99]), "+f"(d[100]), "+f"(d[101]), "+f"(d[102]), "+f"(d[103]),
      "+f"(d[104]), "+f"(d[105]), "+f"(d[106]), "+f"(d[107]), "+f"(d[108]), "+f"(d[109]), "+f"(d[110]), "+f"(d[111]),
      "+f"(d[112]), "+f"(d[113]), "+f"(d[114]), "+f"(d[115]), "+f"(d[116]), "+f"(d[117]), "+f"(d[118]), "+f"(d[119]),
      "+f"(d[120]), "+f"(d[121]), "+f"(d[122]), "+f"(d[123]), "+f"(d[124]), "+f"(d[125]), "+f"(d[126]), "+f"(d[127])
    : "r"(a0), "r"(a1), "r"(a2), "r"(a3), "l"(db), "r"(scale_d));
}
__device__ __forceinline__ void wgmma_n128(float (&d)[64], uint64_t da, uint64_t db) {
  asm volatile("{\n.reg .pred p;\nsetp.ne.b32 p, 1, 0;\n"
    "wgmma.mma_async.sync.aligned.m64n128k16.f32.bf16.bf16 "
    "{%0, %1, %2, %3, %4, %5, %6, %7, %8, %9, %10, %11, %12, %13, %14, %15, %16, %17, %18, %19, %20, %21, %22, %23, %24, %25, %26, %27, %28, %29, %30, %31, %32, %33, %34, %35, %36, %37, %38, %39, %40, %41, %42, %43, %44, %45, %46, %47, %48, %49, %50, %51, %52, %53, %54, %55, %56, %57, %58, %59, %60, %61, %62, %63}, "
    "%64, %65, p, 1, 1, 0, 0;\n}\n"
    : "+f"(d[0]), "+f"(d[1]), "+f"(d[2]), "+f"(d[3]), "+f"(d[4]), "+f"(d[5]), "+f"(d[6]), "+f"(d[7]), "+f"(d[8]), "+f"(d[9]), "+f"(d[10]), "+f"(d[11]), "+f"(d[12]), "+f"(d[13]), "+f"(d[14]), "+f"(d[15]), "+f"(d[16]), "+f"(d[17]), "+f"(d[18]), "+f"(d[19]), "+f"(d[20]), "+f"(d[21]), "+f"(d[22]), "+f"(d[23]), "+f"(d[24]), "+f"(d[25]), "+f"(d[26]), "+f"(d[27]), "+f"(d[28]), "+f"(d[29]), "+f"(d[30]), "+f"(d[31]), "+f"(d[32]), "+f"(d[33]), "+f"(d[34]), "+f"(d[35]), "+f"(d[36]), "+f"(d[37]), "+f"(d[38]), "+f"(d[39]), "+f"(d[40]), "+f"(d[41]), "+f"(d[42]), "+f"(d[43]), "+f"(d[44]), "+f"(d[45]), "+f"(d[46]), "+f"(d[47]), "+f"(d[48]), "+f"(d[49]), "+f"(d[50]), "+f"(d[51]), "+f"(d[52]), "+f"(d[53]), "+f"(d[54]), "+f"(d[55]), "+f"(d[56]), "+f"(d[57]), "+f"(d[58]), "+f"(d[59]), "+f"(d[60]), "+f"(d[61]), "+f"(d[62]), "+f"(d[63])
    : "l"(da), "l"(db));
}
__device__ __forceinline__ void fence_acc64(float (&d)[64]) {
#pragma unroll
  for (int i = 0; i < 64; i++) asm volatile("" : "+f"(d[i]) :: "memory");
}
__device__ __forceinline__ void fence_acc(float (&d)[128]) {
#pragma unroll
  for (int i = 0; i < 128; i++) asm volatile("" : "+f"(d[i]) :: "memory");
}

template<int N, int I = 0, class F> __device__ __forceinline__ void static_for(F&& f) {
  if constexpr (I < N) { f(std::integral_constant<int, I>()); static_for<N, I + 1>(f); }
}

__device__ __forceinline__ void ldsm_x4_t(uint32_t addr, uint32_t& a, uint32_t& b, uint32_t& c, uint32_t& d) {
  asm volatile("ldmatrix.sync.aligned.m8n8.x4.trans.shared.b16 {%0, %1, %2, %3}, [%4];" : "=r"(a), "=r"(b), "=r"(c), "=r"(d) : "r"(addr));
}
__device__ __forceinline__ void sts128(uint32_t addr, uint32_t a, uint32_t b, uint32_t c, uint32_t d) {
  asm volatile("st.shared.v4.b32 [%0], {%1, %2, %3, %4};" :: "r"(addr), "r"(a), "r"(b), "r"(c), "r"(d));
}
__device__ __forceinline__ void mma16816(float (&c)[4], uint32_t a0, uint32_t a1, uint32_t a2, uint32_t a3, uint32_t b0, uint32_t b1) {
  asm volatile("mma.sync.aligned.m16n8k16.row.col.f32.bf16.bf16.f32 {%0, %1, %2, %3}, {%4, %5, %6, %7}, {%8, %9}, {%0, %1, %2, %3};"
      : "+f"(c[0]), "+f"(c[1]), "+f"(c[2]), "+f"(c[3]) : "r"(a0), "r"(a1), "r"(a2), "r"(a3), "r"(b0), "r"(b1));
}
__device__ __forceinline__ void mma1688(float (&c)[4], uint32_t a0, uint32_t a1, uint32_t b0) {
  asm volatile("mma.sync.aligned.m16n8k8.row.col.f32.bf16.bf16.f32 {%0, %1, %2, %3}, {%4, %5}, {%6}, {%0, %1, %2, %3};"
      : "+f"(c[0]), "+f"(c[1]), "+f"(c[2]), "+f"(c[3]) : "r"(a0), "r"(a1), "r"(b0));
}
__device__ __forceinline__ void pin(uint32_t& v) { asm volatile("shfl.sync.bfly.b32 %0, %0, 0, 0x1f, 0xffffffff;" : "+r"(v)); }
template<class T> __device__ __forceinline__ void pin(T*& v) {
  uint32_t lo = (uint32_t)(uint64_t)v, hi = (uint32_t)((uint64_t)v >> 32);
  pin(lo); pin(hi);
  v = (T*)(((uint64_t)hi << 32) | lo);
}
__device__ __forceinline__ float sel4(int q, float a, float b, float c, float d) {
  float r;
  asm("{\n.reg .pred p, o;\n.reg .f32 x, y;\n.reg .b32 t;\nand.b32 t, %1, 1;\nsetp.ne.b32 p, t, 0;\nsetp.gt.s32 o, %1, 1;\n"
      "selp.f32 x, %3, %2, p;\nselp.f32 y, %5, %4, p;\nselp.f32 %0, y, x, o;\n}\n" : "=f"(r) : "r"(q), "f"(a), "f"(b), "f"(c), "f"(d));
  return r;
}
__device__ __forceinline__ uint32_t bfma2(uint32_t a, uint32_t b, uint32_t c) { uint32_t r; asm("fma.rn.bf16x2 %0, %1, %2, %3;" : "=r"(r) : "r"(a), "r"(b), "r"(c)); return r; }
__device__ __forceinline__ void tma_store_5d(const CUtensorMap* tm, uint32_t src, int c0, int c3, int c4) {
  asm volatile("cp.async.bulk.tensor.5d.global.shared::cta.bulk_group [%0, {%2, %3, %3, %4, %5}], [%1];" :: "l"(tm), "r"(src), "r"(c0), "r"(0), "r"(c3), "r"(c4) : "memory");
}
__device__ __forceinline__ float rcp_fast(float x) { float r; asm("rcp.approx.ftz.f32 %0, %1;" : "=f"(r) : "f"(x)); return r; }
__device__ __forceinline__ float sigmoid_fast(float x) { float e; asm("ex2.approx.ftz.f32 %0, %1;" : "=f"(e) : "f"(x * -1.4426950408889634f)); return rcp_fast(1.f + e); }
__device__ __forceinline__ float sqrt_fast(float x) { float r; asm("sqrt.approx.ftz.f32 %0, %1;" : "=f"(r) : "f"(x)); return r; }
__device__ __forceinline__ float ln_sd(float var) { return bf16r(sqrt_fast(bf16r(bf16r(fmaxf(var, 0.f)) + 1e-5f))); }
__device__ __forceinline__ uint32_t norm2(uint32_t h, uint32_t neg_mean2, float inv_sd) {
  const uint32_t d = badd2(h, neg_mean2);
  return pack_bf16(bf_lo(d) * inv_sd, bf_hi(d) * inv_sd);
}
template<int N> __device__ __forceinline__ void delay_clk() {
  if constexpr (N > 0) { const uint32_t t0 = clock(); while ((uint32_t)clock() - t0 < N) {} }
}
template<int V> using IC = std::integral_constant<int, V>;

#define CT(slot) do {} while (0)
#define PT(slot) do {} while (0)

template<int MAP>
__global__ void __cluster_dims__(2, 1, 1) __launch_bounds__(384, 1)
fnet_moe_kernel(const __grid_constant__ Params p) {
  uint32_t sb;
  asm volatile("mov.u32 %0, %1;" : "=r"(sb) : "r"(smem_u32(smem_raw)));
  const int m = blockIdx.x & 1;
  int tau, eps;
  bool idle = false;
  if (MAP == 0) {
    uint32_t smid;
    asm volatile("mov.u32 %0, %%smid;" : "=r"(smid));
    const int c = smid >> 1, e7 = ((c - 32) * 37) >> 8;
    idle = c == 60 || c == 61;
    tau = c < 32 ? (c & 7) : (c < 60 ? c - 31 - 7 * e7 : 0);
    eps = c < 32 ? (c >> 3) : (c < 60 ? 4 + e7 : c - 58);
  } else {
    tau = (blockIdx.x >> 1) & 7; eps = blockIdx.x >> 4;
  }
  const int cid = tau * 16 + eps * 2 + m;
  const bool moe = tau > 0;
  auto BAR = [&](int i) { return sb + OFF_BAR + 8 * i; };
  const CUtensorMap* tmD = m ? &p.tmD1 : &p.tmD0;
  const uint64_t pol_ef = policy_evict_first();
#define LOAD_STREAM(d, tm, bar, c0, c1) tma_load_2d_hint(d, tm, bar, c0, c1, pol_ef)
  if (threadIdx.x < 32 && !idle) {
    if (elect_one()) {
#pragma unroll
      for (int k = 0; k < 4; k++) mbar_init(BAR(B_FULL + k), 1);
      asm volatile("fence.mbarrier_init.release.cluster;" ::: "memory");
#pragma unroll
      for (int k = 0; k < 4; k++) mbar_expect_tx(BAR(B_FULL + k), ST_BYTES);
    }
    PT(50);
    if (elect_one()) {
      tma_load_2d(sb + A_BYTES, &p.tmX, BAR(B_FULL), 0, tau * 256);
      LOAD_STREAM(sb, tmD, BAR(B_FULL), 0, eps * 128);
    }
    PT(52);
    if (elect_one()) {
#pragma unroll
      for (int k = 1; k < 4; k++) {
        tma_load_2d(sb + k * ST_BYTES + A_BYTES, &p.tmX, BAR(B_FULL + k), k * 64, tau * 256);
        LOAD_STREAM(sb + k * ST_BYTES, tmD, BAR(B_FULL + k), k * 64, eps * 128);
      }
    }
    PT(0);
  }
  __syncwarp();
  const int warp = __shfl_sync(0xffffffffu, threadIdx.x >> 5, 0);
  const int tid = __shfl_sync(0xffffffffu, threadIdx.x, threadIdx.x & 31), lane = tid & 31;
  if (idle) {
    __nanosleep(4000);
    const uint32_t tg = ld_relaxed32(&p.s->epoch) + 1;
    uint32_t n = 0;
    do { __nanosleep(1000); } while (!__all_sync(0xffffffffu, pkt_ld64(&p.s->xstat[(tid & 127) * 16]).y == tg) && ++n < 4096);
    return;
  }
  if (warp == 8) {
    if (elect_one()) {
#pragma unroll
      for (int b = B_EMPTY; b < B_COUNT; b++)
        mbar_init(BAR(b), b < B_EPI ? 2 : (b == B_EPI || b == B_EPI0B) ? 4 : (b < B_STD || b == B_OUT) ? 8 : (b == B_STAT || b == B_XS) ? 3 : 1);
      asm volatile("fence.mbarrier_init.release.cluster;" ::: "memory");
      mbar_expect_tx(BAR(B_XCH), 32768);
      SM_(uint32_t, OFF_SEEN) = 0;
    }
  }
  __syncthreads();

  if (warp >= 8) {
    reg_dec<REG_P>();
    asm volatile("barrier.cluster.arrive.relaxed.aligned;" ::: "memory");
    const int abrow = m * 1024 + eps * 128;
    const int f0 = (cid - 16) * 32;
    if (warp == 8) {
      const CUtensorMap* tmW = m ? &p.tmW1 : &p.tmW0;
      const int tA = tau * 256 + m * 128, tB = tau * 256 + (1 - m) * 128;
      uint32_t seen = 0;
#pragma unroll 1
      for (int k = 4; k < 48; k++) {
        const int s = slot_of(k);
        const uint32_t sa = sb + s * ST_BYTES, sbb = sa + A_BYTES;
        const int kb = kblock(tau, k - 16);
        mbar_wait(BAR(B_EMPTY + s), (use_of(k) & 1) ^ 1);
        PT(64 + k);
        if (elect_one()) {
          mbar_expect_tx(BAR(B_FULL + s), (k >> 1) == 9 ? B_BYTES : k == 20 ? ST_BYTES - 8192 : ST_BYTES);
          if (k < 16) {
            LOAD_STREAM(sa, tmD, BAR(B_FULL + s), k * 64, eps * 128);
            tma_load_2d(sbb, &p.tmX, BAR(B_FULL + s), k * 64, tau * 256);
          } else {
            LOAD_STREAM(sbb, tmW, BAR(B_FULL + s), kb * 64, tA);
            LOAD_STREAM(sbb + 16384, tmW, BAR(B_FULL + s), kb * 64, tB);
            if (k < 18) {
              tma_load_2d(sa, &p.tmXr, BAR(B_FULL + s), eps * 128, tA + s * 64);
              tma_load_2d(sa + 8192, &p.tmXr, BAR(B_FULL + s), eps * 128 + 64, tA + s * 64);
            }
          }
        }
        if (k >= 24) {
          uint32_t n = 0;
          while (!((seen >> kb) & 1) && ++n < SPIN_LIMIT * 16) seen = *(volatile uint32_t*)&SM_(uint32_t, OFF_SEEN);
          if (elect_one()) tma_load_2d(sa, &p.tmAbL, BAR(B_FULL + s), kb * 64, abrow);
        }
        if (k == PUB_K1 && elect_one()) mbar_arrive(BAR(B_LATE));
        if (k >= WPF_K0 + WPF_J0 && k < WPF_K0 + WPF_J1 && (eps >> 1) == ((k - WPF_K0) & 3) && elect_one())
          asm volatile("cp.async.bulk.prefetch.tensor.2d.L2.global.tile [%0, {%1, %2}];" :: "l"(tmW), "r"(kblock(tau, k - WPF_K0) * 64), "r"(tau * 256 + (eps & 1) * 128) : "memory");
        if (moe && k >= PF_K0 && !(k & 1)) {
          const int i = k < PF_K1 ? (k - PF_K0) >> 1 : PF_N0 + ((k - PF_K1) >> 1);
          if ((k >= PF_K1 || i < PF_N0) && elect_one()) {
            if (i < 8) asm volatile("cp.async.bulk.prefetch.tensor.2d.L2.global.tile [%0, {%1, %2}];" :: "l"(m ? &p.tmU : &p.tmG), "r"(f0), "r"(i * 128) : "memory");
            else if (i < 12) asm volatile("cp.async.bulk.prefetch.L2.global [%0], %1;" :: "l"(p.wdown + (size_t)f0 * 1024 + (i - 8) * 8192), "r"(16384) : "memory");
          }
        }
        if (moe && k >= MR_K0) {
          const int i = k - MR_K0, r6 = (i * 43) >> 8, u = i - 6 * r6, h = 2 * r6 + (u >> 1);
          if (u < 4 && h < NREG_H + 2) {
            if (h < 2) mbar_wait(BAR(B_STD + 2 + h), 0);
            if (elect_one()) {
              const uint32_t bar = BAR(h < NREG_H ? B_MR + (h & 1) : B_GU);
              if (!(u & 1) && h <= NREG_H) mbar_expect_tx(bar, h < NREG_H ? 16384 : (8 - NREG_H) * 16384);
              LOAD_STREAM(sb + OFF_XCH + u * 8192, (u & 1) ? &p.tmU : &p.tmG, bar, f0, h * 128);
            }
          }
        }
      }
      if (moe) {
        mbar_wait(BAR(B_EMPTY + 0), 1);
        if (elect_one()) mbar_expect_tx(BAR(B_DN), 65536);
#pragma unroll 1
        for (int i = 0; i < 10 - NREG_H; i++) {
          if (i == 3) mbar_wait(BAR(B_EMPTY + 1), 1);
          if (i == 4) {
            mbar_wait(BAR(B_EMPTY + 2), 1);
            mbar_wait(BAR(B_XCH), 0);
          }
          const uint32_t dst = sb + late_off(i);
          if (elect_one()) {
            if (i < 6 - NREG_H) {
              LOAD_STREAM(dst, &p.tmG, BAR(B_GU), f0, (NREG_H + 2 + i) * 128);
              LOAD_STREAM(dst + 8192, &p.tmU, BAR(B_GU), f0, (NREG_H + 2 + i) * 128);
            } else {
#pragma unroll
              for (int b = 0; b < 4; b++) LOAD_STREAM(dst + b * 4096, &p.tmDn, BAR(B_DN), (4 * (i - 6 + NREG_H) + b) * 64, f0);
            }
          }
          const long long t0 = clock64();
          while (i < 9 - NREG_H && clock64() - t0 < MOE_PACE_CLK) {}
        }
      }
    } else {
      const int a = warp - 9;
      const long long t_aux = clock64() - PROLOGUE_CLK;
      auto stage = [&](const bf16* src, int g) {
        if (elect_one()) {
          mbar_expect_tx(BAR(B_AUX + g), 16384);
          bulk_load(sb + OFF_XCH + g * 16384, src + g * 8192, 16384, BAR(B_AUX + g));
        }
      };
      mbar_wait(BAR(B_FULL + 0), 0);
      if (a == 0) PT(1);
      if (a < 2) stage(p.x + (size_t)cid * 16 * 1024, a);
      const uint32_t tag = ld_relaxed32(&p.s->epoch) + 1;
      if (a == 2) {
        float s = 0.f;
#pragma unroll
        for (int q = 0; q < 4; q++) {
          const uint4 v = ldg_nc128(p.wr + (q * 32 + lane) * 8);
          s += ((bf_lo(v.x) + bf_hi(v.x)) + (bf_lo(v.y) + bf_hi(v.y))) + ((bf_lo(v.z) + bf_hi(v.z)) + (bf_lo(v.w) + bf_hi(v.w)));
          const int ch = q * 32 + lane - eps * 16;
          if (ch >= 0 && ch < 16) {
            SM_(uint32_t, OFF_WR + ch * 4) = v.x; SM_(uint32_t, OFF_WR + 80 + ch * 4) = v.y;
            SM_(uint32_t, OFF_WR + 160 + ch * 4) = v.z; SM_(uint32_t, OFF_WR + 240 + ch * 4) = v.w;
          }
        }
        s = warp_sum(s);
        if (lane == 0) { SM_(float, OFF_WSUM) = s; SM_(uint32_t, OFF_TAG) = tag; }
      }
#pragma unroll 1
      for (int it = 0; it < 4; it++) {
        const int g = it & 1;
        mbar_wait(BAR(B_AUX + g), it >> 1);
        if (a == 0) PT(2 + it);
        const uint32_t ad = sb + OFF_XCH + g * 16384 + (lane >> 2) * 2048;
        float s0 = 0.f, s1 = 0.f, q0 = 0.f, q1 = 0.f;
        auto row = [&](auto sq) {
#pragma unroll
          for (int i = 0; i < 11; i++) {
            if (i == 10 && a == 2) break;
            const uint4 v = lds128_v(ad + (((a * 44 + 4 * i + lane) & 127) << 4));
            const uint32_t ww[4] = {v.x, v.y, v.z, v.w};
#pragma unroll
            for (int z = 0; z < 4; z++) {
              const float d0 = bf_lo(ww[z]), d1 = bf_hi(ww[z]);
              s0 += d0; s1 += d1;
              if (decltype(sq)::value) { q0 = fmaf(d0, d0, q0); q1 = fmaf(d1, d1, q1); }
            }
          }
        };
        if (it < 2) row(IC<1>()); else row(IC<0>());
        s0 += s1; q0 += q1;
#pragma unroll
        for (int o = 1; o < 4; o <<= 1) { s0 += __shfl_xor_sync(0xffffffffu, s0, o); q0 += __shfl_xor_sync(0xffffffffu, q0, o); }
        if ((lane & 3) == 0) SM_(float2, OFF_PUB + a * 256 + it * 64 + (lane >> 2) * 8) = make_float2(s0, q0);
        if (it != 2) bar_sync(NB_AUX, 96);
        if (it < 2 && a == 2) stage(cid < 64 ? p.Dre + (size_t)cid * 16 * 1024 : p.Dim + (size_t)(cid - 64) * 16 * 1024, g);
      }
      if (a == 1) {
        const float2 v0 = SM_(float2, OFF_PUB + lane * 8), v1 = SM_(float2, OFF_PUB + 256 + lane * 8), v2 = SM_(float2, OFF_PUB + 512 + lane * 8);
        const float s = v0.x + v1.x + v2.x, mean = s * (1.f / 1024.f);
        const float rs = rcp_fast(ln_sd((v0.y + v1.y + v2.y) * (1.f / 1024.f) - mean * mean));
        pkt_st64((lane < 16 ? p.s->xstat : p.s->dsum) + cid * 16 + (lane & 15), lane < 16 ? pack_bf16(rs, mean) : __float_as_uint(s), tag);
        PT(6);
      }
      auto prefetch = [&](int r) {
        const int l = r * 32 + lane;
        const bf16* ad = l < 1024 ? (((l >> 6) & 1) ? p.wup : p.wgate) + (size_t)((l >> 7) * 128 + m * 64 + (l & 63)) * 3584 + (f0 & ~63)
                                  : p.wdown + (size_t)f0 * 1024 + (l - 1024) * 64;
        if (moe) asm volatile("prefetch.global.L2 [%0];" :: "l"(ad));
      };
      __nanosleep(GATHER_NS);
      {
        const int i0 = a * 32 + lane;
        uint2 v[3], c0, c1; uint32_t n = 0;
        const uint2* dp = &p.s->dsum[abrow];
        while (true) {
#pragma unroll
          for (int q = 0; q < 3; q++) v[q] = pkt_ld64(&p.s->xstat[tau * 256 + min(i0 + 96 * q, 255)]);
          c0 = pkt_ld64(dp + i0); c1 = pkt_ld64(dp + min(i0 + 96, 127));
          if (__all_sync(0xffffffffu, v[0].y == tag && v[1].y == tag && v[2].y == tag && c0.y == tag && c1.y == tag) || ++n > SPIN_LIMIT) break;
          __nanosleep(200);
        }
#pragma unroll
        for (int q = 0; q < 3; q++) {
          const int col = min(i0 + 96 * q, 255);
          SM_(uint16_t, OFF_RS + ((col & 7) >> 1) * 144 + (col >> 3) * 4 + (col & 1) * 2) = (uint16_t)(v[q].x ^ (m << 15));
          const uint32_t nm = (v[q].x >> 16) ^ 0x8000u;
          SM_(uint4, OFF_EXB + (col >> 3) * 256 + (col & 7) * 16) = make_uint4(nm | (nm << 16), nm, 0, 0);
          SM_(uint4, OFF_EXB + (col >> 3) * 256 + 128 + (col & 7) * 16) = make_uint4(0, 0, 0, 0);
        }
#pragma unroll
        for (int q = 0; q < 2; q++) {
          const int e = min(i0 + 96 * q, 127);
          const float c = __uint_as_float(q ? c1.x : c0.x);
          const float hi = bf16r(c), mid = bf16r(c - hi), lo = bf16r((c - hi) - mid);
          SM_(uint4, OFF_EXA + (e >> 3) * 256 + (e & 7) * 16) = make_uint4((__float_as_uint(hi) >> 16) | (__float_as_uint(mid) & 0xFFFF0000u), __float_as_uint(lo) >> 16, 0, 0);
          SM_(uint4, OFF_EXA + (e >> 3) * 256 + 128 + (e & 7) * 16) = make_uint4(0, 0, 0, 0);
        }
        fence_async_smem();
      }
      __syncwarp();
      if (lane == 0) mbar_arrive(BAR(B_STAT));
      if (a == 0) PT(7);
      if (a == 0) {
        const int sg = (lane >> 2) == tau ? (tau + 1) & 7 : lane >> 2;
        const uint32_t* flg = reinterpret_cast<const uint32_t*>(&p.s->abflag[((eps * 2 + m) * 8 + sg) * 2]) + ((lane >> 2) == tau ? 4 : lane & 3);
        uint32_t seen = 0;
        mbar_wait(BAR(B_STDA), 0);
        PT(49);
#pragma unroll 1
        for (int i = 0; i < 5; i++) {
          const int s = i ? i - 1 : 0, sig = (tau + 1 + s) & 7;
          if (i == 1) mbar_wait(BAR(B_STD + 0), 0);
          uint32_t n = 0;
          while (!((seen >> (4 * (i ? sig : tau))) & 1) && ++n < SPIN_LIMIT) seen = __ballot_sync(0xffffffffu, ld_relaxed32(flg) == tag);
          if (i == 0 || i == 4) mbar_wait(BAR(i ? B_STD + 1 : B_EPI0B), 0);
          if (i != 1) mbar_wait(BAR(B_FULL + s), 0);
          PT(i ? 16 + s : 48);
          if (elect_one()) {
            if (i == 1) mbar_expect_tx(BAR(B_A20), 8192);
            tma_load_2d(sb + (i < 3 ? OFF_XCH + i * 8192 : s * ST_BYTES), i < 2 ? &p.tmAbS : &p.tmAbL, BAR(i == 1 ? B_A20 : B_FULL + s), sig * 256,
                        abrow + (i == 1 ? 64 : 0));
          }
        }
        uint32_t n = 0;
        while (true) {
          asm volatile("fence.proxy.async.global;" ::: "memory");
          *(volatile uint32_t*)&SM_(uint32_t, OFF_SEEN) = seen;
          if (seen == 0xFFFFFFFFu || ++n > SPIN_LIMIT) break;
          seen = __ballot_sync(0xffffffffu, ld_relaxed32(flg) == tag);
          __nanosleep(100);
        }
      } else if (a == 1) {
#pragma unroll 1
        for (int c = 0; c < 4; c++) {
          uint32_t* flag = reinterpret_cast<uint32_t*>(&p.s->abflag[((eps * 2 + m) * 8 + tau) * 2]) + c;
          mbar_wait(BAR(B_EPI + c), 0);
          if (c == 1) mbar_wait(BAR(B_LATE), 0);
          PT(8 + c);
          if (c >= 2) {
            bf16* dst = p.s->abT + (size_t)(abrow + (lane >> 3)) * 2048 + tau * 256 + c * 64;
#pragma unroll 4
            for (int i = 0; i < 32; i++) {
              const int row = 4 * i + (lane >> 3);
              const uint4 v = lds128_v(sb + chunk_off(c, 0) + i * 512 + lane * 16);
              asm volatile("st.global.v4.b32 [%0], {%1, %2, %3, %4};" :: "l"(dst + i * 4 * 2048 + (((lane & 7) ^ (row & 7)) << 3)), "r"(v.x), "r"(v.y), "r"(v.z), "r"(v.w));
            }
            __syncwarp();
            if (lane == 0) mbar_arrive(BAR(B_STD + c));
            if (c == 3) {
              asm volatile("fence.acq_rel.gpu;" ::: "memory");
              if (lane < 2) st_relaxed32(flag - lane, tag);
            }
            PT(12 + c);
            continue;
          }
          if (lane == 0) {
            tma_store_2d(&p.tmAbS, sb + chunk_off(c, 0), tau * 256 + c * 64, abrow);
            if (c == 0) {
              bulk_commit();
              bulk_wait_all();
              st_relaxed32(flag + 4, tag);
              mbar_arrive(BAR(B_STDA));
            }
          }
          mbar_wait(BAR(B_EPI0B), 0);
          if (lane == 0) {
            tma_store_2d(&p.tmAbS, sb + chunk_off(c, 1), tau * 256 + c * 64, abrow + 64);
            bulk_commit();
            bulk_wait_all();
            st_relaxed32(flag, tag);
            mbar_arrive(BAR(B_STD + c));
          }
          PT(12 + c);
        }
      } else {
      }
      {
        const uint4* kp = &p.s->key[(tau * 16 + (lane & 15)) * 2];
        const int i0 = a * 32 + lane;
        mbar_wait(BAR(B_KEY), 0);
        if (a == 0) PT(43);
        uint4 kq = pkt_ld128(kp), cv[3];
        uint32_t n = 0, kv;
        int gspec = -1;
        while (true) {
          const bool ok = kq.y == tag && kq.w == tag;
          kv = __reduce_max_sync(0xffffffffu, ok ? kq.x : 0u);
          const int gs = (0xFFFF - (int)(kv & 0xFFFFu)) >> 7;
          const bool cok = gs == gspec && cv[0].y == tag && cv[0].w == tag && cv[1].y == tag && cv[1].w == tag && cv[2].y == tag && cv[2].w == tag;
          if (__all_sync(0xffffffffu, ok && cok) || ++n > SPIN_LIMIT) break;
          if (!ok) kq = pkt_ld128(kp);
          const bool spec = __popc(__ballot_sync(0xffffffffu, ok)) >= 2 * SPEC_MIN;
          if (!cok && spec) {
#pragma unroll
            for (int i = 0; i < 3; i++) cv[i] = pkt_ld128(&p.s->cand[gs * 256 + min(i0 + 96 * i, 255)]);
          }
          if (spec) gspec = gs;
        }
        if (a == 0) PT(45);
        const uint32_t ms = __shfl_sync(0xffffffffu, kq.z, gspec);
        const uint32_t nm = ((ms & 0xFFFFu) ^ 0x8000u) * 0x10001u;
        const float is = rcp_fast(bf_hi(ms));
#pragma unroll
        for (int i = 0; i < 3; i++) {
          const int j = min(i0 + 96 * i, 255);
          SM_(uint2, OFF_XSEL + j * 8) = make_uint2(norm2(cv[i].x, nm, is), norm2(cv[i].z, nm, is));
          SM_(uint2, OFF_HSEL + j * 8) = make_uint2(cv[i].x, cv[i].z);
        }
        SM_(uint32_t, OFF_KV) = kv;
        __syncwarp();
        if (lane == 0) mbar_arrive(BAR(B_XS));
      }
    }
    if (warp == 8) {
      const int lane = threadIdx.x & 31;
      mbar_wait(BAR(B_OUT), 0);
      const uint32_t km = SM_(uint32_t, OFF_WKEY + (lane & 7) * 8);
      const uint32_t bk = __reduce_max_sync(0xffffffffu, km);
      const int ww = __ffs(__ballot_sync(0xffffffffu, km == bk)) - 1;
#pragma unroll 1
      for (int i = 1; i <= 8; i++) {
        const int W = (ww + i) & 7;
        if (i == 8) {
          mbar_wait(BAR(B_XS), 0);
          if (SM_(uint32_t, OFF_KV) == bk) {
#pragma unroll 2
            for (int j = lane; j < 256; j += 32) {
              const int rho = j >> 4, row = (tau * 2 + m) * 128 + 32 * (W >> 1) + 8 * ((rho & 7) >> 1) + 4 * (W & 1) + 2 * (rho >> 3) + (rho & 1);
              const uint4 v = lds128_v(sb + OFF_OUT + (j & 8) * 2048 + (16 * W + rho) * 128 + (((j ^ rho) & 7) << 4));
              if (row != 0xFFFF - (int)(bk & 0xFFFFu))
                asm volatile("st.global.v4.b32 [%0], {%1, %2, %3, %4};" :: "l"(p.out + (size_t)row * 1024 + eps * 128 + (j & 15) * 8), "r"(v.x), "r"(v.y), "r"(v.z), "r"(v.w));
            }
            break;
          }
        }
        if (lane == 0) {
          tma_store_5d(&p.tmOut, sb + OFF_OUT + W * 2048, eps * 128, 2 * (W & 1), tau * 8 + m * 4 + (W >> 1));
          tma_store_5d(&p.tmOut, sb + OFF_OUT + 16384 + W * 2048, eps * 128 + 64, 2 * (W & 1), tau * 8 + m * 4 + (W >> 1));
        }
        const long long t0 = clock64();
        while (i < 7 && clock64() - t0 < OUT_PACE_CLK) {}
      }
      if (lane == 0) { bulk_commit(); bulk_wait_all(); }
      PT(22);
    }
    asm volatile("barrier.cluster.wait.aligned;" ::: "memory");
  } else {
    reg_inc<REG_C>();
    const int w = warp >> 2, wi = warp & 3, t = tid & 127;
    const int g = lane >> 2, q = lane & 3;
    const int turn_me = NB_TURN0 + w, turn_other = NB_TURN1 - w;
    float acc[128];
#pragma unroll
    for (int i = 0; i < 128; i++) acc[i] = 0.f;
    if (w == 1) bar_arrive(NB_TURN0, 256);
    auto kstep = [&](int k, bool first, bool a_in_xch = false) {
      const int s = slot_of(k);
      mbar_wait(BAR(B_FULL + s), use_of(k) & 1);
      CT(64 + k);
      bar_sync(turn_me, 256);
      const uint64_t da = make_desc(sb + (a_in_xch ? OFF_XCH + s * 16384 : s * ST_BYTES) + w * 8192), db = make_desc(sb + s * ST_BYTES + A_BYTES);
      wgmma_fence();
      wgmma_n256(acc, da, db, !first);
#pragma unroll
      for (int kk = 1; kk < 4; kk++) wgmma_n256(acc, da + kk * 2, db + kk * 2, 1);
      wgmma_commit();
      bar_arrive(turn_other, 256);
    };
    auto release = [&](int s) { if (t == 0) mbar_arrive(BAR(B_EMPTY + s)); };
    auto kdone = [&](int k) { wgmma_wait0(); release(slot_of(k)); };
    auto wgmma_wait1 = [&]() { asm volatile("wgmma.wait_group.sync.aligned 1;" ::: "memory"); };

#pragma unroll 1
    for (int k = 0; k < 14; k++) {
      kstep(k, k == 0);
      if (k == 0) CT(0);
      if (k == 8 && warp == 2 && lane < 2) pkt_st128(&p.s->abflag[((eps * 2 + m) * 8 + tau) * 2 + lane], 0, 0, 0, 0);
      kdone(k);
    }
    uint32_t R[64];
    uint32_t tag;
    {
      const uint32_t rsa = sb + OFF_RS + q * 144;
      const uint64_t da2 = make_desc(sb + 2 * ST_BYTES + w * 8192), db2 = make_desc(sb + 2 * ST_BYTES + A_BYTES);
      const uint64_t da3 = make_desc(sb + 3 * ST_BYTES + w * 8192), db3 = make_desc(sb + 3 * ST_BYTES + A_BYTES);
      mbar_wait(BAR(B_FULL + 2), 1);
      CT(64 + 14);
      bar_sync(turn_me, 256);
      wgmma_fence();
#pragma unroll
      for (int kk = 0; kk < 4; kk++) wgmma_n256(acc, da2 + kk * 2, db2 + kk * 2, 1);
      wgmma_commit();
      mbar_wait(BAR(B_FULL + 3), 1);
      CT(64 + 15);
      wgmma_fence();
      wgmma_n256(acc, da3, db3, 1);
      wgmma_n256(acc, da3 + 2, db3 + 2, 1);
      wgmma_commit();
      mbar_wait(BAR(B_STAT), 0);
      tag = SM_(uint32_t, OFF_TAG);
#pragma unroll
      for (int i = 0; i < 8; i++) { const uint4 v = lds128_v(rsa + i * 16); R[8 * i] = v.x; R[8 * i + 2] = v.y; R[8 * i + 4] = v.z; R[8 * i + 6] = v.w; }
      wgmma_wait1();
      release(2);
      wgmma_fence();
      wgmma_n256(acc, da3 + 4, db3 + 4, 1);
      wgmma_n256(acc, da3 + 6, db3 + 6, 1);
      wgmma_n256(acc, make_desc_noswz(sb + OFF_EXA + w * 2048), make_desc_noswz(sb + OFF_EXB), 1);
      wgmma_commit();
      bar_arrive(turn_other, 256);
      kdone(15);
      mbar_wait(BAR(B_STAT), 0);
    }
    fence_acc(acc);
    CT(1);
    auto pack = [&](auto cc) {
      constexpr int c = decltype(cc)::value;
#pragma unroll
      for (int j = 8 * c; j < 8 * c + 8; j++) {
        const uint32_t rs = R[2 * j];
        const float* ac = &acc[4 * j];
        R[2 * j] = bmul2(pack_bf16(ac[0], ac[1]), rs);
        R[2 * j + 1] = bmul2(pack_bf16(ac[2], ac[3]), rs);
      }
    };
    auto put_chunk = [&](auto cc) {
      constexpr int c = decltype(cc)::value;
      const int rho = 16 * wi + (lane & 15);
#pragma unroll
      for (int j = 8 * c; j < 8 * c + 8; j += 2) {
        const int chunk = (j & 7) + (lane >> 4);
        stsm_x4(sb + chunk_off(c, w) + rho * 128 + ((chunk ^ (lane & 7)) << 4), R[2 * j], R[2 * j + 1], R[2 * j + 2], R[2 * j + 3]);
      }
    };
    auto staged = [&](int bar) {
      fence_async_smem();
      __syncwarp();
      if (lane == 0) mbar_arrive(BAR(bar));
    };
    auto mma_rs = [&](auto cc, auto k0, auto k1) {
      constexpr int c = decltype(cc)::value;
      const uint64_t db = make_desc(sb + c * ST_BYTES + A_BYTES);
#pragma unroll
      for (int kk = decltype(k0)::value; kk < decltype(k1)::value; kk++)
        wgmma_n256_rs(acc, R[16 * c + 4 * kk], R[16 * c + 4 * kk + 1], R[16 * c + 4 * kk + 2], R[16 * c + 4 * kk + 3], db + kk * 2, c + kk > 0);
      wgmma_commit();
    };
    auto kdone_x = [&](int k, auto ic) {
      constexpr int i = decltype(ic)::value;
      uint32_t r[8];
#pragma unroll
      for (int z = 0; z < 2; z++) {
        const int tr = 32 * (i & 1) + 16 * z + 8 * (lane >> 4) + (lane & 7), chunk = 2 * wi + ((lane >> 3) & 1);
        ldsm_x4_t(sb + (i >> 1) * ST_BYTES + w * 8192 + tr * 128 + ((chunk ^ (lane & 7)) << 4), r[4 * z], r[4 * z + 1], r[4 * z + 2], r[4 * z + 3]);
      }
      float f[16];
#pragma unroll
      for (int z = 0; z < 8; z++) { f[2 * z] = bf_lo(r[z]); f[2 * z + 1] = bf_hi(r[z]); }
#pragma unroll
      for (int z = 0; z < 16; z++) asm volatile("" : "+f"(f[z]));
      kdone(k);
#pragma unroll
      for (int z = 0; z < 16; z++) asm volatile("add.f32 %0, %0, %1;" : "+f"(acc[16 * i + z]) : "f"(f[z]));
    };
    pack(IC<0>());
    put_chunk(IC<0>());
    staged(w ? B_EPI0B : B_EPI);
    mbar_wait(BAR(B_STAT), 0);
    CT(21);
    pack(IC<1>());
    pack(IC<2>());
    pack(IC<3>());
#pragma unroll
    for (int i = 16; i < 64; i++) asm volatile("" : "+r"(R[i]));
    mbar_wait(BAR(B_FULL + 0), 0);
    CT(2);
    CT(64 + 16);
    bar_sync(turn_me, 256);
    wgmma_fence();
    mma_rs(IC<0>(), IC<0>(), IC<4>());
    mbar_wait(BAR(B_FULL + 1), 0);
    CT(64 + 17);
    wgmma_fence();
    mma_rs(IC<1>(), IC<0>(), IC<2>());
    wgmma_wait1();
    release(0);
    mma_rs(IC<1>(), IC<2>(), IC<4>());
    bar_arrive(turn_other, 256);
    kdone_x(17, IC<0>());
    static_for<2>([&](auto ic) {
      constexpr int c = 2 + decltype(ic)::value;
      mbar_wait(BAR(B_FULL + c), 0);
      CT(64 + 16 + c);
      bar_sync(turn_me, 256);
      wgmma_fence();
      mma_rs(IC<c>(), IC<0>(), IC<4>());
      bar_arrive(turn_other, 256);
      if (c == 2) { put_chunk(IC<1>()); staged(B_EPI + 1); }
      kdone_x(16 + c, IC<c - 1>());
    });
#pragma unroll 1
    for (int k = 20; k < 23; k++) {
      if (w == 1) mbar_wait(BAR(B_A20), 0);
      kstep(k, false, k < 22);
      if (k == 20) {
        kdone_x(k, IC<3>());
      } else {
        if (k == 21) put_chunk(IC<2>()); else put_chunk(IC<3>());
        __syncwarp();
        if (lane == 0) mbar_arrive(BAR(B_EPI + k - 19));
        kdone(k);
      }
    }
    uint32_t wf[32][4];
    auto load_wf = [&](auto hc) {
      constexpr int h = decltype(hc)::value;
      const int d = w * 64 + (lane >> 4) * 8 + (lane & 7);
      const uint32_t ad = sb + round_off(h) + (lane & 8) * 1024 + d * 64 + ((wi ^ ((lane >> 1) & 3)) << 4);
#pragma unroll
      for (int i = 0; i < 4; i++) ldsm_x4_t(ad + i * 1024, wf[4 * h + i][0], wf[4 * h + i][1], wf[4 * h + i][2], wf[4 * h + i][3]);
    };
    auto load_wf_rest = [&]() { static_for<8 - NREG_H>([&](auto ic) { load_wf(IC<NREG_H + decltype(ic)::value>()); }); };
#pragma unroll
    for (int i = 0; i < 4 * NREG_H; i++) { wf[i][0] = 0; wf[i][1] = 0; wf[i][2] = 0; wf[i][3] = 0; }
    const int grp = tau * 2 + m;
#pragma unroll 1
    for (int k = 23; k < 46; k++) {
      kstep(k, false);
      if (moe) {
        static_for<NREG_H>([&](auto hc) {
          constexpr int h = decltype(hc)::value;
          if (k == mr_k(h) + 1) { mbar_wait(BAR(B_MR + (h & 1)), (h >> 1) & 1); load_wf(hc); }
        });
      }
      if (k == 43) {
        if (moe) pkt_st128(&p.s->ypart[cid * 256 + tid], 0, 0, 0, 0);
        if (w == 1) pkt_st128(&p.s->hstat[(grp * 8 + eps) * 128 + t], 0, 0, 0, 0);
        if (warp == 0) pkt_st128(&p.s->cand[grp * 256 + eps * 32 + lane], 0, 0, 0, 0);
        if (eps == 0 && warp == 1 && lane < 16) pkt_st128(&p.s->key[((lane >> 1) * 16 + grp) * 2 + (lane & 1)], 0, 0, 0, 0);
      }
      kdone(k);
    }
    asm volatile("barrier.cluster.arrive.relaxed.aligned;" ::: "memory");
    uint32_t wa[16][2];
    uint32_t cd = code_of(tag);
    uint4* hp_pub = &p.s->hstat[(grp * 8 + eps) * 128 + warp * 16 + g];
    const uint4* hp_poll = &p.s->hstat[(grp * 8 + 2 * q) * 128 + warp * 16 + g];
    const uint32_t vec_off = (2 * wi) * 512 + q * 128 + ((g ^ (2 * q)) << 4);
    {
      float as[64], ak[64];
      fence_acc(acc);
#pragma unroll
      for (int i = 0; i < 64; i++) asm volatile("mov.b32 %0, %1;" : "=f"(as[i]) : "f"(acc[64 + i]));
#pragma unroll
      for (int i = 0; i < 64; i++) asm volatile("mov.b32 %0, %1;" : "=f"(ak[i]) : "f"(acc[i]));
      const uint64_t da1 = make_desc(sb + 2 * ST_BYTES + w * 8192), db1 = make_desc(sb + 2 * ST_BYTES + A_BYTES);
      const uint64_t da2 = make_desc(sb + 3 * ST_BYTES + w * 8192), db2 = make_desc(sb + 3 * ST_BYTES + A_BYTES);
      mbar_wait(BAR(B_FULL + 2), 1);
      CT(64 + 46);
      mbar_wait(BAR(B_FULL + 3), 1);
      CT(64 + 47);
      bar_sync(turn_me, 256);
      wgmma_fence();
#pragma unroll
      for (int kk = 0; kk < 4; kk++) wgmma_n128(as, da1 + kk * 2, db1 + 1024 + kk * 2);
#pragma unroll
      for (int kk = 0; kk < 4; kk++) wgmma_n128(as, da2 + kk * 2, db2 + 1024 + kk * 2);
      wgmma_commit();
      bar_arrive(turn_other, 256);
      const uint32_t rx = mapa(sb + OFF_PEER + w * 4096 + vec_off, 1 - m), rb = mapa(BAR(B_XCH), 1 - m);
      asm volatile("barrier.cluster.wait.aligned;" ::: "memory");
      wgmma_wait0();
      fence_acc64(as);
      auto keep = [&]() {
        bar_sync(turn_me, 256);
        wgmma_fence();
#pragma unroll
        for (int kk = 0; kk < 4; kk++) wgmma_n128(ak, da1 + kk * 2, db1 + kk * 2);
        wgmma_commit();
#pragma unroll
        for (int kk = 0; kk < 4; kk++) wgmma_n128(ak, da2 + kk * 2, db2 + kk * 2);
        wgmma_commit();
        if (w == 0) bar_arrive(turn_other, 256);
      };
      keep();
#pragma unroll
      for (int i = 0; i < 8; i++) {
        const float* ac = &as[16 * (i >> 1) + 2 * (i & 1)];
        st_async_v4(rx + (i >> 1) * 8192 + (i & 1) * 512, rb, pack_bf16(ac[0], ac[1]), pack_bf16(ac[4], ac[5]), pack_bf16(ac[8], ac[9]), pack_bf16(ac[12], ac[13]));
      }
#pragma unroll
      for (int i = 0; i < 4; i++) {
        const uint4 v = lds128_v(sb + OFF_WR + q * 80 + i * 16);
        const uint32_t vv[4] = {v.x, v.y, v.z, v.w};
#pragma unroll
        for (int z = 0; z < 4; z++) {
          asm volatile("{\n.reg .pred p;\nsetp.ne.b32 p, %2, 0;\nselp.b32 %0, %1, 0x3F803F80, p;\n}" : "=r"(wa[4 * i + z][0]) : "r"(vv[z]), "r"(g & 1));
          asm volatile("{\n.reg .pred p;\nsetp.ne.b32 p, %2, 0;\nselp.b32 %0, %1, 0x3F803F80, p;\n}" : "=r"(wa[4 * i + z][1]) : "r"(vv[z]), "r"(g & 1));
        }
      }
      pin(cd); pin(hp_pub); pin(hp_poll);
      wgmma_wait1();
      release(2);
      wgmma_wait0();
      fence_acc64(ak);
      CT(3);
#pragma unroll
      for (int i = 0; i < 8; i++) {
        const float* ac = &ak[16 * (i >> 1) + 2 * (i & 1)];
        sts128(sb + (2 + (i >> 2)) * ST_BYTES + w * 8192 + ((i >> 1) & 1) * 4096 + (i & 1) * 512 + vec_off,
               pack_bf16(ac[0], ac[1]), pack_bf16(ac[4], ac[5]), pack_bf16(ac[8], ac[9]), pack_bf16(ac[12], ac[13]));
      }
    }
    uint32_t h[8][4];
    {
      const int qq = 2 * (warp & 1) + ((lane >> 3) & 1);
      const uint32_t lo = (lane >> 4) * 512 + qq * 128 + (((lane & 7) ^ (2 * qq)) << 4);
      bar_sync(NB_BOTH, 256);
#pragma unroll
      for (int ks = 0; ks < 8; ks++)
        ldsm_x4_t(sb + (2 + w) * ST_BYTES + (ks >> 2) * 8192 + (wi >> 1) * 4096 + (ks & 3) * 1024 + lo, h[ks][0], h[ks][1], h[ks][2], h[ks][3]);
      mbar_wait_cluster(BAR(B_XCH), 0);
      CT(4);
      uint32_t r[8][4];
#pragma unroll
      for (int ks = 0; ks < 8; ks++) ldsm_x4_t(sb + OFF_PEER + (warp >> 1) * 8192 + ks * 1024 + lo, r[ks][0], r[ks][1], r[ks][2], r[ks][3]);
      float d[4][4] = {};
#pragma unroll
      for (int ks = 0; ks < 8; ks++) {
#pragma unroll
        for (int i = 0; i < 4; i++) {
          h[ks][i] = badd2(h[ks][i], r[ks][i]);
          mma1688(d[i], h[ks][i], wa[2 * ks + (i >> 1)][i & 1], h[ks][i]);
        }
      }
#pragma unroll
      for (int i = 0; i < 2; i++) {
        const float sq = (g & 1) ? d[i][1] + d[i + 2][1] : d[i][0] + d[i + 2][0];
        const float e0 = d[i][2] + d[i + 2][2], e1 = d[i][3] + d[i + 2][3];
        const float other = __shfl_xor_sync(0xffffffffu, (g & 1) ? e0 : e1, 4);
        if (q == (g >> 1)) pkt_st128(hp_pub + 8 * i, with_bit((g & 1) ? other : e0, cd), with_bit(sq, cd >> 1), __float_as_uint((g & 1) ? e1 : other), tag);
      }
    }
    CT(5);
    if (tid == 0) mbar_arrive(BAR(B_KEY));
    delay_clk<HOP1_DELAY>();
    float m_bf, sd, inv_sd, r_bf;
    uint4* key_pub = &p.s->key[((lane & 7) * 16 + grp) * 2];
    uint4* cand_pub = &p.s->cand[grp * 256 + eps * 32 + q];
    uint32_t trow_inv = 0xFFFFu - (uint32_t)(grp * 128 + 32 * (warp >> 1) + 8 * (g >> 1) + 4 * (warp & 1) + (q & 2) + (g & 1));
    {
      uint4 u[4];
#pragma unroll
      for (int i = 0; i < 4; i++) u[i] = pkt_ld128(hp_poll + (i & 1) * 128 + (i >> 1) * 8);
      const float wsum = SM_(float, OFF_WSUM);
      pin(key_pub); pin(cand_pub); pin(trow_inv);
      uint32_t n = 0;
      while (true) {
        bool ok[4];
#pragma unroll
        for (int i = 0; i < 4; i++) ok[i] = u[i].w == tag && pair_code(u[i].x, u[i].y) == cd;
        const bool all = __all_sync(0xffffffffu, ok[0] && ok[1] && ok[2] && ok[3]);
        if (all || ++n > SPIN_LIMIT) break;
#pragma unroll
        for (int i = 0; i < 4; i++) pkt_ld128_if(u[i], hp_poll + (i & 1) * 128 + (i >> 1) * 8, !ok[i]);
      }
      CT(6);
      float a[3], b[3];
      a[0] = __uint_as_float(u[0].x & ~1u) + __uint_as_float(u[1].x & ~1u); b[0] = __uint_as_float(u[2].x & ~1u) + __uint_as_float(u[3].x & ~1u);
      a[1] = __uint_as_float(u[0].y & ~1u) + __uint_as_float(u[1].y & ~1u); b[1] = __uint_as_float(u[2].y & ~1u) + __uint_as_float(u[3].y & ~1u);
      a[2] = __uint_as_float(u[0].z) + __uint_as_float(u[1].z); b[2] = __uint_as_float(u[2].z) + __uint_as_float(u[3].z);
#pragma unroll
      for (int i = 0; i < 3; i++) {
        a[i] = ((q & 2) ? b[i] : a[i]) + __shfl_xor_sync(0xffffffffu, (q & 2) ? a[i] : b[i], 2);
        a[i] += __shfl_xor_sync(0xffffffffu, a[i], 1);
      }
      const float mu = a[0] * (1.f / 1024.f);
      m_bf = bf16r(mu);
      sd = ln_sd(a[1] * (1.f / 1024.f) - mu * mu);
      inv_sd = rcp_fast(sd);
      r_bf = bf16r((a[2] - m_bf * wsum) * inv_sd);
    }
    {
      const uint32_t u = __float_as_uint(r_bf);
      const uint32_t ord = (u & 0x80000000u) ? ~u : (u | 0x80000000u);
      const uint32_t key = (ord & 0xFFFF0000u) | trow_inv;
      const uint32_t wk = __reduce_max_sync(0xffffffffu, key);
      if (key == wk) SM_(uint2, OFF_WKEY + warp * 8) = make_uint2(wk, (__float_as_uint(m_bf) >> 16) | __float_as_uint(sd));
      const uint32_t wmask = __ballot_sync(0xffffffffu, key == wk);
      const bool hi = (wmask & 0xCCCCCCCCu) != 0;
      uint32_t c[16];
#pragma unroll
      for (int ks = 0; ks < 8; ks++) { c[2 * ks] = hi ? h[ks][1] : h[ks][0]; c[2 * ks + 1] = hi ? h[ks][3] : h[ks][2]; }
      bar_sync(NB_BOTH, 256);
      const uint2 km = SM_(uint2, OFF_WKEY + (lane & 7) * 8);
      const uint32_t bk = __reduce_max_sync(0xffffffffu, km.x);
      if (wk == bk) {
        if ((wmask >> (lane & 28)) & 15) {
#pragma unroll
          for (int ks = 0; ks < 8; ks++) pkt_st128(cand_pub + ks * 4, c[2 * ks], tag, c[2 * ks + 1], tag);
        }
      } else if (eps == 0) {
        const uint32_t kx = __shfl_sync(0xffffffffu, km.x, warp ^ 1), ms = __shfl_sync(0xffffffffu, km.y, warp ^ 1);
        if (kx == bk && lane < 8) pkt_st128(key_pub, bk, tag, ms, tag);
      }
      CT(7);
    }
    {
      const float ih = bf16r(inv_sd);
      const uint32_t nm = pack_bf16(-m_bf, -m_bf), iv = pack_bf16(ih, inv_sd - ih);
      const uint32_t nm_o = __shfl_xor_sync(0xffffffffu, nm, 2), iv_o = __shfl_xor_sync(0xffffffffu, iv, 2);
      const uint32_t nm2[2] = {(q & 2) ? nm_o : nm, (q & 2) ? nm : nm_o}, iv2[2] = {(q & 2) ? iv_o : iv, (q & 2) ? iv : iv_o};
      const uint32_t hi2[2] = {__byte_perm(iv2[0], 0, 0x1010), __byte_perm(iv2[1], 0, 0x1010)}, lo2[2] = {__byte_perm(iv2[0], 0, 0x3232), __byte_perm(iv2[1], 0, 0x3232)};
      const uint32_t oa = sb + OFF_OUT + (warp * 16 + (lane & 15)) * 128;
#pragma unroll
      for (int ks = 0; ks < 8; ks++) {
        uint32_t o[4];
#pragma unroll
        for (int i = 0; i < 4; i++) {
          const uint32_t dd = badd2(h[ks][i], nm2[i & 1]);
          o[i] = badd2(h[ks][i], bfma2(dd, hi2[i & 1], bmul2(dd, lo2[i & 1])));
        }
        stsm_x4(oa + (ks >> 2) * 16384 + (((2 * (ks & 3) + (lane >> 4)) ^ (lane & 7)) << 4), o[0], o[1], o[2], o[3]);
      }
      staged(B_OUT);
    }
    CT(8);
    uint32_t df[16][4];
    auto load_df = [&]() {
      const int frow = (lane & 7) + ((lane >> 4) << 3), hi = (lane >> 3) & 1;
      const uint32_t base = sb + down_off(warp >> 1) + (warp & 1) * 8192 + frow * 128;
#pragma unroll
      for (int mt = 0; mt < 8; mt++) {
#pragma unroll
        for (int ks = 0; ks < 2; ks++)
          ldsm_x4_t(base + (mt >> 2) * 4096 + ks * 2048 + (((2 * (mt & 3) + hi) ^ (lane & 7)) << 4),
                    df[2 * mt + ks][0], df[2 * mt + ks][1], df[2 * mt + ks][2], df[2 * mt + ks][3]);
      }
    };
    if (moe) {
      mbar_wait(BAR(B_GU), 0);
      load_wf_rest();
      mbar_wait(BAR(B_DN), 0);
      load_df();
    }
    uint4* y_pub = &p.s->ypart[cid * 256 + tid];
    uint32_t xs_ad = sb + OFF_XSEL + (8 * (g >> 2) + 4 * w + (g & 3)) * 32 + q * 8, gp_ad = sb + OFF_GP + (wi * 8 + g) * 32 + w * 16 + q * 4;
    pin(y_pub); pin(xs_ad); pin(gp_ad);
    mbar_wait(BAR(B_XS), 0);
    CT(9);
    if (moe) {
      float gd[8][4] = {};
      uint2 bx[4];
#pragma unroll
      for (int r = 0; r < 4; r++) bx[r] = smem_at<uint2>(xs_ad + r * 512);
#pragma unroll
      for (int r = 0; r < 4; r++) {
#pragma unroll
        for (int i = 0; i < 8; i++) mma16816(gd[i], wf[8 * r + i][0], wf[8 * r + i][1], wf[8 * r + i][2], wf[8 * r + i][3], bx[r].x, bx[r].y);
      }
      const float gs = sel4(q, gd[0][0] + gd[1][1], gd[2][0] + gd[3][1], gd[4][0] + gd[5][1], gd[6][0] + gd[7][1]);
      const float us = sel4(q, gd[0][2] + gd[1][3], gd[2][2] + gd[3][3], gd[4][2] + gd[5][3], gd[6][2] + gd[7][3]);
      float v = ((q & 2) ? us : gs) + __shfl_xor_sync(0xffffffffu, (q & 2) ? gs : us, 2);
      smem_at<float>(gp_ad) = v;
      CT(10);
      bar_sync(NB_BOTH, 256);
      uint32_t bq[4];
      {
        const float4 p0 = SM_(float4, OFF_GP + lane * 32), p1 = SM_(float4, OFF_GP + lane * 32 + 16);
        const float gt = bf16r((p0.x + p0.y) + (p1.x + p1.y)), up = bf16r((p0.z + p0.w) + (p1.z + p1.w));
        const float act = bf16r(gt * sigmoid_fast(gt)) * up;
        const uint32_t pr = pack_bf16(act, __shfl_down_sync(0xffffffffu, act, 1));
#pragma unroll
        for (int i = 0; i < 4; i++) bq[i] = __shfl_sync(0xffffffffu, pr, 8 * i + 2 * q);
      }
      CT(11);
      float yd[8][4] = {};
#pragma unroll
      for (int ks = 0; ks < 2; ks++) {
#pragma unroll
        for (int mt = 0; mt < 8; mt++) mma16816(yd[mt], df[2 * mt + ks][0], df[2 * mt + ks][1], df[2 * mt + ks][2], df[2 * mt + ks][3], bq[2 * ks], bq[2 * ks + 1]);
      }
      pkt_st128(y_pub, with_bit(sel4(q, yd[0][0], yd[2][0], yd[4][0], yd[6][0]), cd), with_bit(sel4(q, yd[0][2], yd[2][2], yd[4][2], yd[6][2]), cd >> 1),
                with_bit(sel4(q, yd[1][0], yd[3][0], yd[5][0], yd[7][0]), cd), with_bit(sel4(q, yd[1][2], yd[3][2], yd[5][2], yd[7][2]), cd >> 1));
    } else {
      const long long tw = clock64();
      while (clock64() - tw < IDLE_WAIT_CLK) __nanosleep(100);
    }
    CT(12);
    const uint32_t kv = SM_(uint32_t, OFF_KV);
    const int tsel = 0xFFFF - (int)(kv & 0xFFFFu);
    const float r_sel = __uint_as_float((kv & 0x80000000u) ? (kv & 0x7FFF0000u) : (~kv & 0xFFFF0000u));
    const float sig = bf16r(sigmoid_fast(r_sel));
    const int pfin = 2 * cid + (tid & 1);
    const int col_fin = (pfin >> 5) * 128 + (pfin & 3) * 32 + ((pfin & 31) >> 2) + 8 * ((tid >> 1) & 3);
    const int sel_off = (col_fin >> 4) * 32 + ((col_fin & 7) >> 1) * 8 + ((col_fin >> 3) & 1) * 4 + (col_fin & 1) * 2;
    const float hn_fin = __uint_as_float((uint32_t)SM_(uint16_t, OFF_XSEL + sel_off) << 16), h_fin = __uint_as_float((uint32_t)SM_(uint16_t, OFF_HSEL + sel_off) << 16);
    bf16* out_fin = p.out + (size_t)tsel * 1024 + col_fin;
    {
      const uint4* src = &p.s->ypart[(16 + (tid >> 1)) * 256 + pfin];
      pin(src); pin(out_fin);
      uint4 v = make_uint4(0, 0, 0, 0);
      if (warp < 7) {
        delay_clk<HOP3_DELAY>();
        uint32_t n = 0;
        bool ok = false;
        do {
          pkt_ld128_if(v, src, !ok);
          ok = pair_code(v.x, v.y) == cd && pair_code(v.z, v.w) == cd;
        } while (!__all_sync(0xffffffffu, ok) && ++n < SPIN_LIMIT);
      }
      CT(13);
      const float y0 = __uint_as_float(v.x & ~1u), y1 = __uint_as_float(v.y & ~1u), y2 = __uint_as_float(v.z & ~1u), y3 = __uint_as_float(v.w & ~1u);
      const float a0 = ((lane & 2) ? y1 : y0) + __shfl_xor_sync(0xffffffffu, (lane & 2) ? y0 : y1, 2);
      const float a1 = ((lane & 2) ? y3 : y2) + __shfl_xor_sync(0xffffffffu, (lane & 2) ? y2 : y3, 2);
      float b = ((lane & 4) ? a1 : a0) + __shfl_xor_sync(0xffffffffu, (lane & 4) ? a0 : a1, 4);
      b += __shfl_xor_sync(0xffffffffu, b, 8);
      b += __shfl_xor_sync(0xffffffffu, b, 16);
      if (lane < 8) SM_(float, OFF_FIN + lane * 32 + warp * 4) = b;
    }
    bar_sync(NB_BOTH, 256);
    if (tid < 8) {
      const float4 y0 = SM_(float4, OFF_FIN + tid * 32), y1 = SM_(float4, OFF_FIN + tid * 32 + 16);
      const float y = ((y0.x + y0.y) + (y0.z + y0.w)) + ((y1.x + y1.y) + y1.z);
      *out_fin = __float2bfloat16_rn(h_fin + bf16r(hn_fin + bf16r(bf16r(y) * sig)));
      if (cid == 0 && tid == 0) st_relaxed32(&p.s->epoch, tag);
    }
    CT(14);
  }
}

__global__ void __launch_bounds__(384, 1) occupancy_probe_kernel() {}

typedef CUresult (*EncodeFn)(CUtensorMap*, CUtensorMapDataType, cuuint32_t, void*, const cuuint64_t*, const cuuint64_t*, const cuuint32_t*, const cuuint32_t*,
                             CUtensorMapInterleave, CUtensorMapSwizzle, CUtensorMapL2promotion, CUtensorMapFloatOOBfill);

static void make_tm(EncodeFn enc, CUtensorMap* tm, const void* ptr, uint64_t rows, uint64_t cols, uint32_t brows, uint32_t bcols, CUtensorMapSwizzle sw,
                    CUtensorMapL2promotion promo = CU_TENSOR_MAP_L2_PROMOTION_L2_256B) {
  cuuint64_t dims[2] = {cols, rows};
  cuuint64_t strides[1] = {cols * 2};
  cuuint32_t box[2] = {bcols, brows};
  cuuint32_t es[2] = {1, 1};
  enc(tm, CU_TENSOR_MAP_DATA_TYPE_BFLOAT16, 2, const_cast<void*>(ptr), dims, strides, box, es, CU_TENSOR_MAP_INTERLEAVE_NONE, sw,
      promo, CU_TENSOR_MAP_FLOAT_OOB_FILL_NONE);
}

extern "C" void kernel_launch(void* const* d_in, const int* in_sizes, int n_in, void* d_out, int out_size) {
  (void)in_sizes; (void)n_in; (void)out_size;
  static EncodeFn enc = nullptr;
  static void* abT = nullptr;
  static int map = 0;
  if (!enc) {
    void* fn = nullptr; cudaDriverEntryPointQueryResult st;
    cudaGetDriverEntryPoint("cuTensorMapEncodeTiled", &fn, cudaEnableDefault, &st);
    enc = (EncodeFn)fn;
    cudaGetSymbolAddress(&abT, g_scratch);
    cudaFuncSetAttribute(fnet_moe_kernel<0>, cudaFuncAttributeMaxDynamicSharedMemorySize, SMEM_TOTAL);
    cudaFuncSetAttribute(fnet_moe_kernel<1>, cudaFuncAttributeMaxDynamicSharedMemorySize, SMEM_TOTAL);
    cudaFuncSetAttribute(occupancy_probe_kernel, cudaFuncAttributeMaxDynamicSharedMemorySize, SMEM_TOTAL);
    cudaFuncSetAttribute(occupancy_probe_kernel, cudaFuncAttributeNonPortableClusterSizeAllowed, 1);
    auto max_clusters = [&](int size) {
      cudaLaunchConfig_t cfg = {};
      cfg.gridDim = dim3(128); cfg.blockDim = dim3(384); cfg.dynamicSmemBytes = SMEM_TOTAL;
      cudaLaunchAttribute at[1];
      at[0].id = cudaLaunchAttributeClusterDimension; at[0].val.clusterDim.x = size; at[0].val.clusterDim.y = 1; at[0].val.clusterDim.z = 1;
      cfg.attrs = at; cfg.numAttrs = 1;
      int ncl = 0;
      return cudaOccupancyMaxActiveClusters(&ncl, occupancy_probe_kernel, &cfg) == cudaSuccess ? ncl : 0;
    };
    int dev = 0, sms = 0;
    cudaGetDevice(&dev);
    cudaDeviceGetAttribute(&sms, cudaDevAttrMultiProcessorCount, dev);
    map = (!getenv("MAP1") && sms == 132 && max_clusters(2) == 66 && max_clusters(16) == 7) ? 0 : 1;
    (void)cudaGetLastError();
  }
  Params p;
  const bf16* x = (const bf16*)d_in[0];
  make_tm(enc, &p.tmD0, d_in[3], 1024, 1024, 128, 64, CU_TENSOR_MAP_SWIZZLE_128B);
  make_tm(enc, &p.tmD1, d_in[4], 1024, 1024, 128, 64, CU_TENSOR_MAP_SWIZZLE_128B);
  make_tm(enc, &p.tmX, x, 2048, 1024, 256, 64, CU_TENSOR_MAP_SWIZZLE_128B);
  make_tm(enc, &p.tmXr, x, 2048, 1024, 64, 64, CU_TENSOR_MAP_SWIZZLE_128B);
  make_tm(enc, &p.tmAbS, abT, 2048, 2048, 64, 64, CU_TENSOR_MAP_SWIZZLE_128B);
  make_tm(enc, &p.tmAbL, abT, 2048, 2048, 128, 64, CU_TENSOR_MAP_SWIZZLE_128B);
  make_tm(enc, &p.tmW0, d_in[1], 2048, 2048, 128, 64, CU_TENSOR_MAP_SWIZZLE_128B, W_PROMO);
  make_tm(enc, &p.tmW1, d_in[2], 2048, 2048, 128, 64, CU_TENSOR_MAP_SWIZZLE_128B, W_PROMO);
  {
    cuuint64_t dims[5] = {1024, 2, 4, 4, 64};
    cuuint64_t strides[4] = {2048, 8 * 2048, 2 * 2048, 32 * 2048};
    cuuint32_t box[5] = {64, 2, 4, 2, 1};
    cuuint32_t es[5] = {1, 1, 1, 1, 1};
    enc(&p.tmOut, CU_TENSOR_MAP_DATA_TYPE_BFLOAT16, 5, d_out, dims, strides, box, es, CU_TENSOR_MAP_INTERLEAVE_NONE, CU_TENSOR_MAP_SWIZZLE_128B,
        CU_TENSOR_MAP_L2_PROMOTION_NONE, CU_TENSOR_MAP_FLOAT_OOB_FILL_NONE);
  }
  make_tm(enc, &p.tmG, d_in[7], 1024, 3584, 128, 32, CU_TENSOR_MAP_SWIZZLE_64B, CU_TENSOR_MAP_L2_PROMOTION_L2_128B);
  make_tm(enc, &p.tmU, d_in[8], 1024, 3584, 128, 32, CU_TENSOR_MAP_SWIZZLE_64B, CU_TENSOR_MAP_L2_PROMOTION_L2_128B);
  make_tm(enc, &p.tmDn, d_in[9], 3584, 1024, 32, 64, CU_TENSOR_MAP_SWIZZLE_128B);
  p.x = x; p.Dre = (const bf16*)d_in[3]; p.Dim = (const bf16*)d_in[4];
  p.wr = (const bf16*)d_in[6]; p.wdown = (const bf16*)d_in[9]; p.wgate = (const bf16*)d_in[7]; p.wup = (const bf16*)d_in[8];
  p.out = (bf16*)d_out; p.s = (Scratch*)abT;
  if (map == 1) fnet_moe_kernel<1><<<128, 384, SMEM_TOTAL>>>(p);
  else fnet_moe_kernel<0><<<132, 384, SMEM_TOTAL>>>(p);
}
```

```cpp
#include <cuda.h>
#include <cuda_runtime.h>
#include <cuda_bf16.h>
#include <stdint.h>
#include <stdlib.h>
#include <type_traits>

typedef __nv_bfloat16 bf16;

#define REG_C 232
#define REG_P 40
__device__ __forceinline__ int kblock(int tau, int j) {
  int i = j - 4;
  if (i >= 19 && i < 23) i += i < 21 ? 2 : -2;
  const int c = (i * 37) >> 8;
  return j < 4 ? tau * 4 + j : ((tau + 1 + i - 7 * c) & 7) * 4 + c;
}
#define HOP1_DELAY 150
#define HOP3_DELAY 300
#define SPEC_MIN 10
#define PF_K0 8
#define PF_N0 2
#define PF_K1 24
#define OUT_PACE_CLK 100
#define WPF_K0 12
#define WPF_J0 0
#define WPF_J1 10
#define PUBMODE 0
#define MR_P 6
#define PUB_K1 22
#define NREG_H 5
#define MR_K0 29
__host__ __device__ constexpr int mr_k(int h) { return MR_K0 + MR_P * (h >> 1) + 2 * (h & 1); }
constexpr int A_BYTES = 128 * 64 * 2;
constexpr int B_BYTES = 256 * 64 * 2;
constexpr int ST_BYTES = A_BYTES + B_BYTES;
constexpr int OFF_XCH = 4 * ST_BYTES;
constexpr int OFF_BAR = OFF_XCH + 32768;
constexpr int OFF_WR = OFF_BAR + 384;
constexpr int OFF_RS = OFF_WR + 384;
constexpr int OFF_PUB = OFF_RS + 640;
constexpr int OFF_MISC = OFF_PUB + 768;
constexpr int SMEM_TOTAL = OFF_MISC + 256;
constexpr int OFF_WSUM = OFF_MISC, OFF_TAG = OFF_MISC + 4;
constexpr int OFF_SEEN = OFF_MISC + 8;
constexpr int OFF_KV = OFF_MISC + 12;
constexpr int OFF_WKEY = OFF_MISC + 32;
constexpr int OFF_EXA = OFF_XCH;
constexpr int OFF_EXB = OFF_XCH + 4096;
__host__ __device__ constexpr int chunk_off(int c, int w) { return (c < 2 ? (c + 2) * ST_BYTES : OFF_XCH + (c - 2) * 16384) + w * 8192; }
__host__ __device__ constexpr int late_off(int i) { return i < 4 ? i * 16384 : 2 * ST_BYTES + A_BYTES + (i - 4) * 16384; }
__host__ __device__ constexpr int round_off(int h) { return h < NREG_H + 2 ? OFF_XCH + (h & 1) * 16384 : late_off(h - NREG_H - 2); }
__host__ __device__ constexpr int down_off(int i) { return late_off(6 - NREG_H + i); }
constexpr int OFF_PEER = ST_BYTES + A_BYTES;
constexpr int OFF_OUT = 3 * ST_BYTES + A_BYTES;
constexpr int OFF_XSEL = OFF_PEER;
constexpr int OFF_HSEL = OFF_PEER + 4096;
constexpr int OFF_GP = OFF_PEER + 8192;
constexpr int OFF_FIN = OFF_PEER + 9216;
__device__ __forceinline__ int slot_of(int k) { return k & 3; }
__device__ __forceinline__ int use_of(int k) { return k >> 2; }
enum { B_FULL = 0, B_EMPTY = 4, B_EPI = 8, B_STD = 12, B_EPI0B = 16, B_LATE = 17, B_STAT = 18, B_XCH = 19, B_MR = 20  , B_GU = 22,
       B_DN = 23, B_AUX = 24  , B_OUT = 26, B_KEY = 27, B_XS = 28, B_A20 = 29, B_STDA = 30, B_COUNT = 31 };
enum { NB_TURN0 = 1, NB_TURN1 = 2, NB_BOTH = 5, NB_AUX = 6 };

struct Scratch {
  bf16 abT[2048 * 2048];
  uint2 xstat[2048];
  uint2 dsum[2048];
  uint4 abflag[16 * 8 * 2];
  uint4 hstat[16 * 8 * 128];
  uint4 cand[16 * 256];
  uint4 key[8 * 16 * 2];
  uint4 ypart[128 * 256];
  uint32_t epoch;
};
__device__ __align__(1024) Scratch g_scratch;

struct Params {
  Scratch* s; bf16* out;
  const bf16* x; const bf16* Dre; const bf16* Dim; const bf16* wr; const bf16* wdown; const bf16* wgate; const bf16* wup;
  CUtensorMap tmX, tmD0, tmD1, tmXr, tmAbS, tmAbL, tmW0, tmW1, tmOut, tmG, tmU, tmDn;
};

#define SPIN_LIMIT (1u << 14)
#define MBAR_LIMIT (1u << 10)
#define GATHER_NS 400
#define W_PROMO CU_TENSOR_MAP_L2_PROMOTION_L2_128B
#define MOE_PACE_CLK 300
constexpr int IDLE_WAIT_CLK = 1200;
__device__ __forceinline__ uint32_t smem_u32(const void* p) { return (uint32_t)__cvta_generic_to_shared(p); }
__device__ __forceinline__ void mbar_init(uint32_t bar, uint32_t cnt) { asm volatile("mbarrier.init.shared::cta.b64 [%0], %1;" :: "r"(bar), "r"(cnt) : "memory"); }
__device__ __forceinline__ void mbar_expect_tx(uint32_t bar, uint32_t bytes) { asm volatile("mbarrier.arrive.expect_tx.shared::cta.b64 _, [%0], %1;" :: "r"(bar), "r"(bytes) : "memory"); }
__device__ __forceinline__ void mbar_arrive(uint32_t bar) { asm volatile("mbarrier.arrive.shared::cta.b64 _, [%0];" :: "r"(bar) : "memory"); }
__device__ __forceinline__ void mbar_wait(uint32_t bar, uint32_t parity) {
  uint32_t ok, n = 0;
  do {
    asm volatile("{\n.reg .pred p;\nmbarrier.try_wait.parity.shared::cta.b64 p, [%1], %2;\nselp.u32 %0, 1, 0, p;\n}\n" : "=r"(ok) : "r"(bar), "r"(parity) : "memory");
  } while (!ok && ++n < MBAR_LIMIT);
}
__device__ __forceinline__ bool mbar_test(uint32_t bar, uint32_t parity) {
  uint32_t ok;
  asm volatile("{\n.reg .pred p;\nmbarrier.test_wait.parity.shared::cta.b64 p, [%1], %2;\nselp.u32 %0, 1, 0, p;\n}\n" : "=r"(ok) : "r"(bar), "r"(parity) : "memory");
  return ok != 0;
}
__device__ __forceinline__ void mbar_wait_cluster(uint32_t bar, uint32_t parity) {
  uint32_t ok, n = 0;
  do {
    asm volatile("{\n.reg .pred p;\nmbarrier.try_wait.parity.acquire.cluster.shared::cta.b64 p, [%1], %2;\nselp.u32 %0, 1, 0, p;\n}\n" : "=r"(ok) : "r"(bar), "r"(parity) : "memory");
  } while (!ok && ++n < MBAR_LIMIT);
}
__device__ __forceinline__ void tma_load_2d(uint32_t dst, const CUtensorMap* tm, uint32_t bar, int c0, int c1) {
  asm volatile("cp.async.bulk.tensor.2d.shared::cluster.global.mbarrier::complete_tx::bytes [%0], [%1, {%3, %4}], [%2];"
    :: "r"(dst), "l"(tm), "r"(bar), "r"(c0), "r"(c1) : "memory");
}
__device__ __forceinline__ void tma_load_2d_hint(uint32_t dst, const CUtensorMap* tm, uint32_t bar, int c0, int c1, uint64_t pol) {
  asm volatile("cp.async.bulk.tensor.2d.shared::cluster.global.mbarrier::complete_tx::bytes.L2::cache_hint [%0], [%1, {%3, %4}], [%2], %5;"
    :: "r"(dst), "l"(tm), "r"(bar), "r"(c0), "r"(c1), "l"(pol) : "memory");
}
__device__ __forceinline__ uint64_t policy_evict_first() { uint64_t p; asm volatile("createpolicy.fractional.L2::evict_first.b64 %0, 1.0;" : "=l"(p)); return p; }
__device__ __forceinline__ void tma_store_2d(const CUtensorMap* tm, uint32_t src, int c0, int c1) {
  asm volatile("cp.async.bulk.tensor.2d.global.shared::cta.bulk_group [%0, {%2, %3}], [%1];" :: "l"(tm), "r"(src), "r"(c0), "r"(c1) : "memory");
}
__device__ __forceinline__ void bulk_load(uint32_t dst, const void* src, uint32_t bytes, uint32_t bar) {
  asm volatile("cp.async.bulk.shared::cluster.global.mbarrier::complete_tx::bytes [%0], [%1], %2, [%3];" :: "r"(dst), "l"(src), "r"(bytes), "r"(bar) : "memory");
}
__device__ __forceinline__ void bulk_commit() { asm volatile("cp.async.bulk.commit_group;" ::: "memory"); }
__device__ __forceinline__ void bulk_wait_all() { asm volatile("cp.async.bulk.wait_group 0;" ::: "memory"); }
__device__ __forceinline__ void fence_async_smem() { asm volatile("fence.proxy.async.shared::cta;" ::: "memory"); }
__device__ __forceinline__ void wgmma_fence() { asm volatile("wgmma.fence.sync.aligned;" ::: "memory"); }
__device__ __forceinline__ void wgmma_commit() { asm volatile("wgmma.commit_group.sync.aligned;" ::: "memory"); }
__device__ __forceinline__ void wgmma_wait0() { asm volatile("wgmma.wait_group.sync.aligned 0;" ::: "memory"); }
__device__ __forceinline__ void bar_sync(int id, int n) { asm volatile("bar.sync %0, %1;" :: "r"(id), "r"(n) : "memory"); }
__device__ __forceinline__ void bar_arrive(int id, int n) { asm volatile("bar.arrive %0, %1;" :: "r"(id), "r"(n) : "memory"); }
template<int R> __device__ __forceinline__ void reg_inc() { asm volatile("setmaxnreg.inc.sync.aligned.u32 %0;" :: "n"(R)); }
template<int R> __device__ __forceinline__ void reg_dec() { asm volatile("setmaxnreg.dec.sync.aligned.u32 %0;" :: "n"(R)); }
__device__ __forceinline__ bool elect_one() {
  uint32_t p;
  asm volatile("{\n.reg .pred q;\nelect.sync _|q, 0xffffffff;\nselp.u32 %0, 1, 0, q;\n}\n" : "=r"(p));
  return p != 0;
}
__device__ __forceinline__ uint32_t mapa(uint32_t addr, uint32_t cta) { uint32_t r; asm volatile("mapa.shared::cluster.u32 %0, %1, %2;" : "=r"(r) : "r"(addr), "r"(cta)); return r; }
__device__ __forceinline__ void st_async_v4(uint32_t addr, uint32_t bar, uint32_t a, uint32_t b, uint32_t c, uint32_t d) {
  asm volatile("st.async.weak.shared::cluster.mbarrier::complete_tx::bytes.v4.b32 [%0], {%2, %3, %4, %5}, [%1];" :: "r"(addr), "r"(bar), "r"(a), "r"(b), "r"(c), "r"(d) : "memory");
}
__device__ __forceinline__ void stsm_x4(uint32_t addr, uint32_t a, uint32_t b, uint32_t c, uint32_t d) {
  asm volatile("stmatrix.sync.aligned.m8n8.x4.shared.b16 [%0], {%1, %2, %3, %4};" :: "r"(addr), "r"(a), "r"(b), "r"(c), "r"(d));
}
__device__ __forceinline__ uint4 lds128_v(uint32_t addr) { uint4 v; asm volatile("ld.shared.v4.b32 {%0, %1, %2, %3}, [%4];" : "=r"(v.x), "=r"(v.y), "=r"(v.z), "=r"(v.w) : "r"(addr)); return v; }
extern __shared__ __align__(1024) uint8_t smem_raw[];
template<class T> __device__ __forceinline__ T& smem_at(uint32_t addr) { return *reinterpret_cast<T*>(__cvta_shared_to_generic(addr)); }
#define SM_(T, off) smem_at<T>(sb + (off))
__device__ __forceinline__ uint4 ldg_nc128(const void* p) { uint4 v; asm volatile("ld.global.nc.v4.b32 {%0, %1, %2, %3}, [%4];" : "=r"(v.x), "=r"(v.y), "=r"(v.z), "=r"(v.w) : "l"(p)); return v; }
__device__ __forceinline__ void pkt_st128(void* p, uint32_t a, uint32_t b, uint32_t c, uint32_t d) {
  asm volatile("{\n.reg .b128 v;\n.reg .b64 lo, hi;\nmov.b64 lo, {%1, %2};\nmov.b64 hi, {%3, %4};\nmov.b128 v, {lo, hi};\nst.relaxed.gpu.global.b128 [%0], v;\n}\n"
    :: "l"(p), "r"(a), "r"(b), "r"(c), "r"(d) : "memory");
}
__device__ __forceinline__ uint4 pkt_ld128(const void* p) {
  uint4 r;
  asm volatile("{\n.reg .b128 v;\n.reg .b64 lo, hi;\nld.relaxed.gpu.global.b128 v, [%4];\nmov.b128 {lo, hi}, v;\nmov.b64 {%0, %1}, lo;\nmov.b64 {%2, %3}, hi;\n}\n"
    : "=r"(r.x), "=r"(r.y), "=r"(r.z), "=r"(r.w) : "l"(p) : "memory");
  return r;
}
__device__ __forceinline__ void pkt_ld128_if(uint4& r, const void* p, bool cond) {
  asm volatile("{\n.reg .pred q;\nsetp.ne.b32 q, %5, 0;\n@q ld.relaxed.gpu.global.v4.b32 {%0, %1, %2, %3}, [%4];\n}\n"
    : "+r"(r.x), "+r"(r.y), "+r"(r.z), "+r"(r.w) : "l"(p), "r"((uint32_t)cond) : "memory");
}
__device__ __forceinline__ void pkt_st64(void* p, uint32_t a, uint32_t b) {
  asm volatile("{\n.reg .b64 v;\nmov.b64 v, {%1, %2};\nst.relaxed.gpu.global.b64 [%0], v;\n}\n" :: "l"(p), "r"(a), "r"(b) : "memory");
}
__device__ __forceinline__ uint2 pkt_ld64(const void* p) {
  uint2 r;
  asm volatile("{\n.reg .b64 v;\nld.relaxed.gpu.global.b64 v, [%2];\nmov.b64 {%0, %1}, v;\n}\n" : "=r"(r.x), "=r"(r.y) : "l"(p) : "memory");
  return r;
}
__device__ __forceinline__ uint32_t ld_relaxed32(const void* p) { uint32_t v; asm volatile("ld.relaxed.gpu.global.b32 %0, [%1];" : "=r"(v) : "l"(p) : "memory"); return v; }
__device__ __forceinline__ void st_relaxed32(void* p, uint32_t v) { asm volatile("st.relaxed.gpu.global.b32 [%0], %1;" :: "l"(p), "r"(v) : "memory"); }
__device__ __forceinline__ uint32_t code_of(uint32_t tag) { return tag % 3u + 1u; }
__device__ __forceinline__ uint32_t with_bit(float v, uint32_t bit) { return (__float_as_uint(v) & ~1u) | (bit & 1u); }
__device__ __forceinline__ uint32_t pair_code(uint32_t a, uint32_t b) { return (a & 1u) | ((b & 1u) << 1); }
__device__ __forceinline__ uint32_t pack_bf16(float lo, float hi) { uint32_t r; asm("cvt.rn.bf16x2.f32 %0, %1, %2;" : "=r"(r) : "f"(hi), "f"(lo)); return r; }
__device__ __forceinline__ float bf_lo(uint32_t v) { return __uint_as_float(v << 16); }
__device__ __forceinline__ float bf_hi(uint32_t v) { return __uint_as_float(v & 0xFFFF0000u); }
__device__ __forceinline__ float bf16r(float x) { return __uint_as_float(pack_bf16(0.f, x)); }
__device__ __forceinline__ uint32_t badd2(uint32_t a, uint32_t b) { uint32_t r; asm("add.rn.bf16x2 %0, %1, %2;" : "=r"(r) : "r"(a), "r"(b)); return r; }
__device__ __forceinline__ uint32_t bmul2(uint32_t a, uint32_t b) { uint32_t r; asm("mul.rn.bf16x2 %0, %1, %2;" : "=r"(r) : "r"(a), "r"(b)); return r; }
__device__ __forceinline__ float warp_sum(float v) {
#pragma unroll
  for (int o = 16; o > 0; o >>= 1) v += __shfl_xor_sync(0xffffffffu, v, o);
  return v;
}
__device__ __forceinline__ uint64_t make_desc(uint32_t addr) {
  return (uint64_t)((addr & 0x3FFFF) >> 4) | ((uint64_t)1 << 16) | ((uint64_t)64 << 32) | ((uint64_t)1 << 62);
}
__device__ __forceinline__ uint64_t make_desc_noswz(uint32_t addr) {
  return (uint64_t)((addr & 0x3FFFF) >> 4) | ((uint64_t)8 << 16) | ((uint64_t)16 << 32);
}
__device__ __forceinline__ void wgmma_n256(float (&d)[128], uint64_t da, uint64_t db, int scale_d) {
  asm volatile("{\n.reg .pred p;\nsetp.ne.b32 p, %130, 0;\n"
    "wgmma.mma_async.sync.aligned.m64n256k16.f32.bf16.bf16 "
    "{%0, %1, %2, %3, %4, %5, %6, %7, %8, %9, %10, %11, %12, %13, %14, %15, %16, %17, %18, %19, %20, %21, %22, %23, %24, %25, %26, %27, %28, %29, %30, %31, "
    "%32, %33, %34, %35, %36, %37, %38, %39, %40, %41, %42, %43, %44, %45, %46, %47, %48, %49, %50, %51, %52, %53, %54, %55, %56, %57, %58, %59, %60, %61, %62, %63, "
    "%64, %65, %66, %67, %68, %69, %70, %71, %72, %73, %74, %75, %76, %77, %78, %79, %80, %81, %82, %83, %84, %85, %86, %87, %88, %89, %90, %91, %92, %93, %94, %95, "
    "%96, %97, %98, %99, %100, %101, %102, %103, %104, %105, %106, %107, %108, %109, %110, %111, %112, %113, %114, %115, %116, %117, %118, %119, %120, %121, %122, %123, %124, %125, %126, %127}, "
    "%128, %129, p, 1, 1, 0, 0;\n}\n"
    : "+f"(d[0]), "+f"(d[1]), "+f"(d[2]), "+f"(d[3]), "+f"(d[4]), "+f"(d[5]), "+f"(d[6]), "+f"(d[7]),
      "+f"(d[8]), "+f"(d[9]), "+f"(d[10]), "+f"(d[11]), "+f"(d[12]), "+f"(d[13]), "+f"(d[14]), "+f"(d[15]),
      "+f"(d[16]), "+f"(d[17]), "+f"(d[18]), "+f"(d[19]), "+f"(d[20]), "+f"(d[21]), "+f"(d[22]), "+f"(d[23]),
      "+f"(d[24]), "+f"(d[25]), "+f"(d[26]), "+f"(d[27]), "+f"(d[28]), "+f"(d[29]), "+f"(d[30]), "+f"(d[31]),
      "+f"(d[32]), "+f"(d[33]), "+f"(d[34]), "+f"(d[35]), "+f"(d[36]), "+f"(d[37]), "+f"(d[38]), "+f"(d[39]),
      "+f"(d[40]), "+f"(d[41]), "+f"(d[42]), "+f"(d[43]), "+f"(d[44]), "+f"(d[45]), "+f"(d[46]), "+f"(d[47]),
      "+f"(d[48]), "+f"(d[49]), "+f"(d[50]), "+f"(d[51]), "+f"(d[52]), "+f"(d[53]), "+f"(d[54]), "+f"(d[55]),
      "+f"(d[56]), "+f"(d[57]), "+f"(d[58]), "+f"(d[59]), "+f"(d[60]), "+f"(d[61]), "+f"(d[62]), "+f"(d[63]),
      "+f"(d[64]), "+f"(d[65]), "+f"(d[66]), "+f"(d[67]), "+f"(d[68]), "+f"(d[69]), "+f"(d[70]), "+f"(d[71]),
      "+f"(d[72]), "+f"(d[73]), "+f"(d[74]), "+f"(d[75]), "+f"(d[76]), "+f"(d[77]), "+f"(d[78]), "+f"(d[79]),
      "+f"(d[80]), "+f"(d[81]), "+f"(d[82]), "+f"(d[83]), "+f"(d[84]), "+f"(d[85]), "+f"(d[86]), "+f"(d[87]),
      "+f"(d[88]), "+f"(d[89]), "+f"(d[90]), "+f"(d[91]), "+f"(d[92]), "+f"(d[93]), "+f"(d[94]), "+f"(d[95]),
      "+f"(d[96]), "+f"(d[97]), "+f"(d[98]), "+f"(d[99]), "+f"(d[100]), "+f"(d[101]), "+f"(d[102]), "+f"(d[103]),
      "+f"(d[104]), "+f"(d[105]), "+f"(d[106]), "+f"(d[107]), "+f"(d[108]), "+f"(d[109]), "+f"(d[110]), "+f"(d[111]),
      "+f"(d[112]), "+f"(d[113]), "+f"(d[114]), "+f"(d[115]), "+f"(d[116]), "+f"(d[117]), "+f"(d[118]), "+f"(d[119]),
      "+f"(d[120]), "+f"(d[121]), "+f"(d[122]), "+f"(d[123]), "+f"(d[124]), "+f"(d[125]), "+f"(d[126]), "+f"(d[127])
    : "l"(da), "l"(db), "r"(scale_d));
}
__device__ __forceinline__ void wgmma_n256_rs(float (&d)[128], uint32_t a0, uint32_t a1, uint32_t a2, uint32_t a3, uint64_t db, int scale_d) {
  asm volatile("{\n.reg .pred p;\nsetp.ne.b32 p, %133, 0;\n"
    "wgmma.mma_async.sync.aligned.m64n256k16.f32.bf16.bf16 "
    "{%0, %1, %2, %3, %4, %5, %6, %7, %8, %9, %10, %11, %12, %13, %14, %15, %16, %17, %18, %19, %20, %21, %22, %23, %24, %25, %26, %27, %28, %29, %30, %31, "
    "%32, %33, %34, %35, %36, %37, %38, %39, %40, %41, %42, %43, %44, %45, %46, %47, %48, %49, %50, %51, %52, %53, %54, %55, %56, %57, %58, %59, %60, %61, %62, %63, "
    "%64, %65, %66, %67, %68, %69, %70, %71, %72, %73, %74, %75, %76, %77, %78, %79, %80, %81, %82, %83, %84, %85, %86, %87, %88, %89, %90, %91, %92, %93, %94, %95, "
    "%96, %97, %98, %99, %100, %101, %102, %103, %104, %105, %106, %107, %108, %109, %110, %111, %112, %113, %114, %115, %116, %117, %118, %119, %120, %121, %122, %123, %124, %125, %126, %127}, "
    "{%128, %129, %130, %131}, %132, p, 1, 1, 0;\n}\n"
    : "+f"(d[0]), "+f"(d[1]), "+f"(d[2]), "+f"(d[3]), "+f"(d[4]), "+f"(d[5]), "+f"(d[6]), "+f"(d[7]),
      "+f"(d[8]), "+f"(d[9]), "+f"(d[10]), "+f"(d[11]), "+f"(d[12]), "+f"(d[13]), "+f"(d[14]), "+f"(d[15]),
      "+f"(d[16]), "+f"(d[17]), "+f"(d[18]), "+f"(d[19]), "+f"(d[20]), "+f"(d[21]), "+f"(d[22]), "+f"(d[23]),
      "+f"(d[24]), "+f"(d[25]), "+f"(d[26]), "+f"(d[27]), "+f"(d[28]), "+f"(d[29]), "+f"(d[30]), "+f"(d[31]),
      "+f"(d[32]), "+f"(d[33]), "+f"(d[34]), "+f"(d[35]), "+f"(d[36]), "+f"(d[37]), "+f"(d[38]), "+f"(d[39]),
      "+f"(d[40]), "+f"(d[41]), "+f"(d[42]), "+f"(d[43]), "+f"(d[44]), "+f"(d[45]), "+f"(d[46]), "+f"(d[47]),
      "+f"(d[48]), "+f"(d[49]), "+f"(d[50]), "+f"(d[51]), "+f"(d[52]), "+f"(d[53]), "+f"(d[54]), "+f"(d[55]),
      "+f"(d[56]), "+f"(d[57]), "+f"(d[58]), "+f"(d[59]), "+f"(d[60]), "+f"(d[61]), "+f"(d[62]), "+f"(d[63]),
      "+f"(d[64]), "+f"(d[65]), "+f"(d[66]), "+f"(d[67]), "+f"(d[68]), "+f"(d[69]), "+f"(d[70]), "+f"(d[71]),
      "+f"(d[72]), "+f"(d[73]), "+f"(d[74]), "+f"(d[75]), "+f"(d[76]), "+f"(d[77]), "+f"(d[78]), "+f"(d[79]),
      "+f"(d[80]), "+f"(d[81]), "+f"(d[82]), "+f"(d[83]), "+f"(d[84]), "+f"(d[85]), "+f"(d[86]), "+f"(d[87]),
      "+f"(d[88]), "+f"(d[89]), "+f"(d[90]), "+f"(d[91]), "+f"(d[92]), "+f"(d[93]), "+f"(d[94]), "+f"(d[95]),
      "+f"(d[96]), "+f"(d[97]), "+f"(d[98]), "+f"(d[99]), "+f"(d[100]), "+f"(d[101]), "+f"(d[102]), "+f"(d[103]),
      "+f"(d[104]), "+f"(d[105]), "+f"(d[106]), "+f"(d[107]), "+f"(d[108]), "+f"(d[109]), "+f"(d[110]), "+f"(d[111]),
      "+f"(d[112]), "+f"(d[113]), "+f"(d[114]), "+f"(d[115]), "+f"(d[116]), "+f"(d[117]), "+f"(d[118]), "+f"(d[119]),
      "+f"(d[120]), "+f"(d[121]), "+f"(d[122]), "+f"(d[123]), "+f"(d[124]), "+f"(d[125]), "+f"(d[126]), "+f"(d[127])
    : "r"(a0), "r"(a1), "r"(a2), "r"(a3), "l"(db), "r"(scale_d));
}
__device__ __forceinline__ void wgmma_n128(float (&d)[64], uint64_t da, uint64_t db) {
  asm volatile("{\n.reg .pred p;\nsetp.ne.b32 p, 1, 0;\n"
    "wgmma.mma_async.sync.aligned.m64n128k16.f32.bf16.bf16 "
    "{%0, %1, %2, %3, %4, %5, %6, %7, %8, %9, %10, %11, %12, %13, %14, %15, %16, %17, %18, %19, %20, %21, %22, %23, %24, %25, %26, %27, %28, %29, %30, %31, %32, %33, %34, %35, %36, %37, %38, %39, %40, %41, %42, %43, %44, %45, %46, %47, %48, %49, %50, %51, %52, %53, %54, %55, %56, %57, %58, %59, %60, %61, %62, %63}, "
    "%64, %65, p, 1, 1, 0, 0;\n}\n"
    : "+f"(d[0]), "+f"(d[1]), "+f"(d[2]), "+f"(d[3]), "+f"(d[4]), "+f"(d[5]), "+f"(d[6]), "+f"(d[7]), "+f"(d[8]), "+f"(d[9]), "+f"(d[10]), "+f"(d[11]), "+f"(d[12]), "+f"(d[13]), "+f"(d[14]), "+f"(d[15]), "+f"(d[16]), "+f"(d[17]), "+f"(d[18]), "+f"(d[19]), "+f"(d[20]), "+f"(d[21]), "+f"(d[22]), "+f"(d[23]), "+f"(d[24]), "+f"(d[25]), "+f"(d[26]), "+f"(d[27]), "+f"(d[28]), "+f"(d[29]), "+f"(d[30]), "+f"(d[31]), "+f"(d[32]), "+f"(d[33]), "+f"(d[34]), "+f"(d[35]), "+f"(d[36]), "+f"(d[37]), "+f"(d[38]), "+f"(d[39]), "+f"(d[40]), "+f"(d[41]), "+f"(d[42]), "+f"(d[43]), "+f"(d[44]), "+f"(d[45]), "+f"(d[46]), "+f"(d[47]), "+f"(d[48]), "+f"(d[49]), "+f"(d[50]), "+f"(d[51]), "+f"(d[52]), "+f"(d[53]), "+f"(d[54]), "+f"(d[55]), "+f"(d[56]), "+f"(d[57]), "+f"(d[58]), "+f"(d[59]), "+f"(d[60]), "+f"(d[61]), "+f"(d[62]), "+f"(d[63])
    : "l"(da), "l"(db));
}
__device__ __forceinline__ void fence_acc64(float (&d)[64]) {
#pragma unroll
  for (int i = 0; i < 64; i++) asm volatile("" : "+f"(d[i]) :: "memory");
}
__device__ __forceinline__ void fence_acc(float (&d)[128]) {
#pragma unroll
  for (int i = 0; i < 128; i++) asm volatile("" : "+f"(d[i]) :: "memory");
}

template<int N, int I = 0, class F> __device__ __forceinline__ void static_for(F&& f) {
  if constexpr (I < N) { f(std::integral_constant<int, I>()); static_for<N, I + 1>(f); }
}

__device__ __forceinline__ void ldsm_x4_t(uint32_t addr, uint32_t& a, uint32_t& b, uint32_t& c, uint32_t& d) {
  asm volatile("ldmatrix.sync.aligned.m8n8.x4.trans.shared.b16 {%0, %1, %2, %3}, [%4];" : "=r"(a), "=r"(b), "=r"(c), "=r"(d) : "r"(addr));
}
__device__ __forceinline__ void sts128(uint32_t addr, uint32_t a, uint32_t b, uint32_t c, uint32_t d) {
  asm volatile("st.shared.v4.b32 [%0], {%1, %2, %3, %4};" :: "r"(addr), "r"(a), "r"(b), "r"(c), "r"(d));
}
__device__ __forceinline__ void mma16816(float (&c)[4], uint32_t a0, uint32_t a1, uint32_t a2, uint32_t a3, uint32_t b0, uint32_t b1) {
  asm volatile("mma.sync.aligned.m16n8k16.row.col.f32.bf16.bf16.f32 {%0, %1, %2, %3}, {%4, %5, %6, %7}, {%8, %9}, {%0, %1, %2, %3};"
      : "+f"(c[0]), "+f"(c[1]), "+f"(c[2]), "+f"(c[3]) : "r"(a0), "r"(a1), "r"(a2), "r"(a3), "r"(b0), "r"(b1));
}
__device__ __forceinline__ void mma1688(float (&c)[4], uint32_t a0, uint32_t a1, uint32_t b0) {
  asm volatile("mma.sync.aligned.m16n8k8.row.col.f32.bf16.bf16.f32 {%0, %1, %2, %3}, {%4, %5}, {%6}, {%0, %1, %2, %3};"
      : "+f"(c[0]), "+f"(c[1]), "+f"(c[2]), "+f"(c[3]) : "r"(a0), "r"(a1), "r"(b0));
}
__device__ __forceinline__ void pin(uint32_t& v) { asm volatile("shfl.sync.bfly.b32 %0, %0, 0, 0x1f, 0xffffffff;" : "+r"(v)); }
template<class T> __device__ __forceinline__ void pin(T*& v) {
  uint32_t lo = (uint32_t)(uint64_t)v, hi = (uint32_t)((uint64_t)v >> 32);
  pin(lo); pin(hi);
  v = (T*)(((uint64_t)hi << 32) | lo);
}
__device__ __forceinline__ float sel4(int q, float a, float b, float c, float d) {
  float r;
  asm("{\n.reg .pred p, o;\n.reg .f32 x, y;\n.reg .b32 t;\nand.b32 t, %1, 1;\nsetp.ne.b32 p, t, 0;\nsetp.gt.s32 o, %1, 1;\n"
      "selp.f32 x, %3, %2, p;\nselp.f32 y, %5, %4, p;\nselp.f32 %0, y, x, o;\n}\n" : "=f"(r) : "r"(q), "f"(a), "f"(b), "f"(c), "f"(d));
  return r;
}
__device__ __forceinline__ uint32_t bfma2(uint32_t a, uint32_t b, uint32_t c) { uint32_t r; asm("fma.rn.bf16x2 %0, %1, %2, %3;" : "=r"(r) : "r"(a), "r"(b), "r"(c)); return r; }
__device__ __forceinline__ void tma_store_5d(const CUtensorMap* tm, uint32_t src, int c0, int c3, int c4) {
  asm volatile("cp.async.bulk.tensor.5d.global.shared::cta.bulk_group [%0, {%2, %3, %3, %4, %5}], [%1];" :: "l"(tm), "r"(src), "r"(c0), "r"(0), "r"(c3), "r"(c4) : "memory");
}
__device__ __forceinline__ float rcp_fast(float x) { float r; asm("rcp.approx.ftz.f32 %0, %1;" : "=f"(r) : "f"(x)); return r; }
__device__ __forceinline__ float sigmoid_fast(float x) { float e; asm("ex2.approx.ftz.f32 %0, %1;" : "=f"(e) : "f"(x * -1.4426950408889634f)); return rcp_fast(1.f + e); }
__device__ __forceinline__ float sqrt_fast(float x) { float r; asm("sqrt.approx.ftz.f32 %0, %1;" : "=f"(r) : "f"(x)); return r; }
__device__ __forceinline__ float ln_sd(float var) { return bf16r(sqrt_fast(bf16r(bf16r(fmaxf(var, 0.f)) + 1e-5f))); }
__device__ __forceinline__ uint32_t norm2(uint32_t h, uint32_t neg_mean2, float inv_sd) {
  const uint32_t d = badd2(h, neg_mean2);
  return pack_bf16(bf_lo(d) * inv_sd, bf_hi(d) * inv_sd);
}
template<int N> __device__ __forceinline__ void delay_clk() {
  if constexpr (N > 0) { const uint32_t t0 = clock(); while ((uint32_t)clock() - t0 < N) {} }
}
template<int V> using IC = std::integral_constant<int, V>;

#define CT(slot) do {} while (0)
#define PT(slot) do {} while (0)

template<int MAP>
__global__ void __cluster_dims__(2, 1, 1) __launch_bounds__(384, 1)
fnet_moe_kernel(const __grid_constant__ Params p) {
  uint32_t sb;
  asm volatile("mov.u32 %0, %1;" : "=r"(sb) : "r"(smem_u32(smem_raw)));
  const int m = blockIdx.x & 1;
  int tau, eps;
  bool idle = false;
  if (MAP == 0) {
    uint32_t smid;
    asm volatile("mov.u32 %0, %%smid;" : "=r"(smid));
    const int c = smid >> 1, e7 = ((c - 32) * 37) >> 8;
    idle = c == 60 || c == 61;
    tau = c < 32 ? (c & 7) : (c < 60 ? c - 31 - 7 * e7 : 0);
    eps = c < 32 ? (c >> 3) : (c < 60 ? 4 + e7 : c - 58);
  } else {
    tau = (blockIdx.x >> 1) & 7; eps = blockIdx.x >> 4;
  }
  const int cid = tau * 16 + eps * 2 + m;
  const bool moe = tau > 0;
  auto BAR = [&](int i) { return sb + OFF_BAR + 8 * i; };
  const CUtensorMap* tmD = m ? &p.tmD1 : &p.tmD0;
  const uint64_t pol_ef = policy_evict_first();
#define LOAD_STREAM(d, tm, bar, c0, c1) tma_load_2d_hint(d, tm, bar, c0, c1, pol_ef)
  if (threadIdx.x < 32 && !idle) {
    if (elect_one()) {
#pragma unroll
      for (int k = 0; k < 4; k++) mbar_init(BAR(B_FULL + k), 1);
      asm volatile("fence.mbarrier_init.release.cluster;" ::: "memory");
#pragma unroll
      for (int k = 0; k < 4; k++) mbar_expect_tx(BAR(B_FULL + k), ST_BYTES);
    }
    PT(50);
    if (elect_one()) {
      tma_load_2d(sb + A_BYTES, &p.tmX, BAR(B_FULL), 0, tau * 256);
      LOAD_STREAM(sb, tmD, BAR(B_FULL), 0, eps * 128);
    }
    PT(52);
    if (elect_one()) {
#pragma unroll
      for (int k = 1; k < 4; k++) {
        tma_load_2d(sb + k * ST_BYTES + A_BYTES, &p.tmX, BAR(B_FULL + k), k * 64, tau * 256);
        LOAD_STREAM(sb + k * ST_BYTES, tmD, BAR(B_FULL + k), k * 64, eps * 128);
      }
    }
    PT(0);
  }
  __syncwarp();
  const int warp = __shfl_sync(0xffffffffu, threadIdx.x >> 5, 0);
  const int tid = __shfl_sync(0xffffffffu, threadIdx.x, threadIdx.x & 31), lane = tid & 31;
  if (idle) {
    __nanosleep(4000);
    const uint32_t tg = ld_relaxed32(&p.s->epoch) + 1;
    uint32_t n = 0;
    do { __nanosleep(1000); } while (!__all_sync(0xffffffffu, pkt_ld64(&p.s->xstat[(tid & 127) * 16]).y == tg) && ++n < 4096);
    return;
  }
  if (warp == 8) {
    if (elect_one()) {
#pragma unroll
      for (int b = B_EMPTY; b < B_COUNT; b++)
        mbar_init(BAR(b), b < B_EPI ? 2 : (b == B_EPI || b == B_EPI0B) ? 4 : (b < B_STD || b == B_OUT) ? 8 : (b == B_STAT || b == B_XS) ? 3 : 1);
      asm volatile("fence.mbarrier_init.release.cluster;" ::: "memory");
      mbar_expect_tx(BAR(B_XCH), 32768);
      SM_(uint32_t, OFF_SEEN) = 0;
    }
  }
  __syncthreads();

  if (warp >= 8) {
    reg_dec<REG_P>();
    asm volatile("barrier.cluster.arrive.relaxed.aligned;" ::: "memory");
    const int abrow = m * 1024 + eps * 128;
    const int f0 = (cid - 16) * 32;
    if (warp == 8) {
      const CUtensorMap* tmW = m ? &p.tmW1 : &p.tmW0;
      const int tA = tau * 256 + m * 128, tB = tau * 256 + (1 - m) * 128;
      uint32_t seen = 0;
#pragma unroll 1
      for (int k = 4; k < 48; k++) {
        const int s = slot_of(k);
        const uint32_t sa = sb + s * ST_BYTES, sbb = sa + A_BYTES;
        const int kb = kblock(tau, k - 16);
        mbar_wait(BAR(B_EMPTY + s), (use_of(k) & 1) ^ 1);
        PT(64 + k);
        if (elect_one()) {
          mbar_expect_tx(BAR(B_FULL + s), (k >> 1) == 9 ? B_BYTES : k == 20 ? ST_BYTES - 8192 : ST_BYTES);
          if (k < 16) {
            LOAD_STREAM(sa, tmD, BAR(B_FULL + s), k * 64, eps * 128);
            tma_load_2d(sbb, &p.tmX, BAR(B_FULL + s), k * 64, tau * 256);
          } else {
            LOAD_STREAM(sbb, tmW, BAR(B_FULL + s), kb * 64, tA);
            LOAD_STREAM(sbb + 16384, tmW, BAR(B_FULL + s), kb * 64, tB);
            if (k < 18) {
              tma_load_2d(sa, &p.tmXr, BAR(B_FULL + s), eps * 128, tA + s * 64);
              tma_load_2d(sa + 8192, &p.tmXr, BAR(B_FULL + s), eps * 128 + 64, tA + s * 64);
            }
          }
        }
        if (k >= 24) {
          uint32_t n = 0;
          while (!((seen >> kb) & 1) && ++n < SPIN_LIMIT * 16) seen = *(volatile uint32_t*)&SM_(uint32_t, OFF_SEEN);
          if (elect_one()) tma_load_2d(sa, &p.tmAbL, BAR(B_FULL + s), kb * 64, abrow);
        }
        if (k == PUB_K1 && elect_one()) mbar_arrive(BAR(B_LATE));
        if (k >= WPF_K0 + WPF_J0 && k < WPF_K0 + WPF_J1 && (eps >> 1) == ((k - WPF_K0) & 3) && elect_one())
          asm volatile("cp.async.bulk.prefetch.tensor.2d.L2.global.tile [%0, {%1, %2}];" :: "l"(tmW), "r"(kblock(tau, k - WPF_K0) * 64), "r"(tau * 256 + (eps & 1) * 128) : "memory");
        if (moe && k >= PF_K0 && !(k & 1)) {
          const int i = k < PF_K1 ? (k - PF_K0) >> 1 : PF_N0 + ((k - PF_K1) >> 1);
          if ((k >= PF_K1 || i < PF_N0) && elect_one()) {
            if (i < 8) asm volatile("cp.async.bulk.prefetch.tensor.2d.L2.global.tile [%0, {%1, %2}];" :: "l"(m ? &p.tmU : &p.tmG), "r"(f0), "r"(i * 128) : "memory");
            else if (i < 12) asm volatile("cp.async.bulk.prefetch.L2.global [%0], %1;" :: "l"(p.wdown + (size_t)f0 * 1024 + (i - 8) * 8192), "r"(16384) : "memory");
          }
        }
        if (moe && k >= MR_K0) {
          const int i = k - MR_K0, r6 = i / MR_P, u = i - MR_P * r6, h = 2 * r6 + (u >> 1);
          if (u < 4 && h < NREG_H + 2) {
            if (h < 2) mbar_wait(BAR(B_STD + 2 + h), 0);
            if (elect_one()) {
              const uint32_t bar = BAR(h < NREG_H ? B_MR + (h & 1) : B_GU);
              if (!(u & 1) && h <= NREG_H) mbar_expect_tx(bar, h < NREG_H ? 16384 : (8 - NREG_H) * 16384);
              LOAD_STREAM(sb + OFF_XCH + u * 8192, (u & 1) ? &p.tmU : &p.tmG, bar, f0, h * 128);
              if (mr_k(NREG_H + 1) == 47 && k == 47) LOAD_STREAM(sb + OFF_XCH + u * 8192 + 8192, &p.tmU, bar, f0, h * 128);
            }
          }
        }
      }
      if (moe) {
        mbar_wait(BAR(B_EMPTY + 0), 1);
        if (elect_one()) mbar_expect_tx(BAR(B_DN), 65536);
#pragma unroll 1
        for (int i = 0; i < 10 - NREG_H; i++) {
          if (i == 3) mbar_wait(BAR(B_EMPTY + 1), 1);
          if (i == 4) {
            mbar_wait(BAR(B_EMPTY + 2), 1);
            mbar_wait(BAR(B_XCH), 0);
          }
          const uint32_t dst = sb + late_off(i);
          if (elect_one()) {
            if (i < 6 - NREG_H) {
              LOAD_STREAM(dst, &p.tmG, BAR(B_GU), f0, (NREG_H + 2 + i) * 128);
              LOAD_STREAM(dst + 8192, &p.tmU, BAR(B_GU), f0, (NREG_H + 2 + i) * 128);
            } else {
#pragma unroll
              for (int b = 0; b < 4; b++) LOAD_STREAM(dst + b * 4096, &p.tmDn, BAR(B_DN), (4 * (i - 6 + NREG_H) + b) * 64, f0);
            }
          }
          const long long t0 = clock64();
          while (i < 9 - NREG_H && clock64() - t0 < MOE_PACE_CLK) {}
        }
      }
    } else {
      const int a = warp - 9;
      auto stage = [&](const bf16* src, int g) {
        if (elect_one()) {
          mbar_expect_tx(BAR(B_AUX + g), 16384);
          bulk_load(sb + OFF_XCH + g * 16384, src + g * 8192, 16384, BAR(B_AUX + g));
        }
      };
      mbar_wait(BAR(B_FULL + 0), 0);
      if (a == 0) PT(1);
      if (a < 2) stage(p.x + (size_t)cid * 16 * 1024, a);
      const uint32_t tag = ld_relaxed32(&p.s->epoch) + 1;
      if (a == 2) {
        float s = 0.f;
#pragma unroll
        for (int q = 0; q < 4; q++) {
          const uint4 v = ldg_nc128(p.wr + (q * 32 + lane) * 8);
          s += ((bf_lo(v.x) + bf_hi(v.x)) + (bf_lo(v.y) + bf_hi(v.y))) + ((bf_lo(v.z) + bf_hi(v.z)) + (bf_lo(v.w) + bf_hi(v.w)));
          const int ch = q * 32 + lane - eps * 16;
          if (ch >= 0 && ch < 16) {
            SM_(uint32_t, OFF_WR + ch * 4) = v.x; SM_(uint32_t, OFF_WR + 80 + ch * 4) = v.y;
            SM_(uint32_t, OFF_WR + 160 + ch * 4) = v.z; SM_(uint32_t, OFF_WR + 240 + ch * 4) = v.w;
          }
        }
        s = warp_sum(s);
        if (lane == 0) { SM_(float, OFF_WSUM) = s; SM_(uint32_t, OFF_TAG) = tag; }
      }
#pragma unroll 1
      for (int it = 0; it < 4; it++) {
        const int g = it & 1;
        mbar_wait(BAR(B_AUX + g), it >> 1);
        if (a == 0) PT(2 + it);
        const uint32_t ad = sb + OFF_XCH + g * 16384 + (lane >> 2) * 2048;
        float s0 = 0.f, s1 = 0.f, q0 = 0.f, q1 = 0.f;
        auto row = [&](auto sq) {
#pragma unroll
          for (int i = 0; i < 11; i++) {
            if (i == 10 && a == 2) break;
            const uint4 v = lds128_v(ad + (((a * 44 + 4 * i + lane) & 127) << 4));
            const uint32_t ww[4] = {v.x, v.y, v.z, v.w};
#pragma unroll
            for (int z = 0; z < 4; z++) {
              const float d0 = bf_lo(ww[z]), d1 = bf_hi(ww[z]);
              s0 += d0; s1 += d1;
              if (decltype(sq)::value) { q0 = fmaf(d0, d0, q0); q1 = fmaf(d1, d1, q1); }
            }
          }
        };
        if (it < 2) row(IC<1>()); else row(IC<0>());
        s0 += s1; q0 += q1;
#pragma unroll
        for (int o = 1; o < 4; o <<= 1) { s0 += __shfl_xor_sync(0xffffffffu, s0, o); q0 += __shfl_xor_sync(0xffffffffu, q0, o); }
        if ((lane & 3) == 0) SM_(float2, OFF_PUB + a * 256 + it * 64 + (lane >> 2) * 8) = make_float2(s0, q0);
        if (it != 2) bar_sync(NB_AUX, 96);
        if (it < 2 && a == 2) stage(cid < 64 ? p.Dre + (size_t)cid * 16 * 1024 : p.Dim + (size_t)(cid - 64) * 16 * 1024, g);
      }
      if (a == 1) {
        const float2 v0 = SM_(float2, OFF_PUB + lane * 8), v1 = SM_(float2, OFF_PUB + 256 + lane * 8), v2 = SM_(float2, OFF_PUB + 512 + lane * 8);
        const float s = v0.x + v1.x + v2.x, mean = s * (1.f / 1024.f);
        const float rs = rcp_fast(ln_sd((v0.y + v1.y + v2.y) * (1.f / 1024.f) - mean * mean));
        pkt_st64((lane < 16 ? p.s->xstat : p.s->dsum) + cid * 16 + (lane & 15), lane < 16 ? pack_bf16(rs, mean) : __float_as_uint(s), tag);
        PT(6);
      }
      __nanosleep(GATHER_NS);
      {
        const int i0 = a * 32 + lane;
        uint2 v[3], c0, c1; uint32_t n = 0;
        const uint2* dp = &p.s->dsum[abrow];
        while (true) {
#pragma unroll
          for (int q = 0; q < 3; q++) v[q] = pkt_ld64(&p.s->xstat[tau * 256 + min(i0 + 96 * q, 255)]);
          c0 = pkt_ld64(dp + i0); c1 = pkt_ld64(dp + min(i0 + 96, 127));
          if (__all_sync(0xffffffffu, v[0].y == tag && v[1].y == tag && v[2].y == tag && c0.y == tag && c1.y == tag) || ++n > SPIN_LIMIT) break;
          __nanosleep(200);
        }
#pragma unroll
        for (int q = 0; q < 3; q++) {
          const int col = min(i0 + 96 * q, 255);
          SM_(uint16_t, OFF_RS + ((col & 7) >> 1) * 144 + (col >> 3) * 4 + (col & 1) * 2) = (uint16_t)(v[q].x ^ (m << 15));
          const uint32_t nm = (v[q].x >> 16) ^ 0x8000u;
          SM_(uint4, OFF_EXB + (col >> 3) * 256 + (col & 7) * 16) = make_uint4(nm | (nm << 16), nm, 0, 0);
          SM_(uint4, OFF_EXB + (col >> 3) * 256 + 128 + (col & 7) * 16) = make_uint4(0, 0, 0, 0);
        }
#pragma unroll
        for (int q = 0; q < 2; q++) {
          const int e = min(i0 + 96 * q, 127);
          const float c = __uint_as_float(q ? c1.x : c0.x);
          const float hi = bf16r(c), mid = bf16r(c - hi), lo = bf16r((c - hi) - mid);
          SM_(uint4, OFF_EXA + (e >> 3) * 256 + (e & 7) * 16) = make_uint4((__float_as_uint(hi) >> 16) | (__float_as_uint(mid) & 0xFFFF0000u), __float_as_uint(lo) >> 16, 0, 0);
          SM_(uint4, OFF_EXA + (e >> 3) * 256 + 128 + (e & 7) * 16) = make_uint4(0, 0, 0, 0);
        }
        fence_async_smem();
      }
      __syncwarp();
      if (lane == 0) mbar_arrive(BAR(B_STAT));
      if (a == 0) PT(7);
      if (a == 0) {
        const int sg = (lane >> 2) == tau ? (tau + 1) & 7 : lane >> 2;
        const uint32_t* flg = reinterpret_cast<const uint32_t*>(&p.s->abflag[((eps * 2 + m) * 8 + sg) * 2]) + ((lane >> 2) == tau ? 4 : lane & 3);
        uint32_t seen = 0;
        mbar_wait(BAR(B_STDA), 0);
        PT(49);
#pragma unroll 1
        for (int i = 0; i < 5; i++) {
          const int s = i ? i - 1 : 0, sig = (tau + 1 + s) & 7;
          if (i == 1) mbar_wait(BAR(B_STD + 0), 0);
          uint32_t n = 0;
          while (!((seen >> (4 * (i ? sig : tau))) & 1) && ++n < SPIN_LIMIT) seen = __ballot_sync(0xffffffffu, ld_relaxed32(flg) == tag);
          if (i == 0 || i == 4) mbar_wait(BAR(i ? B_STD + 1 : B_EPI0B), 0);
          if (i != 1) mbar_wait(BAR(B_FULL + s), 0);
          PT(i ? 16 + s : 48);
          if (elect_one()) {
            if (i == 1) mbar_expect_tx(BAR(B_A20), 8192);
            tma_load_2d(sb + (i < 3 ? OFF_XCH + i * 8192 : s * ST_BYTES), i < 2 ? &p.tmAbS : &p.tmAbL, BAR(i == 1 ? B_A20 : B_FULL + s), sig * 256,
                        abrow + (i == 1 ? 64 : 0));
          }
        }
        uint32_t n = 0;
        while (true) {
          asm volatile("fence.proxy.async.global;" ::: "memory");
          *(volatile uint32_t*)&SM_(uint32_t, OFF_SEEN) = seen;
          if (seen == 0xFFFFFFFFu || ++n > SPIN_LIMIT) break;
          seen = __ballot_sync(0xffffffffu, ld_relaxed32(flg) == tag);
          __nanosleep(100);
        }
      } else {
        uint32_t* flag = reinterpret_cast<uint32_t*>(&p.s->abflag[((eps * 2 + m) * 8 + tau) * 2]);
        mbar_wait(BAR(a == 1 ? B_EPI : B_EPI0B), 0);
        if (a == 1) PT(8);
        if (lane == 0) {
          tma_store_2d(&p.tmAbS, sb + chunk_off(0, a - 1), tau * 256, abrow + (a - 1) * 64);
          bulk_commit();
          bulk_wait_all();
        }
        if (a == 2) mbar_wait(BAR(B_STDA), 0);
        if (lane == 0) {
          st_relaxed32(flag + (a == 1 ? 4 : 0), tag);
          mbar_arrive(BAR(a == 1 ? B_STDA : B_STD));
        }
        if (a == 2) PT(12);
        if (a == 1) {
          mbar_wait(BAR(B_EPI + 1), 0);
          mbar_wait(BAR(B_LATE), 0);
          PT(9);
          if (lane == 0) {
            tma_store_2d(&p.tmAbS, sb + chunk_off(1, 0), tau * 256 + 64, abrow);
            tma_store_2d(&p.tmAbS, sb + chunk_off(1, 1), tau * 256 + 64, abrow + 64);
            bulk_commit();
            bulk_wait_all();
            st_relaxed32(flag + 1, tag);
            mbar_arrive(BAR(B_STD + 1));
          }
          PT(13);
        }
        auto copy_out = [&](int c) {
          mbar_wait(BAR(B_EPI + c), 0);
          PT(8 + c);
          bf16* dst = p.s->abT + (size_t)(abrow + (lane >> 3)) * 2048 + tau * 256 + c * 64;
#pragma unroll 4
          for (int i = 0; i < 32; i++) {
            const int row = 4 * i + (lane >> 3);
            const uint4 v = lds128_v(sb + chunk_off(c, 0) + i * 512 + lane * 16);
            asm volatile("st.global.v4.b32 [%0], {%1, %2, %3, %4};" :: "l"(dst + i * 4 * 2048 + (((lane & 7) ^ (row & 7)) << 3)), "r"(v.x), "r"(v.y), "r"(v.z), "r"(v.w));
          }
          __syncwarp();
          if (lane == 0) mbar_arrive(BAR(B_STD + c));
        };
        if (a == 2) {
#pragma unroll 1
          for (int c = 2; c < 4; c++) copy_out(c);
          asm volatile("fence.acq_rel.gpu;" ::: "memory");
          __syncwarp();
          if (lane < 2) st_relaxed32(flag + 2 + lane, tag);
          PT(15);
        }
      }
      {
        const uint4* kp = &p.s->key[(tau * 16 + (lane & 15)) * 2];
        const int i0 = a * 32 + lane;
        mbar_wait(BAR(B_KEY), 0);
        if (a == 0) PT(43);
        uint4 kq = pkt_ld128(kp), cv[3];
        uint32_t n = 0, kv;
        int gspec = -1;
        while (true) {
          const bool ok = kq.y == tag && kq.w == tag;
          kv = __reduce_max_sync(0xffffffffu, ok ? kq.x : 0u);
          const int gs = (0xFFFF - (int)(kv & 0xFFFFu)) >> 7;
          const bool cok = gs == gspec && cv[0].y == tag && cv[0].w == tag && cv[1].y == tag && cv[1].w == tag && cv[2].y == tag && cv[2].w == tag;
          if (__all_sync(0xffffffffu, ok && cok) || ++n > SPIN_LIMIT) break;
          if (!ok) kq = pkt_ld128(kp);
          const bool spec = __popc(__ballot_sync(0xffffffffu, ok)) >= 2 * SPEC_MIN;
          if (!cok && spec) {
#pragma unroll
            for (int i = 0; i < 3; i++) cv[i] = pkt_ld128(&p.s->cand[gs * 256 + min(i0 + 96 * i, 255)]);
          }
          if (spec) gspec = gs;
        }
        if (a == 0) PT(45);
        const uint32_t ms = __shfl_sync(0xffffffffu, kq.z, gspec);
        const uint32_t nm = ((ms & 0xFFFFu) ^ 0x8000u) * 0x10001u;
        const float is = rcp_fast(bf_hi(ms));
#pragma unroll
        for (int i = 0; i < 3; i++) {
          const int j = min(i0 + 96 * i, 255);
          SM_(uint2, OFF_XSEL + j * 8) = make_uint2(norm2(cv[i].x, nm, is), norm2(cv[i].z, nm, is));
          SM_(uint2, OFF_HSEL + j * 8) = make_uint2(cv[i].x, cv[i].z);
        }
        SM_(uint32_t, OFF_KV) = kv;
        __syncwarp();
        if (lane == 0) mbar_arrive(BAR(B_XS));
      }
    }
    if (warp == 8) {
      const int lane = threadIdx.x & 31;
      mbar_wait(BAR(B_OUT), 0);
      const uint32_t km = SM_(uint32_t, OFF_WKEY + (lane & 7) * 8);
      const uint32_t bk = __reduce_max_sync(0xffffffffu, km);
      const int ww = __ffs(__ballot_sync(0xffffffffu, km == bk)) - 1;
#pragma unroll 1
      for (int i = 1; i <= 8; i++) {
        const int W = (ww + i) & 7;
        if (i == 8) {
          mbar_wait(BAR(B_XS), 0);
          if (SM_(uint32_t, OFF_KV) == bk) {
#pragma unroll 2
            for (int j = lane; j < 256; j += 32) {
              const int rho = j >> 4, row = (tau * 2 + m) * 128 + 32 * (W >> 1) + 8 * ((rho & 7) >> 1) + 4 * (W & 1) + 2 * (rho >> 3) + (rho & 1);
              const uint4 v = lds128_v(sb + OFF_OUT + (j & 8) * 2048 + (16 * W + rho) * 128 + (((j ^ rho) & 7) << 4));
              if (row != 0xFFFF - (int)(bk & 0xFFFFu))
                asm volatile("st.global.v4.b32 [%0], {%1, %2, %3, %4};" :: "l"(p.out + (size_t)row * 1024 + eps * 128 + (j & 15) * 8), "r"(v.x), "r"(v.y), "r"(v.z), "r"(v.w));
            }
            break;
          }
        }
        if (lane == 0) {
          tma_store_5d(&p.tmOut, sb + OFF_OUT + W * 2048, eps * 128, 2 * (W & 1), tau * 8 + m * 4 + (W >> 1));
          tma_store_5d(&p.tmOut, sb + OFF_OUT + 16384 + W * 2048, eps * 128 + 64, 2 * (W & 1), tau * 8 + m * 4 + (W >> 1));
        }
        const long long t0 = clock64();
        while (i < 7 && clock64() - t0 < OUT_PACE_CLK) {}
      }
      if (lane == 0) { bulk_commit(); bulk_wait_all(); }
      PT(22);
    }
    asm volatile("barrier.cluster.wait.aligned;" ::: "memory");
  } else {
    reg_inc<REG_C>();
    const int w = warp >> 2, wi = warp & 3, t = tid & 127;
    const int g = lane >> 2, q = lane & 3;
    const int turn_me = NB_TURN0 + w, turn_other = NB_TURN1 - w;
    float acc[128];
#pragma unroll
    for (int i = 0; i < 128; i++) acc[i] = 0.f;
    if (w == 1) bar_arrive(NB_TURN0, 256);
    auto kstep = [&](int k, bool first, bool a_in_xch = false) {
      const int s = slot_of(k);
      mbar_wait(BAR(B_FULL + s), use_of(k) & 1);
      CT(64 + k);
      bar_sync(turn_me, 256);
      const uint64_t da = make_desc(sb + (a_in_xch ? OFF_XCH + s * 16384 : s * ST_BYTES) + w * 8192), db = make_desc(sb + s * ST_BYTES + A_BYTES);
      wgmma_fence();
      wgmma_n256(acc, da, db, !first);
#pragma unroll
      for (int kk = 1; kk < 4; kk++) wgmma_n256(acc, da + kk * 2, db + kk * 2, 1);
      wgmma_commit();
      bar_arrive(turn_other, 256);
    };
    auto release = [&](int s) { if (t == 0) mbar_arrive(BAR(B_EMPTY + s)); };
    auto kdone = [&](int k) { wgmma_wait0(); release(slot_of(k)); };
    auto wgmma_wait1 = [&]() { asm volatile("wgmma.wait_group.sync.aligned 1;" ::: "memory"); };

#pragma unroll 1
    for (int k = 0; k < 14; k++) {
      kstep(k, k == 0);
      if (k == 0) CT(0);
      if (k == 8 && warp == 2 && lane < 2) pkt_st128(&p.s->abflag[((eps * 2 + m) * 8 + tau) * 2 + lane], 0, 0, 0, 0);
      kdone(k);
    }
    uint32_t R[64];
    uint32_t tag;
    {
      const uint32_t rsa = sb + OFF_RS + q * 144;
      const uint64_t da2 = make_desc(sb + 2 * ST_BYTES + w * 8192), db2 = make_desc(sb + 2 * ST_BYTES + A_BYTES);
      const uint64_t da3 = make_desc(sb + 3 * ST_BYTES + w * 8192), db3 = make_desc(sb + 3 * ST_BYTES + A_BYTES);
      mbar_wait(BAR(B_FULL + 2), 1);
      CT(64 + 14);
      bar_sync(turn_me, 256);
      wgmma_fence();
#pragma unroll
      for (int kk = 0; kk < 4; kk++) wgmma_n256(acc, da2 + kk * 2, db2 + kk * 2, 1);
      wgmma_commit();
      mbar_wait(BAR(B_FULL + 3), 1);
      CT(64 + 15);
      wgmma_fence();
      wgmma_n256(acc, da3, db3, 1);
      wgmma_n256(acc, da3 + 2, db3 + 2, 1);
      wgmma_commit();
      mbar_wait(BAR(B_STAT), 0);
      tag = SM_(uint32_t, OFF_TAG);
#pragma unroll
      for (int i = 0; i < 8; i++) { const uint4 v = lds128_v(rsa + i * 16); R[8 * i] = v.x; R[8 * i + 2] = v.y; R[8 * i + 4] = v.z; R[8 * i + 6] = v.w; }
      wgmma_wait1();
      release(2);
      wgmma_fence();
      wgmma_n256(acc, da3 + 4, db3 + 4, 1);
      wgmma_n256(acc, da3 + 6, db3 + 6, 1);
      wgmma_n256(acc, make_desc_noswz(sb + OFF_EXA + w * 2048), make_desc_noswz(sb + OFF_EXB), 1);
      wgmma_commit();
      bar_arrive(turn_other, 256);
      kdone(15);
      mbar_wait(BAR(B_STAT), 0);
    }
    fence_acc(acc);
    CT(1);
    auto pack = [&](auto cc) {
      constexpr int c = decltype(cc)::value;
#pragma unroll
      for (int j = 8 * c; j < 8 * c + 8; j++) {
        const uint32_t rs = R[2 * j];
        const float* ac = &acc[4 * j];
        R[2 * j] = bmul2(pack_bf16(ac[0], ac[1]), rs);
        R[2 * j + 1] = bmul2(pack_bf16(ac[2], ac[3]), rs);
      }
    };
    auto put_chunk = [&](auto cc) {
      constexpr int c = decltype(cc)::value;
      const int rho = 16 * wi + (lane & 15);
#pragma unroll
      for (int j = 8 * c; j < 8 * c + 8; j += 2) {
        const int chunk = (j & 7) + (lane >> 4);
        stsm_x4(sb + chunk_off(c, w) + rho * 128 + ((chunk ^ (lane & 7)) << 4), R[2 * j], R[2 * j + 1], R[2 * j + 2], R[2 * j + 3]);
      }
    };
    auto staged = [&](int bar) {
      fence_async_smem();
      __syncwarp();
      if (lane == 0) mbar_arrive(BAR(bar));
    };
    auto mma_rs = [&](auto cc, auto k0, auto k1) {
      constexpr int c = decltype(cc)::value;
      const uint64_t db = make_desc(sb + c * ST_BYTES + A_BYTES);
#pragma unroll
      for (int kk = decltype(k0)::value; kk < decltype(k1)::value; kk++)
        wgmma_n256_rs(acc, R[16 * c + 4 * kk], R[16 * c + 4 * kk + 1], R[16 * c + 4 * kk + 2], R[16 * c + 4 * kk + 3], db + kk * 2, c + kk > 0);
      wgmma_commit();
    };
    auto kdone_x = [&](int k, auto ic) {
      constexpr int i = decltype(ic)::value;
      uint32_t r[8];
#pragma unroll
      for (int z = 0; z < 2; z++) {
        const int tr = 32 * (i & 1) + 16 * z + 8 * (lane >> 4) + (lane & 7), chunk = 2 * wi + ((lane >> 3) & 1);
        ldsm_x4_t(sb + (i >> 1) * ST_BYTES + w * 8192 + tr * 128 + ((chunk ^ (lane & 7)) << 4), r[4 * z], r[4 * z + 1], r[4 * z + 2], r[4 * z + 3]);
      }
      float f[16];
#pragma unroll
      for (int z = 0; z < 8; z++) { f[2 * z] = bf_lo(r[z]); f[2 * z + 1] = bf_hi(r[z]); }
#pragma unroll
      for (int z = 0; z < 16; z++) asm volatile("" : "+f"(f[z]));
      kdone(k);
#pragma unroll
      for (int z = 0; z < 16; z++) asm volatile("add.f32 %0, %0, %1;" : "+f"(acc[16 * i + z]) : "f"(f[z]));
    };
    pack(IC<0>());
    put_chunk(IC<0>());
    staged(w ? B_EPI0B : B_EPI);
    mbar_wait(BAR(B_STAT), 0);
    CT(21);
    pack(IC<1>());
    pack(IC<2>());
    pack(IC<3>());
#pragma unroll
    for (int i = 16; i < 64; i++) asm volatile("" : "+r"(R[i]));
    mbar_wait(BAR(B_FULL + 0), 0);
    CT(2);
    CT(64 + 16);
    bar_sync(turn_me, 256);
    wgmma_fence();
    mma_rs(IC<0>(), IC<0>(), IC<4>());
    mbar_wait(BAR(B_FULL + 1), 0);
    CT(64 + 17);
    wgmma_fence();
    mma_rs(IC<1>(), IC<0>(), IC<2>());
    wgmma_wait1();
    release(0);
    mma_rs(IC<1>(), IC<2>(), IC<4>());
    bar_arrive(turn_other, 256);
    kdone_x(17, IC<0>());
    static_for<2>([&](auto ic) {
      constexpr int c = 2 + decltype(ic)::value;
      mbar_wait(BAR(B_FULL + c), 0);
      CT(64 + 16 + c);
      bar_sync(turn_me, 256);
      wgmma_fence();
      mma_rs(IC<c>(), IC<0>(), IC<4>());
      bar_arrive(turn_other, 256);
      if (c == 2) { put_chunk(IC<1>()); staged(B_EPI + 1); }
      kdone_x(16 + c, IC<c - 1>());
    });
#pragma unroll 1
    for (int k = 20; k < 23; k++) {
      if (w == 1) mbar_wait(BAR(B_A20), 0);
      kstep(k, false, k < 22);
      if (k == 20) {
        kdone_x(k, IC<3>());
      } else {
        if (k == 21) { put_chunk(IC<2>()); if (PUBMODE == 2) fence_async_smem(); } else put_chunk(IC<3>());
        __syncwarp();
        if (lane == 0) mbar_arrive(BAR(B_EPI + k - 19));
        kdone(k);
      }
    }
    uint32_t wf[32][4];
    auto load_wf = [&](auto hc) {
      constexpr int h = decltype(hc)::value;
      const int d = w * 64 + (lane >> 4) * 8 + (lane & 7);
      const uint32_t ad = sb + round_off(h) + (lane & 8) * 1024 + d * 64 + ((wi ^ ((lane >> 1) & 3)) << 4);
#pragma unroll
      for (int i = 0; i < 4; i++) ldsm_x4_t(ad + i * 1024, wf[4 * h + i][0], wf[4 * h + i][1], wf[4 * h + i][2], wf[4 * h + i][3]);
    };
    auto load_wf_rest = [&]() { static_for<8 - NREG_H>([&](auto ic) { load_wf(IC<NREG_H + decltype(ic)::value>()); }); };
#pragma unroll
    for (int i = 0; i < 4 * NREG_H; i++) { wf[i][0] = 0; wf[i][1] = 0; wf[i][2] = 0; wf[i][3] = 0; }
    const int grp = tau * 2 + m;
#pragma unroll 1
    for (int k = 23; k < 46; k++) {
      kstep(k, false);
      if (moe) {
        static_for<NREG_H>([&](auto hc) {
          constexpr int h = decltype(hc)::value;
          if (k == mr_k(h) + 1) { mbar_wait(BAR(B_MR + (h & 1)), (h >> 1) & 1); load_wf(hc); }
        });
      }
      if (k == 43) {
        if (moe) pkt_st128(&p.s->ypart[cid * 256 + tid], 0, 0, 0, 0);
        if (w == 1) pkt_st128(&p.s->hstat[(grp * 8 + eps) * 128 + t], 0, 0, 0, 0);
        if (warp == 0) pkt_st128(&p.s->cand[grp * 256 + eps * 32 + lane], 0, 0, 0, 0);
        if (eps == 0 && warp == 1 && lane < 16) pkt_st128(&p.s->key[((lane >> 1) * 16 + grp) * 2 + (lane & 1)], 0, 0, 0, 0);
      }
      kdone(k);
    }
    asm volatile("barrier.cluster.arrive.relaxed.aligned;" ::: "memory");
    uint32_t wa[16][2];
    uint32_t cd = code_of(tag);
    uint4* hp_pub = &p.s->hstat[(grp * 8 + eps) * 128 + warp * 16 + g];
    const uint4* hp_poll = &p.s->hstat[(grp * 8 + 2 * q) * 128 + warp * 16 + g];
    const uint32_t vec_off = (2 * wi) * 512 + q * 128 + ((g ^ (2 * q)) << 4);
    {
      float as[64], ak[64];
      fence_acc(acc);
#pragma unroll
      for (int i = 0; i < 64; i++) asm volatile("mov.b32 %0, %1;" : "=f"(as[i]) : "f"(acc[64 + i]));
#pragma unroll
      for (int i = 0; i < 64; i++) asm volatile("mov.b32 %0, %1;" : "=f"(ak[i]) : "f"(acc[i]));
      const uint64_t da1 = make_desc(sb + 2 * ST_BYTES + w * 8192), db1 = make_desc(sb + 2 * ST_BYTES + A_BYTES);
      const uint64_t da2 = make_desc(sb + 3 * ST_BYTES + w * 8192), db2 = make_desc(sb + 3 * ST_BYTES + A_BYTES);
      mbar_wait(BAR(B_FULL + 2), 1);
      CT(64 + 46);
      mbar_wait(BAR(B_FULL + 3), 1);
      CT(64 + 47);
      bar_sync(turn_me, 256);
      wgmma_fence();
#pragma unroll
      for (int kk = 0; kk < 4; kk++) wgmma_n128(as, da1 + kk * 2, db1 + 1024 + kk * 2);
#pragma unroll
      for (int kk = 0; kk < 4; kk++) wgmma_n128(as, da2 + kk * 2, db2 + 1024 + kk * 2);
      wgmma_commit();
      bar_arrive(turn_other, 256);
      const uint32_t rx = mapa(sb + OFF_PEER + w * 4096 + vec_off, 1 - m), rb = mapa(BAR(B_XCH), 1 - m);
      asm volatile("barrier.cluster.wait.aligned;" ::: "memory");
      wgmma_wait0();
      fence_acc64(as);
      auto keep = [&]() {
        bar_sync(turn_me, 256);
        wgmma_fence();
#pragma unroll
        for (int kk = 0; kk < 4; kk++) wgmma_n128(ak, da1 + kk * 2, db1 + kk * 2);
        wgmma_commit();
#pragma unroll
        for (int kk = 0; kk < 4; kk++) wgmma_n128(ak, da2 + kk * 2, db2 + kk * 2);
        wgmma_commit();
        if (w == 0) bar_arrive(turn_other, 256);
      };
      keep();
#pragma unroll
      for (int i = 0; i < 8; i++) {
        const float* ac = &as[16 * (i >> 1) + 2 * (i & 1)];
        st_async_v4(rx + (i >> 1) * 8192 + (i & 1) * 512, rb, pack_bf16(ac[0], ac[1]), pack_bf16(ac[4], ac[5]), pack_bf16(ac[8], ac[9]), pack_bf16(ac[12], ac[13]));
      }
#pragma unroll
      for (int i = 0; i < 4; i++) {
        const uint4 v = lds128_v(sb + OFF_WR + q * 80 + i * 16);
        const uint32_t vv[4] = {v.x, v.y, v.z, v.w};
#pragma unroll
        for (int z = 0; z < 4; z++) {
          asm volatile("{\n.reg .pred p;\nsetp.ne.b32 p, %2, 0;\nselp.b32 %0, %1, 0x3F803F80, p;\n}" : "=r"(wa[4 * i + z][0]) : "r"(vv[z]), "r"(g & 1));
          asm volatile("{\n.reg .pred p;\nsetp.ne.b32 p, %2, 0;\nselp.b32 %0, %1, 0x3F803F80, p;\n}" : "=r"(wa[4 * i + z][1]) : "r"(vv[z]), "r"(g & 1));
        }
      }
      pin(cd); pin(hp_pub); pin(hp_poll);
      wgmma_wait1();
      release(2);
      wgmma_wait0();
      fence_acc64(ak);
      CT(3);
#pragma unroll
      for (int i = 0; i < 8; i++) {
        const float* ac = &ak[16 * (i >> 1) + 2 * (i & 1)];
        sts128(sb + (2 + (i >> 2)) * ST_BYTES + w * 8192 + ((i >> 1) & 1) * 4096 + (i & 1) * 512 + vec_off,
               pack_bf16(ac[0], ac[1]), pack_bf16(ac[4], ac[5]), pack_bf16(ac[8], ac[9]), pack_bf16(ac[12], ac[13]));
      }
    }
    uint32_t h[8][4];
    {
      const int qq = 2 * (warp & 1) + ((lane >> 3) & 1);
      const uint32_t lo = (lane >> 4) * 512 + qq * 128 + (((lane & 7) ^ (2 * qq)) << 4);
      bar_sync(NB_BOTH, 256);
#pragma unroll
      for (int ks = 0; ks < 8; ks++)
        ldsm_x4_t(sb + (2 + w) * ST_BYTES + (ks >> 2) * 8192 + (wi >> 1) * 4096 + (ks & 3) * 1024 + lo, h[ks][0], h[ks][1], h[ks][2], h[ks][3]);
      mbar_wait_cluster(BAR(B_XCH), 0);
      CT(4);
      uint32_t r[8][4];
#pragma unroll
      for (int ks = 0; ks < 8; ks++) ldsm_x4_t(sb + OFF_PEER + (warp >> 1) * 8192 + ks * 1024 + lo, r[ks][0], r[ks][1], r[ks][2], r[ks][3]);
      float d[4][4] = {};
#pragma unroll
      for (int ks = 0; ks < 8; ks++) {
#pragma unroll
        for (int i = 0; i < 4; i++) {
          h[ks][i] = badd2(h[ks][i], r[ks][i]);
          mma1688(d[i], h[ks][i], wa[2 * ks + (i >> 1)][i & 1], h[ks][i]);
        }
      }
#pragma unroll
      for (int i = 0; i < 2; i++) {
        const float sq = (g & 1) ? d[i][1] + d[i + 2][1] : d[i][0] + d[i + 2][0];
        const float e0 = d[i][2] + d[i + 2][2], e1 = d[i][3] + d[i + 2][3];
        const float other = __shfl_xor_sync(0xffffffffu, (g & 1) ? e0 : e1, 4);
        if (q == (g >> 1)) pkt_st128(hp_pub + 8 * i, with_bit((g & 1) ? other : e0, cd), with_bit(sq, cd >> 1), __float_as_uint((g & 1) ? e1 : other), tag);
      }
    }
    CT(5);
    if (tid == 0) mbar_arrive(BAR(B_KEY));
    delay_clk<HOP1_DELAY>();
    float m_bf, sd, inv_sd, r_bf;
    uint4* key_pub = &p.s->key[((lane & 7) * 16 + grp) * 2];
    uint4* cand_pub = &p.s->cand[grp * 256 + eps * 32 + q];
    uint32_t trow_inv = 0xFFFFu - (uint32_t)(grp * 128 + 32 * (warp >> 1) + 8 * (g >> 1) + 4 * (warp & 1) + (q & 2) + (g & 1));
    {
      uint4 u[4];
#pragma unroll
      for (int i = 0; i < 4; i++) u[i] = pkt_ld128(hp_poll + (i & 1) * 128 + (i >> 1) * 8);
      const float wsum = SM_(float, OFF_WSUM);
      pin(key_pub); pin(cand_pub); pin(trow_inv);
      uint32_t n = 0;
      while (true) {
        bool ok[4];
#pragma unroll
        for (int i = 0; i < 4; i++) ok[i] = u[i].w == tag && pair_code(u[i].x, u[i].y) == cd;
        const bool all = __all_sync(0xffffffffu, ok[0] && ok[1] && ok[2] && ok[3]);
        if (all || ++n > SPIN_LIMIT) break;
#pragma unroll
        for (int i = 0; i < 4; i++) pkt_ld128_if(u[i], hp_poll + (i & 1) * 128 + (i >> 1) * 8, !ok[i]);
      }
      CT(6);
      float a[3], b[3];
      a[0] = __uint_as_float(u[0].x & ~1u) + __uint_as_float(u[1].x & ~1u); b[0] = __uint_as_float(u[2].x & ~1u) + __uint_as_float(u[3].x & ~1u);
      a[1] = __uint_as_float(u[0].y & ~1u) + __uint_as_float(u[1].y & ~1u); b[1] = __uint_as_float(u[2].y & ~1u) + __uint_as_float(u[3].y & ~1u);
      a[2] = __uint_as_float(u[0].z) + __uint_as_float(u[1].z); b[2] = __uint_as_float(u[2].z) + __uint_as_float(u[3].z);
#pragma unroll
      for (int i = 0; i < 3; i++) {
        a[i] = ((q & 2) ? b[i] : a[i]) + __shfl_xor_sync(0xffffffffu, (q & 2) ? a[i] : b[i], 2);
        a[i] += __shfl_xor_sync(0xffffffffu, a[i], 1);
      }
      const float mu = a[0] * (1.f / 1024.f);
      m_bf = bf16r(mu);
      sd = ln_sd(a[1] * (1.f / 1024.f) - mu * mu);
      inv_sd = rcp_fast(sd);
      r_bf = bf16r((a[2] - m_bf * wsum) * inv_sd);
    }
    {
      const uint32_t u = __float_as_uint(r_bf);
      const uint32_t ord = (u & 0x80000000u) ? ~u : (u | 0x80000000u);
      const uint32_t key = (ord & 0xFFFF0000u) | trow_inv;
      const uint32_t wk = __reduce_max_sync(0xffffffffu, key);
      if (key == wk) SM_(uint2, OFF_WKEY + warp * 8) = make_uint2(wk, (__float_as_uint(m_bf) >> 16) | __float_as_uint(sd));
      const uint32_t wmask = __ballot_sync(0xffffffffu, key == wk);
      const bool hi = (wmask & 0xCCCCCCCCu) != 0;
      uint32_t c[16];
#pragma unroll
      for (int ks = 0; ks < 8; ks++) { c[2 * ks] = hi ? h[ks][1] : h[ks][0]; c[2 * ks + 1] = hi ? h[ks][3] : h[ks][2]; }
      bar_sync(NB_BOTH, 256);
      const uint2 km = SM_(uint2, OFF_WKEY + (lane & 7) * 8);
      const uint32_t bk = __reduce_max_sync(0xffffffffu, km.x);
      if (wk == bk) {
        if ((wmask >> (lane & 28)) & 15) {
#pragma unroll
          for (int ks = 0; ks < 8; ks++) pkt_st128(cand_pub + ks * 4, c[2 * ks], tag, c[2 * ks + 1], tag);
        }
      } else if (eps == 0) {
        const uint32_t kx = __shfl_sync(0xffffffffu, km.x, warp ^ 1), ms = __shfl_sync(0xffffffffu, km.y, warp ^ 1);
        if (kx == bk && lane < 8) pkt_st128(key_pub, bk, tag, ms, tag);
      }
      CT(7);
    }
    {
      const float ih = bf16r(inv_sd);
      const uint32_t nm = pack_bf16(-m_bf, -m_bf), iv = pack_bf16(ih, inv_sd - ih);
      const uint32_t nm_o = __shfl_xor_sync(0xffffffffu, nm, 2), iv_o = __shfl_xor_sync(0xffffffffu, iv, 2);
      const uint32_t nm2[2] = {(q & 2) ? nm_o : nm, (q & 2) ? nm : nm_o}, iv2[2] = {(q & 2) ? iv_o : iv, (q & 2) ? iv : iv_o};
      const uint32_t hi2[2] = {__byte_perm(iv2[0], 0, 0x1010), __byte_perm(iv2[1], 0, 0x1010)}, lo2[2] = {__byte_perm(iv2[0], 0, 0x3232), __byte_perm(iv2[1], 0, 0x3232)};
      const uint32_t oa = sb + OFF_OUT + (warp * 16 + (lane & 15)) * 128;
#pragma unroll
      for (int ks = 0; ks < 8; ks++) {
        uint32_t o[4];
#pragma unroll
        for (int i = 0; i < 4; i++) {
          const uint32_t dd = badd2(h[ks][i], nm2[i & 1]);
          o[i] = badd2(h[ks][i], bfma2(dd, hi2[i & 1], bmul2(dd, lo2[i & 1])));
        }
        stsm_x4(oa + (ks >> 2) * 16384 + (((2 * (ks & 3) + (lane >> 4)) ^ (lane & 7)) << 4), o[0], o[1], o[2], o[3]);
      }
      staged(B_OUT);
    }
    CT(8);
    uint32_t df[16][4];
    auto load_df = [&]() {
      const int frow = (lane & 7) + ((lane >> 4) << 3), hi = (lane >> 3) & 1;
      const uint32_t base = sb + down_off(warp >> 1) + (warp & 1) * 8192 + frow * 128;
#pragma unroll
      for (int mt = 0; mt < 8; mt++) {
#pragma unroll
        for (int ks = 0; ks < 2; ks++)
          ldsm_x4_t(base + (mt >> 2) * 4096 + ks * 2048 + (((2 * (mt & 3) + hi) ^ (lane & 7)) << 4),
                    df[2 * mt + ks][0], df[2 * mt + ks][1], df[2 * mt + ks][2], df[2 * mt + ks][3]);
      }
    };
    if (moe) {
      mbar_wait(BAR(B_GU), 0);
      load_wf_rest();
      mbar_wait(BAR(B_DN), 0);
      load_df();
    }
    uint4* y_pub = &p.s->ypart[cid * 256 + tid];
    uint32_t xs_ad = sb + OFF_XSEL + (8 * (g >> 2) + 4 * w + (g & 3)) * 32 + q * 8, gp_ad = sb + OFF_GP + (wi * 8 + g) * 32 + w * 16 + q * 4;
    pin(y_pub); pin(xs_ad); pin(gp_ad);
    mbar_wait(BAR(B_XS), 0);
    CT(9);
    if (moe) {
      float gd[8][4] = {};
      uint2 bx[4];
#pragma unroll
      for (int r = 0; r < 4; r++) bx[r] = smem_at<uint2>(xs_ad + r * 512);
#pragma unroll
      for (int r = 0; r < 4; r++) {
#pragma unroll
        for (int i = 0; i < 8; i++) mma16816(gd[i], wf[8 * r + i][0], wf[8 * r + i][1], wf[8 * r + i][2], wf[8 * r + i][3], bx[r].x, bx[r].y);
      }
      const float gs = sel4(q, gd[0][0] + gd[1][1], gd[2][0] + gd[3][1], gd[4][0] + gd[5][1], gd[6][0] + gd[7][1]);
      const float us = sel4(q, gd[0][2] + gd[1][3], gd[2][2] + gd[3][3], gd[4][2] + gd[5][3], gd[6][2] + gd[7][3]);
      float v = ((q & 2) ? us : gs) + __shfl_xor_sync(0xffffffffu, (q & 2) ? gs : us, 2);
      smem_at<float>(gp_ad) = v;
      CT(10);
      bar_sync(NB_BOTH, 256);
      uint32_t bq[4];
      {
        const float4 p0 = SM_(float4, OFF_GP + lane * 32), p1 = SM_(float4, OFF_GP + lane * 32 + 16);
        const float gt = bf16r((p0.x + p0.y) + (p1.x + p1.y)), up = bf16r((p0.z + p0.w) + (p1.z + p1.w));
        const float act = bf16r(gt * sigmoid_fast(gt)) * up;
        const uint32_t pr = pack_bf16(act, __shfl_down_sync(0xffffffffu, act, 1));
#pragma unroll
        for (int i = 0; i < 4; i++) bq[i] = __shfl_sync(0xffffffffu, pr, 8 * i + 2 * q);
      }
      CT(11);
      float yd[8][4] = {};
#pragma unroll
      for (int ks = 0; ks < 2; ks++) {
#pragma unroll
        for (int mt = 0; mt < 8; mt++) mma16816(yd[mt], df[2 * mt + ks][0], df[2 * mt + ks][1], df[2 * mt + ks][2], df[2 * mt + ks][3], bq[2 * ks], bq[2 * ks + 1]);
      }
      pkt_st128(y_pub, with_bit(sel4(q, yd[0][0], yd[2][0], yd[4][0], yd[6][0]), cd), with_bit(sel4(q, yd[0][2], yd[2][2], yd[4][2], yd[6][2]), cd >> 1),
                with_bit(sel4(q, yd[1][0], yd[3][0], yd[5][0], yd[7][0]), cd), with_bit(sel4(q, yd[1][2], yd[3][2], yd[5][2], yd[7][2]), cd >> 1));
    } else {
      const long long tw = clock64();
      while (clock64() - tw < IDLE_WAIT_CLK) __nanosleep(100);
    }
    CT(12);
    const uint32_t kv = SM_(uint32_t, OFF_KV);
    const int tsel = 0xFFFF - (int)(kv & 0xFFFFu);
    const float r_sel = __uint_as_float((kv & 0x80000000u) ? (kv & 0x7FFF0000u) : (~kv & 0xFFFF0000u));
    const float sig = bf16r(sigmoid_fast(r_sel));
    const int pfin = 2 * cid + (tid & 1);
    const int col_fin = (pfin >> 5) * 128 + (pfin & 3) * 32 + ((pfin & 31) >> 2) + 8 * ((tid >> 1) & 3);
    const int sel_off = (col_fin >> 4) * 32 + ((col_fin & 7) >> 1) * 8 + ((col_fin >> 3) & 1) * 4 + (col_fin & 1) * 2;
    const float hn_fin = __uint_as_float((uint32_t)SM_(uint16_t, OFF_XSEL + sel_off) << 16), h_fin = __uint_as_float((uint32_t)SM_(uint16_t, OFF_HSEL + sel_off) << 16);
    bf16* out_fin = p.out + (size_t)tsel * 1024 + col_fin;
    {
      const uint4* src = &p.s->ypart[(16 + (tid >> 1)) * 256 + pfin];
      pin(src); pin(out_fin);
      uint4 v = make_uint4(0, 0, 0, 0);
      if (warp < 7) {
        delay_clk<HOP3_DELAY>();
        uint32_t n = 0;
        bool ok = false;
        do {
          pkt_ld128_if(v, src, !ok);
          ok = pair_code(v.x, v.y) == cd && pair_code(v.z, v.w) == cd;
        } while (!__all_sync(0xffffffffu, ok) && ++n < SPIN_LIMIT);
      }
      CT(13);
      const float y0 = __uint_as_float(v.x & ~1u), y1 = __uint_as_float(v.y & ~1u), y2 = __uint_as_float(v.z & ~1u), y3 = __uint_as_float(v.w & ~1u);
      const float a0 = ((lane & 2) ? y1 : y0) + __shfl_xor_sync(0xffffffffu, (lane & 2) ? y0 : y1, 2);
      const float a1 = ((lane & 2) ? y3 : y2) + __shfl_xor_sync(0xffffffffu, (lane & 2) ? y2 : y3, 2);
      float b = ((lane & 4) ? a1 : a0) + __shfl_xor_sync(0xffffffffu, (lane & 4) ? a0 : a1, 4);
      b += __shfl_xor_sync(0xffffffffu, b, 8);
      b += __shfl_xor_sync(0xffffffffu, b, 16);
      if (lane < 8) SM_(float, OFF_FIN + lane * 32 + warp * 4) = b;
    }
    bar_sync(NB_BOTH, 256);
    if (tid < 8) {
      const float4 y0 = SM_(float4, OFF_FIN + tid * 32), y1 = SM_(float4, OFF_FIN + tid * 32 + 16);
      const float y = ((y0.x + y0.y) + (y0.z + y0.w)) + ((y1.x + y1.y) + y1.z);
      *out_fin = __float2bfloat16_rn(h_fin + bf16r(hn_fin + bf16r(bf16r(y) * sig)));
      if (cid == 0 && tid == 0) st_relaxed32(&p.s->epoch, tag);
    }
    CT(14);
  }
}

__global__ void __launch_bounds__(384, 1) occupancy_probe_kernel() {}

typedef CUresult (*EncodeFn)(CUtensorMap*, CUtensorMapDataType, cuuint32_t, void*, const cuuint64_t*, const cuuint64_t*, const cuuint32_t*, const cuuint32_t*,
                             CUtensorMapInterleave, CUtensorMapSwizzle, CUtensorMapL2promotion, CUtensorMapFloatOOBfill);

static void make_tm(EncodeFn enc, CUtensorMap* tm, const void* ptr, uint64_t rows, uint64_t cols, uint32_t brows, uint32_t bcols, CUtensorMapSwizzle sw,
                    CUtensorMapL2promotion promo = CU_TENSOR_MAP_L2_PROMOTION_L2_256B) {
  cuuint64_t dims[2] = {cols, rows};
  cuuint64_t strides[1] = {cols * 2};
  cuuint32_t box[2] = {bcols, brows};
  cuuint32_t es[2] = {1, 1};
  enc(tm, CU_TENSOR_MAP_DATA_TYPE_BFLOAT16, 2, const_cast<void*>(ptr), dims, strides, box, es, CU_TENSOR_MAP_INTERLEAVE_NONE, sw,
      promo, CU_TENSOR_MAP_FLOAT_OOB_FILL_NONE);
}

extern "C" void kernel_launch(void* const* d_in, const int* in_sizes, int n_in, void* d_out, int out_size) {
  (void)in_sizes; (void)n_in; (void)out_size;
  static EncodeFn enc = nullptr;
  static void* abT = nullptr;
  static int map = 0;
  if (!enc) {
    void* fn = nullptr; cudaDriverEntryPointQueryResult st;
    cudaGetDriverEntryPoint("cuTensorMapEncodeTiled", &fn, cudaEnableDefault, &st);
    enc = (EncodeFn)fn;
    cudaGetSymbolAddress(&abT, g_scratch);
    cudaFuncSetAttribute(fnet_moe_kernel<0>, cudaFuncAttributeMaxDynamicSharedMemorySize, SMEM_TOTAL);
    cudaFuncSetAttribute(fnet_moe_kernel<1>, cudaFuncAttributeMaxDynamicSharedMemorySize, SMEM_TOTAL);
    cudaFuncSetAttribute(occupancy_probe_kernel, cudaFuncAttributeMaxDynamicSharedMemorySize, SMEM_TOTAL);
    cudaFuncSetAttribute(occupancy_probe_kernel, cudaFuncAttributeNonPortableClusterSizeAllowed, 1);
    auto max_clusters = [&](int size) {
      cudaLaunchConfig_t cfg = {};
      cfg.gridDim = dim3(128); cfg.blockDim = dim3(384); cfg.dynamicSmemBytes = SMEM_TOTAL;
      cudaLaunchAttribute at[1];
      at[0].id = cudaLaunchAttributeClusterDimension; at[0].val.clusterDim.x = size; at[0].val.clusterDim.y = 1; at[0].val.clusterDim.z = 1;
      cfg.attrs = at; cfg.numAttrs = 1;
      int ncl = 0;
      return cudaOccupancyMaxActiveClusters(&ncl, occupancy_probe_kernel, &cfg) == cudaSuccess ? ncl : 0;
    };
    int dev = 0, sms = 0;
    cudaGetDevice(&dev);
    cudaDeviceGetAttribute(&sms, cudaDevAttrMultiProcessorCount, dev);
    map = (!getenv("MAP1") && sms == 132 && max_clusters(2) == 66 && max_clusters(16) == 7) ? 0 : 1;
    (void)cudaGetLastError();
  }
  Params p;
  const bf16* x = (const bf16*)d_in[0];
  make_tm(enc, &p.tmD0, d_in[3], 1024, 1024, 128, 64, CU_TENSOR_MAP_SWIZZLE_128B);
  make_tm(enc, &p.tmD1, d_in[4], 1024, 1024, 128, 64, CU_TENSOR_MAP_SWIZZLE_128B);
  make_tm(enc, &p.tmX, x, 2048, 1024, 256, 64, CU_TENSOR_MAP_SWIZZLE_128B);
  make_tm(enc, &p.tmXr, x, 2048, 1024, 64, 64, CU_TENSOR_MAP_SWIZZLE_128B);
  make_tm(enc, &p.tmAbS, abT, 2048, 2048, 64, 64, CU_TENSOR_MAP_SWIZZLE_128B);
  make_tm(enc, &p.tmAbL, abT, 2048, 2048, 128, 64, CU_TENSOR_MAP_SWIZZLE_128B);
  make_tm(enc, &p.tmW0, d_in[1], 2048, 2048, 128, 64, CU_TENSOR_MAP_SWIZZLE_128B, W_PROMO);
  make_tm(enc, &p.tmW1, d_in[2], 2048, 2048, 128, 64, CU_TENSOR_MAP_SWIZZLE_128B, W_PROMO);
  {
    cuuint64_t dims[5] = {1024, 2, 4, 4, 64};
    cuuint64_t strides[4] = {2048, 8 * 2048, 2 * 2048, 32 * 2048};
    cuuint32_t box[5] = {64, 2, 4, 2, 1};
    cuuint32_t es[5] = {1, 1, 1, 1, 1};
    enc(&p.tmOut, CU_TENSOR_MAP_DATA_TYPE_BFLOAT16, 5, d_out, dims, strides, box, es, CU_TENSOR_MAP_INTERLEAVE_NONE, CU_TENSOR_MAP_SWIZZLE_128B,
        CU_TENSOR_MAP_L2_PROMOTION_NONE, CU_TENSOR_MAP_FLOAT_OOB_FILL_NONE);
  }
  make_tm(enc, &p.tmG, d_in[7], 1024, 3584, 128, 32, CU_TENSOR_MAP_SWIZZLE_64B, CU_TENSOR_MAP_L2_PROMOTION_L2_128B);
  make_tm(enc, &p.tmU, d_in[8], 1024, 3584, 128, 32, CU_TENSOR_MAP_SWIZZLE_64B, CU_TENSOR_MAP_L2_PROMOTION_L2_128B);
  make_tm(enc, &p.tmDn, d_in[9], 3584, 1024, 32, 64, CU_TENSOR_MAP_SWIZZLE_128B);
  p.x = x; p.Dre = (const bf16*)d_in[3]; p.Dim = (const bf16*)d_in[4];
  p.wr = (const bf16*)d_in[6]; p.wdown = (const bf16*)d_in[9]; p.wgate = (const bf16*)d_in[7]; p.wup = (const bf16*)d_in[8];
  p.out = (bf16*)d_out; p.s = (Scratch*)abT;
  if (map == 1) fnet_moe_kernel<1><<<128, 384, SMEM_TOTAL>>>(p);
  else fnet_moe_kernel<0><<<132, 384, SMEM_TOTAL>>>(p);
}
```

```cpp
#include <cuda.h>
#include <cuda_runtime.h>
#include <cuda_bf16.h>
#include <stdint.h>
#include <stdlib.h>
#include <type_traits>

typedef __nv_bfloat16 bf16;

#define REG_C 232
#define REG_P 40
__device__ __forceinline__ int kblock(int tau, int j) {
  int i = j - 4;
  if (i >= 19 && i < 23) i += i < 21 ? 2 : -2;
  const int c = (i * 37) >> 8;
  return j < 4 ? tau * 4 + j : ((tau + 1 + i - 7 * c) & 7) * 4 + c;
}
#define HOP1_DELAY 150
#define HOP3_DELAY 300
#define SPEC_MIN 10
#define PF_K0 8
#define PF_N0 2
#define PF_K1 24
#define OUT_PACE_CLK 100
#define WPF_K0 12
#define WPF_J0 0
#define WPF_J1 10
#define PUBMODE 0
#define MR_P 6
#define SEND_FIRST 2
#define RESET_K 39
#define PUB_K1 22
#define NREG_H 5
#define MR_K0 29
__host__ __device__ constexpr int mr_k(int h) { return MR_K0 + MR_P * (h >> 1) + 2 * (h & 1); }
constexpr int A_BYTES = 128 * 64 * 2;
constexpr int B_BYTES = 256 * 64 * 2;
constexpr int ST_BYTES = A_BYTES + B_BYTES;
constexpr int OFF_XCH = 4 * ST_BYTES;
constexpr int OFF_BAR = OFF_XCH + 32768;
constexpr int OFF_WR = OFF_BAR + 384;
constexpr int OFF_RS = OFF_WR + 384;
constexpr int OFF_PUB = OFF_RS + 640;
constexpr int OFF_MISC = OFF_PUB + 768;
constexpr int SMEM_TOTAL = OFF_MISC + 256;
constexpr int OFF_WSUM = OFF_MISC, OFF_TAG = OFF_MISC + 4;
constexpr int OFF_SEEN = OFF_MISC + 8;
constexpr int OFF_KV = OFF_MISC + 12;
constexpr int OFF_WKEY = OFF_MISC + 32;
constexpr int OFF_EXA = OFF_XCH;
constexpr int OFF_EXB = OFF_XCH + 4096;
__host__ __device__ constexpr int chunk_off(int c, int w) { return (c < 2 ? (c + 2) * ST_BYTES : OFF_XCH + (c - 2) * 16384) + w * 8192; }
__host__ __device__ constexpr int late_off(int i) { return i < 4 ? i * 16384 : 2 * ST_BYTES + A_BYTES + (i - 4) * 16384; }
__host__ __device__ constexpr int round_off(int h) { return h < NREG_H + 2 ? OFF_XCH + (h & 1) * 16384 : late_off(h - NREG_H - 2); }
__host__ __device__ constexpr int down_off(int i) { return late_off(6 - NREG_H + i); }
constexpr int OFF_PEER = ST_BYTES + A_BYTES;
constexpr int OFF_OUT = 3 * ST_BYTES + A_BYTES;
constexpr int OFF_XSEL = OFF_PEER;
constexpr int OFF_HSEL = OFF_PEER + 4096;
constexpr int OFF_GP = OFF_PEER + 8192;
constexpr int OFF_FIN = OFF_PEER + 9216;
__device__ __forceinline__ int slot_of(int k) { return k & 3; }
__device__ __forceinline__ int use_of(int k) { return k >> 2; }
enum { B_FULL = 0, B_EMPTY = 4, B_EPI = 8, B_STD = 12, B_EPI0B = 16, B_LATE = 17, B_STAT = 18, B_XCH = 19, B_MR = 20  , B_GU = 22,
       B_DN = 23, B_AUX = 24  , B_OUT = 26, B_KEY = 27, B_XS = 28, B_A20 = 29, B_STDA = 30, B_COUNT = 31 };
enum { NB_TURN0 = 1, NB_TURN1 = 2, NB_BOTH = 5, NB_AUX = 6 };

struct Scratch {
  bf16 abT[2048 * 2048];
  uint2 xstat[2048];
  uint2 dsum[2048];
  uint4 abflag[16 * 8 * 2];
  uint4 hstat[16 * 8 * 128];
  uint4 cand[16 * 256];
  uint4 key[8 * 16 * 2];
  uint4 ypart[128 * 256];
  uint32_t epoch;
};
__device__ __align__(1024) Scratch g_scratch;

struct Params {
  Scratch* s; bf16* out;
  const bf16* x; const bf16* Dre; const bf16* Dim; const bf16* wr; const bf16* wdown; const bf16* wgate; const bf16* wup;
  CUtensorMap tmX, tmD0, tmD1, tmXr, tmAbS, tmAbL, tmW0, tmW1, tmOut, tmG, tmU, tmDn;
};

#define SPIN_LIMIT (1u << 14)
#define MBAR_LIMIT (1u << 10)
#define GATHER_NS 400
#define W_PROMO CU_TENSOR_MAP_L2_PROMOTION_L2_128B
#define MOE_PACE_CLK 300
constexpr int IDLE_WAIT_CLK = 1200;
__device__ __forceinline__ uint32_t smem_u32(const void* p) { return (uint32_t)__cvta_generic_to_shared(p); }
__device__ __forceinline__ void mbar_init(uint32_t bar, uint32_t cnt) { asm volatile("mbarrier.init.shared::cta.b64 [%0], %1;" :: "r"(bar), "r"(cnt) : "memory"); }
__device__ __forceinline__ void mbar_expect_tx(uint32_t bar, uint32_t bytes) { asm volatile("mbarrier.arrive.expect_tx.shared::cta.b64 _, [%0], %1;" :: "r"(bar), "r"(bytes) : "memory"); }
__device__ __forceinline__ void mbar_arrive(uint32_t bar) { asm volatile("mbarrier.arrive.shared::cta.b64 _, [%0];" :: "r"(bar) : "memory"); }
__device__ __forceinline__ void mbar_wait(uint32_t bar, uint32_t parity) {
  uint32_t ok, n = 0;
  do {
    asm volatile("{\n.reg .pred p;\nmbarrier.try_wait.parity.shared::cta.b64 p, [%1], %2;\nselp.u32 %0, 1, 0, p;\n}\n" : "=r"(ok) : "r"(bar), "r"(parity) : "memory");
  } while (!ok && ++n < MBAR_LIMIT);
}
__device__ __forceinline__ bool mbar_test(uint32_t bar, uint32_t parity) {
  uint32_t ok;
  asm volatile("{\n.reg .pred p;\nmbarrier.test_wait.parity.shared::cta.b64 p, [%1], %2;\nselp.u32 %0, 1, 0, p;\n}\n" : "=r"(ok) : "r"(bar), "r"(parity) : "memory");
  return ok != 0;
}
__device__ __forceinline__ void mbar_wait_cluster(uint32_t bar, uint32_t parity) {
  uint32_t ok, n = 0;
  do {
    asm volatile("{\n.reg .pred p;\nmbarrier.try_wait.parity.acquire.cluster.shared::cta.b64 p, [%1], %2;\nselp.u32 %0, 1, 0, p;\n}\n" : "=r"(ok) : "r"(bar), "r"(parity) : "memory");
  } while (!ok && ++n < MBAR_LIMIT);
}
__device__ __forceinline__ void tma_load_2d(uint32_t dst, const CUtensorMap* tm, uint32_t bar, int c0, int c1) {
  asm volatile("cp.async.bulk.tensor.2d.shared::cluster.global.mbarrier::complete_tx::bytes [%0], [%1, {%3, %4}], [%2];"
    :: "r"(dst), "l"(tm), "r"(bar), "r"(c0), "r"(c1) : "memory");
}
__device__ __forceinline__ void tma_load_2d_hint(uint32_t dst, const CUtensorMap* tm, uint32_t bar, int c0, int c1, uint64_t pol) {
  asm volatile("cp.async.bulk.tensor.2d.shared::cluster.global.mbarrier::complete_tx::bytes.L2::cache_hint [%0], [%1, {%3, %4}], [%2], %5;"
    :: "r"(dst), "l"(tm), "r"(bar), "r"(c0), "r"(c1), "l"(pol) : "memory");
}
__device__ __forceinline__ uint64_t policy_evict_first() { uint64_t p; asm volatile("createpolicy.fractional.L2::evict_first.b64 %0, 1.0;" : "=l"(p)); return p; }
__device__ __forceinline__ void tma_store_2d(const CUtensorMap* tm, uint32_t src, int c0, int c1) {
  asm volatile("cp.async.bulk.tensor.2d.global.shared::cta.bulk_group [%0, {%2, %3}], [%1];" :: "l"(tm), "r"(src), "r"(c0), "r"(c1) : "memory");
}
__device__ __forceinline__ void bulk_load(uint32_t dst, const void* src, uint32_t bytes, uint32_t bar) {
  asm volatile("cp.async.bulk.shared::cluster.global.mbarrier::complete_tx::bytes [%0], [%1], %2, [%3];" :: "r"(dst), "l"(src), "r"(bytes), "r"(bar) : "memory");
}
__device__ __forceinline__ void bulk_commit() { asm volatile("cp.async.bulk.commit_group;" ::: "memory"); }
__device__ __forceinline__ void bulk_wait_all() { asm volatile("cp.async.bulk.wait_group 0;" ::: "memory"); }
__device__ __forceinline__ void fence_async_smem() { asm volatile("fence.proxy.async.shared::cta;" ::: "memory"); }
__device__ __forceinline__ void wgmma_fence() { asm volatile("wgmma.fence.sync.aligned;" ::: "memory"); }
__device__ __forceinline__ void wgmma_commit() { asm volatile("wgmma.commit_group.sync.aligned;" ::: "memory"); }
__device__ __forceinline__ void wgmma_wait0() { asm volatile("wgmma.wait_group.sync.aligned 0;" ::: "memory"); }
__device__ __forceinline__ void bar_sync(int id, int n) { asm volatile("bar.sync %0, %1;" :: "r"(id), "r"(n) : "memory"); }
__device__ __forceinline__ void bar_arrive(int id, int n) { asm volatile("bar.arrive %0, %1;" :: "r"(id), "r"(n) : "memory"); }
template<int R> __device__ __forceinline__ void reg_inc() { asm volatile("setmaxnreg.inc.sync.aligned.u32 %0;" :: "n"(R)); }
template<int R> __device__ __forceinline__ void reg_dec() { asm volatile("setmaxnreg.dec.sync.aligned.u32 %0;" :: "n"(R)); }
__device__ __forceinline__ bool elect_one() {
  uint32_t p;
  asm volatile("{\n.reg .pred q;\nelect.sync _|q, 0xffffffff;\nselp.u32 %0, 1, 0, q;\n}\n" : "=r"(p));
  return p != 0;
}
__device__ __forceinline__ uint32_t mapa(uint32_t addr, uint32_t cta) { uint32_t r; asm volatile("mapa.shared::cluster.u32 %0, %1, %2;" : "=r"(r) : "r"(addr), "r"(cta)); return r; }
__device__ __forceinline__ void st_async_v4(uint32_t addr, uint32_t bar, uint32_t a, uint32_t b, uint32_t c, uint32_t d) {
  asm volatile("st.async.weak.shared::cluster.mbarrier::complete_tx::bytes.v4.b32 [%0], {%2, %3, %4, %5}, [%1];" :: "r"(addr), "r"(bar), "r"(a), "r"(b), "r"(c), "r"(d) : "memory");
}
__device__ __forceinline__ void stsm_x4(uint32_t addr, uint32_t a, uint32_t b, uint32_t c, uint32_t d) {
  asm volatile("stmatrix.sync.aligned.m8n8.x4.shared.b16 [%0], {%1, %2, %3, %4};" :: "r"(addr), "r"(a), "r"(b), "r"(c), "r"(d));
}
__device__ __forceinline__ uint4 lds128_v(uint32_t addr) { uint4 v; asm volatile("ld.shared.v4.b32 {%0, %1, %2, %3}, [%4];" : "=r"(v.x), "=r"(v.y), "=r"(v.z), "=r"(v.w) : "r"(addr)); return v; }
extern __shared__ __align__(1024) uint8_t smem_raw[];
template<class T> __device__ __forceinline__ T& smem_at(uint32_t addr) { return *reinterpret_cast<T*>(__cvta_shared_to_generic(addr)); }
#define SM_(T, off) smem_at<T>(sb + (off))
__device__ __forceinline__ uint4 ldg_nc128(const void* p) { uint4 v; asm volatile("ld.global.nc.v4.b32 {%0, %1, %2, %3}, [%4];" : "=r"(v.x), "=r"(v.y), "=r"(v.z), "=r"(v.w) : "l"(p)); return v; }
__device__ __forceinline__ void pkt_st128(void* p, uint32_t a, uint32_t b, uint32_t c, uint32_t d) {
  asm volatile("{\n.reg .b128 v;\n.reg .b64 lo, hi;\nmov.b64 lo, {%1, %2};\nmov.b64 hi, {%3, %4};\nmov.b128 v, {lo, hi};\nst.relaxed.gpu.global.b128 [%0], v;\n}\n"
    :: "l"(p), "r"(a), "r"(b), "r"(c), "r"(d) : "memory");
}
__device__ __forceinline__ uint4 pkt_ld128(const void* p) {
  uint4 r;
  asm volatile("{\n.reg .b128 v;\n.reg .b64 lo, hi;\nld.relaxed.gpu.global.b128 v, [%4];\nmov.b128 {lo, hi}, v;\nmov.b64 {%0, %1}, lo;\nmov.b64 {%2, %3}, hi;\n}\n"
    : "=r"(r.x), "=r"(r.y), "=r"(r.z), "=r"(r.w) : "l"(p) : "memory");
  return r;
}
__device__ __forceinline__ void pkt_ld128_if(uint4& r, const void* p, bool cond) {
  asm volatile("{\n.reg .pred q;\nsetp.ne.b32 q, %5, 0;\n@q ld.relaxed.gpu.global.v4.b32 {%0, %1, %2, %3}, [%4];\n}\n"
    : "+r"(r.x), "+r"(r.y), "+r"(r.z), "+r"(r.w) : "l"(p), "r"((uint32_t)cond) : "memory");
}
__device__ __forceinline__ void pkt_st64(void* p, uint32_t a, uint32_t b) {
  asm volatile("{\n.reg .b64 v;\nmov.b64 v, {%1, %2};\nst.relaxed.gpu.global.b64 [%0], v;\n}\n" :: "l"(p), "r"(a), "r"(b) : "memory");
}
__device__ __forceinline__ uint2 pkt_ld64(const void* p) {
  uint2 r;
  asm volatile("{\n.reg .b64 v;\nld.relaxed.gpu.global.b64 v, [%2];\nmov.b64 {%0, %1}, v;\n}\n" : "=r"(r.x), "=r"(r.y) : "l"(p) : "memory");
  return r;
}
__device__ __forceinline__ uint32_t ld_relaxed32(const void* p) { uint32_t v; asm volatile("ld.relaxed.gpu.global.b32 %0, [%1];" : "=r"(v) : "l"(p) : "memory"); return v; }
__device__ __forceinline__ void st_relaxed32(void* p, uint32_t v) { asm volatile("st.relaxed.gpu.global.b32 [%0], %1;" :: "l"(p), "r"(v) : "memory"); }
__device__ __forceinline__ uint32_t code_of(uint32_t tag) { return tag % 3u + 1u; }
__device__ __forceinline__ uint32_t with_bit(float v, uint32_t bit) { return (__float_as_uint(v) & ~1u) | (bit & 1u); }
__device__ __forceinline__ uint32_t pair_code(uint32_t a, uint32_t b) { return (a & 1u) | ((b & 1u) << 1); }
__device__ __forceinline__ uint32_t pack_bf16(float lo, float hi) { uint32_t r; asm("cvt.rn.bf16x2.f32 %0, %1, %2;" : "=r"(r) : "f"(hi), "f"(lo)); return r; }
__device__ __forceinline__ float bf_lo(uint32_t v) { return __uint_as_float(v << 16); }
__device__ __forceinline__ float bf_hi(uint32_t v) { return __uint_as_float(v & 0xFFFF0000u); }
__device__ __forceinline__ float bf16r(float x) { return __uint_as_float(pack_bf16(0.f, x)); }
__device__ __forceinline__ uint32_t badd2(uint32_t a, uint32_t b) { uint32_t r; asm("add.rn.bf16x2 %0, %1, %2;" : "=r"(r) : "r"(a), "r"(b)); return r; }
__device__ __forceinline__ uint32_t bmul2(uint32_t a, uint32_t b) { uint32_t r; asm("mul.rn.bf16x2 %0, %1, %2;" : "=r"(r) : "r"(a), "r"(b)); return r; }
__device__ __forceinline__ float warp_sum(float v) {
#pragma unroll
  for (int o = 16; o > 0; o >>= 1) v += __shfl_xor_sync(0xffffffffu, v, o);
  return v;
}
__device__ __forceinline__ uint64_t make_desc(uint32_t addr) {
  return (uint64_t)((addr & 0x3FFFF) >> 4) | ((uint64_t)1 << 16) | ((uint64_t)64 << 32) | ((uint64_t)1 << 62);
}
__device__ __forceinline__ uint64_t make_desc_noswz(uint32_t addr) {
  return (uint64_t)((addr & 0x3FFFF) >> 4) | ((uint64_t)8 << 16) | ((uint64_t)16 << 32);
}
__device__ __forceinline__ void wgmma_n256(float (&d)[128], uint64_t da, uint64_t db, int scale_d) {
  asm volatile("{\n.reg .pred p;\nsetp.ne.b32 p, %130, 0;\n"
    "wgmma.mma_async.sync.aligned.m64n256k16.f32.bf16.bf16 "
    "{%0, %1, %2, %3, %4, %5, %6, %7, %8, %9, %10, %11, %12, %13, %14, %15, %16, %17, %18, %19, %20, %21, %22, %23, %24, %25, %26, %27, %28, %29, %30, %31, "
    "%32, %33, %34, %35, %36, %37, %38, %39, %40, %41, %42, %43, %44, %45, %46, %47, %48, %49, %50, %51, %52, %53, %54, %55, %56, %57, %58, %59, %60, %61, %62, %63, "
    "%64, %65, %66, %67, %68, %69, %70, %71, %72, %73, %74, %75, %76, %77, %78, %79, %80, %81, %82, %83, %84, %85, %86, %87, %88, %89, %90, %91, %92, %93, %94, %95, "
    "%96, %97, %98, %99, %100, %101, %102, %103, %104, %105, %106, %107, %108, %109, %110, %111, %112, %113, %114, %115, %116, %117, %118, %119, %120, %121, %122, %123, %124, %125, %126, %127}, "
    "%128, %129, p, 1, 1, 0, 0;\n}\n"
    : "+f"(d[0]), "+f"(d[1]), "+f"(d[2]), "+f"(d[3]), "+f"(d[4]), "+f"(d[5]), "+f"(d[6]), "+f"(d[7]),
      "+f"(d[8]), "+f"(d[9]), "+f"(d[10]), "+f"(d[11]), "+f"(d[12]), "+f"(d[13]), "+f"(d[14]), "+f"(d[15]),
      "+f"(d[16]), "+f"(d[17]), "+f"(d[18]), "+f"(d[19]), "+f"(d[20]), "+f"(d[21]), "+f"(d[22]), "+f"(d[23]),
      "+f"(d[24]), "+f"(d[25]), "+f"(d[26]), "+f"(d[27]), "+f"(d[28]), "+f"(d[29]), "+f"(d[30]), "+f"(d[31]),
      "+f"(d[32]), "+f"(d[33]), "+f"(d[34]), "+f"(d[35]), "+f"(d[36]), "+f"(d[37]), "+f"(d[38]), "+f"(d[39]),
      "+f"(d[40]), "+f"(d[41]), "+f"(d[42]), "+f"(d[43]), "+f"(d[44]), "+f"(d[45]), "+f"(d[46]), "+f"(d[47]),
      "+f"(d[48]), "+f"(d[49]), "+f"(d[50]), "+f"(d[51]), "+f"(d[52]), "+f"(d[53]), "+f"(d[54]), "+f"(d[55]),
      "+f"(d[56]), "+f"(d[57]), "+f"(d[58]), "+f"(d[59]), "+f"(d[60]), "+f"(d[61]), "+f"(d[62]), "+f"(d[63]),
      "+f"(d[64]), "+f"(d[65]), "+f"(d[66]), "+f"(d[67]), "+f"(d[68]), "+f"(d[69]), "+f"(d[70]), "+f"(d[71]),
      "+f"(d[72]), "+f"(d[73]), "+f"(d[74]), "+f"(d[75]), "+f"(d[76]), "+f"(d[77]), "+f"(d[78]), "+f"(d[79]),
      "+f"(d[80]), "+f"(d[81]), "+f"(d[82]), "+f"(d[83]), "+f"(d[84]), "+f"(d[85]), "+f"(d[86]), "+f"(d[87]),
      "+f"(d[88]), "+f"(d[89]), "+f"(d[90]), "+f"(d[91]), "+f"(d[92]), "+f"(d[93]), "+f"(d[94]), "+f"(d[95]),
      "+f"(d[96]), "+f"(d[97]), "+f"(d[98]), "+f"(d[99]), "+f"(d[100]), "+f"(d[101]), "+f"(d[102]), "+f"(d[103]),
      "+f"(d[104]), "+f"(d[105]), "+f"(d[106]), "+f"(d[107]), "+f"(d[108]), "+f"(d[109]), "+f"(d[110]), "+f"(d[111]),
      "+f"(d[112]), "+f"(d[113]), "+f"(d[114]), "+f"(d[115]), "+f"(d[116]), "+f"(d[117]), "+f"(d[118]), "+f"(d[119]),
      "+f"(d[120]), "+f"(d[121]), "+f"(d[122]), "+f"(d[123]), "+f"(d[124]), "+f"(d[125]), "+f"(d[126]), "+f"(d[127])
    : "l"(da), "l"(db), "r"(scale_d));
}
__device__ __forceinline__ void wgmma_n256_rs(float (&d)[128], uint32_t a0, uint32_t a1, uint32_t a2, uint32_t a3, uint64_t db, int scale_d) {
  asm volatile("{\n.reg .pred p;\nsetp.ne.b32 p, %133, 0;\n"
    "wgmma.mma_async.sync.aligned.m64n256k16.f32.bf16.bf16 "
    "{%0, %1, %2, %3, %4, %5, %6, %7, %8, %9, %10, %11, %12, %13, %14, %15, %16, %17, %18, %19, %20, %21, %22, %23, %24, %25, %26, %27, %28, %29, %30, %31, "
    "%32, %33, %34, %35, %36, %37, %38, %39, %40, %41, %42, %43, %44, %45, %46, %47, %48, %49, %50, %51, %52, %53, %54, %55, %56, %57, %58, %59, %60, %61, %62, %63, "
    "%64, %65, %66, %67, %68, %69, %70, %71, %72, %73, %74, %75, %76, %77, %78, %79, %80, %81, %82, %83, %84, %85, %86, %87, %88, %89, %90, %91, %92, %93, %94, %95, "
    "%96, %97, %98, %99, %100, %101, %102, %103, %104, %105, %106, %107, %108, %109, %110, %111, %112, %113, %114, %115, %116, %117, %118, %119, %120, %121, %122, %123, %124, %125, %126, %127}, "
    "{%128, %129, %130, %131}, %132, p, 1, 1, 0;\n}\n"
    : "+f"(d[0]), "+f"(d[1]), "+f"(d[2]), "+f"(d[3]), "+f"(d[4]), "+f"(d[5]), "+f"(d[6]), "+f"(d[7]),
      "+f"(d[8]), "+f"(d[9]), "+f"(d[10]), "+f"(d[11]), "+f"(d[12]), "+f"(d[13]), "+f"(d[14]), "+f"(d[15]),
      "+f"(d[16]), "+f"(d[17]), "+f"(d[18]), "+f"(d[19]), "+f"(d[20]), "+f"(d[21]), "+f"(d[22]), "+f"(d[23]),
      "+f"(d[24]), "+f"(d[25]), "+f"(d[26]), "+f"(d[27]), "+f"(d[28]), "+f"(d[29]), "+f"(d[30]), "+f"(d[31]),
      "+f"(d[32]), "+f"(d[33]), "+f"(d[34]), "+f"(d[35]), "+f"(d[36]), "+f"(d[37]), "+f"(d[38]), "+f"(d[39]),
      "+f"(d[40]), "+f"(d[41]), "+f"(d[42]), "+f"(d[43]), "+f"(d[44]), "+f"(d[45]), "+f"(d[46]), "+f"(d[47]),
      "+f"(d[48]), "+f"(d[49]), "+f"(d[50]), "+f"(d[51]), "+f"(d[52]), "+f"(d[53]), "+f"(d[54]), "+f"(d[55]),
      "+f"(d[56]), "+f"(d[57]), "+f"(d[58]), "+f"(d[59]), "+f"(d[60]), "+f"(d[61]), "+f"(d[62]), "+f"(d[63]),
      "+f"(d[64]), "+f"(d[65]), "+f"(d[66]), "+f"(d[67]), "+f"(d[68]), "+f"(d[69]), "+f"(d[70]), "+f"(d[71]),
      "+f"(d[72]), "+f"(d[73]), "+f"(d[74]), "+f"(d[75]), "+f"(d[76]), "+f"(d[77]), "+f"(d[78]), "+f"(d[79]),
      "+f"(d[80]), "+f"(d[81]), "+f"(d[82]), "+f"(d[83]), "+f"(d[84]), "+f"(d[85]), "+f"(d[86]), "+f"(d[87]),
      "+f"(d[88]), "+f"(d[89]), "+f"(d[90]), "+f"(d[91]), "+f"(d[92]), "+f"(d[93]), "+f"(d[94]), "+f"(d[95]),
      "+f"(d[96]), "+f"(d[97]), "+f"(d[98]), "+f"(d[99]), "+f"(d[100]), "+f"(d[101]), "+f"(d[102]), "+f"(d[103]),
      "+f"(d[104]), "+f"(d[105]), "+f"(d[106]), "+f"(d[107]), "+f"(d[108]), "+f"(d[109]), "+f"(d[110]), "+f"(d[111]),
      "+f"(d[112]), "+f"(d[113]), "+f"(d[114]), "+f"(d[115]), "+f"(d[116]), "+f"(d[117]), "+f"(d[118]), "+f"(d[119]),
      "+f"(d[120]), "+f"(d[121]), "+f"(d[122]), "+f"(d[123]), "+f"(d[124]), "+f"(d[125]), "+f"(d[126]), "+f"(d[127])
    : "r"(a0), "r"(a1), "r"(a2), "r"(a3), "l"(db), "r"(scale_d));
}
__device__ __forceinline__ void wgmma_n128(float (&d)[64], uint64_t da, uint64_t db) {
  asm volatile("{\n.reg .pred p;\nsetp.ne.b32 p, 1, 0;\n"
    "wgmma.mma_async.sync.aligned.m64n128k16.f32.bf16.bf16 "
    "{%0, %1, %2, %3, %4, %5, %6, %7, %8, %9, %10, %11, %12, %13, %14, %15, %16, %17, %18, %19, %20, %21, %22, %23, %24, %25, %26, %27, %28, %29, %30, %31, %32, %33, %34, %35, %36, %37, %38, %39, %40, %41, %42, %43, %44, %45, %46, %47, %48, %49, %50, %51, %52, %53, %54, %55, %56, %57, %58, %59, %60, %61, %62, %63}, "
    "%64, %65, p, 1, 1, 0, 0;\n}\n"
    : "+f"(d[0]), "+f"(d[1]), "+f"(d[2]), "+f"(d[3]), "+f"(d[4]), "+f"(d[5]), "+f"(d[6]), "+f"(d[7]), "+f"(d[8]), "+f"(d[9]), "+f"(d[10]), "+f"(d[11]), "+f"(d[12]), "+f"(d[13]), "+f"(d[14]), "+f"(d[15]), "+f"(d[16]), "+f"(d[17]), "+f"(d[18]), "+f"(d[19]), "+f"(d[20]), "+f"(d[21]), "+f"(d[22]), "+f"(d[23]), "+f"(d[24]), "+f"(d[25]), "+f"(d[26]), "+f"(d[27]), "+f"(d[28]), "+f"(d[29]), "+f"(d[30]), "+f"(d[31]), "+f"(d[32]), "+f"(d[33]), "+f"(d[34]), "+f"(d[35]), "+f"(d[36]), "+f"(d[37]), "+f"(d[38]), "+f"(d[39]), "+f"(d[40]), "+f"(d[41]), "+f"(d[42]), "+f"(d[43]), "+f"(d[44]), "+f"(d[45]), "+f"(d[46]), "+f"(d[47]), "+f"(d[48]), "+f"(d[49]), "+f"(d[50]), "+f"(d[51]), "+f"(d[52]), "+f"(d[53]), "+f"(d[54]), "+f"(d[55]), "+f"(d[56]), "+f"(d[57]), "+f"(d[58]), "+f"(d[59]), "+f"(d[60]), "+f"(d[61]), "+f"(d[62]), "+f"(d[63])
    : "l"(da), "l"(db));
}
__device__ __forceinline__ void fence_acc64(float (&d)[64]) {
#pragma unroll
  for (int i = 0; i < 64; i++) asm volatile("" : "+f"(d[i]) :: "memory");
}
__device__ __forceinline__ void fence_acc(float (&d)[128]) {
#pragma unroll
  for (int i = 0; i < 128; i++) asm volatile("" : "+f"(d[i]) :: "memory");
}

template<int N, int I = 0, class F> __device__ __forceinline__ void static_for(F&& f) {
  if constexpr (I < N) { f(std::integral_constant<int, I>()); static_for<N, I + 1>(f); }
}

__device__ __forceinline__ void ldsm_x4_t(uint32_t addr, uint32_t& a, uint32_t& b, uint32_t& c, uint32_t& d) {
  asm volatile("ldmatrix.sync.aligned.m8n8.x4.trans.shared.b16 {%0, %1, %2, %3}, [%4];" : "=r"(a), "=r"(b), "=r"(c), "=r"(d) : "r"(addr));
}
__device__ __forceinline__ void sts128(uint32_t addr, uint32_t a, uint32_t b, uint32_t c, uint32_t d) {
  asm volatile("st.shared.v4.b32 [%0], {%1, %2, %3, %4};" :: "r"(addr), "r"(a), "r"(b), "r"(c), "r"(d));
}
__device__ __forceinline__ void mma16816(float (&c)[4], uint32_t a0, uint32_t a1, uint32_t a2, uint32_t a3, uint32_t b0, uint32_t b1) {
  asm volatile("mma.sync.aligned.m16n8k16.row.col.f32.bf16.bf16.f32 {%0, %1, %2, %3}, {%4, %5, %6, %7}, {%8, %9}, {%0, %1, %2, %3};"
      : "+f"(c[0]), "+f"(c[1]), "+f"(c[2]), "+f"(c[3]) : "r"(a0), "r"(a1), "r"(a2), "r"(a3), "r"(b0), "r"(b1));
}
__device__ __forceinline__ void mma1688(float (&c)[4], uint32_t a0, uint32_t a1, uint32_t b0) {
  asm volatile("mma.sync.aligned.m16n8k8.row.col.f32.bf16.bf16.f32 {%0, %1, %2, %3}, {%4, %5}, {%6}, {%0, %1, %2, %3};"
      : "+f"(c[0]), "+f"(c[1]), "+f"(c[2]), "+f"(c[3]) : "r"(a0), "r"(a1), "r"(b0));
}
__device__ __forceinline__ void pin(uint32_t& v) { asm volatile("shfl.sync.bfly.b32 %0, %0, 0, 0x1f, 0xffffffff;" : "+r"(v)); }
template<class T> __device__ __forceinline__ void pin(T*& v) {
  uint32_t lo = (uint32_t)(uint64_t)v, hi = (uint32_t)((uint64_t)v >> 32);
  pin(lo); pin(hi);
  v = (T*)(((uint64_t)hi << 32) | lo);
}
__device__ __forceinline__ float sel4(int q, float a, float b, float c, float d) {
  float r;
  asm("{\n.reg .pred p, o;\n.reg .f32 x, y;\n.reg .b32 t;\nand.b32 t, %1, 1;\nsetp.ne.b32 p, t, 0;\nsetp.gt.s32 o, %1, 1;\n"
      "selp.f32 x, %3, %2, p;\nselp.f32 y, %5, %4, p;\nselp.f32 %0, y, x, o;\n}\n" : "=f"(r) : "r"(q), "f"(a), "f"(b), "f"(c), "f"(d));
  return r;
}
__device__ __forceinline__ uint32_t bfma2(uint32_t a, uint32_t b, uint32_t c) { uint32_t r; asm("fma.rn.bf16x2 %0, %1, %2, %3;" : "=r"(r) : "r"(a), "r"(b), "r"(c)); return r; }
__device__ __forceinline__ void tma_store_5d(const CUtensorMap* tm, uint32_t src, int c0, int c3, int c4) {
  asm volatile("cp.async.bulk.tensor.5d.global.shared::cta.bulk_group [%0, {%2, %3, %3, %4, %5}], [%1];" :: "l"(tm), "r"(src), "r"(c0), "r"(0), "r"(c3), "r"(c4) : "memory");
}
__device__ __forceinline__ float rcp_fast(float x) { float r; asm("rcp.approx.ftz.f32 %0, %1;" : "=f"(r) : "f"(x)); return r; }
__device__ __forceinline__ float sigmoid_fast(float x) { float e; asm("ex2.approx.ftz.f32 %0, %1;" : "=f"(e) : "f"(x * -1.4426950408889634f)); return rcp_fast(1.f + e); }
__device__ __forceinline__ float sqrt_fast(float x) { float r; asm("sqrt.approx.ftz.f32 %0, %1;" : "=f"(r) : "f"(x)); return r; }
__device__ __forceinline__ float ln_sd(float var) { return bf16r(sqrt_fast(bf16r(bf16r(fmaxf(var, 0.f)) + 1e-5f))); }
__device__ __forceinline__ uint32_t norm2(uint32_t h, uint32_t neg_mean2, float inv_sd) {
  const uint32_t d = badd2(h, neg_mean2);
  return pack_bf16(bf_lo(d) * inv_sd, bf_hi(d) * inv_sd);
}
template<int N> __device__ __forceinline__ void delay_clk() {
  if constexpr (N > 0) { const uint32_t t0 = clock(); while ((uint32_t)clock() - t0 < N) {} }
}
template<int V> using IC = std::integral_constant<int, V>;

#define CT(slot) do {} while (0)
#define PT(slot) do {} while (0)

template<int MAP>
__global__ void __cluster_dims__(2, 1, 1) __launch_bounds__(384, 1)
fnet_moe_kernel(const __grid_constant__ Params p) {
  uint32_t sb;
  asm volatile("mov.u32 %0, %1;" : "=r"(sb) : "r"(smem_u32(smem_raw)));
  const int m = blockIdx.x & 1;
  int tau, eps;
  bool idle = false;
  if (MAP == 0) {
    uint32_t smid;
    asm volatile("mov.u32 %0, %%smid;" : "=r"(smid));
    const int c = smid >> 1, e7 = ((c - 32) * 37) >> 8;
    idle = c == 60 || c == 61;
    tau = c < 32 ? (c & 7) : (c < 60 ? c - 31 - 7 * e7 : 0);
    eps = c < 32 ? (c >> 3) : (c < 60 ? 4 + e7 : c - 58);
  } else {
    tau = (blockIdx.x >> 1) & 7; eps = blockIdx.x >> 4;
  }
  const int cid = tau * 16 + eps * 2 + m;
  const bool moe = tau > 0;
  auto BAR = [&](int i) { return sb + OFF_BAR + 8 * i; };
  const CUtensorMap* tmD = m ? &p.tmD1 : &p.tmD0;
  const uint64_t pol_ef = policy_evict_first();
#define LOAD_STREAM(d, tm, bar, c0, c1) tma_load_2d_hint(d, tm, bar, c0, c1, pol_ef)
  if (threadIdx.x < 32 && !idle) {
    if (elect_one()) {
#pragma unroll
      for (int k = 0; k < 4; k++) mbar_init(BAR(B_FULL + k), 1);
      asm volatile("fence.mbarrier_init.release.cluster;" ::: "memory");
#pragma unroll
      for (int k = 0; k < 4; k++) mbar_expect_tx(BAR(B_FULL + k), ST_BYTES);
    }
    PT(50);
    if (elect_one()) {
      tma_load_2d(sb + A_BYTES, &p.tmX, BAR(B_FULL), 0, tau * 256);
      LOAD_STREAM(sb, tmD, BAR(B_FULL), 0, eps * 128);
    }
    PT(52);
    if (elect_one()) {
#pragma unroll
      for (int k = 1; k < 4; k++) {
        tma_load_2d(sb + k * ST_BYTES + A_BYTES, &p.tmX, BAR(B_FULL + k), k * 64, tau * 256);
        LOAD_STREAM(sb + k * ST_BYTES, tmD, BAR(B_FULL + k), k * 64, eps * 128);
      }
    }
    PT(0);
  }
  __syncwarp();
  const int warp = __shfl_sync(0xffffffffu, threadIdx.x >> 5, 0);
  const int tid = __shfl_sync(0xffffffffu, threadIdx.x, threadIdx.x & 31), lane = tid & 31;
  if (idle) {
    __nanosleep(4000);
    const uint32_t tg = ld_relaxed32(&p.s->epoch) + 1;
    uint32_t n = 0;
    do { __nanosleep(1000); } while (!__all_sync(0xffffffffu, pkt_ld64(&p.s->xstat[(tid & 127) * 16]).y == tg) && ++n < 4096);
    return;
  }
  if (warp == 8) {
    if (elect_one()) {
#pragma unroll
      for (int b = B_EMPTY; b < B_COUNT; b++)
        mbar_init(BAR(b), b < B_EPI ? 2 : (b == B_EPI || b == B_EPI0B) ? 4 : (b < B_STD || b == B_OUT) ? 8 : (b == B_STAT || b == B_XS) ? 3 : 1);
      asm volatile("fence.mbarrier_init.release.cluster;" ::: "memory");
      mbar_expect_tx(BAR(B_XCH), 32768);
      SM_(uint32_t, OFF_SEEN) = 0;
    }
  }
  __syncthreads();

  if (warp >= 8) {
    reg_dec<REG_P>();
    asm volatile("barrier.cluster.arrive.relaxed.aligned;" ::: "memory");
    const int abrow = m * 1024 + eps * 128;
    const int f0 = (cid - 16) * 32;
    if (warp == 8) {
      const CUtensorMap* tmW = m ? &p.tmW1 : &p.tmW0;
      const int tA = tau * 256 + m * 128, tB = tau * 256 + (1 - m) * 128;
      uint32_t seen = 0;
#pragma unroll 1
      for (int k = 4; k < 48; k++) {
        const int s = slot_of(k);
        const uint32_t sa = sb + s * ST_BYTES, sbb = sa + A_BYTES;
        const int kb = kblock(tau, k - 16);
        mbar_wait(BAR(B_EMPTY + s), (use_of(k) & 1) ^ 1);
        PT(64 + k);
        if (elect_one()) {
          mbar_expect_tx(BAR(B_FULL + s), (k >> 1) == 9 ? B_BYTES : k == 20 ? ST_BYTES - 8192 : ST_BYTES);
          if (k < 16) {
            LOAD_STREAM(sa, tmD, BAR(B_FULL + s), k * 64, eps * 128);
            tma_load_2d(sbb, &p.tmX, BAR(B_FULL + s), k * 64, tau * 256);
          } else {
            LOAD_STREAM(sbb, tmW, BAR(B_FULL + s), kb * 64, tA);
            LOAD_STREAM(sbb + 16384, tmW, BAR(B_FULL + s), kb * 64, tB);
            if (k < 18) {
              tma_load_2d(sa, &p.tmXr, BAR(B_FULL + s), eps * 128, tA + s * 64);
              tma_load_2d(sa + 8192, &p.tmXr, BAR(B_FULL + s), eps * 128 + 64, tA + s * 64);
            }
          }
        }
        if (k >= 24) {
          uint32_t n = 0;
          while (!((seen >> kb) & 1) && ++n < SPIN_LIMIT * 16) seen = *(volatile uint32_t*)&SM_(uint32_t, OFF_SEEN);
          if (elect_one()) tma_load_2d(sa, &p.tmAbL, BAR(B_FULL + s), kb * 64, abrow);
        }
        if (k == PUB_K1 && elect_one()) mbar_arrive(BAR(B_LATE));
        if (k >= WPF_K0 + WPF_J0 && k < WPF_K0 + WPF_J1 && (eps >> 1) == ((k - WPF_K0) & 3) && elect_one())
          asm volatile("cp.async.bulk.prefetch.tensor.2d.L2.global.tile [%0, {%1, %2}];" :: "l"(tmW), "r"(kblock(tau, k - WPF_K0) * 64), "r"(tau * 256 + (eps & 1) * 128) : "memory");
        if (moe && k >= PF_K0 && !(k & 1)) {
          const int i = k < PF_K1 ? (k - PF_K0) >> 1 : PF_N0 + ((k - PF_K1) >> 1);
          if ((k >= PF_K1 || i < PF_N0) && elect_one()) {
            if (i < 8) asm volatile("cp.async.bulk.prefetch.tensor.2d.L2.global.tile [%0, {%1, %2}];" :: "l"(m ? &p.tmU : &p.tmG), "r"(f0), "r"(i * 128) : "memory");
            else if (i < 12) asm volatile("cp.async.bulk.prefetch.L2.global [%0], %1;" :: "l"(p.wdown + (size_t)f0 * 1024 + (i - 8) * 8192), "r"(16384) : "memory");
          }
        }
        if (moe && k >= MR_K0) {
          const int i = k - MR_K0, r6 = i / MR_P, u = i - MR_P * r6, h = 2 * r6 + (u >> 1);
          if (u < 4 && h < NREG_H + 2) {
            if (h < 2) mbar_wait(BAR(B_STD + 2 + h), 0);
            if (elect_one()) {
              const uint32_t bar = BAR(h < NREG_H ? B_MR + (h & 1) : B_GU);
              if (!(u & 1) && h <= NREG_H) mbar_expect_tx(bar, h < NREG_H ? 16384 : (8 - NREG_H) * 16384);
              LOAD_STREAM(sb + OFF_XCH + u * 8192, (u & 1) ? &p.tmU : &p.tmG, bar, f0, h * 128);
              if (mr_k(NREG_H + 1) == 47 && k == 47) LOAD_STREAM(sb + OFF_XCH + u * 8192 + 8192, &p.tmU, bar, f0, h * 128);
            }
          }
        }
      }
      if (moe) {
        mbar_wait(BAR(B_EMPTY + 0), 1);
        if (elect_one()) mbar_expect_tx(BAR(B_DN), 65536);
#pragma unroll 1
        for (int i = 0; i < 10 - NREG_H; i++) {
          if (i == 3) mbar_wait(BAR(B_EMPTY + 1), 1);
          if (i == 4) {
            mbar_wait(BAR(B_EMPTY + 2), 1);
            mbar_wait(BAR(B_XCH), 0);
            PT(53);
          }
          const uint32_t dst = sb + late_off(i);
          if (elect_one()) {
            if (i < 6 - NREG_H) {
              LOAD_STREAM(dst, &p.tmG, BAR(B_GU), f0, (NREG_H + 2 + i) * 128);
              LOAD_STREAM(dst + 8192, &p.tmU, BAR(B_GU), f0, (NREG_H + 2 + i) * 128);
            } else {
#pragma unroll
              for (int b = 0; b < 4; b++) LOAD_STREAM(dst + b * 4096, &p.tmDn, BAR(B_DN), (4 * (i - 6 + NREG_H) + b) * 64, f0);
            }
          }
          const long long t0 = clock64();
          while (i < 9 - NREG_H && clock64() - t0 < MOE_PACE_CLK) {}
        }
      }
    } else {
      const int a = warp - 9;
      auto stage = [&](const bf16* src, int g) {
        if (elect_one()) {
          mbar_expect_tx(BAR(B_AUX + g), 16384);
          bulk_load(sb + OFF_XCH + g * 16384, src + g * 8192, 16384, BAR(B_AUX + g));
        }
      };
      mbar_wait(BAR(B_FULL + 0), 0);
      if (a == 0) PT(1);
      if (a < 2) stage(p.x + (size_t)cid * 16 * 1024, a);
      const uint32_t tag = ld_relaxed32(&p.s->epoch) + 1;
      if (a == 2) {
        float s = 0.f;
#pragma unroll
        for (int q = 0; q < 4; q++) {
          const uint4 v = ldg_nc128(p.wr + (q * 32 + lane) * 8);
          s += ((bf_lo(v.x) + bf_hi(v.x)) + (bf_lo(v.y) + bf_hi(v.y))) + ((bf_lo(v.z) + bf_hi(v.z)) + (bf_lo(v.w) + bf_hi(v.w)));
          const int ch = q * 32 + lane - eps * 16;
          if (ch >= 0 && ch < 16) {
            SM_(uint32_t, OFF_WR + ch * 4) = v.x; SM_(uint32_t, OFF_WR + 80 + ch * 4) = v.y;
            SM_(uint32_t, OFF_WR + 160 + ch * 4) = v.z; SM_(uint32_t, OFF_WR + 240 + ch * 4) = v.w;
          }
        }
        s = warp_sum(s);
        if (lane == 0) { SM_(float, OFF_WSUM) = s; SM_(uint32_t, OFF_TAG) = tag; }
      }
#pragma unroll 1
      for (int it = 0; it < 4; it++) {
        const int g = it & 1;
        mbar_wait(BAR(B_AUX + g), it >> 1);
        if (a == 0) PT(2 + it);
        const uint32_t ad = sb + OFF_XCH + g * 16384 + (lane >> 2) * 2048;
        float s0 = 0.f, s1 = 0.f, q0 = 0.f, q1 = 0.f;
        auto row = [&](auto sq) {
#pragma unroll
          for (int i = 0; i < 11; i++) {
            if (i == 10 && a == 2) break;
            const uint4 v = lds128_v(ad + (((a * 44 + 4 * i + lane) & 127) << 4));
            const uint32_t ww[4] = {v.x, v.y, v.z, v.w};
#pragma unroll
            for (int z = 0; z < 4; z++) {
              const float d0 = bf_lo(ww[z]), d1 = bf_hi(ww[z]);
              s0 += d0; s1 += d1;
              if (decltype(sq)::value) { q0 = fmaf(d0, d0, q0); q1 = fmaf(d1, d1, q1); }
            }
          }
        };
        if (it < 2) row(IC<1>()); else row(IC<0>());
        s0 += s1; q0 += q1;
#pragma unroll
        for (int o = 1; o < 4; o <<= 1) { s0 += __shfl_xor_sync(0xffffffffu, s0, o); q0 += __shfl_xor_sync(0xffffffffu, q0, o); }
        if ((lane & 3) == 0) SM_(float2, OFF_PUB + a * 256 + it * 64 + (lane >> 2) * 8) = make_float2(s0, q0);
        if (it != 2) bar_sync(NB_AUX, 96);
        if (it < 2 && a == 2) stage(cid < 64 ? p.Dre + (size_t)cid * 16 * 1024 : p.Dim + (size_t)(cid - 64) * 16 * 1024, g);
      }
      if (a == 1) {
        const float2 v0 = SM_(float2, OFF_PUB + lane * 8), v1 = SM_(float2, OFF_PUB + 256 + lane * 8), v2 = SM_(float2, OFF_PUB + 512 + lane * 8);
        const float s = v0.x + v1.x + v2.x, mean = s * (1.f / 1024.f);
        const float rs = rcp_fast(ln_sd((v0.y + v1.y + v2.y) * (1.f / 1024.f) - mean * mean));
        pkt_st64((lane < 16 ? p.s->xstat : p.s->dsum) + cid * 16 + (lane & 15), lane < 16 ? pack_bf16(rs, mean) : __float_as_uint(s), tag);
        PT(6);
      }
      __nanosleep(GATHER_NS);
      {
        const int i0 = a * 32 + lane;
        uint2 v[3], c0, c1; uint32_t n = 0;
        const uint2* dp = &p.s->dsum[abrow];
        while (true) {
#pragma unroll
          for (int q = 0; q < 3; q++) v[q] = pkt_ld64(&p.s->xstat[tau * 256 + min(i0 + 96 * q, 255)]);
          c0 = pkt_ld64(dp + i0); c1 = pkt_ld64(dp + min(i0 + 96, 127));
          if (__all_sync(0xffffffffu, v[0].y == tag && v[1].y == tag && v[2].y == tag && c0.y == tag && c1.y == tag) || ++n > SPIN_LIMIT) break;
          __nanosleep(200);
        }
#pragma unroll
        for (int q = 0; q < 3; q++) {
          const int col = min(i0 + 96 * q, 255);
          SM_(uint16_t, OFF_RS + ((col & 7) >> 1) * 144 + (col >> 3) * 4 + (col & 1) * 2) = (uint16_t)(v[q].x ^ (m << 15));
          const uint32_t nm = (v[q].x >> 16) ^ 0x8000u;
          SM_(uint4, OFF_EXB + (col >> 3) * 256 + (col & 7) * 16) = make_uint4(nm | (nm << 16), nm, 0, 0);
          SM_(uint4, OFF_EXB + (col >> 3) * 256 + 128 + (col & 7) * 16) = make_uint4(0, 0, 0, 0);
        }
#pragma unroll
        for (int q = 0; q < 2; q++) {
          const int e = min(i0 + 96 * q, 127);
          const float c = __uint_as_float(q ? c1.x : c0.x);
          const float hi = bf16r(c), mid = bf16r(c - hi), lo = bf16r((c - hi) - mid);
          SM_(uint4, OFF_EXA + (e >> 3) * 256 + (e & 7) * 16) = make_uint4((__float_as_uint(hi) >> 16) | (__float_as_uint(mid) & 0xFFFF0000u), __float_as_uint(lo) >> 16, 0, 0);
          SM_(uint4, OFF_EXA + (e >> 3) * 256 + 128 + (e & 7) * 16) = make_uint4(0, 0, 0, 0);
        }
        fence_async_smem();
      }
      __syncwarp();
      if (lane == 0) mbar_arrive(BAR(B_STAT));
      if (a == 0) PT(7);
      if (a == 0) {
        const int sg = (lane >> 2) == tau ? (tau + 1) & 7 : lane >> 2;
        const uint32_t* flg = reinterpret_cast<const uint32_t*>(&p.s->abflag[((eps * 2 + m) * 8 + sg) * 2]) + ((lane >> 2) == tau ? 4 : lane & 3);
        uint32_t seen = 0;
        mbar_wait(BAR(B_STDA), 0);
        PT(49);
#pragma unroll 1
        for (int i = 0; i < 5; i++) {
          const int s = i ? i - 1 : 0, sig = (tau + 1 + s) & 7;
          if (i == 1) mbar_wait(BAR(B_STD + 0), 0);
          uint32_t n = 0;
          while (!((seen >> (4 * (i ? sig : tau))) & 1) && ++n < SPIN_LIMIT) seen = __ballot_sync(0xffffffffu, ld_relaxed32(flg) == tag);
          if (i == 0 || i == 4) mbar_wait(BAR(i ? B_STD + 1 : B_EPI0B), 0);
          if (i != 1) mbar_wait(BAR(B_FULL + s), 0);
          PT(i ? 16 + s : 48);
          if (elect_one()) {
            if (i == 1) mbar_expect_tx(BAR(B_A20), 8192);
            tma_load_2d(sb + (i < 3 ? OFF_XCH + i * 8192 : s * ST_BYTES), i < 2 ? &p.tmAbS : &p.tmAbL, BAR(i == 1 ? B_A20 : B_FULL + s), sig * 256,
                        abrow + (i == 1 ? 64 : 0));
          }
        }
        uint32_t n = 0;
        while (true) {
          asm volatile("fence.proxy.async.global;" ::: "memory");
          *(volatile uint32_t*)&SM_(uint32_t, OFF_SEEN) = seen;
          if (seen == 0xFFFFFFFFu || ++n > SPIN_LIMIT) break;
          seen = __ballot_sync(0xffffffffu, ld_relaxed32(flg) == tag);
          __nanosleep(100);
        }
      } else {
        uint32_t* flag = reinterpret_cast<uint32_t*>(&p.s->abflag[((eps * 2 + m) * 8 + tau) * 2]);
        mbar_wait(BAR(a == 1 ? B_EPI : B_EPI0B), 0);
        if (a == 1) PT(8);
        if (lane == 0) {
          tma_store_2d(&p.tmAbS, sb + chunk_off(0, a - 1), tau * 256, abrow + (a - 1) * 64);
          bulk_commit();
          bulk_wait_all();
        }
        if (a == 2) mbar_wait(BAR(B_STDA), 0);
        if (lane == 0) {
          st_relaxed32(flag + (a == 1 ? 4 : 0), tag);
          mbar_arrive(BAR(a == 1 ? B_STDA : B_STD));
        }
        if (a == 2) PT(12);
        if (a == 1) {
          mbar_wait(BAR(B_EPI + 1), 0);
          mbar_wait(BAR(B_LATE), 0);
          PT(9);
          if (lane == 0) {
            tma_store_2d(&p.tmAbS, sb + chunk_off(1, 0), tau * 256 + 64, abrow);
            tma_store_2d(&p.tmAbS, sb + chunk_off(1, 1), tau * 256 + 64, abrow + 64);
            bulk_commit();
            bulk_wait_all();
            st_relaxed32(flag + 1, tag);
            mbar_arrive(BAR(B_STD + 1));
          }
          PT(13);
        }
        auto copy_out = [&](int c) {
          mbar_wait(BAR(B_EPI + c), 0);
          PT(8 + c);
          bf16* dst = p.s->abT + (size_t)(abrow + (lane >> 3)) * 2048 + tau * 256 + c * 64;
#pragma unroll 4
          for (int i = 0; i < 32; i++) {
            const int row = 4 * i + (lane >> 3);
            const uint4 v = lds128_v(sb + chunk_off(c, 0) + i * 512 + lane * 16);
            asm volatile("st.global.v4.b32 [%0], {%1, %2, %3, %4};" :: "l"(dst + i * 4 * 2048 + (((lane & 7) ^ (row & 7)) << 3)), "r"(v.x), "r"(v.y), "r"(v.z), "r"(v.w));
          }
          __syncwarp();
          if (lane == 0) mbar_arrive(BAR(B_STD + c));
        };
        if (a == 2) {
#pragma unroll 1
          for (int c = 2; c < 4; c++) copy_out(c);
          asm volatile("fence.acq_rel.gpu;" ::: "memory");
          __syncwarp();
          if (lane < 2) st_relaxed32(flag + 2 + lane, tag);
          PT(15);
        }
      }
      {
        mbar_wait(BAR(B_LATE), 1);
        const int grp = tau * 2 + m;
#pragma unroll 1
        for (int i = a; i < 14; i += 3) {
          uint4* dst = i < 8 ? &p.s->ypart[cid * 256 + i * 32 + lane] : i < 12 ? &p.s->hstat[(grp * 8 + eps) * 128 + (i - 8) * 32 + lane]
                     : i == 12 ? &p.s->cand[grp * 256 + eps * 32 + lane] : &p.s->key[(((lane >> 1) & 7) * 16 + grp) * 2 + (lane & 1)];
          if (i < 13 || eps == 0) pkt_st128(dst, 0, 0, 0, 0);
          __nanosleep(200);
        }
        __syncwarp();
        if (lane == 0) mbar_arrive(BAR(B_STAT));
      }
      {
        const uint4* kp = &p.s->key[(tau * 16 + (lane & 15)) * 2];
        const int i0 = a * 32 + lane;
        mbar_wait(BAR(B_KEY), 0);
        if (a == 0) PT(43);
        uint4 kq = pkt_ld128(kp), cv[3];
        uint32_t n = 0, kv;
        int gspec = -1;
        while (true) {
          const bool ok = kq.y == tag && kq.w == tag;
          kv = __reduce_max_sync(0xffffffffu, ok ? kq.x : 0u);
          const int gs = (0xFFFF - (int)(kv & 0xFFFFu)) >> 7;
          const bool cok = gs == gspec && cv[0].y == tag && cv[0].w == tag && cv[1].y == tag && cv[1].w == tag && cv[2].y == tag && cv[2].w == tag;
          if (__all_sync(0xffffffffu, ok && cok) || ++n > SPIN_LIMIT) break;
          if (!ok) kq = pkt_ld128(kp);
          const bool spec = __popc(__ballot_sync(0xffffffffu, ok)) >= 2 * SPEC_MIN;
          if (!cok && spec) {
#pragma unroll
            for (int i = 0; i < 3; i++) cv[i] = pkt_ld128(&p.s->cand[gs * 256 + min(i0 + 96 * i, 255)]);
          }
          if (spec) gspec = gs;
        }
        if (a == 0) PT(45);
        const uint32_t ms = __shfl_sync(0xffffffffu, kq.z, gspec);
        const uint32_t nm = ((ms & 0xFFFFu) ^ 0x8000u) * 0x10001u;
        const float is = rcp_fast(bf_hi(ms));
#pragma unroll
        for (int i = 0; i < 3; i++) {
          const int j = min(i0 + 96 * i, 255);
          SM_(uint2, OFF_XSEL + j * 8) = make_uint2(norm2(cv[i].x, nm, is), norm2(cv[i].z, nm, is));
        }
#pragma unroll
        for (int i = 0; i < 3; i++) SM_(uint2, OFF_HSEL + min(i0 + 96 * i, 255) * 8) = make_uint2(cv[i].x, cv[i].z);
        SM_(uint32_t, OFF_KV) = kv;
        __syncwarp();
        if (lane == 0) mbar_arrive(BAR(B_XS));
      }
    }
    if (warp == 8) {
      const int lane = threadIdx.x & 31;
      mbar_wait(BAR(B_OUT), 0);
      const uint32_t km = SM_(uint32_t, OFF_WKEY + (lane & 7) * 8);
      const uint32_t bk = __reduce_max_sync(0xffffffffu, km);
      const int ww = __ffs(__ballot_sync(0xffffffffu, km == bk)) - 1;
#pragma unroll 1
      for (int i = 1; i <= 8; i++) {
        const int W = (ww + i) & 7;
        if (i == 8) {
          mbar_wait(BAR(B_XS), 0);
          if (SM_(uint32_t, OFF_KV) == bk) {
#pragma unroll 2
            for (int j = lane; j < 256; j += 32) {
              const int rho = j >> 4, row = (tau * 2 + m) * 128 + 32 * (W >> 1) + 8 * ((rho & 7) >> 1) + 4 * (W & 1) + 2 * (rho >> 3) + (rho & 1);
              const uint4 v = lds128_v(sb + OFF_OUT + (j & 8) * 2048 + (16 * W + rho) * 128 + (((j ^ rho) & 7) << 4));
              if (row != 0xFFFF - (int)(bk & 0xFFFFu))
                asm volatile("st.global.v4.b32 [%0], {%1, %2, %3, %4};" :: "l"(p.out + (size_t)row * 1024 + eps * 128 + (j & 15) * 8), "r"(v.x), "r"(v.y), "r"(v.z), "r"(v.w));
            }
            break;
          }
        }
        if (lane == 0) {
          tma_store_5d(&p.tmOut, sb + OFF_OUT + W * 2048, eps * 128, 2 * (W & 1), tau * 8 + m * 4 + (W >> 1));
          tma_store_5d(&p.tmOut, sb + OFF_OUT + 16384 + W * 2048, eps * 128 + 64, 2 * (W & 1), tau * 8 + m * 4 + (W >> 1));
        }
        const long long t0 = clock64();
        while (i < 7 && clock64() - t0 < OUT_PACE_CLK) {}
      }
      if (lane == 0) { bulk_commit(); bulk_wait_all(); }
      PT(22);
    }
    asm volatile("barrier.cluster.wait.aligned;" ::: "memory");
  } else {
    reg_inc<REG_C>();
    const int w = warp >> 2, wi = warp & 3, t = tid & 127;
    const int g = lane >> 2, q = lane & 3;
    const int turn_me = NB_TURN0 + w, turn_other = NB_TURN1 - w;
    float acc[128];
#pragma unroll
    for (int i = 0; i < 128; i++) acc[i] = 0.f;
    if (w == 1) bar_arrive(NB_TURN0, 256);
    auto kstep = [&](int k, bool first, bool a_in_xch = false) {
      const int s = slot_of(k);
      mbar_wait(BAR(B_FULL + s), use_of(k) & 1);
      CT(64 + k);
      bar_sync(turn_me, 256);
      const uint64_t da = make_desc(sb + (a_in_xch ? OFF_XCH + s * 16384 : s * ST_BYTES) + w * 8192), db = make_desc(sb + s * ST_BYTES + A_BYTES);
      wgmma_fence();
      wgmma_n256(acc, da, db, !first);
#pragma unroll
      for (int kk = 1; kk < 4; kk++) wgmma_n256(acc, da + kk * 2, db + kk * 2, 1);
      wgmma_commit();
      bar_arrive(turn_other, 256);
    };
    auto release = [&](int s) { if (t == 0) mbar_arrive(BAR(B_EMPTY + s)); };
    auto kdone = [&](int k) { wgmma_wait0(); release(slot_of(k)); };
    auto wgmma_wait1 = [&]() { asm volatile("wgmma.wait_group.sync.aligned 1;" ::: "memory"); };

#pragma unroll 1
    for (int k = 0; k < 14; k++) {
      kstep(k, k == 0);
      if (k == 0) CT(0);
      if (k == 8 && warp == 2 && lane < 2) pkt_st128(&p.s->abflag[((eps * 2 + m) * 8 + tau) * 2 + lane], 0, 0, 0, 0);
      kdone(k);
    }
    uint32_t R[64];
    uint32_t tag;
    {
      const uint32_t rsa = sb + OFF_RS + q * 144;
      const uint64_t da2 = make_desc(sb + 2 * ST_BYTES + w * 8192), db2 = make_desc(sb + 2 * ST_BYTES + A_BYTES);
      const uint64_t da3 = make_desc(sb + 3 * ST_BYTES + w * 8192), db3 = make_desc(sb + 3 * ST_BYTES + A_BYTES);
      mbar_wait(BAR(B_FULL + 2), 1);
      CT(64 + 14);
      bar_sync(turn_me, 256);
      wgmma_fence();
#pragma unroll
      for (int kk = 0; kk < 4; kk++) wgmma_n256(acc, da2 + kk * 2, db2 + kk * 2, 1);
      wgmma_commit();
      mbar_wait(BAR(B_FULL + 3), 1);
      CT(64 + 15);
      wgmma_fence();
      wgmma_n256(acc, da3, db3, 1);
      wgmma_n256(acc, da3 + 2, db3 + 2, 1);
      wgmma_commit();
      mbar_wait(BAR(B_STAT), 0);
      tag = SM_(uint32_t, OFF_TAG);
#pragma unroll
      for (int i = 0; i < 8; i++) { const uint4 v = lds128_v(rsa + i * 16); R[8 * i] = v.x; R[8 * i + 2] = v.y; R[8 * i + 4] = v.z; R[8 * i + 6] = v.w; }
      wgmma_wait1();
      release(2);
      wgmma_fence();
      wgmma_n256(acc, da3 + 4, db3 + 4, 1);
      wgmma_n256(acc, da3 + 6, db3 + 6, 1);
      wgmma_n256(acc, make_desc_noswz(sb + OFF_EXA + w * 2048), make_desc_noswz(sb + OFF_EXB), 1);
      wgmma_commit();
      bar_arrive(turn_other, 256);
      kdone(15);
      mbar_wait(BAR(B_STAT), 0);
    }
    fence_acc(acc);
    CT(1);
    auto pack = [&](auto cc) {
      constexpr int c = decltype(cc)::value;
#pragma unroll
      for (int j = 8 * c; j < 8 * c + 8; j++) {
        const uint32_t rs = R[2 * j];
        const float* ac = &acc[4 * j];
        R[2 * j] = bmul2(pack_bf16(ac[0], ac[1]), rs);
        R[2 * j + 1] = bmul2(pack_bf16(ac[2], ac[3]), rs);
      }
    };
    auto put_chunk = [&](auto cc) {
      constexpr int c = decltype(cc)::value;
      const int rho = 16 * wi + (lane & 15);
#pragma unroll
      for (int j = 8 * c; j < 8 * c + 8; j += 2) {
        const int chunk = (j & 7) + (lane >> 4);
        stsm_x4(sb + chunk_off(c, w) + rho * 128 + ((chunk ^ (lane & 7)) << 4), R[2 * j], R[2 * j + 1], R[2 * j + 2], R[2 * j + 3]);
      }
    };
    auto staged = [&](int bar) {
      fence_async_smem();
      __syncwarp();
      if (lane == 0) mbar_arrive(BAR(bar));
    };
    auto mma_rs = [&](auto cc, auto k0, auto k1) {
      constexpr int c = decltype(cc)::value;
      const uint64_t db = make_desc(sb + c * ST_BYTES + A_BYTES);
#pragma unroll
      for (int kk = decltype(k0)::value; kk < decltype(k1)::value; kk++)
        wgmma_n256_rs(acc, R[16 * c + 4 * kk], R[16 * c + 4 * kk + 1], R[16 * c + 4 * kk + 2], R[16 * c + 4 * kk + 3], db + kk * 2, c + kk > 0);
      wgmma_commit();
    };
    auto kdone_x = [&](int k, auto ic) {
      constexpr int i = decltype(ic)::value;
      uint32_t r[8];
#pragma unroll
      for (int z = 0; z < 2; z++) {
        const int tr = 32 * (i & 1) + 16 * z + 8 * (lane >> 4) + (lane & 7), chunk = 2 * wi + ((lane >> 3) & 1);
        ldsm_x4_t(sb + (i >> 1) * ST_BYTES + w * 8192 + tr * 128 + ((chunk ^ (lane & 7)) << 4), r[4 * z], r[4 * z + 1], r[4 * z + 2], r[4 * z + 3]);
      }
      float f[16];
#pragma unroll
      for (int z = 0; z < 8; z++) { f[2 * z] = bf_lo(r[z]); f[2 * z + 1] = bf_hi(r[z]); }
#pragma unroll
      for (int z = 0; z < 16; z++) asm volatile("" : "+f"(f[z]));
      kdone(k);
#pragma unroll
      for (int z = 0; z < 16; z++) asm volatile("add.f32 %0, %0, %1;" : "+f"(acc[16 * i + z]) : "f"(f[z]));
    };
    pack(IC<0>());
    put_chunk(IC<0>());
    staged(w ? B_EPI0B : B_EPI);
    mbar_wait(BAR(B_STAT), 0);
    CT(21);
    pack(IC<1>());
    pack(IC<2>());
    pack(IC<3>());
#pragma unroll
    for (int i = 16; i < 64; i++) asm volatile("" : "+r"(R[i]));
    mbar_wait(BAR(B_FULL + 0), 0);
    CT(2);
    CT(64 + 16);
    bar_sync(turn_me, 256);
    wgmma_fence();
    mma_rs(IC<0>(), IC<0>(), IC<4>());
    mbar_wait(BAR(B_FULL + 1), 0);
    CT(64 + 17);
    wgmma_fence();
    mma_rs(IC<1>(), IC<0>(), IC<2>());
    wgmma_wait1();
    release(0);
    mma_rs(IC<1>(), IC<2>(), IC<4>());
    bar_arrive(turn_other, 256);
    kdone_x(17, IC<0>());
    static_for<2>([&](auto ic) {
      constexpr int c = 2 + decltype(ic)::value;
      mbar_wait(BAR(B_FULL + c), 0);
      CT(64 + 16 + c);
      bar_sync(turn_me, 256);
      wgmma_fence();
      mma_rs(IC<c>(), IC<0>(), IC<4>());
      bar_arrive(turn_other, 256);
      if (c == 2) { put_chunk(IC<1>()); staged(B_EPI + 1); }
      kdone_x(16 + c, IC<c - 1>());
    });
#pragma unroll 1
    for (int k = 20; k < 23; k++) {
      if (w == 1) mbar_wait(BAR(B_A20), 0);
      kstep(k, false, k < 22);
      if (k == 20) {
        kdone_x(k, IC<3>());
      } else {
        if (k == 21) { put_chunk(IC<2>()); if (PUBMODE == 2) fence_async_smem(); } else put_chunk(IC<3>());
        __syncwarp();
        if (lane == 0) mbar_arrive(BAR(B_EPI + k - 19));
        kdone(k);
      }
    }
    uint32_t wf[32][4];
    auto load_wf = [&](auto hc) {
      constexpr int h = decltype(hc)::value;
      const int d = w * 64 + (lane >> 4) * 8 + (lane & 7);
      const uint32_t ad = sb + round_off(h) + (lane & 8) * 1024 + d * 64 + ((wi ^ ((lane >> 1) & 3)) << 4);
#pragma unroll
      for (int i = 0; i < 4; i++) ldsm_x4_t(ad + i * 1024, wf[4 * h + i][0], wf[4 * h + i][1], wf[4 * h + i][2], wf[4 * h + i][3]);
    };
    auto load_wf_rest = [&]() { static_for<8 - NREG_H>([&](auto ic) { load_wf(IC<NREG_H + decltype(ic)::value>()); }); };
#pragma unroll
    for (int i = 0; i < 4 * NREG_H; i++) { wf[i][0] = 0; wf[i][1] = 0; wf[i][2] = 0; wf[i][3] = 0; }
    const int grp = tau * 2 + m;
#pragma unroll 1
    for (int k = 23; k < 46; k++) {
      kstep(k, false);
      if (moe) {
        static_for<NREG_H>([&](auto hc) {
          constexpr int h = decltype(hc)::value;
          if (k == mr_k(h) + 1) { mbar_wait(BAR(B_MR + (h & 1)), (h >> 1) & 1); load_wf(hc); }
        });
      }
      if (k == RESET_K && tid == 0) mbar_arrive(BAR(B_LATE));
      kdone(k);
    }
    asm volatile("barrier.cluster.arrive.relaxed.aligned;" ::: "memory");
    mbar_wait(BAR(B_STAT), 1);
    uint32_t wa[16][2];
    uint32_t cd = code_of(tag);
    uint4* hp_pub = &p.s->hstat[(grp * 8 + eps) * 128 + warp * 16 + g];
    const uint4* hp_poll = &p.s->hstat[(grp * 8 + 2 * q) * 128 + warp * 16 + g];
    const uint32_t vec_off = (2 * wi) * 512 + q * 128 + ((g ^ (2 * q)) << 4);
    {
      float as[64], ak[64];
      fence_acc(acc);
#pragma unroll
      for (int i = 0; i < 64; i++) asm volatile("mov.b32 %0, %1;" : "=f"(as[i]) : "f"(acc[64 + i]));
#pragma unroll
      for (int i = 0; i < 64; i++) asm volatile("mov.b32 %0, %1;" : "=f"(ak[i]) : "f"(acc[i]));
      const uint64_t da1 = make_desc(sb + 2 * ST_BYTES + w * 8192), db1 = make_desc(sb + 2 * ST_BYTES + A_BYTES);
      const uint64_t da2 = make_desc(sb + 3 * ST_BYTES + w * 8192), db2 = make_desc(sb + 3 * ST_BYTES + A_BYTES);
      mbar_wait(BAR(B_FULL + 2), 1);
      CT(64 + 46);
      mbar_wait(BAR(B_FULL + 3), 1);
      CT(64 + 47);
      bar_sync(turn_me, 256);
      wgmma_fence();
#pragma unroll
      for (int kk = 0; kk < 4; kk++) wgmma_n128(as, da1 + kk * 2, db1 + 1024 + kk * 2);
#pragma unroll
      for (int kk = 0; kk < 4; kk++) wgmma_n128(as, da2 + kk * 2, db2 + 1024 + kk * 2);
      wgmma_commit();
      bar_arrive(turn_other, 256);
      const uint32_t rx = mapa(sb + OFF_PEER + w * 4096 + vec_off, 1 - m), rb = mapa(BAR(B_XCH), 1 - m);
      asm volatile("barrier.cluster.wait.aligned;" ::: "memory");
      CT(24);
      wgmma_wait0();
      fence_acc64(as);
      CT(25);
      auto keep = [&]() {
        bar_sync(turn_me, 256);
        wgmma_fence();
#pragma unroll
        for (int kk = 0; kk < 4; kk++) wgmma_n128(ak, da1 + kk * 2, db1 + kk * 2);
        wgmma_commit();
#pragma unroll
        for (int kk = 0; kk < 4; kk++) wgmma_n128(ak, da2 + kk * 2, db2 + kk * 2);
        wgmma_commit();
        if (w == 0) bar_arrive(turn_other, 256);
      };
#pragma unroll
      for (int i = 0; i < 8; i++) {
        if (i == SEND_FIRST) keep();
        const float* ac = &as[16 * (i >> 1) + 2 * (i & 1)];
        st_async_v4(rx + (i >> 1) * 8192 + (i & 1) * 512, rb, pack_bf16(ac[0], ac[1]), pack_bf16(ac[4], ac[5]), pack_bf16(ac[8], ac[9]), pack_bf16(ac[12], ac[13]));
      }
      if (SEND_FIRST == 8) keep();
      CT(26);
#pragma unroll
      for (int i = 0; i < 4; i++) {
        const uint4 v = lds128_v(sb + OFF_WR + q * 80 + i * 16);
        const uint32_t vv[4] = {v.x, v.y, v.z, v.w};
#pragma unroll
        for (int z = 0; z < 4; z++) {
          asm volatile("{\n.reg .pred p;\nsetp.ne.b32 p, %2, 0;\nselp.b32 %0, %1, 0x3F803F80, p;\n}" : "=r"(wa[4 * i + z][0]) : "r"(vv[z]), "r"(g & 1));
          asm volatile("{\n.reg .pred p;\nsetp.ne.b32 p, %2, 0;\nselp.b32 %0, %1, 0x3F803F80, p;\n}" : "=r"(wa[4 * i + z][1]) : "r"(vv[z]), "r"(g & 1));
        }
      }
      pin(cd); pin(hp_pub); pin(hp_poll);
      CT(27);
      wgmma_wait1();
      release(2);
      wgmma_wait0();
      fence_acc64(ak);
      CT(3);
#pragma unroll
      for (int i = 0; i < 8; i++) {
        const float* ac = &ak[16 * (i >> 1) + 2 * (i & 1)];
        sts128(sb + (2 + (i >> 2)) * ST_BYTES + w * 8192 + ((i >> 1) & 1) * 4096 + (i & 1) * 512 + vec_off,
               pack_bf16(ac[0], ac[1]), pack_bf16(ac[4], ac[5]), pack_bf16(ac[8], ac[9]), pack_bf16(ac[12], ac[13]));
      }
    }
    uint32_t h[8][4];
    {
      const int qq = 2 * (warp & 1) + ((lane >> 3) & 1);
      const uint32_t lo = (lane >> 4) * 512 + qq * 128 + (((lane & 7) ^ (2 * qq)) << 4);
      bar_sync(NB_BOTH, 256);
#pragma unroll
      for (int ks = 0; ks < 8; ks++)
        ldsm_x4_t(sb + (2 + w) * ST_BYTES + (ks >> 2) * 8192 + (wi >> 1) * 4096 + (ks & 3) * 1024 + lo, h[ks][0], h[ks][1], h[ks][2], h[ks][3]);
      CT(28);
      mbar_wait_cluster(BAR(B_XCH), 0);
      CT(4);
      uint32_t r[8][4];
#pragma unroll
      for (int ks = 0; ks < 8; ks++) ldsm_x4_t(sb + OFF_PEER + (warp >> 1) * 8192 + ks * 1024 + lo, r[ks][0], r[ks][1], r[ks][2], r[ks][3]);
      float d[4][4] = {};
#pragma unroll
      for (int ks = 0; ks < 8; ks++) {
#pragma unroll
        for (int i = 0; i < 4; i++) {
          h[ks][i] = badd2(h[ks][i], r[ks][i]);
          mma1688(d[i], h[ks][i], wa[2 * ks + (i >> 1)][i & 1], h[ks][i]);
        }
      }
#pragma unroll
      for (int i = 0; i < 2; i++) {
        const float sq = (g & 1) ? d[i][1] + d[i + 2][1] : d[i][0] + d[i + 2][0];
        const float e0 = d[i][2] + d[i + 2][2], e1 = d[i][3] + d[i + 2][3];
        const float other = __shfl_xor_sync(0xffffffffu, (g & 1) ? e0 : e1, 4);
        if (q == (g >> 1)) pkt_st128(hp_pub + 8 * i, with_bit((g & 1) ? other : e0, cd), with_bit(sq, cd >> 1), __float_as_uint((g & 1) ? e1 : other), tag);
      }
    }
    CT(5);
    if (tid == 0) mbar_arrive(BAR(B_KEY));
    delay_clk<HOP1_DELAY>();
    float m_bf, sd, inv_sd, r_bf;
    uint4* key_pub = &p.s->key[((lane & 7) * 16 + grp) * 2];
    uint4* cand_pub = &p.s->cand[grp * 256 + eps * 32 + q];
    uint32_t trow_inv = 0xFFFFu - (uint32_t)(grp * 128 + 32 * (warp >> 1) + 8 * (g >> 1) + 4 * (warp & 1) + (q & 2) + (g & 1));
    {
      uint4 u[4];
#pragma unroll
      for (int i = 0; i < 4; i++) u[i] = pkt_ld128(hp_poll + (i & 1) * 128 + (i >> 1) * 8);
      const float wsum = SM_(float, OFF_WSUM);
      pin(key_pub); pin(cand_pub); pin(trow_inv);
      uint32_t n = 0;
      while (true) {
        bool ok[4];
#pragma unroll
        for (int i = 0; i < 4; i++) ok[i] = u[i].w == tag && pair_code(u[i].x, u[i].y) == cd;
        const bool all = __all_sync(0xffffffffu, ok[0] && ok[1] && ok[2] && ok[3]);
        if (all || ++n > SPIN_LIMIT) break;
#pragma unroll
        for (int i = 0; i < 4; i++) pkt_ld128_if(u[i], hp_poll + (i & 1) * 128 + (i >> 1) * 8, !ok[i]);
      }
      CT(6);
      float a[3], b[3];
      a[0] = __uint_as_float(u[0].x & ~1u) + __uint_as_float(u[1].x & ~1u); b[0] = __uint_as_float(u[2].x & ~1u) + __uint_as_float(u[3].x & ~1u);
      a[1] = __uint_as_float(u[0].y & ~1u) + __uint_as_float(u[1].y & ~1u); b[1] = __uint_as_float(u[2].y & ~1u) + __uint_as_float(u[3].y & ~1u);
      a[2] = __uint_as_float(u[0].z) + __uint_as_float(u[1].z); b[2] = __uint_as_float(u[2].z) + __uint_as_float(u[3].z);
#pragma unroll
      for (int i = 0; i < 3; i++) {
        a[i] = ((q & 2) ? b[i] : a[i]) + __shfl_xor_sync(0xffffffffu, (q & 2) ? a[i] : b[i], 2);
        a[i] += __shfl_xor_sync(0xffffffffu, a[i], 1);
      }
      const float mu = a[0] * (1.f / 1024.f);
      m_bf = bf16r(mu);
      sd = ln_sd(a[1] * (1.f / 1024.f) - mu * mu);
      inv_sd = rcp_fast(sd);
      r_bf = bf16r((a[2] - m_bf * wsum) * inv_sd);
    }
    {
      const uint32_t u = __float_as_uint(r_bf);
      const uint32_t ord = (u & 0x80000000u) ? ~u : (u | 0x80000000u);
      const uint32_t key = (ord & 0xFFFF0000u) | trow_inv;
      const uint32_t wk = __reduce_max_sync(0xffffffffu, key);
      if (key == wk) SM_(uint2, OFF_WKEY + warp * 8) = make_uint2(wk, (__float_as_uint(m_bf) >> 16) | __float_as_uint(sd));
      const uint32_t wmask = __ballot_sync(0xffffffffu, key == wk);
      const bool hi = (wmask & 0xCCCCCCCCu) != 0;
      uint32_t c[16];
#pragma unroll
      for (int ks = 0; ks < 8; ks++) { c[2 * ks] = hi ? h[ks][1] : h[ks][0]; c[2 * ks + 1] = hi ? h[ks][3] : h[ks][2]; }
      bar_sync(NB_BOTH, 256);
      const uint2 km = SM_(uint2, OFF_WKEY + (lane & 7) * 8);
      const uint32_t bk = __reduce_max_sync(0xffffffffu, km.x);
      if (wk == bk) {
        if ((wmask >> (lane & 28)) & 15) {
#pragma unroll
          for (int ks = 0; ks < 8; ks++) pkt_st128(cand_pub + ks * 4, c[2 * ks], tag, c[2 * ks + 1], tag);
        }
      } else if (eps == 0) {
        const uint32_t kx = __shfl_sync(0xffffffffu, km.x, warp ^ 1), ms = __shfl_sync(0xffffffffu, km.y, warp ^ 1);
        if (kx == bk && lane < 8) pkt_st128(key_pub, bk, tag, ms, tag);
      }
      CT(7);
    }
    {
      const float ih = bf16r(inv_sd);
      const uint32_t nm = pack_bf16(-m_bf, -m_bf), iv = pack_bf16(ih, inv_sd - ih);
      const uint32_t nm_o = __shfl_xor_sync(0xffffffffu, nm, 2), iv_o = __shfl_xor_sync(0xffffffffu, iv, 2);
      const uint32_t nm2[2] = {(q & 2) ? nm_o : nm, (q & 2) ? nm : nm_o}, iv2[2] = {(q & 2) ? iv_o : iv, (q & 2) ? iv : iv_o};
      const uint32_t hi2[2] = {__byte_perm(iv2[0], 0, 0x1010), __byte_perm(iv2[1], 0, 0x1010)}, lo2[2] = {__byte_perm(iv2[0], 0, 0x3232), __byte_perm(iv2[1], 0, 0x3232)};
      const uint32_t oa = sb + OFF_OUT + (warp * 16 + (lane & 15)) * 128;
#pragma unroll
      for (int ks = 0; ks < 8; ks++) {
        uint32_t o[4];
#pragma unroll
        for (int i = 0; i < 4; i++) {
          const uint32_t dd = badd2(h[ks][i], nm2[i & 1]);
          o[i] = badd2(h[ks][i], bfma2(dd, hi2[i & 1], bmul2(dd, lo2[i & 1])));
        }
        stsm_x4(oa + (ks >> 2) * 16384 + (((2 * (ks & 3) + (lane >> 4)) ^ (lane & 7)) << 4), o[0], o[1], o[2], o[3]);
      }
      staged(B_OUT);
    }
    CT(8);
    uint32_t df[16][4];
    auto load_df = [&]() {
      const int frow = (lane & 7) + ((lane >> 4) << 3), hi = (lane >> 3) & 1;
      const uint32_t base = sb + down_off(warp >> 1) + (warp & 1) * 8192 + frow * 128;
#pragma unroll
      for (int mt = 0; mt < 8; mt++) {
#pragma unroll
        for (int ks = 0; ks < 2; ks++)
          ldsm_x4_t(base + (mt >> 2) * 4096 + ks * 2048 + (((2 * (mt & 3) + hi) ^ (lane & 7)) << 4),
                    df[2 * mt + ks][0], df[2 * mt + ks][1], df[2 * mt + ks][2], df[2 * mt + ks][3]);
      }
    };
    if (moe) {
      mbar_wait(BAR(B_GU), 0);
      load_wf_rest();
      mbar_wait(BAR(B_DN), 0);
      load_df();
    }
    uint4* y_pub = &p.s->ypart[cid * 256 + tid];
    uint32_t xs_ad = sb + OFF_XSEL + (8 * (g >> 2) + 4 * w + (g & 3)) * 32 + q * 8, gp_ad = sb + OFF_GP + (wi * 8 + g) * 16 + w * 8 + (q >> 1) * 4;
    pin(y_pub); pin(xs_ad); pin(gp_ad);
    mbar_wait(BAR(B_XS), 0);
    CT(9);
    if (moe) {
      float gd[8][4] = {};
      uint2 bx[4];
#pragma unroll
      for (int r = 0; r < 4; r++) bx[r] = smem_at<uint2>(xs_ad + r * 512);
#pragma unroll
      for (int r = 0; r < 4; r++) {
#pragma unroll
        for (int i = 0; i < 8; i++) mma16816(gd[i], wf[8 * r + i][0], wf[8 * r + i][1], wf[8 * r + i][2], wf[8 * r + i][3], bx[r].x, bx[r].y);
      }
      const float gs = sel4(q, gd[0][0] + gd[1][1], gd[2][0] + gd[3][1], gd[4][0] + gd[5][1], gd[6][0] + gd[7][1]);
      const float us = sel4(q, gd[0][2] + gd[1][3], gd[2][2] + gd[3][3], gd[4][2] + gd[5][3], gd[6][2] + gd[7][3]);
      float v = ((q & 2) ? us : gs) + __shfl_xor_sync(0xffffffffu, (q & 2) ? gs : us, 2);
      v += __shfl_xor_sync(0xffffffffu, v, 1);
      smem_at<float>(gp_ad) = v;
      CT(10);
      bar_sync(NB_BOTH, 256);
      uint32_t bq[4];
      {
        const float4 p0 = SM_(float4, OFF_GP + lane * 16);
        const float gt = bf16r(p0.x + p0.z), up = bf16r(p0.y + p0.w);
        const float act = bf16r(gt * sigmoid_fast(gt)) * up;
        const uint32_t pr = pack_bf16(act, __shfl_down_sync(0xffffffffu, act, 1));
#pragma unroll
        for (int i = 0; i < 4; i++) bq[i] = __shfl_sync(0xffffffffu, pr, 8 * i + 2 * q);
      }
      CT(11);
      float yd[8][4] = {};
#pragma unroll
      for (int ks = 0; ks < 2; ks++) {
#pragma unroll
        for (int mt = 0; mt < 8; mt++) mma16816(yd[mt], df[2 * mt + ks][0], df[2 * mt + ks][1], df[2 * mt + ks][2], df[2 * mt + ks][3], bq[2 * ks], bq[2 * ks + 1]);
      }
      pkt_st128(y_pub, with_bit(sel4(q, yd[0][0], yd[2][0], yd[4][0], yd[6][0]), cd), with_bit(sel4(q, yd[0][2], yd[2][2], yd[4][2], yd[6][2]), cd >> 1),
                with_bit(sel4(q, yd[1][0], yd[3][0], yd[5][0], yd[7][0]), cd), with_bit(sel4(q, yd[1][2], yd[3][2], yd[5][2], yd[7][2]), cd >> 1));
    } else {
      const long long tw = clock64();
      while (clock64() - tw < IDLE_WAIT_CLK) __nanosleep(100);
    }
    CT(12);
    const uint32_t kv = SM_(uint32_t, OFF_KV);
    const int tsel = 0xFFFF - (int)(kv & 0xFFFFu);
    const float r_sel = __uint_as_float((kv & 0x80000000u) ? (kv & 0x7FFF0000u) : (~kv & 0xFFFF0000u));
    const float sig = bf16r(sigmoid_fast(r_sel));
    const int pfin = 2 * cid + (tid & 1);
    const int col_fin = (pfin >> 5) * 128 + (pfin & 3) * 32 + ((pfin & 31) >> 2) + 8 * ((tid >> 1) & 3);
    const int sel_off = (col_fin >> 4) * 32 + ((col_fin & 7) >> 1) * 8 + ((col_fin >> 3) & 1) * 4 + (col_fin & 1) * 2;
    const float hn_fin = __uint_as_float((uint32_t)SM_(uint16_t, OFF_XSEL + sel_off) << 16), h_fin = __uint_as_float((uint32_t)SM_(uint16_t, OFF_HSEL + sel_off) << 16);
    bf16* out_fin = p.out + (size_t)tsel * 1024 + col_fin;
    {
      const uint4* src = &p.s->ypart[(16 + (tid >> 1)) * 256 + pfin];
      pin(src); pin(out_fin);
      uint4 v = make_uint4(0, 0, 0, 0);
      if (warp < 7) {
        delay_clk<HOP3_DELAY>();
        uint32_t n = 0;
        bool ok = false;
        do {
          pkt_ld128_if(v, src, !ok);
          ok = pair_code(v.x, v.y) == cd && pair_code(v.z, v.w) == cd;
        } while (!__all_sync(0xffffffffu, ok) && ++n < SPIN_LIMIT);
      }
      CT(13);
      const float y0 = __uint_as_float(v.x & ~1u), y1 = __uint_as_float(v.y & ~1u), y2 = __uint_as_float(v.z & ~1u), y3 = __uint_as_float(v.w & ~1u);
      const float a0 = ((lane & 2) ? y1 : y0) + __shfl_xor_sync(0xffffffffu, (lane & 2) ? y0 : y1, 2);
      const float a1 = ((lane & 2) ? y3 : y2) + __shfl_xor_sync(0xffffffffu, (lane & 2) ? y2 : y3, 2);
      float b = ((lane & 4) ? a1 : a0) + __shfl_xor_sync(0xffffffffu, (lane & 4) ? a0 : a1, 4);
      b += __shfl_xor_sync(0xffffffffu, b, 8);
      b += __shfl_xor_sync(0xffffffffu, b, 16);
      if (lane < 8) SM_(float, OFF_FIN + lane * 32 + warp * 4) = b;
    }
    bar_sync(NB_BOTH, 256);
    if (tid < 8) {
      const float4 y0 = SM_(float4, OFF_FIN + tid * 32), y1 = SM_(float4, OFF_FIN + tid * 32 + 16);
      const float y = ((y0.x + y0.y) + (y0.z + y0.w)) + ((y1.x + y1.y) + y1.z);
      *out_fin = __float2bfloat16_rn(h_fin + bf16r(hn_fin + bf16r(bf16r(y) * sig)));
      if (cid == 0 && tid == 0) st_relaxed32(&p.s->epoch, tag);
    }
    CT(14);
  }
}

__global__ void __launch_bounds__(384, 1) occupancy_probe_kernel() {}

typedef CUresult (*EncodeFn)(CUtensorMap*, CUtensorMapDataType, cuuint32_t, void*, const cuuint64_t*, const cuuint64_t*, const cuuint32_t*, const cuuint32_t*,
                             CUtensorMapInterleave, CUtensorMapSwizzle, CUtensorMapL2promotion, CUtensorMapFloatOOBfill);

static void make_tm(EncodeFn enc, CUtensorMap* tm, const void* ptr, uint64_t rows, uint64_t cols, uint32_t brows, uint32_t bcols, CUtensorMapSwizzle sw,
                    CUtensorMapL2promotion promo = CU_TENSOR_MAP_L2_PROMOTION_L2_256B) {
  cuuint64_t dims[2] = {cols, rows};
  cuuint64_t strides[1] = {cols * 2};
  cuuint32_t box[2] = {bcols, brows};
  cuuint32_t es[2] = {1, 1};
  enc(tm, CU_TENSOR_MAP_DATA_TYPE_BFLOAT16, 2, const_cast<void*>(ptr), dims, strides, box, es, CU_TENSOR_MAP_INTERLEAVE_NONE, sw,
      promo, CU_TENSOR_MAP_FLOAT_OOB_FILL_NONE);
}

extern "C" void kernel_launch(void* const* d_in, const int* in_sizes, int n_in, void* d_out, int out_size) {
  (void)in_sizes; (void)n_in; (void)out_size;
  static EncodeFn enc = nullptr;
  static void* abT = nullptr;
  static int map = 0;
  if (!enc) {
    void* fn = nullptr; cudaDriverEntryPointQueryResult st;
    cudaGetDriverEntryPoint("cuTensorMapEncodeTiled", &fn, cudaEnableDefault, &st);
    enc = (EncodeFn)fn;
    cudaGetSymbolAddress(&abT, g_scratch);
    cudaFuncSetAttribute(fnet_moe_kernel<0>, cudaFuncAttributeMaxDynamicSharedMemorySize, SMEM_TOTAL);
    cudaFuncSetAttribute(fnet_moe_kernel<1>, cudaFuncAttributeMaxDynamicSharedMemorySize, SMEM_TOTAL);
    cudaFuncSetAttribute(occupancy_probe_kernel, cudaFuncAttributeMaxDynamicSharedMemorySize, SMEM_TOTAL);
    cudaFuncSetAttribute(occupancy_probe_kernel, cudaFuncAttributeNonPortableClusterSizeAllowed, 1);
    auto max_clusters = [&](int size) {
      cudaLaunchConfig_t cfg = {};
      cfg.gridDim = dim3(128); cfg.blockDim = dim3(384); cfg.dynamicSmemBytes = SMEM_TOTAL;
      cudaLaunchAttribute at[1];
      at[0].id = cudaLaunchAttributeClusterDimension; at[0].val.clusterDim.x = size; at[0].val.clusterDim.y = 1; at[0].val.clusterDim.z = 1;
      cfg.attrs = at; cfg.numAttrs = 1;
      int ncl = 0;
      return cudaOccupancyMaxActiveClusters(&ncl, occupancy_probe_kernel, &cfg) == cudaSuccess ? ncl : 0;
    };
    int dev = 0, sms = 0;
    cudaGetDevice(&dev);
    cudaDeviceGetAttribute(&sms, cudaDevAttrMultiProcessorCount, dev);
    map = (!getenv("MAP1") && sms == 132 && max_clusters(2) == 66 && max_clusters(16) == 7) ? 0 : 1;
    (void)cudaGetLastError();
  }
  Params p;
  const bf16* x = (const bf16*)d_in[0];
  make_tm(enc, &p.tmD0, d_in[3], 1024, 1024, 128, 64, CU_TENSOR_MAP_SWIZZLE_128B);
  make_tm(enc, &p.tmD1, d_in[4], 1024, 1024, 128, 64, CU_TENSOR_MAP_SWIZZLE_128B);
  make_tm(enc, &p.tmX, x, 2048, 1024, 256, 64, CU_TENSOR_MAP_SWIZZLE_128B);
  make_tm(enc, &p.tmXr, x, 2048, 1024, 64, 64, CU_TENSOR_MAP_SWIZZLE_128B);
  make_tm(enc, &p.tmAbS, abT, 2048, 2048, 64, 64, CU_TENSOR_MAP_SWIZZLE_128B);
  make_tm(enc, &p.tmAbL, abT, 2048, 2048, 128, 64, CU_TENSOR_MAP_SWIZZLE_128B);
  make_tm(enc, &p.tmW0, d_in[1], 2048, 2048, 128, 64, CU_TENSOR_MAP_SWIZZLE_128B, W_PROMO);
  make_tm(enc, &p.tmW1, d_in[2], 2048, 2048, 128, 64, CU_TENSOR_MAP_SWIZZLE_128B, W_PROMO);
  {
    cuuint64_t dims[5] = {1024, 2, 4, 4, 64};
    cuuint64_t strides[4] = {2048, 8 * 2048, 2 * 2048, 32 * 2048};
    cuuint32_t box[5] = {64, 2, 4, 2, 1};
    cuuint32_t es[5] = {1, 1, 1, 1, 1};
    enc(&p.tmOut, CU_TENSOR_MAP_DATA_TYPE_BFLOAT16, 5, d_out, dims, strides, box, es, CU_TENSOR_MAP_INTERLEAVE_NONE, CU_TENSOR_MAP_SWIZZLE_128B,
        CU_TENSOR_MAP_L2_PROMOTION_NONE, CU_TENSOR_MAP_FLOAT_OOB_FILL_NONE);
  }
  make_tm(enc, &p.tmG, d_in[7], 1024, 3584, 128, 32, CU_TENSOR_MAP_SWIZZLE_64B, CU_TENSOR_MAP_L2_PROMOTION_L2_128B);
  make_tm(enc, &p.tmU, d_in[8], 1024, 3584, 128, 32, CU_TENSOR_MAP_SWIZZLE_64B, CU_TENSOR_MAP_L2_PROMOTION_L2_128B);
  make_tm(enc, &p.tmDn, d_in[9], 3584, 1024, 32, 64, CU_TENSOR_MAP_SWIZZLE_128B);
  p.x = x; p.Dre = (const bf16*)d_in[3]; p.Dim = (const bf16*)d_in[4];
  p.wr = (const bf16*)d_in[6]; p.wdown = (const bf16*)d_in[9]; p.wgate = (const bf16*)d_in[7]; p.wup = (const bf16*)d_in[8];
  p.out = (bf16*)d_out; p.s = (Scratch*)abT;
  if (map == 1) fnet_moe_kernel<1><<<128, 384, SMEM_TOTAL>>>(p);
  else fnet_moe_kernel<0><<<132, 384, SMEM_TOTAL>>>(p);
}
```

```cpp
#include <cuda.h>
#include <cuda_runtime.h>
#include <cuda_bf16.h>
#include <stdint.h>
#include <stdlib.h>
#include <type_traits>

typedef __nv_bfloat16 bf16;

#define REG_C 232
#define REG_P 40
__device__ __forceinline__ int kblock(int tau, int j) {
  int i = j - 4;
  if (i >= 19 && i < 23) i += i < 21 ? 2 : -2;
  const int c = (i * 37) >> 8;
  return j < 4 ? tau * 4 + j : ((tau + 1 + i - 7 * c) & 7) * 4 + c;
}
#define HOP1_DELAY 150
#define HOP3_DELAY 300
#define SPEC_MIN 10
#define PF_K0 8
#define PF_N0 2
#define PF_K1 24
#define OUT_PACE_CLK 100
#define WPF_K0 12
#define WPF_J0 0
#define WPF_J1 10
#define PUBMODE 0
#define MR_P 6
#define SEND_FIRST 2
#define RESET_K 39
#define AUX_AFTER 1
#define XD_PROMO CU_TENSOR_MAP_L2_PROMOTION_L2_128B
#define DEF_PROMO CU_TENSOR_MAP_L2_PROMOTION_L2_128B
#define PUB_K1 22
#define NREG_H 5
#define MR_K0 29
__host__ __device__ constexpr int mr_k(int h) { return MR_K0 + MR_P * (h >> 1) + 2 * (h & 1); }
constexpr int A_BYTES = 128 * 64 * 2;
constexpr int B_BYTES = 256 * 64 * 2;
constexpr int ST_BYTES = A_BYTES + B_BYTES;
constexpr int OFF_XCH = 4 * ST_BYTES;
constexpr int OFF_BAR = OFF_XCH + 32768;
constexpr int OFF_WR = OFF_BAR + 384;
constexpr int OFF_RS = OFF_WR + 384;
constexpr int OFF_PUB = OFF_RS + 640;
constexpr int OFF_MISC = OFF_PUB + 768;
constexpr int SMEM_TOTAL = OFF_MISC + 256;
constexpr int OFF_WSUM = OFF_MISC, OFF_TAG = OFF_MISC + 4;
constexpr int OFF_SEEN = OFF_MISC + 8;
constexpr int OFF_KV = OFF_MISC + 12;
constexpr int OFF_WKEY = OFF_MISC + 32;
constexpr int OFF_EXA = OFF_XCH;
constexpr int OFF_EXB = OFF_XCH + 4096;
__host__ __device__ constexpr int chunk_off(int c, int w) { return (c < 2 ? (c + 2) * ST_BYTES : OFF_XCH + (c - 2) * 16384) + w * 8192; }
__host__ __device__ constexpr int late_off(int i) { return i < 4 ? i * 16384 : 2 * ST_BYTES + A_BYTES + (i - 4) * 16384; }
__host__ __device__ constexpr int round_off(int h) { return h < NREG_H + 2 ? OFF_XCH + (h & 1) * 16384 : late_off(h - NREG_H - 2); }
__host__ __device__ constexpr int down_off(int i) { return late_off(6 - NREG_H + i); }
constexpr int OFF_PEER = ST_BYTES + A_BYTES;
constexpr int OFF_OUT = 3 * ST_BYTES + A_BYTES;
constexpr int OFF_XSEL = OFF_PEER;
constexpr int OFF_HSEL = OFF_PEER + 4096;
constexpr int OFF_GP = OFF_PEER + 8192;
constexpr int OFF_FIN = OFF_PEER + 9216;
__device__ __forceinline__ int slot_of(int k) { return k & 3; }
__device__ __forceinline__ int use_of(int k) { return k >> 2; }
enum { B_FULL = 0, B_EMPTY = 4, B_EPI = 8, B_STD = 12, B_EPI0B = 16, B_LATE = 17, B_STAT = 18, B_XCH = 19, B_MR = 20  , B_GU = 22,
       B_DN = 23, B_AUX = 24  , B_OUT = 26, B_KEY = 27, B_XS = 28, B_A20 = 29, B_STDA = 30, B_COUNT = 31 };
enum { NB_TURN0 = 1, NB_TURN1 = 2, NB_BOTH = 5, NB_AUX = 6 };

struct Scratch {
  bf16 abT[2048 * 2048];
  uint2 xstat[2048];
  uint2 dsum[2048];
  uint4 abflag[16 * 8 * 2];
  uint4 hstat[16 * 8 * 128];
  uint4 cand[16 * 256];
  uint4 key[8 * 16 * 2];
  uint4 ypart[128 * 256];
  uint32_t epoch;
};
__device__ __align__(1024) Scratch g_scratch;

struct Params {
  Scratch* s; bf16* out;
  const bf16* x; const bf16* Dre; const bf16* Dim; const bf16* wr; const bf16* wdown; const bf16* wgate; const bf16* wup;
  CUtensorMap tmX, tmD0, tmD1, tmXr, tmAbS, tmAbL, tmW0, tmW1, tmOut, tmG, tmU, tmDn;
};

#define SPIN_LIMIT (1u << 14)
#define MBAR_LIMIT (1u << 10)
#define GATHER_NS 400
#define W_PROMO CU_TENSOR_MAP_L2_PROMOTION_L2_128B
#define MOE_PACE_CLK 300
constexpr int IDLE_WAIT_CLK = 1200;
__device__ __forceinline__ uint32_t smem_u32(const void* p) { return (uint32_t)__cvta_generic_to_shared(p); }
__device__ __forceinline__ void mbar_init(uint32_t bar, uint32_t cnt) { asm volatile("mbarrier.init.shared::cta.b64 [%0], %1;" :: "r"(bar), "r"(cnt) : "memory"); }
__device__ __forceinline__ void mbar_expect_tx(uint32_t bar, uint32_t bytes) { asm volatile("mbarrier.arrive.expect_tx.shared::cta.b64 _, [%0], %1;" :: "r"(bar), "r"(bytes) : "memory"); }
__device__ __forceinline__ void mbar_arrive(uint32_t bar) { asm volatile("mbarrier.arrive.shared::cta.b64 _, [%0];" :: "r"(bar) : "memory"); }
__device__ __forceinline__ void mbar_wait(uint32_t bar, uint32_t parity) {
  uint32_t ok, n = 0;
  do {
    asm volatile("{\n.reg .pred p;\nmbarrier.try_wait.parity.shared::cta.b64 p, [%1], %2;\nselp.u32 %0, 1, 0, p;\n}\n" : "=r"(ok) : "r"(bar), "r"(parity) : "memory");
  } while (!ok && ++n < MBAR_LIMIT);
}
__device__ __forceinline__ bool mbar_test(uint32_t bar, uint32_t parity) {
  uint32_t ok;
  asm volatile("{\n.reg .pred p;\nmbarrier.test_wait.parity.shared::cta.b64 p, [%1], %2;\nselp.u32 %0, 1, 0, p;\n}\n" : "=r"(ok) : "r"(bar), "r"(parity) : "memory");
  return ok != 0;
}
__device__ __forceinline__ void mbar_wait_cluster(uint32_t bar, uint32_t parity) {
  uint32_t ok, n = 0;
  do {
    asm volatile("{\n.reg .pred p;\nmbarrier.try_wait.parity.acquire.cluster.shared::cta.b64 p, [%1], %2;\nselp.u32 %0, 1, 0, p;\n}\n" : "=r"(ok) : "r"(bar), "r"(parity) : "memory");
  } while (!ok && ++n < MBAR_LIMIT);
}
__device__ __forceinline__ void tma_load_2d(uint32_t dst, const CUtensorMap* tm, uint32_t bar, int c0, int c1) {
  asm volatile("cp.async.bulk.tensor.2d.shared::cluster.global.mbarrier::complete_tx::bytes [%0], [%1, {%3, %4}], [%2];"
    :: "r"(dst), "l"(tm), "r"(bar), "r"(c0), "r"(c1) : "memory");
}
__device__ __forceinline__ void tma_load_2d_hint(uint32_t dst, const CUtensorMap* tm, uint32_t bar, int c0, int c1, uint64_t pol) {
  asm volatile("cp.async.bulk.tensor.2d.shared::cluster.global.mbarrier::complete_tx::bytes.L2::cache_hint [%0], [%1, {%3, %4}], [%2], %5;"
    :: "r"(dst), "l"(tm), "r"(bar), "r"(c0), "r"(c1), "l"(pol) : "memory");
}
__device__ __forceinline__ uint64_t policy_evict_first() { uint64_t p; asm volatile("createpolicy.fractional.L2::evict_first.b64 %0, 1.0;" : "=l"(p)); return p; }
__device__ __forceinline__ void tma_store_2d(const CUtensorMap* tm, uint32_t src, int c0, int c1) {
  asm volatile("cp.async.bulk.tensor.2d.global.shared::cta.bulk_group [%0, {%2, %3}], [%1];" :: "l"(tm), "r"(src), "r"(c0), "r"(c1) : "memory");
}
__device__ __forceinline__ void bulk_load(uint32_t dst, const void* src, uint32_t bytes, uint32_t bar) {
  asm volatile("cp.async.bulk.shared::cluster.global.mbarrier::complete_tx::bytes [%0], [%1], %2, [%3];" :: "r"(dst), "l"(src), "r"(bytes), "r"(bar) : "memory");
}
__device__ __forceinline__ void bulk_commit() { asm volatile("cp.async.bulk.commit_group;" ::: "memory"); }
__device__ __forceinline__ void bulk_wait_all() { asm volatile("cp.async.bulk.wait_group 0;" ::: "memory"); }
__device__ __forceinline__ void fence_async_smem() { asm volatile("fence.proxy.async.shared::cta;" ::: "memory"); }
__device__ __forceinline__ void wgmma_fence() { asm volatile("wgmma.fence.sync.aligned;" ::: "memory"); }
__device__ __forceinline__ void wgmma_commit() { asm volatile("wgmma.commit_group.sync.aligned;" ::: "memory"); }
__device__ __forceinline__ void wgmma_wait0() { asm volatile("wgmma.wait_group.sync.aligned 0;" ::: "memory"); }
__device__ __forceinline__ void bar_sync(int id, int n) { asm volatile("bar.sync %0, %1;" :: "r"(id), "r"(n) : "memory"); }
__device__ __forceinline__ void bar_arrive(int id, int n) { asm volatile("bar.arrive %0, %1;" :: "r"(id), "r"(n) : "memory"); }
template<int R> __device__ __forceinline__ void reg_inc() { asm volatile("setmaxnreg.inc.sync.aligned.u32 %0;" :: "n"(R)); }
template<int R> __device__ __forceinline__ void reg_dec() { asm volatile("setmaxnreg.dec.sync.aligned.u32 %0;" :: "n"(R)); }
__device__ __forceinline__ bool elect_one() {
  uint32_t p;
  asm volatile("{\n.reg .pred q;\nelect.sync _|q, 0xffffffff;\nselp.u32 %0, 1, 0, q;\n}\n" : "=r"(p));
  return p != 0;
}
__device__ __forceinline__ uint32_t mapa(uint32_t addr, uint32_t cta) { uint32_t r; asm volatile("mapa.shared::cluster.u32 %0, %1, %2;" : "=r"(r) : "r"(addr), "r"(cta)); return r; }
__device__ __forceinline__ void st_async_v4(uint32_t addr, uint32_t bar, uint32_t a, uint32_t b, uint32_t c, uint32_t d) {
  asm volatile("st.async.weak.shared::cluster.mbarrier::complete_tx::bytes.v4.b32 [%0], {%2, %3, %4, %5}, [%1];" :: "r"(addr), "r"(bar), "r"(a), "r"(b), "r"(c), "r"(d) : "memory");
}
__device__ __forceinline__ void stsm_x4(uint32_t addr, uint32_t a, uint32_t b, uint32_t c, uint32_t d) {
  asm volatile("stmatrix.sync.aligned.m8n8.x4.shared.b16 [%0], {%1, %2, %3, %4};" :: "r"(addr), "r"(a), "r"(b), "r"(c), "r"(d));
}
__device__ __forceinline__ uint4 lds128_v(uint32_t addr) { uint4 v; asm volatile("ld.shared.v4.b32 {%0, %1, %2, %3}, [%4];" : "=r"(v.x), "=r"(v.y), "=r"(v.z), "=r"(v.w) : "r"(addr)); return v; }
extern __shared__ __align__(1024) uint8_t smem_raw[];
template<class T> __device__ __forceinline__ T& smem_at(uint32_t addr) { return *reinterpret_cast<T*>(__cvta_shared_to_generic(addr)); }
#define SM_(T, off) smem_at<T>(sb + (off))
__device__ __forceinline__ uint4 ldg_nc128(const void* p) { uint4 v; asm volatile("ld.global.nc.v4.b32 {%0, %1, %2, %3}, [%4];" : "=r"(v.x), "=r"(v.y), "=r"(v.z), "=r"(v.w) : "l"(p)); return v; }
__device__ __forceinline__ void pkt_st128(void* p, uint32_t a, uint32_t b, uint32_t c, uint32_t d) {
  asm volatile("{\n.reg .b128 v;\n.reg .b64 lo, hi;\nmov.b64 lo, {%1, %2};\nmov.b64 hi, {%3, %4};\nmov.b128 v, {lo, hi};\nst.relaxed.gpu.global.b128 [%0], v;\n}\n"
    :: "l"(p), "r"(a), "r"(b), "r"(c), "r"(d) : "memory");
}
__device__ __forceinline__ uint4 pkt_ld128(const void* p) {
  uint4 r;
  asm volatile("{\n.reg .b128 v;\n.reg .b64 lo, hi;\nld.relaxed.gpu.global.b128 v, [%4];\nmov.b128 {lo, hi}, v;\nmov.b64 {%0, %1}, lo;\nmov.b64 {%2, %3}, hi;\n}\n"
    : "=r"(r.x), "=r"(r.y), "=r"(r.z), "=r"(r.w) : "l"(p) : "memory");
  return r;
}
__device__ __forceinline__ void pkt_ld128_if(uint4& r, const void* p, bool cond) {
  asm volatile("{\n.reg .pred q;\nsetp.ne.b32 q, %5, 0;\n@q ld.relaxed.gpu.global.v4.b32 {%0, %1, %2, %3}, [%4];\n}\n"
    : "+r"(r.x), "+r"(r.y), "+r"(r.z), "+r"(r.w) : "l"(p), "r"((uint32_t)cond) : "memory");
}
__device__ __forceinline__ void pkt_st64(void* p, uint32_t a, uint32_t b) {
  asm volatile("{\n.reg .b64 v;\nmov.b64 v, {%1, %2};\nst.relaxed.gpu.global.b64 [%0], v;\n}\n" :: "l"(p), "r"(a), "r"(b) : "memory");
}
__device__ __forceinline__ uint2 pkt_ld64(const void* p) {
  uint2 r;
  asm volatile("{\n.reg .b64 v;\nld.relaxed.gpu.global.b64 v, [%2];\nmov.b64 {%0, %1}, v;\n}\n" : "=r"(r.x), "=r"(r.y) : "l"(p) : "memory");
  return r;
}
__device__ __forceinline__ uint32_t ld_relaxed32(const void* p) { uint32_t v; asm volatile("ld.relaxed.gpu.global.b32 %0, [%1];" : "=r"(v) : "l"(p) : "memory"); return v; }
__device__ __forceinline__ void st_relaxed32(void* p, uint32_t v) { asm volatile("st.relaxed.gpu.global.b32 [%0], %1;" :: "l"(p), "r"(v) : "memory"); }
__device__ __forceinline__ uint32_t code_of(uint32_t tag) { return tag % 3u + 1u; }
__device__ __forceinline__ uint32_t with_bit(float v, uint32_t bit) { return (__float_as_uint(v) & ~1u) | (bit & 1u); }
__device__ __forceinline__ uint32_t pair_code(uint32_t a, uint32_t b) { return (a & 1u) | ((b & 1u) << 1); }
__device__ __forceinline__ uint32_t pack_bf16(float lo, float hi) { uint32_t r; asm("cvt.rn.bf16x2.f32 %0, %1, %2;" : "=r"(r) : "f"(hi), "f"(lo)); return r; }
__device__ __forceinline__ float bf_lo(uint32_t v) { return __uint_as_float(v << 16); }
__device__ __forceinline__ float bf_hi(uint32_t v) { return __uint_as_float(v & 0xFFFF0000u); }
__device__ __forceinline__ float bf16r(float x) { return __uint_as_float(pack_bf16(0.f, x)); }
__device__ __forceinline__ uint32_t badd2(uint32_t a, uint32_t b) { uint32_t r; asm("add.rn.bf16x2 %0, %1, %2;" : "=r"(r) : "r"(a), "r"(b)); return r; }
__device__ __forceinline__ uint32_t bmul2(uint32_t a, uint32_t b) { uint32_t r; asm("mul.rn.bf16x2 %0, %1, %2;" : "=r"(r) : "r"(a), "r"(b)); return r; }
__device__ __forceinline__ float warp_sum(float v) {
#pragma unroll
  for (int o = 16; o > 0; o >>= 1) v += __shfl_xor_sync(0xffffffffu, v, o);
  return v;
}
__device__ __forceinline__ uint64_t make_desc(uint32_t addr) {
  return (uint64_t)((addr & 0x3FFFF) >> 4) | ((uint64_t)1 << 16) | ((uint64_t)64 << 32) | ((uint64_t)1 << 62);
}
__device__ __forceinline__ uint64_t make_desc_noswz(uint32_t addr) {
  return (uint64_t)((addr & 0x3FFFF) >> 4) | ((uint64_t)8 << 16) | ((uint64_t)16 << 32);
}
__device__ __forceinline__ void wgmma_n256(float (&d)[128], uint64_t da, uint64_t db, int scale_d) {
  asm volatile("{\n.reg .pred p;\nsetp.ne.b32 p, %130, 0;\n"
    "wgmma.mma_async.sync.aligned.m64n256k16.f32.bf16.bf16 "
    "{%0, %1, %2, %3, %4, %5, %6, %7, %8, %9, %10, %11, %12, %13, %14, %15, %16, %17, %18, %19, %20, %21, %22, %23, %24, %25, %26, %27, %28, %29, %30, %31, "
    "%32, %33, %34, %35, %36, %37, %38, %39, %40, %41, %42, %43, %44, %45, %46, %47, %48, %49, %50, %51, %52, %53, %54, %55, %56, %57, %58, %59, %60, %61, %62, %63, "
    "%64, %65, %66, %67, %68, %69, %70, %71, %72, %73, %74, %75, %76, %77, %78, %79, %80, %81, %82, %83, %84, %85, %86, %87, %88, %89, %90, %91, %92, %93, %94, %95, "
    "%96, %97, %98, %99, %100, %101, %102, %103, %104, %105, %106, %107, %108, %109, %110, %111, %112, %113, %114, %115, %116, %117, %118, %119, %120, %121, %122, %123, %124, %125, %126, %127}, "
    "%128, %129, p, 1, 1, 0, 0;\n}\n"
    : "+f"(d[0]), "+f"(d[1]), "+f"(d[2]), "+f"(d[3]), "+f"(d[4]), "+f"(d[5]), "+f"(d[6]), "+f"(d[7]),
      "+f"(d[8]), "+f"(d[9]), "+f"(d[10]), "+f"(d[11]), "+f"(d[12]), "+f"(d[13]), "+f"(d[14]), "+f"(d[15]),
      "+f"(d[16]), "+f"(d[17]), "+f"(d[18]), "+f"(d[19]), "+f"(d[20]), "+f"(d[21]), "+f"(d[22]), "+f"(d[23]),
      "+f"(d[24]), "+f"(d[25]), "+f"(d[26]), "+f"(d[27]), "+f"(d[28]), "+f"(d[29]), "+f"(d[30]), "+f"(d[31]),
      "+f"(d[32]), "+f"(d[33]), "+f"(d[34]), "+f"(d[35]), "+f"(d[36]), "+f"(d[37]), "+f"(d[38]), "+f"(d[39]),
      "+f"(d[40]), "+f"(d[41]), "+f"(d[42]), "+f"(d[43]), "+f"(d[44]), "+f"(d[45]), "+f"(d[46]), "+f"(d[47]),
      "+f"(d[48]), "+f"(d[49]), "+f"(d[50]), "+f"(d[51]), "+f"(d[52]), "+f"(d[53]), "+f"(d[54]), "+f"(d[55]),
      "+f"(d[56]), "+f"(d[57]), "+f"(d[58]), "+f"(d[59]), "+f"(d[60]), "+f"(d[61]), "+f"(d[62]), "+f"(d[63]),
      "+f"(d[64]), "+f"(d[65]), "+f"(d[66]), "+f"(d[67]), "+f"(d[68]), "+f"(d[69]), "+f"(d[70]), "+f"(d[71]),
      "+f"(d[72]), "+f"(d[73]), "+f"(d[74]), "+f"(d[75]), "+f"(d[76]), "+f"(d[77]), "+f"(d[78]), "+f"(d[79]),
      "+f"(d[80]), "+f"(d[81]), "+f"(d[82]), "+f"(d[83]), "+f"(d[84]), "+f"(d[85]), "+f"(d[86]), "+f"(d[87]),
      "+f"(d[88]), "+f"(d[89]), "+f"(d[90]), "+f"(d[91]), "+f"(d[92]), "+f"(d[93]), "+f"(d[94]), "+f"(d[95]),
      "+f"(d[96]), "+f"(d[97]), "+f"(d[98]), "+f"(d[99]), "+f"(d[100]), "+f"(d[101]), "+f"(d[102]), "+f"(d[103]),
      "+f"(d[104]), "+f"(d[105]), "+f"(d[106]), "+f"(d[107]), "+f"(d[108]), "+f"(d[109]), "+f"(d[110]), "+f"(d[111]),
      "+f"(d[112]), "+f"(d[113]), "+f"(d[114]), "+f"(d[115]), "+f"(d[116]), "+f"(d[117]), "+f"(d[118]), "+f"(d[119]),
      "+f"(d[120]), "+f"(d[121]), "+f"(d[122]), "+f"(d[123]), "+f"(d[124]), "+f"(d[125]), "+f"(d[126]), "+f"(d[127])
    : "l"(da), "l"(db), "r"(scale_d));
}
__device__ __forceinline__ void wgmma_n256_rs(float (&d)[128], uint32_t a0, uint32_t a1, uint32_t a2, uint32_t a3, uint64_t db, int scale_d) {
  asm volatile("{\n.reg .pred p;\nsetp.ne.b32 p, %133, 0;\n"
    "wgmma.mma_async.sync.aligned.m64n256k16.f32.bf16.bf16 "
    "{%0, %1, %2, %3, %4, %5, %6, %7, %8, %9, %10, %11, %12, %13, %14, %15, %16, %17, %18, %19, %20, %21, %22, %23, %24, %25, %26, %27, %28, %29, %30, %31, "
    "%32, %33, %34, %35, %36, %37, %38, %39, %40, %41, %42, %43, %44, %45, %46, %47, %48, %49, %50, %51, %52, %53, %54, %55, %56, %57, %58, %59, %60, %61, %62, %63, "
    "%64, %65, %66, %67, %68, %69, %70, %71, %72, %73, %74, %75, %76, %77, %78, %79, %80, %81, %82, %83, %84, %85, %86, %87, %88, %89, %90, %91, %92, %93, %94, %95, "
    "%96, %97, %98, %99, %100, %101, %102, %103, %104, %105, %106, %107, %108, %109, %110, %111, %112, %113, %114, %115, %116, %117, %118, %119, %120, %121, %122, %123, %124, %125, %126, %127}, "
    "{%128, %129, %130, %131}, %132, p, 1, 1, 0;\n}\n"
    : "+f"(d[0]), "+f"(d[1]), "+f"(d[2]), "+f"(d[3]), "+f"(d[4]), "+f"(d[5]), "+f"(d[6]), "+f"(d[7]),
      "+f"(d[8]), "+f"(d[9]), "+f"(d[10]), "+f"(d[11]), "+f"(d[12]), "+f"(d[13]), "+f"(d[14]), "+f"(d[15]),
      "+f"(d[16]), "+f"(d[17]), "+f"(d[18]), "+f"(d[19]), "+f"(d[20]), "+f"(d[21]), "+f"(d[22]), "+f"(d[23]),
      "+f"(d[24]), "+f"(d[25]), "+f"(d[26]), "+f"(d[27]), "+f"(d[28]), "+f"(d[29]), "+f"(d[30]), "+f"(d[31]),
      "+f"(d[32]), "+f"(d[33]), "+f"(d[34]), "+f"(d[35]), "+f"(d[36]), "+f"(d[37]), "+f"(d[38]), "+f"(d[39]),
      "+f"(d[40]), "+f"(d[41]), "+f"(d[42]), "+f"(d[43]), "+f"(d[44]), "+f"(d[45]), "+f"(d[46]), "+f"(d[47]),
      "+f"(d[48]), "+f"(d[49]), "+f"(d[50]), "+f"(d[51]), "+f"(d[52]), "+f"(d[53]), "+f"(d[54]), "+f"(d[55]),
      "+f"(d[56]), "+f"(d[57]), "+f"(d[58]), "+f"(d[59]), "+f"(d[60]), "+f"(d[61]), "+f"(d[62]), "+f"(d[63]),
      "+f"(d[64]), "+f"(d[65]), "+f"(d[66]), "+f"(d[67]), "+f"(d[68]), "+f"(d[69]), "+f"(d[70]), "+f"(d[71]),
      "+f"(d[72]), "+f"(d[73]), "+f"(d[74]), "+f"(d[75]), "+f"(d[76]), "+f"(d[77]), "+f"(d[78]), "+f"(d[79]),
      "+f"(d[80]), "+f"(d[81]), "+f"(d[82]), "+f"(d[83]), "+f"(d[84]), "+f"(d[85]), "+f"(d[86]), "+f"(d[87]),
      "+f"(d[88]), "+f"(d[89]), "+f"(d[90]), "+f"(d[91]), "+f"(d[92]), "+f"(d[93]), "+f"(d[94]), "+f"(d[95]),
      "+f"(d[96]), "+f"(d[97]), "+f"(d[98]), "+f"(d[99]), "+f"(d[100]), "+f"(d[101]), "+f"(d[102]), "+f"(d[103]),
      "+f"(d[104]), "+f"(d[105]), "+f"(d[106]), "+f"(d[107]), "+f"(d[108]), "+f"(d[109]), "+f"(d[110]), "+f"(d[111]),
      "+f"(d[112]), "+f"(d[113]), "+f"(d[114]), "+f"(d[115]), "+f"(d[116]), "+f"(d[117]), "+f"(d[118]), "+f"(d[119]),
      "+f"(d[120]), "+f"(d[121]), "+f"(d[122]), "+f"(d[123]), "+f"(d[124]), "+f"(d[125]), "+f"(d[126]), "+f"(d[127])
    : "r"(a0), "r"(a1), "r"(a2), "r"(a3), "l"(db), "r"(scale_d));
}
__device__ __forceinline__ void wgmma_n128(float (&d)[64], uint64_t da, uint64_t db) {
  asm volatile("{\n.reg .pred p;\nsetp.ne.b32 p, 1, 0;\n"
    "wgmma.mma_async.sync.aligned.m64n128k16.f32.bf16.bf16 "
    "{%0, %1, %2, %3, %4, %5, %6, %7, %8, %9, %10, %11, %12, %13, %14, %15, %16, %17, %18, %19, %20, %21, %22, %23, %24, %25, %26, %27, %28, %29, %30, %31, %32, %33, %34, %35, %36, %37, %38, %39, %40, %41, %42, %43, %44, %45, %46, %47, %48, %49, %50, %51, %52, %53, %54, %55, %56, %57, %58, %59, %60, %61, %62, %63}, "
    "%64, %65, p, 1, 1, 0, 0;\n}\n"
    : "+f"(d[0]), "+f"(d[1]), "+f"(d[2]), "+f"(d[3]), "+f"(d[4]), "+f"(d[5]), "+f"(d[6]), "+f"(d[7]), "+f"(d[8]), "+f"(d[9]), "+f"(d[10]), "+f"(d[11]), "+f"(d[12]), "+f"(d[13]), "+f"(d[14]), "+f"(d[15]), "+f"(d[16]), "+f"(d[17]), "+f"(d[18]), "+f"(d[19]), "+f"(d[20]), "+f"(d[21]), "+f"(d[22]), "+f"(d[23]), "+f"(d[24]), "+f"(d[25]), "+f"(d[26]), "+f"(d[27]), "+f"(d[28]), "+f"(d[29]), "+f"(d[30]), "+f"(d[31]), "+f"(d[32]), "+f"(d[33]), "+f"(d[34]), "+f"(d[35]), "+f"(d[36]), "+f"(d[37]), "+f"(d[38]), "+f"(d[39]), "+f"(d[40]), "+f"(d[41]), "+f"(d[42]), "+f"(d[43]), "+f"(d[44]), "+f"(d[45]), "+f"(d[46]), "+f"(d[47]), "+f"(d[48]), "+f"(d[49]), "+f"(d[50]), "+f"(d[51]), "+f"(d[52]), "+f"(d[53]), "+f"(d[54]), "+f"(d[55]), "+f"(d[56]), "+f"(d[57]), "+f"(d[58]), "+f"(d[59]), "+f"(d[60]), "+f"(d[61]), "+f"(d[62]), "+f"(d[63])
    : "l"(da), "l"(db));
}
__device__ __forceinline__ void fence_acc64(float (&d)[64]) {
#pragma unroll
  for (int i = 0; i < 64; i++) asm volatile("" : "+f"(d[i]) :: "memory");
}
__device__ __forceinline__ void fence_acc(float (&d)[128]) {
#pragma unroll
  for (int i = 0; i < 128; i++) asm volatile("" : "+f"(d[i]) :: "memory");
}

template<int N, int I = 0, class F> __device__ __forceinline__ void static_for(F&& f) {
  if constexpr (I < N) { f(std::integral_constant<int, I>()); static_for<N, I + 1>(f); }
}

__device__ __forceinline__ void ldsm_x4_t(uint32_t addr, uint32_t& a, uint32_t& b, uint32_t& c, uint32_t& d) {
  asm volatile("ldmatrix.sync.aligned.m8n8.x4.trans.shared.b16 {%0, %1, %2, %3}, [%4];" : "=r"(a), "=r"(b), "=r"(c), "=r"(d) : "r"(addr));
}
__device__ __forceinline__ void sts128(uint32_t addr, uint32_t a, uint32_t b, uint32_t c, uint32_t d) {
  asm volatile("st.shared.v4.b32 [%0], {%1, %2, %3, %4};" :: "r"(addr), "r"(a), "r"(b), "r"(c), "r"(d));
}
__device__ __forceinline__ void mma16816(float (&c)[4], uint32_t a0, uint32_t a1, uint32_t a2, uint32_t a3, uint32_t b0, uint32_t b1) {
  asm volatile("mma.sync.aligned.m16n8k16.row.col.f32.bf16.bf16.f32 {%0, %1, %2, %3}, {%4, %5, %6, %7}, {%8, %9}, {%0, %1, %2, %3};"
      : "+f"(c[0]), "+f"(c[1]), "+f"(c[2]), "+f"(c[3]) : "r"(a0), "r"(a1), "r"(a2), "r"(a3), "r"(b0), "r"(b1));
}
__device__ __forceinline__ void mma1688(float (&c)[4], uint32_t a0, uint32_t a1, uint32_t b0) {
  asm volatile("mma.sync.aligned.m16n8k8.row.col.f32.bf16.bf16.f32 {%0, %1, %2, %3}, {%4, %5}, {%6}, {%0, %1, %2, %3};"
      : "+f"(c[0]), "+f"(c[1]), "+f"(c[2]), "+f"(c[3]) : "r"(a0), "r"(a1), "r"(b0));
}
__device__ __forceinline__ void pin(uint32_t& v) { asm volatile("shfl.sync.bfly.b32 %0, %0, 0, 0x1f, 0xffffffff;" : "+r"(v)); }
template<class T> __device__ __forceinline__ void pin(T*& v) {
  uint32_t lo = (uint32_t)(uint64_t)v, hi = (uint32_t)((uint64_t)v >> 32);
  pin(lo); pin(hi);
  v = (T*)(((uint64_t)hi << 32) | lo);
}
__device__ __forceinline__ float sel4(int q, float a, float b, float c, float d) {
  float r;
  asm("{\n.reg .pred p, o;\n.reg .f32 x, y;\n.reg .b32 t;\nand.b32 t, %1, 1;\nsetp.ne.b32 p, t, 0;\nsetp.gt.s32 o, %1, 1;\n"
      "selp.f32 x, %3, %2, p;\nselp.f32 y, %5, %4, p;\nselp.f32 %0, y, x, o;\n}\n" : "=f"(r) : "r"(q), "f"(a), "f"(b), "f"(c), "f"(d));
  return r;
}
__device__ __forceinline__ uint32_t bfma2(uint32_t a, uint32_t b, uint32_t c) { uint32_t r; asm("fma.rn.bf16x2 %0, %1, %2, %3;" : "=r"(r) : "r"(a), "r"(b), "r"(c)); return r; }
__device__ __forceinline__ void tma_store_5d(const CUtensorMap* tm, uint32_t src, int c0, int c3, int c4) {
  asm volatile("cp.async.bulk.tensor.5d.global.shared::cta.bulk_group [%0, {%2, %3, %3, %4, %5}], [%1];" :: "l"(tm), "r"(src), "r"(c0), "r"(0), "r"(c3), "r"(c4) : "memory");
}
__device__ __forceinline__ float rcp_fast(float x) { float r; asm("rcp.approx.ftz.f32 %0, %1;" : "=f"(r) : "f"(x)); return r; }
__device__ __forceinline__ float sigmoid_fast(float x) { float e; asm("ex2.approx.ftz.f32 %0, %1;" : "=f"(e) : "f"(x * -1.4426950408889634f)); return rcp_fast(1.f + e); }
__device__ __forceinline__ float sqrt_fast(float x) { float r; asm("sqrt.approx.ftz.f32 %0, %1;" : "=f"(r) : "f"(x)); return r; }
__device__ __forceinline__ float ln_sd(float var) { return bf16r(sqrt_fast(bf16r(bf16r(fmaxf(var, 0.f)) + 1e-5f))); }
__device__ __forceinline__ uint32_t norm2(uint32_t h, uint32_t neg_mean2, float inv_sd) {
  const uint32_t d = badd2(h, neg_mean2);
  return pack_bf16(bf_lo(d) * inv_sd, bf_hi(d) * inv_sd);
}
template<int N> __device__ __forceinline__ void delay_clk() {
  if constexpr (N > 0) { const uint32_t t0 = clock(); while ((uint32_t)clock() - t0 < N) {} }
}
template<int V> using IC = std::integral_constant<int, V>;

#define CT(slot) do {} while (0)
#define PT(slot) do {} while (0)

template<int MAP>
__global__ void __cluster_dims__(2, 1, 1) __launch_bounds__(384, 1)
fnet_moe_kernel(const __grid_constant__ Params p) {
  uint32_t sb;
  asm volatile("mov.u32 %0, %1;" : "=r"(sb) : "r"(smem_u32(smem_raw)));
  const int m = blockIdx.x & 1;
  int tau, eps;
  bool idle = false;
  if (MAP == 0) {
    uint32_t smid;
    asm volatile("mov.u32 %0, %%smid;" : "=r"(smid));
    const int c = smid >> 1, e7 = ((c - 32) * 37) >> 8;
    idle = c == 60 || c == 61;
    tau = c < 32 ? (c & 7) : (c < 60 ? c - 31 - 7 * e7 : 0);
    eps = c < 32 ? (c >> 3) : (c < 60 ? 4 + e7 : c - 58);
  } else {
    tau = (blockIdx.x >> 1) & 7; eps = blockIdx.x >> 4;
  }
  const int cid = tau * 16 + eps * 2 + m;
  const bool moe = tau > 0;
  auto BAR = [&](int i) { return sb + OFF_BAR + 8 * i; };
  const CUtensorMap* tmD = m ? &p.tmD1 : &p.tmD0;
  const uint64_t pol_ef = policy_evict_first();
#define LOAD_STREAM(d, tm, bar, c0, c1) tma_load_2d_hint(d, tm, bar, c0, c1, pol_ef)
  if (threadIdx.x < 32 && !idle) {
    if (elect_one()) {
#pragma unroll
      for (int k = 0; k < 4; k++) mbar_init(BAR(B_FULL + k), 1);
      asm volatile("fence.mbarrier_init.release.cluster;" ::: "memory");
#pragma unroll
      for (int k = 0; k < 4; k++) mbar_expect_tx(BAR(B_FULL + k), ST_BYTES);
    }
    PT(50);
    if (elect_one()) {
      tma_load_2d(sb + A_BYTES, &p.tmX, BAR(B_FULL), 0, tau * 256);
      LOAD_STREAM(sb, tmD, BAR(B_FULL), 0, eps * 128);
    }
    PT(52);
    if (elect_one()) {
#pragma unroll
      for (int k = 1; k < 4; k++) {
        tma_load_2d(sb + k * ST_BYTES + A_BYTES, &p.tmX, BAR(B_FULL + k), k * 64, tau * 256);
        LOAD_STREAM(sb + k * ST_BYTES, tmD, BAR(B_FULL + k), k * 64, eps * 128);
      }
    }
    PT(0);
  }
  __syncwarp();
  const int warp = __shfl_sync(0xffffffffu, threadIdx.x >> 5, 0);
  const int tid = __shfl_sync(0xffffffffu, threadIdx.x, threadIdx.x & 31), lane = tid & 31;
  if (idle) {
    __nanosleep(4000);
    const uint32_t tg = ld_relaxed32(&p.s->epoch) + 1;
    uint32_t n = 0;
    do { __nanosleep(1000); } while (!__all_sync(0xffffffffu, pkt_ld64(&p.s->xstat[(tid & 127) * 16]).y == tg) && ++n < 4096);
    return;
  }
  if (warp == 8) {
    if (elect_one()) {
#pragma unroll
      for (int b = B_EMPTY; b < B_COUNT; b++)
        mbar_init(BAR(b), b < B_EPI ? 2 : (b == B_EPI || b == B_EPI0B) ? 4 : (b < B_STD || b == B_OUT) ? 8 : (b == B_STAT || b == B_XS) ? 3 : 1);
      asm volatile("fence.mbarrier_init.release.cluster;" ::: "memory");
      mbar_expect_tx(BAR(B_XCH), 32768);
      SM_(uint32_t, OFF_SEEN) = 0;
    }
  }
  __syncthreads();

  if (warp >= 8) {
    reg_dec<REG_P>();
    asm volatile("barrier.cluster.arrive.relaxed.aligned;" ::: "memory");
    const int abrow = m * 1024 + eps * 128;
    const int f0 = (cid - 16) * 32;
    if (warp == 8) {
      const CUtensorMap* tmW = m ? &p.tmW1 : &p.tmW0;
      const int tA = tau * 256 + m * 128, tB = tau * 256 + (1 - m) * 128;
      uint32_t seen = 0;
#pragma unroll 1
      for (int k = 4; k < 48; k++) {
        const int s = slot_of(k);
        const uint32_t sa = sb + s * ST_BYTES, sbb = sa + A_BYTES;
        const int kb = kblock(tau, k - 16);
        mbar_wait(BAR(B_EMPTY + s), (use_of(k) & 1) ^ 1);
        PT(64 + k);
        if (elect_one()) {
          mbar_expect_tx(BAR(B_FULL + s), (k >> 1) == 9 ? B_BYTES : k == 20 ? ST_BYTES - 8192 : ST_BYTES);
          if (k < 16) {
            LOAD_STREAM(sa, tmD, BAR(B_FULL + s), k * 64, eps * 128);
            tma_load_2d(sbb, &p.tmX, BAR(B_FULL + s), k * 64, tau * 256);
          } else {
            LOAD_STREAM(sbb, tmW, BAR(B_FULL + s), kb * 64, tA);
            LOAD_STREAM(sbb + 16384, tmW, BAR(B_FULL + s), kb * 64, tB);
            if (k < 18) {
              tma_load_2d(sa, &p.tmXr, BAR(B_FULL + s), eps * 128, tA + s * 64);
              tma_load_2d(sa + 8192, &p.tmXr, BAR(B_FULL + s), eps * 128 + 64, tA + s * 64);
            }
          }
        }
        if (k >= 24) {
          uint32_t n = 0;
          while (!((seen >> kb) & 1) && ++n < SPIN_LIMIT * 16) seen = *(volatile uint32_t*)&SM_(uint32_t, OFF_SEEN);
          if (elect_one()) tma_load_2d(sa, &p.tmAbL, BAR(B_FULL + s), kb * 64, abrow);
        }
        if (k == PUB_K1 && elect_one()) mbar_arrive(BAR(B_LATE));
        if (k >= WPF_K0 + WPF_J0 && k < WPF_K0 + WPF_J1 && (eps >> 1) == ((k - WPF_K0) & 3) && elect_one())
          asm volatile("cp.async.bulk.prefetch.tensor.2d.L2.global.tile [%0, {%1, %2}];" :: "l"(tmW), "r"(kblock(tau, k - WPF_K0) * 64), "r"(tau * 256 + (eps & 1) * 128) : "memory");
        if (moe && k >= PF_K0 && !(k & 1)) {
          const int i = k < PF_K1 ? (k - PF_K0) >> 1 : PF_N0 + ((k - PF_K1) >> 1);
          if ((k >= PF_K1 || i < PF_N0) && elect_one()) {
            if (i < 8) asm volatile("cp.async.bulk.prefetch.tensor.2d.L2.global.tile [%0, {%1, %2}];" :: "l"(m ? &p.tmU : &p.tmG), "r"(f0), "r"(i * 128) : "memory");
            else if (i < 12) asm volatile("cp.async.bulk.prefetch.L2.global [%0], %1;" :: "l"(p.wdown + (size_t)f0 * 1024 + (i - 8) * 8192), "r"(16384) : "memory");
          }
        }
        if (moe && k >= MR_K0) {
          const int i = k - MR_K0, r6 = i / MR_P, u = i - MR_P * r6, h = 2 * r6 + (u >> 1);
          if (u < 4 && h < NREG_H + 2) {
            if (h < 2) mbar_wait(BAR(B_STD + 2 + h), 0);
            if (elect_one()) {
              const uint32_t bar = BAR(h < NREG_H ? B_MR + (h & 1) : B_GU);
              if (!(u & 1) && h <= NREG_H) mbar_expect_tx(bar, h < NREG_H ? 16384 : (8 - NREG_H) * 16384);
              LOAD_STREAM(sb + OFF_XCH + u * 8192, (u & 1) ? &p.tmU : &p.tmG, bar, f0, h * 128);
              if (mr_k(NREG_H + 1) == 47 && k == 47) LOAD_STREAM(sb + OFF_XCH + u * 8192 + 8192, &p.tmU, bar, f0, h * 128);
            }
          }
        }
      }
      if (moe) {
        mbar_wait(BAR(B_EMPTY + 0), 1);
        if (elect_one()) mbar_expect_tx(BAR(B_DN), 65536);
#pragma unroll 1
        for (int i = 0; i < 10 - NREG_H; i++) {
          if (i == 3) mbar_wait(BAR(B_EMPTY + 1), 1);
          if (i == 4) {
            mbar_wait(BAR(B_EMPTY + 2), 1);
            mbar_wait(BAR(B_XCH), 0);
            PT(53);
          }
          const uint32_t dst = sb + late_off(i);
          if (elect_one()) {
            if (i < 6 - NREG_H) {
              LOAD_STREAM(dst, &p.tmG, BAR(B_GU), f0, (NREG_H + 2 + i) * 128);
              LOAD_STREAM(dst + 8192, &p.tmU, BAR(B_GU), f0, (NREG_H + 2 + i) * 128);
            } else {
#pragma unroll
              for (int b = 0; b < 4; b++) LOAD_STREAM(dst + b * 4096, &p.tmDn, BAR(B_DN), (4 * (i - 6 + NREG_H) + b) * 64, f0);
            }
          }
          const long long t0 = clock64();
          while (i < 9 - NREG_H && clock64() - t0 < MOE_PACE_CLK) {}
        }
      }
    } else {
      const int a = warp - 9;
      auto stage = [&](const bf16* src, int g) {
        if (elect_one()) {
          mbar_expect_tx(BAR(B_AUX + g), 16384);
          bulk_load(sb + OFF_XCH + g * 16384, src + g * 8192, 16384, BAR(B_AUX + g));
        }
      };
      mbar_wait(BAR(B_FULL + AUX_AFTER), 0);
      if (a == 0) PT(1);
      if (a < 2) stage(p.x + (size_t)cid * 16 * 1024, a);
      const uint32_t tag = ld_relaxed32(&p.s->epoch) + 1;
      if (a == 2 && lane < 16) asm volatile("prefetch.global.L2 [%0];" :: "l"(p.wr + lane * 64));
#pragma unroll 1
      for (int it = 0; it < 4; it++) {
        const int g = it & 1;
        mbar_wait(BAR(B_AUX + g), it >> 1);
        if (a == 0) PT(2 + it);
        const uint32_t ad = sb + OFF_XCH + g * 16384 + (lane >> 2) * 2048;
        float s0 = 0.f, s1 = 0.f, q0 = 0.f, q1 = 0.f;
        auto row = [&](auto sq) {
#pragma unroll
          for (int i = 0; i < 11; i++) {
            if (i == 10 && a == 2) break;
            const uint4 v = lds128_v(ad + (((a * 44 + 4 * i + lane) & 127) << 4));
            const uint32_t ww[4] = {v.x, v.y, v.z, v.w};
#pragma unroll
            for (int z = 0; z < 4; z++) {
              const float d0 = bf_lo(ww[z]), d1 = bf_hi(ww[z]);
              s0 += d0; s1 += d1;
              if (decltype(sq)::value) { q0 = fmaf(d0, d0, q0); q1 = fmaf(d1, d1, q1); }
            }
          }
        };
        if (it < 2) row(IC<1>()); else row(IC<0>());
        s0 += s1; q0 += q1;
#pragma unroll
        for (int o = 1; o < 4; o <<= 1) { s0 += __shfl_xor_sync(0xffffffffu, s0, o); q0 += __shfl_xor_sync(0xffffffffu, q0, o); }
        if ((lane & 3) == 0) SM_(float2, OFF_PUB + a * 256 + it * 64 + (lane >> 2) * 8) = make_float2(s0, q0);
        if (it != 2) bar_sync(NB_AUX, 96);
        if (it < 2 && a == 2) stage(cid < 64 ? p.Dre + (size_t)cid * 16 * 1024 : p.Dim + (size_t)(cid - 64) * 16 * 1024, g);
      }
      if (a == 1) {
        const float2 v0 = SM_(float2, OFF_PUB + lane * 8), v1 = SM_(float2, OFF_PUB + 256 + lane * 8), v2 = SM_(float2, OFF_PUB + 512 + lane * 8);
        const float s = v0.x + v1.x + v2.x, mean = s * (1.f / 1024.f);
        const float rs = rcp_fast(ln_sd((v0.y + v1.y + v2.y) * (1.f / 1024.f) - mean * mean));
        pkt_st64((lane < 16 ? p.s->xstat : p.s->dsum) + cid * 16 + (lane & 15), lane < 16 ? pack_bf16(rs, mean) : __float_as_uint(s), tag);
        PT(6);
      }
      if (a == 2) {
        float s = 0.f;
#pragma unroll
        for (int q = 0; q < 4; q++) {
          const uint4 v = ldg_nc128(p.wr + (q * 32 + lane) * 8);
          s += ((bf_lo(v.x) + bf_hi(v.x)) + (bf_lo(v.y) + bf_hi(v.y))) + ((bf_lo(v.z) + bf_hi(v.z)) + (bf_lo(v.w) + bf_hi(v.w)));
          const int ch = q * 32 + lane - eps * 16;
          if (ch >= 0 && ch < 16) {
            SM_(uint32_t, OFF_WR + ch * 4) = v.x; SM_(uint32_t, OFF_WR + 80 + ch * 4) = v.y;
            SM_(uint32_t, OFF_WR + 160 + ch * 4) = v.z; SM_(uint32_t, OFF_WR + 240 + ch * 4) = v.w;
          }
        }
        s = warp_sum(s);
        if (lane == 0) { SM_(float, OFF_WSUM) = s; SM_(uint32_t, OFF_TAG) = tag; }
      }
      if (a < 2) __nanosleep(GATHER_NS);
      {
        const int i0 = a * 32 + lane;
        uint2 v[3], c0, c1; uint32_t n = 0;
        const uint2* dp = &p.s->dsum[abrow];
        while (true) {
#pragma unroll
          for (int q = 0; q < 3; q++) v[q] = pkt_ld64(&p.s->xstat[tau * 256 + min(i0 + 96 * q, 255)]);
          c0 = pkt_ld64(dp + i0); c1 = pkt_ld64(dp + min(i0 + 96, 127));
          if (__all_sync(0xffffffffu, v[0].y == tag && v[1].y == tag && v[2].y == tag && c0.y == tag && c1.y == tag) || ++n > SPIN_LIMIT) break;
          __nanosleep(200);
        }
#pragma unroll
        for (int q = 0; q < 3; q++) {
          const int col = min(i0 + 96 * q, 255);
          SM_(uint16_t, OFF_RS + ((col & 7) >> 1) * 144 + (col >> 3) * 4 + (col & 1) * 2) = (uint16_t)(v[q].x ^ (m << 15));
          const uint32_t nm = (v[q].x >> 16) ^ 0x8000u;
          SM_(uint4, OFF_EXB + (col >> 3) * 256 + (col & 7) * 16) = make_uint4(nm | (nm << 16), nm, 0, 0);
          SM_(uint4, OFF_EXB + (col >> 3) * 256 + 128 + (col & 7) * 16) = make_uint4(0, 0, 0, 0);
        }
#pragma unroll
        for (int q = 0; q < 2; q++) {
          const int e = min(i0 + 96 * q, 127);
          const float c = __uint_as_float(q ? c1.x : c0.x);
          const float hi = bf16r(c), mid = bf16r(c - hi), lo = bf16r((c - hi) - mid);
          SM_(uint4, OFF_EXA + (e >> 3) * 256 + (e & 7) * 16) = make_uint4((__float_as_uint(hi) >> 16) | (__float_as_uint(mid) & 0xFFFF0000u), __float_as_uint(lo) >> 16, 0, 0);
          SM_(uint4, OFF_EXA + (e >> 3) * 256 + 128 + (e & 7) * 16) = make_uint4(0, 0, 0, 0);
        }
        fence_async_smem();
      }
      __syncwarp();
      if (lane == 0) mbar_arrive(BAR(B_STAT));
      if (a == 0) PT(7);
      if (a == 0) {
        const int sg = (lane >> 2) == tau ? (tau + 1) & 7 : lane >> 2;
        const uint32_t* flg = reinterpret_cast<const uint32_t*>(&p.s->abflag[((eps * 2 + m) * 8 + sg) * 2]) + ((lane >> 2) == tau ? 4 : lane & 3);
        uint32_t seen = 0;
        mbar_wait(BAR(B_STDA), 0);
        PT(49);
#pragma unroll 1
        for (int i = 0; i < 5; i++) {
          const int s = i ? i - 1 : 0, sig = (tau + 1 + s) & 7;
          if (i == 1) mbar_wait(BAR(B_STD + 0), 0);
          uint32_t n = 0;
          while (!((seen >> (4 * (i ? sig : tau))) & 1) && ++n < SPIN_LIMIT) seen = __ballot_sync(0xffffffffu, ld_relaxed32(flg) == tag);
          if (i == 0 || i == 4) mbar_wait(BAR(i ? B_STD + 1 : B_EPI0B), 0);
          if (i != 1) mbar_wait(BAR(B_FULL + s), 0);
          PT(i ? 16 + s : 48);
          if (elect_one()) {
            if (i == 1) mbar_expect_tx(BAR(B_A20), 8192);
            tma_load_2d(sb + (i < 3 ? OFF_XCH + i * 8192 : s * ST_BYTES), i < 2 ? &p.tmAbS : &p.tmAbL, BAR(i == 1 ? B_A20 : B_FULL + s), sig * 256,
                        abrow + (i == 1 ? 64 : 0));
          }
        }
        uint32_t n = 0;
        while (true) {
          asm volatile("fence.proxy.async.global;" ::: "memory");
          *(volatile uint32_t*)&SM_(uint32_t, OFF_SEEN) = seen;
          if (seen == 0xFFFFFFFFu || ++n > SPIN_LIMIT) break;
          seen = __ballot_sync(0xffffffffu, ld_relaxed32(flg) == tag);
          __nanosleep(100);
        }
      } else {
        uint32_t* flag = reinterpret_cast<uint32_t*>(&p.s->abflag[((eps * 2 + m) * 8 + tau) * 2]);
        mbar_wait(BAR(a == 1 ? B_EPI : B_EPI0B), 0);
        if (a == 1) PT(8);
        if (lane == 0) {
          tma_store_2d(&p.tmAbS, sb + chunk_off(0, a - 1), tau * 256, abrow + (a - 1) * 64);
          bulk_commit();
          bulk_wait_all();
        }
        if (a == 2) mbar_wait(BAR(B_STDA), 0);
        if (lane == 0) {
          st_relaxed32(flag + (a == 1 ? 4 : 0), tag);
          mbar_arrive(BAR(a == 1 ? B_STDA : B_STD));
        }
        if (a == 2) PT(12);
        if (a == 1) {
          mbar_wait(BAR(B_EPI + 1), 0);
          mbar_wait(BAR(B_LATE), 0);
          PT(9);
          if (lane == 0) {
            tma_store_2d(&p.tmAbS, sb + chunk_off(1, 0), tau * 256 + 64, abrow);
            tma_store_2d(&p.tmAbS, sb + chunk_off(1, 1), tau * 256 + 64, abrow + 64);
            bulk_commit();
            bulk_wait_all();
            st_relaxed32(flag + 1, tag);
            mbar_arrive(BAR(B_STD + 1));
          }
          PT(13);
        }
        auto copy_out = [&](int c) {
          mbar_wait(BAR(B_EPI + c), 0);
          PT(8 + c);
          bf16* dst = p.s->abT + (size_t)(abrow + (lane >> 3)) * 2048 + tau * 256 + c * 64;
#pragma unroll 4
          for (int i = 0; i < 32; i++) {
            const int row = 4 * i + (lane >> 3);
            const uint4 v = lds128_v(sb + chunk_off(c, 0) + i * 512 + lane * 16);
            asm volatile("st.global.v4.b32 [%0], {%1, %2, %3, %4};" :: "l"(dst + i * 4 * 2048 + (((lane & 7) ^ (row & 7)) << 3)), "r"(v.x), "r"(v.y), "r"(v.z), "r"(v.w));
          }
          __syncwarp();
          if (lane == 0) mbar_arrive(BAR(B_STD + c));
        };
        if (a == 2) {
#pragma unroll 1
          for (int c = 2; c < 4; c++) copy_out(c);
          asm volatile("fence.acq_rel.gpu;" ::: "memory");
          __syncwarp();
          if (lane < 2) st_relaxed32(flag + 2 + lane, tag);
          PT(15);
        }
      }
      {
        mbar_wait(BAR(B_LATE), 1);
        const int grp = tau * 2 + m;
#pragma unroll 1
        for (int i = a; i < 14; i += 3) {
          uint4* dst = i < 8 ? &p.s->ypart[cid * 256 + i * 32 + lane] : i < 12 ? &p.s->hstat[(grp * 8 + eps) * 128 + (i - 8) * 32 + lane]
                     : i == 12 ? &p.s->cand[grp * 256 + eps * 32 + lane] : &p.s->key[(((lane >> 1) & 7) * 16 + grp) * 2 + (lane & 1)];
          if (i < 13 || eps == 0) pkt_st128(dst, 0, 0, 0, 0);
          __nanosleep(200);
        }
        __syncwarp();
        if (lane == 0) mbar_arrive(BAR(B_STAT));
      }
      {
        const uint4* kp = &p.s->key[(tau * 16 + (lane & 15)) * 2];
        const int i0 = a * 32 + lane;
        mbar_wait(BAR(B_KEY), 0);
        if (a == 0) PT(43);
        uint4 kq = pkt_ld128(kp), cv[3];
        uint32_t n = 0, kv;
        int gspec = -1;
        while (true) {
          const bool ok = kq.y == tag && kq.w == tag;
          kv = __reduce_max_sync(0xffffffffu, ok ? kq.x : 0u);
          const int gs = (0xFFFF - (int)(kv & 0xFFFFu)) >> 7;
          const bool cok = gs == gspec && cv[0].y == tag && cv[0].w == tag && cv[1].y == tag && cv[1].w == tag && cv[2].y == tag && cv[2].w == tag;
          if (__all_sync(0xffffffffu, ok && cok) || ++n > SPIN_LIMIT) break;
          if (!ok) kq = pkt_ld128(kp);
          const bool spec = __popc(__ballot_sync(0xffffffffu, ok)) >= 2 * SPEC_MIN;
          if (!cok && spec) {
#pragma unroll
            for (int i = 0; i < 3; i++) cv[i] = pkt_ld128(&p.s->cand[gs * 256 + min(i0 + 96 * i, 255)]);
          }
          if (spec) gspec = gs;
        }
        if (a == 0) PT(45);
        const uint32_t ms = __shfl_sync(0xffffffffu, kq.z, gspec);
        const uint32_t nm = ((ms & 0xFFFFu) ^ 0x8000u) * 0x10001u;
        const float is = rcp_fast(bf_hi(ms));
#pragma unroll
        for (int i = 0; i < 3; i++) {
          const int j = min(i0 + 96 * i, 255);
          SM_(uint2, OFF_XSEL + j * 8) = make_uint2(norm2(cv[i].x, nm, is), norm2(cv[i].z, nm, is));
        }
#pragma unroll
        for (int i = 0; i < 3; i++) SM_(uint2, OFF_HSEL + min(i0 + 96 * i, 255) * 8) = make_uint2(cv[i].x, cv[i].z);
        SM_(uint32_t, OFF_KV) = kv;
        __syncwarp();
        if (lane == 0) mbar_arrive(BAR(B_XS));
      }
    }
    if (warp == 8) {
      const int lane = threadIdx.x & 31;
      mbar_wait(BAR(B_OUT), 0);
      const uint32_t km = SM_(uint32_t, OFF_WKEY + (lane & 7) * 8);
      const uint32_t bk = __reduce_max_sync(0xffffffffu, km);
      const int ww = __ffs(__ballot_sync(0xffffffffu, km == bk)) - 1;
#pragma unroll 1
      for (int i = 1; i <= 8; i++) {
        const int W = (ww + i) & 7;
        if (i == 8) {
          mbar_wait(BAR(B_XS), 0);
          if (SM_(uint32_t, OFF_KV) == bk) {
#pragma unroll 2
            for (int j = lane; j < 256; j += 32) {
              const int rho = j >> 4, row = (tau * 2 + m) * 128 + 32 * (W >> 1) + 8 * ((rho & 7) >> 1) + 4 * (W & 1) + 2 * (rho >> 3) + (rho & 1);
              const uint4 v = lds128_v(sb + OFF_OUT + (j & 8) * 2048 + (16 * W + rho) * 128 + (((j ^ rho) & 7) << 4));
              if (row != 0xFFFF - (int)(bk & 0xFFFFu))
                asm volatile("st.global.v4.b32 [%0], {%1, %2, %3, %4};" :: "l"(p.out + (size_t)row * 1024 + eps * 128 + (j & 15) * 8), "r"(v.x), "r"(v.y), "r"(v.z), "r"(v.w));
            }
            break;
          }
        }
        if (lane == 0) {
          tma_store_5d(&p.tmOut, sb + OFF_OUT + W * 2048, eps * 128, 2 * (W & 1), tau * 8 + m * 4 + (W >> 1));
          tma_store_5d(&p.tmOut, sb + OFF_OUT + 16384 + W * 2048, eps * 128 + 64, 2 * (W & 1), tau * 8 + m * 4 + (W >> 1));
        }
        const long long t0 = clock64();
        while (i < 7 && clock64() - t0 < OUT_PACE_CLK) {}
      }
      if (lane == 0) { bulk_commit(); bulk_wait_all(); }
      PT(22);
    }
    asm volatile("barrier.cluster.wait.aligned;" ::: "memory");
  } else {
    reg_inc<REG_C>();
    const int w = warp >> 2, wi = warp & 3, t = tid & 127;
    const int g = lane >> 2, q = lane & 3;
    const int turn_me = NB_TURN0 + w, turn_other = NB_TURN1 - w;
    float acc[128];
#pragma unroll
    for (int i = 0; i < 128; i++) acc[i] = 0.f;
    if (w == 1) bar_arrive(NB_TURN0, 256);
    auto kstep = [&](int k, bool first, bool a_in_xch = false) {
      const int s = slot_of(k);
      mbar_wait(BAR(B_FULL + s), use_of(k) & 1);
      CT(64 + k);
      bar_sync(turn_me, 256);
      const uint64_t da = make_desc(sb + (a_in_xch ? OFF_XCH + s * 16384 : s * ST_BYTES) + w * 8192), db = make_desc(sb + s * ST_BYTES + A_BYTES);
      wgmma_fence();
      wgmma_n256(acc, da, db, !first);
#pragma unroll
      for (int kk = 1; kk < 4; kk++) wgmma_n256(acc, da + kk * 2, db + kk * 2, 1);
      wgmma_commit();
      bar_arrive(turn_other, 256);
    };
    auto release = [&](int s) { if (t == 0) mbar_arrive(BAR(B_EMPTY + s)); };
    auto kdone = [&](int k) { wgmma_wait0(); release(slot_of(k)); };
    auto wgmma_wait1 = [&]() { asm volatile("wgmma.wait_group.sync.aligned 1;" ::: "memory"); };

#pragma unroll 1
    for (int k = 0; k < 14; k++) {
      kstep(k, k == 0);
      if (k == 0) CT(0);
      if (k == 8 && warp == 2 && lane < 2) pkt_st128(&p.s->abflag[((eps * 2 + m) * 8 + tau) * 2 + lane], 0, 0, 0, 0);
      kdone(k);
    }
    uint32_t R[64];
    uint32_t tag;
    {
      const uint32_t rsa = sb + OFF_RS + q * 144;
      const uint64_t da2 = make_desc(sb + 2 * ST_BYTES + w * 8192), db2 = make_desc(sb + 2 * ST_BYTES + A_BYTES);
      const uint64_t da3 = make_desc(sb + 3 * ST_BYTES + w * 8192), db3 = make_desc(sb + 3 * ST_BYTES + A_BYTES);
      mbar_wait(BAR(B_FULL + 2), 1);
      CT(64 + 14);
      bar_sync(turn_me, 256);
      wgmma_fence();
#pragma unroll
      for (int kk = 0; kk < 4; kk++) wgmma_n256(acc, da2 + kk * 2, db2 + kk * 2, 1);
      wgmma_commit();
      mbar_wait(BAR(B_FULL + 3), 1);
      CT(64 + 15);
      wgmma_fence();
      wgmma_n256(acc, da3, db3, 1);
      wgmma_n256(acc, da3 + 2, db3 + 2, 1);
      wgmma_commit();
      mbar_wait(BAR(B_STAT), 0);
      tag = SM_(uint32_t, OFF_TAG);
#pragma unroll
      for (int i = 0; i < 8; i++) { const uint4 v = lds128_v(rsa + i * 16); R[8 * i] = v.x; R[8 * i + 2] = v.y; R[8 * i + 4] = v.z; R[8 * i + 6] = v.w; }
      wgmma_wait1();
      release(2);
      wgmma_fence();
      wgmma_n256(acc, da3 + 4, db3 + 4, 1);
      wgmma_n256(acc, da3 + 6, db3 + 6, 1);
      wgmma_n256(acc, make_desc_noswz(sb + OFF_EXA + w * 2048), make_desc_noswz(sb + OFF_EXB), 1);
      wgmma_commit();
      bar_arrive(turn_other, 256);
      kdone(15);
      mbar_wait(BAR(B_STAT), 0);
    }
    fence_acc(acc);
    CT(1);
    auto pack = [&](auto cc) {
      constexpr int c = decltype(cc)::value;
#pragma unroll
      for (int j = 8 * c; j < 8 * c + 8; j++) {
        const uint32_t rs = R[2 * j];
        const float* ac = &acc[4 * j];
        R[2 * j] = bmul2(pack_bf16(ac[0], ac[1]), rs);
        R[2 * j + 1] = bmul2(pack_bf16(ac[2], ac[3]), rs);
      }
    };
    auto put_chunk = [&](auto cc) {
      constexpr int c = decltype(cc)::value;
      const int rho = 16 * wi + (lane & 15);
#pragma unroll
      for (int j = 8 * c; j < 8 * c + 8; j += 2) {
        const int chunk = (j & 7) + (lane >> 4);
        stsm_x4(sb + chunk_off(c, w) + rho * 128 + ((chunk ^ (lane & 7)) << 4), R[2 * j], R[2 * j + 1], R[2 * j + 2], R[2 * j + 3]);
      }
    };
    auto staged = [&](int bar) {
      fence_async_smem();
      __syncwarp();
      if (lane == 0) mbar_arrive(BAR(bar));
    };
    auto mma_rs = [&](auto cc, auto k0, auto k1) {
      constexpr int c = decltype(cc)::value;
      const uint64_t db = make_desc(sb + c * ST_BYTES + A_BYTES);
#pragma unroll
      for (int kk = decltype(k0)::value; kk < decltype(k1)::value; kk++)
        wgmma_n256_rs(acc, R[16 * c + 4 * kk], R[16 * c + 4 * kk + 1], R[16 * c + 4 * kk + 2], R[16 * c + 4 * kk + 3], db + kk * 2, c + kk > 0);
      wgmma_commit();
    };
    auto kdone_x = [&](int k, auto ic) {
      constexpr int i = decltype(ic)::value;
      uint32_t r[8];
#pragma unroll
      for (int z = 0; z < 2; z++) {
        const int tr = 32 * (i & 1) + 16 * z + 8 * (lane >> 4) + (lane & 7), chunk = 2 * wi + ((lane >> 3) & 1);
        ldsm_x4_t(sb + (i >> 1) * ST_BYTES + w * 8192 + tr * 128 + ((chunk ^ (lane & 7)) << 4), r[4 * z], r[4 * z + 1], r[4 * z + 2], r[4 * z + 3]);
      }
      float f[16];
#pragma unroll
      for (int z = 0; z < 8; z++) { f[2 * z] = bf_lo(r[z]); f[2 * z + 1] = bf_hi(r[z]); }
#pragma unroll
      for (int z = 0; z < 16; z++) asm volatile("" : "+f"(f[z]));
      kdone(k);
#pragma unroll
      for (int z = 0; z < 16; z++) asm volatile("add.f32 %0, %0, %1;" : "+f"(acc[16 * i + z]) : "f"(f[z]));
    };
    pack(IC<0>());
    put_chunk(IC<0>());
    staged(w ? B_EPI0B : B_EPI);
    mbar_wait(BAR(B_STAT), 0);
    CT(21);
    pack(IC<1>());
    pack(IC<2>());
    pack(IC<3>());
#pragma unroll
    for (int i = 16; i < 64; i++) asm volatile("" : "+r"(R[i]));
    mbar_wait(BAR(B_FULL + 0), 0);
    CT(2);
    CT(64 + 16);
    bar_sync(turn_me, 256);
    wgmma_fence();
    mma_rs(IC<0>(), IC<0>(), IC<4>());
    mbar_wait(BAR(B_FULL + 1), 0);
    CT(64 + 17);
    wgmma_fence();
    mma_rs(IC<1>(), IC<0>(), IC<2>());
    wgmma_wait1();
    release(0);
    mma_rs(IC<1>(), IC<2>(), IC<4>());
    bar_arrive(turn_other, 256);
    kdone_x(17, IC<0>());
    static_for<2>([&](auto ic) {
      constexpr int c = 2 + decltype(ic)::value;
      mbar_wait(BAR(B_FULL + c), 0);
      CT(64 + 16 + c);
      bar_sync(turn_me, 256);
      wgmma_fence();
      mma_rs(IC<c>(), IC<0>(), IC<4>());
      bar_arrive(turn_other, 256);
      if (c == 2) { put_chunk(IC<1>()); staged(B_EPI + 1); }
      kdone_x(16 + c, IC<c - 1>());
    });
#pragma unroll 1
    for (int k = 20; k < 23; k++) {
      if (w == 1) mbar_wait(BAR(B_A20), 0);
      kstep(k, false, k < 22);
      if (k == 20) {
        kdone_x(k, IC<3>());
      } else {
        if (k == 21) { put_chunk(IC<2>()); if (PUBMODE == 2) fence_async_smem(); } else put_chunk(IC<3>());
        __syncwarp();
        if (lane == 0) mbar_arrive(BAR(B_EPI + k - 19));
        kdone(k);
      }
    }
    uint32_t wf[32][4];
    auto load_wf = [&](auto hc) {
      constexpr int h = decltype(hc)::value;
      const int d = w * 64 + (lane >> 4) * 8 + (lane & 7);
      const uint32_t ad = sb + round_off(h) + (lane & 8) * 1024 + d * 64 + ((wi ^ ((lane >> 1) & 3)) << 4);
#pragma unroll
      for (int i = 0; i < 4; i++) ldsm_x4_t(ad + i * 1024, wf[4 * h + i][0], wf[4 * h + i][1], wf[4 * h + i][2], wf[4 * h + i][3]);
    };
    auto load_wf_rest = [&]() { static_for<8 - NREG_H>([&](auto ic) { load_wf(IC<NREG_H + decltype(ic)::value>()); }); };
#pragma unroll
    for (int i = 0; i < 4 * NREG_H; i++) { wf[i][0] = 0; wf[i][1] = 0; wf[i][2] = 0; wf[i][3] = 0; }
    const int grp = tau * 2 + m;
#pragma unroll 1
    for (int k = 23; k < 46; k++) {
      kstep(k, false);
      if (moe) {
        static_for<NREG_H>([&](auto hc) {
          constexpr int h = decltype(hc)::value;
          if (k == mr_k(h) + 1) { mbar_wait(BAR(B_MR + (h & 1)), (h >> 1) & 1); load_wf(hc); }
        });
      }
      if (k == RESET_K && tid == 0) mbar_arrive(BAR(B_LATE));
      kdone(k);
    }
    asm volatile("barrier.cluster.arrive.relaxed.aligned;" ::: "memory");
    mbar_wait(BAR(B_STAT), 1);
    uint32_t wa[16][2];
    uint32_t cd = code_of(tag);
    uint4* hp_pub = &p.s->hstat[(grp * 8 + eps) * 128 + warp * 16 + g];
    const uint4* hp_poll = &p.s->hstat[(grp * 8 + 2 * q) * 128 + warp * 16 + g];
    const uint32_t vec_off = (2 * wi) * 512 + q * 128 + ((g ^ (2 * q)) << 4);
    {
      float as[64], ak[64];
      fence_acc(acc);
#pragma unroll
      for (int i = 0; i < 64; i++) asm volatile("mov.b32 %0, %1;" : "=f"(as[i]) : "f"(acc[64 + i]));
#pragma unroll
      for (int i = 0; i < 64; i++) asm volatile("mov.b32 %0, %1;" : "=f"(ak[i]) : "f"(acc[i]));
      const uint64_t da1 = make_desc(sb + 2 * ST_BYTES + w * 8192), db1 = make_desc(sb + 2 * ST_BYTES + A_BYTES);
      const uint64_t da2 = make_desc(sb + 3 * ST_BYTES + w * 8192), db2 = make_desc(sb + 3 * ST_BYTES + A_BYTES);
      mbar_wait(BAR(B_FULL + 2), 1);
      CT(64 + 46);
      mbar_wait(BAR(B_FULL + 3), 1);
      CT(64 + 47);
      bar_sync(turn_me, 256);
      wgmma_fence();
#pragma unroll
      for (int kk = 0; kk < 4; kk++) wgmma_n128(as, da1 + kk * 2, db1 + 1024 + kk * 2);
#pragma unroll
      for (int kk = 0; kk < 4; kk++) wgmma_n128(as, da2 + kk * 2, db2 + 1024 + kk * 2);
      wgmma_commit();
      bar_arrive(turn_other, 256);
      const uint32_t rx = mapa(sb + OFF_PEER + w * 4096 + vec_off, 1 - m), rb = mapa(BAR(B_XCH), 1 - m);
      asm volatile("barrier.cluster.wait.aligned;" ::: "memory");
      CT(24);
      wgmma_wait0();
      fence_acc64(as);
      CT(25);
      auto keep = [&]() {
        bar_sync(turn_me, 256);
        wgmma_fence();
#pragma unroll
        for (int kk = 0; kk < 4; kk++) wgmma_n128(ak, da1 + kk * 2, db1 + kk * 2);
        wgmma_commit();
#pragma unroll
        for (int kk = 0; kk < 4; kk++) wgmma_n128(ak, da2 + kk * 2, db2 + kk * 2);
        wgmma_commit();
        if (w == 0) bar_arrive(turn_other, 256);
      };
#pragma unroll
      for (int i = 0; i < 8; i++) {
        if (i == SEND_FIRST) keep();
        const float* ac = &as[16 * (i >> 1) + 2 * (i & 1)];
        st_async_v4(rx + (i >> 1) * 8192 + (i & 1) * 512, rb, pack_bf16(ac[0], ac[1]), pack_bf16(ac[4], ac[5]), pack_bf16(ac[8], ac[9]), pack_bf16(ac[12], ac[13]));
      }
      CT(26);
#pragma unroll
      for (int i = 0; i < 4; i++) {
        const uint4 v = lds128_v(sb + OFF_WR + q * 80 + i * 16);
        const uint32_t vv[4] = {v.x, v.y, v.z, v.w};
#pragma unroll
        for (int z = 0; z < 4; z++) {
          asm volatile("{\n.reg .pred p;\nsetp.ne.b32 p, %2, 0;\nselp.b32 %0, %1, 0x3F803F80, p;\n}" : "=r"(wa[4 * i + z][0]) : "r"(vv[z]), "r"(g & 1));
          asm volatile("{\n.reg .pred p;\nsetp.ne.b32 p, %2, 0;\nselp.b32 %0, %1, 0x3F803F80, p;\n}" : "=r"(wa[4 * i + z][1]) : "r"(vv[z]), "r"(g & 1));
        }
      }
      pin(cd); pin(hp_pub); pin(hp_poll);
      CT(27);
      wgmma_wait1();
      release(2);
      wgmma_wait0();
      fence_acc64(ak);
      CT(3);
#pragma unroll
      for (int i = 0; i < 8; i++) {
        const float* ac = &ak[16 * (i >> 1) + 2 * (i & 1)];
        sts128(sb + (2 + (i >> 2)) * ST_BYTES + w * 8192 + ((i >> 1) & 1) * 4096 + (i & 1) * 512 + vec_off,
               pack_bf16(ac[0], ac[1]), pack_bf16(ac[4], ac[5]), pack_bf16(ac[8], ac[9]), pack_bf16(ac[12], ac[13]));
      }
    }
    uint32_t h[8][4];
    {
      const int qq = 2 * (warp & 1) + ((lane >> 3) & 1);
      const uint32_t lo = (lane >> 4) * 512 + qq * 128 + (((lane & 7) ^ (2 * qq)) << 4);
      bar_sync(NB_BOTH, 256);
#pragma unroll
      for (int ks = 0; ks < 8; ks++)
        ldsm_x4_t(sb + (2 + w) * ST_BYTES + (ks >> 2) * 8192 + (wi >> 1) * 4096 + (ks & 3) * 1024 + lo, h[ks][0], h[ks][1], h[ks][2], h[ks][3]);
      CT(28);
      mbar_wait_cluster(BAR(B_XCH), 0);
      CT(4);
      uint32_t r[8][4];
#pragma unroll
      for (int ks = 0; ks < 8; ks++) ldsm_x4_t(sb + OFF_PEER + (warp >> 1) * 8192 + ks * 1024 + lo, r[ks][0], r[ks][1], r[ks][2], r[ks][3]);
      float d[4][4] = {};
#pragma unroll
      for (int ks = 0; ks < 8; ks++) {
#pragma unroll
        for (int i = 0; i < 4; i++) {
          h[ks][i] = badd2(h[ks][i], r[ks][i]);
          mma1688(d[i], h[ks][i], wa[2 * ks + (i >> 1)][i & 1], h[ks][i]);
        }
      }
#pragma unroll
      for (int i = 0; i < 2; i++) {
        const float sq = (g & 1) ? d[i][1] + d[i + 2][1] : d[i][0] + d[i + 2][0];
        const float e0 = d[i][2] + d[i + 2][2], e1 = d[i][3] + d[i + 2][3];
        const float other = __shfl_xor_sync(0xffffffffu, (g & 1) ? e0 : e1, 4);
        if (q == (g >> 1)) pkt_st128(hp_pub + 8 * i, with_bit((g & 1) ? other : e0, cd), with_bit(sq, cd >> 1), __float_as_uint((g & 1) ? e1 : other), tag);
      }
    }
    CT(5);
    if (tid == 0) mbar_arrive(BAR(B_KEY));
    delay_clk<HOP1_DELAY>();
    float m_bf, sd, inv_sd, r_bf;
    uint4* key_pub = &p.s->key[((lane & 7) * 16 + grp) * 2];
    uint4* cand_pub = &p.s->cand[grp * 256 + eps * 32 + q];
    uint32_t trow_inv = 0xFFFFu - (uint32_t)(grp * 128 + 32 * (warp >> 1) + 8 * (g >> 1) + 4 * (warp & 1) + (q & 2) + (g & 1));
    {
      uint4 u[4];
#pragma unroll
      for (int i = 0; i < 4; i++) u[i] = pkt_ld128(hp_poll + (i & 1) * 128 + (i >> 1) * 8);
      const float wsum = SM_(float, OFF_WSUM);
      pin(key_pub); pin(cand_pub); pin(trow_inv);
      uint32_t n = 0;
      while (true) {
        bool ok[4];
#pragma unroll
        for (int i = 0; i < 4; i++) ok[i] = u[i].w == tag && pair_code(u[i].x, u[i].y) == cd;
        const bool all = __all_sync(0xffffffffu, ok[0] && ok[1] && ok[2] && ok[3]);
        if (all || ++n > SPIN_LIMIT) break;
#pragma unroll
        for (int i = 0; i < 4; i++) pkt_ld128_if(u[i], hp_poll + (i & 1) * 128 + (i >> 1) * 8, !ok[i]);
      }
      CT(6);
      float a[3], b[3];
      a[0] = __uint_as_float(u[0].x & ~1u) + __uint_as_float(u[1].x & ~1u); b[0] = __uint_as_float(u[2].x & ~1u) + __uint_as_float(u[3].x & ~1u);
      a[1] = __uint_as_float(u[0].y & ~1u) + __uint_as_float(u[1].y & ~1u); b[1] = __uint_as_float(u[2].y & ~1u) + __uint_as_float(u[3].y & ~1u);
      a[2] = __uint_as_float(u[0].z) + __uint_as_float(u[1].z); b[2] = __uint_as_float(u[2].z) + __uint_as_float(u[3].z);
#pragma unroll
      for (int i = 0; i < 3; i++) {
        a[i] = ((q & 2) ? b[i] : a[i]) + __shfl_xor_sync(0xffffffffu, (q & 2) ? a[i] : b[i], 2);
        a[i] += __shfl_xor_sync(0xffffffffu, a[i], 1);
      }
      const float mu = a[0] * (1.f / 1024.f);
      m_bf = bf16r(mu);
      sd = ln_sd(a[1] * (1.f / 1024.f) - mu * mu);
      inv_sd = rcp_fast(sd);
      r_bf = bf16r((a[2] - m_bf * wsum) * inv_sd);
    }
    {
      const uint32_t u = __float_as_uint(r_bf);
      const uint32_t ord = (u & 0x80000000u) ? ~u : (u | 0x80000000u);
      const uint32_t key = (ord & 0xFFFF0000u) | trow_inv;
      const uint32_t wk = __reduce_max_sync(0xffffffffu, key);
      if (key == wk) SM_(uint2, OFF_WKEY + warp * 8) = make_uint2(wk, (__float_as_uint(m_bf) >> 16) | __float_as_uint(sd));
      const uint32_t wmask = __ballot_sync(0xffffffffu, key == wk);
      const bool hi = (wmask & 0xCCCCCCCCu) != 0;
      uint32_t c[16];
#pragma unroll
      for (int ks = 0; ks < 8; ks++) { c[2 * ks] = hi ? h[ks][1] : h[ks][0]; c[2 * ks + 1] = hi ? h[ks][3] : h[ks][2]; }
      bar_sync(NB_BOTH, 256);
      const uint2 km = SM_(uint2, OFF_WKEY + (lane & 7) * 8);
      const uint32_t bk = __reduce_max_sync(0xffffffffu, km.x);
      if (wk == bk) {
        if ((wmask >> (lane & 28)) & 15) {
#pragma unroll
          for (int ks = 0; ks < 8; ks++) pkt_st128(cand_pub + ks * 4, c[2 * ks], tag, c[2 * ks + 1], tag);
        }
      } else if (eps == 0) {
        const uint32_t kx = __shfl_sync(0xffffffffu, km.x, warp ^ 1), ms = __shfl_sync(0xffffffffu, km.y, warp ^ 1);
        if (kx == bk && lane < 8) pkt_st128(key_pub, bk, tag, ms, tag);
      }
      CT(7);
    }
    {
      const float ih = bf16r(inv_sd);
      const uint32_t nm = pack_bf16(-m_bf, -m_bf), iv = pack_bf16(ih, inv_sd - ih);
      const uint32_t nm_o = __shfl_xor_sync(0xffffffffu, nm, 2), iv_o = __shfl_xor_sync(0xffffffffu, iv, 2);
      const uint32_t nm2[2] = {(q & 2) ? nm_o : nm, (q & 2) ? nm : nm_o}, iv2[2] = {(q & 2) ? iv_o : iv, (q & 2) ? iv : iv_o};
      const uint32_t hi2[2] = {__byte_perm(iv2[0], 0, 0x1010), __byte_perm(iv2[1], 0, 0x1010)}, lo2[2] = {__byte_perm(iv2[0], 0, 0x3232), __byte_perm(iv2[1], 0, 0x3232)};
      const uint32_t oa = sb + OFF_OUT + (warp * 16 + (lane & 15)) * 128;
#pragma unroll
      for (int ks = 0; ks < 8; ks++) {
        uint32_t o[4];
#pragma unroll
        for (int i = 0; i < 4; i++) {
          const uint32_t dd = badd2(h[ks][i], nm2[i & 1]);
          o[i] = badd2(h[ks][i], bfma2(dd, hi2[i & 1], bmul2(dd, lo2[i & 1])));
        }
        stsm_x4(oa + (ks >> 2) * 16384 + (((2 * (ks & 3) + (lane >> 4)) ^ (lane & 7)) << 4), o[0], o[1], o[2], o[3]);
      }
      staged(B_OUT);
    }
    CT(8);
    uint32_t df[16][4];
    auto load_df = [&]() {
      const int frow = (lane & 7) + ((lane >> 4) << 3), hi = (lane >> 3) & 1;
      const uint32_t base = sb + down_off(warp >> 1) + (warp & 1) * 8192 + frow * 128;
#pragma unroll
      for (int mt = 0; mt < 8; mt++) {
#pragma unroll
        for (int ks = 0; ks < 2; ks++)
          ldsm_x4_t(base + (mt >> 2) * 4096 + ks * 2048 + (((2 * (mt & 3) + hi) ^ (lane & 7)) << 4),
                    df[2 * mt + ks][0], df[2 * mt + ks][1], df[2 * mt + ks][2], df[2 * mt + ks][3]);
      }
    };
    if (moe) {
      mbar_wait(BAR(B_GU), 0);
      load_wf_rest();
      mbar_wait(BAR(B_DN), 0);
      load_df();
    }
    uint4* y_pub = &p.s->ypart[cid * 256 + tid];
    uint32_t xs_ad = sb + OFF_XSEL + (8 * (g >> 2) + 4 * w + (g & 3)) * 32 + q * 8, gp_ad = sb + OFF_GP + (wi * 8 + g) * 16 + w * 8 + (q >> 1) * 4;
    pin(y_pub); pin(xs_ad); pin(gp_ad);
    mbar_wait(BAR(B_XS), 0);
    CT(9);
    if (moe) {
      float gd[8][4] = {};
      uint2 bx[4];
#pragma unroll
      for (int r = 0; r < 4; r++) bx[r] = smem_at<uint2>(xs_ad + r * 512);
#pragma unroll
      for (int r = 0; r < 4; r++) {
#pragma unroll
        for (int i = 0; i < 8; i++) mma16816(gd[i], wf[8 * r + i][0], wf[8 * r + i][1], wf[8 * r + i][2], wf[8 * r + i][3], bx[r].x, bx[r].y);
      }
      const float gs = sel4(q, gd[0][0] + gd[1][1], gd[2][0] + gd[3][1], gd[4][0] + gd[5][1], gd[6][0] + gd[7][1]);
      const float us = sel4(q, gd[0][2] + gd[1][3], gd[2][2] + gd[3][3], gd[4][2] + gd[5][3], gd[6][2] + gd[7][3]);
      float v = ((q & 2) ? us : gs) + __shfl_xor_sync(0xffffffffu, (q & 2) ? gs : us, 2);
      v += __shfl_xor_sync(0xffffffffu, v, 1);
      smem_at<float>(gp_ad) = v;
      CT(10);
      bar_sync(NB_BOTH, 256);
      uint32_t bq[4];
      {
        const float4 p0 = SM_(float4, OFF_GP + lane * 16);
        const float gt = bf16r(p0.x + p0.z), up = bf16r(p0.y + p0.w);
        const float act = bf16r(gt * sigmoid_fast(gt)) * up;
        const uint32_t pr = pack_bf16(act, __shfl_down_sync(0xffffffffu, act, 1));
#pragma unroll
        for (int i = 0; i < 4; i++) bq[i] = __shfl_sync(0xffffffffu, pr, 8 * i + 2 * q);
      }
      CT(11);
      float yd[8][4] = {};
#pragma unroll
      for (int ks = 0; ks < 2; ks++) {
#pragma unroll
        for (int mt = 0; mt < 8; mt++) mma16816(yd[mt], df[2 * mt + ks][0], df[2 * mt + ks][1], df[2 * mt + ks][2], df[2 * mt + ks][3], bq[2 * ks], bq[2 * ks + 1]);
      }
      pkt_st128(y_pub, with_bit(sel4(q, yd[0][0], yd[2][0], yd[4][0], yd[6][0]), cd), with_bit(sel4(q, yd[0][2], yd[2][2], yd[4][2], yd[6][2]), cd >> 1),
                with_bit(sel4(q, yd[1][0], yd[3][0], yd[5][0], yd[7][0]), cd), with_bit(sel4(q, yd[1][2], yd[3][2], yd[5][2], yd[7][2]), cd >> 1));
    } else {
      const long long tw = clock64();
      while (clock64() - tw < IDLE_WAIT_CLK) __nanosleep(100);
    }
    CT(12);
    const uint32_t kv = SM_(uint32_t, OFF_KV);
    const int tsel = 0xFFFF - (int)(kv & 0xFFFFu);
    const float r_sel = __uint_as_float((kv & 0x80000000u) ? (kv & 0x7FFF0000u) : (~kv & 0xFFFF0000u));
    const float sig = bf16r(sigmoid_fast(r_sel));
    const int pfin = 2 * cid + (tid & 1);
    const int col_fin = (pfin >> 5) * 128 + (pfin & 3) * 32 + ((pfin & 31) >> 2) + 8 * ((tid >> 1) & 3);
    const int sel_off = (col_fin >> 4) * 32 + ((col_fin & 7) >> 1) * 8 + ((col_fin >> 3) & 1) * 4 + (col_fin & 1) * 2;
    const float hn_fin = __uint_as_float((uint32_t)SM_(uint16_t, OFF_XSEL + sel_off) << 16), h_fin = __uint_as_float((uint32_t)SM_(uint16_t, OFF_HSEL + sel_off) << 16);
    bf16* out_fin = p.out + (size_t)tsel * 1024 + col_fin;
    {
      const uint4* src = &p.s->ypart[(16 + (tid >> 1)) * 256 + pfin];
      pin(src); pin(out_fin);
      uint4 v = make_uint4(0, 0, 0, 0);
      if (warp < 7) {
        delay_clk<HOP3_DELAY>();
        uint32_t n = 0;
        bool ok = false;
        do {
          pkt_ld128_if(v, src, !ok);
          ok = pair_code(v.x, v.y) == cd && pair_code(v.z, v.w) == cd;
        } while (!__all_sync(0xffffffffu, ok) && ++n < SPIN_LIMIT);
      }
      CT(13);
      const float y0 = __uint_as_float(v.x & ~1u), y1 = __uint_as_float(v.y & ~1u), y2 = __uint_as_float(v.z & ~1u), y3 = __uint_as_float(v.w & ~1u);
      const float a0 = ((lane & 2) ? y1 : y0) + __shfl_xor_sync(0xffffffffu, (lane & 2) ? y0 : y1, 2);
      const float a1 = ((lane & 2) ? y3 : y2) + __shfl_xor_sync(0xffffffffu, (lane & 2) ? y2 : y3, 2);
      float b = ((lane & 4) ? a1 : a0) + __shfl_xor_sync(0xffffffffu, (lane & 4) ? a0 : a1, 4);
      b += __shfl_xor_sync(0xffffffffu, b, 8);
      b += __shfl_xor_sync(0xffffffffu, b, 16);
      if (lane < 8) SM_(float, OFF_FIN + lane * 32 + warp * 4) = b;
    }
    bar_sync(NB_BOTH, 256);
    if (tid < 8) {
      const float4 y0 = SM_(float4, OFF_FIN + tid * 32), y1 = SM_(float4, OFF_FIN + tid * 32 + 16);
      const float y = ((y0.x + y0.y) + (y0.z + y0.w)) + ((y1.x + y1.y) + y1.z);
      *out_fin = __float2bfloat16_rn(h_fin + bf16r(hn_fin + bf16r(bf16r(y) * sig)));
      if (cid == 0 && tid == 0) st_relaxed32(&p.s->epoch, tag);
    }
    CT(14);
  }
}

__global__ void __launch_bounds__(384, 1) occupancy_probe_kernel() {}

typedef CUresult (*EncodeFn)(CUtensorMap*, CUtensorMapDataType, cuuint32_t, void*, const cuuint64_t*, const cuuint64_t*, const cuuint32_t*, const cuuint32_t*,
                             CUtensorMapInterleave, CUtensorMapSwizzle, CUtensorMapL2promotion, CUtensorMapFloatOOBfill);

static void make_tm(EncodeFn enc, CUtensorMap* tm, const void* ptr, uint64_t rows, uint64_t cols, uint32_t brows, uint32_t bcols, CUtensorMapSwizzle sw,
                    CUtensorMapL2promotion promo = DEF_PROMO) {
  cuuint64_t dims[2] = {cols, rows};
  cuuint64_t strides[1] = {cols * 2};
  cuuint32_t box[2] = {bcols, brows};
  cuuint32_t es[2] = {1, 1};
  enc(tm, CU_TENSOR_MAP_DATA_TYPE_BFLOAT16, 2, const_cast<void*>(ptr), dims, strides, box, es, CU_TENSOR_MAP_INTERLEAVE_NONE, sw,
      promo, CU_TENSOR_MAP_FLOAT_OOB_FILL_NONE);
}

extern "C" void kernel_launch(void* const* d_in, const int* in_sizes, int n_in, void* d_out, int out_size) {
  (void)in_sizes; (void)n_in; (void)out_size;
  static EncodeFn enc = nullptr;
  static void* abT = nullptr;
  static int map = 0;
  if (!enc) {
    void* fn = nullptr; cudaDriverEntryPointQueryResult st;
    cudaGetDriverEntryPoint("cuTensorMapEncodeTiled", &fn, cudaEnableDefault, &st);
    enc = (EncodeFn)fn;
    cudaGetSymbolAddress(&abT, g_scratch);
    cudaFuncSetAttribute(fnet_moe_kernel<0>, cudaFuncAttributeMaxDynamicSharedMemorySize, SMEM_TOTAL);
    cudaFuncSetAttribute(fnet_moe_kernel<1>, cudaFuncAttributeMaxDynamicSharedMemorySize, SMEM_TOTAL);
    cudaFuncSetAttribute(occupancy_probe_kernel, cudaFuncAttributeMaxDynamicSharedMemorySize, SMEM_TOTAL);
    cudaFuncSetAttribute(occupancy_probe_kernel, cudaFuncAttributeNonPortableClusterSizeAllowed, 1);
    auto max_clusters = [&](int size) {
      cudaLaunchConfig_t cfg = {};
      cfg.gridDim = dim3(128); cfg.blockDim = dim3(384); cfg.dynamicSmemBytes = SMEM_TOTAL;
      cudaLaunchAttribute at[1];
      at[0].id = cudaLaunchAttributeClusterDimension; at[0].val.clusterDim.x = size; at[0].val.clusterDim.y = 1; at[0].val.clusterDim.z = 1;
      cfg.attrs = at; cfg.numAttrs = 1;
      int ncl = 0;
      return cudaOccupancyMaxActiveClusters(&ncl, occupancy_probe_kernel, &cfg) == cudaSuccess ? ncl : 0;
    };
    int dev = 0, sms = 0;
    cudaGetDevice(&dev);
    cudaDeviceGetAttribute(&sms, cudaDevAttrMultiProcessorCount, dev);
    map = (!getenv("MAP1") && sms == 132 && max_clusters(2) == 66 && max_clusters(16) == 7) ? 0 : 1;
    (void)cudaGetLastError();
  }
  Params p;
  const bf16* x = (const bf16*)d_in[0];
  make_tm(enc, &p.tmD0, d_in[3], 1024, 1024, 128, 64, CU_TENSOR_MAP_SWIZZLE_128B, XD_PROMO);
  make_tm(enc, &p.tmD1, d_in[4], 1024, 1024, 128, 64, CU_TENSOR_MAP_SWIZZLE_128B, XD_PROMO);
  make_tm(enc, &p.tmX, x, 2048, 1024, 256, 64, CU_TENSOR_MAP_SWIZZLE_128B, XD_PROMO);
  make_tm(enc, &p.tmXr, x, 2048, 1024, 64, 64, CU_TENSOR_MAP_SWIZZLE_128B);
  make_tm(enc, &p.tmAbS, abT, 2048, 2048, 64, 64, CU_TENSOR_MAP_SWIZZLE_128B);
  make_tm(enc, &p.tmAbL, abT, 2048, 2048, 128, 64, CU_TENSOR_MAP_SWIZZLE_128B);
  make_tm(enc, &p.tmW0, d_in[1], 2048, 2048, 128, 64, CU_TENSOR_MAP_SWIZZLE_128B, W_PROMO);
  make_tm(enc, &p.tmW1, d_in[2], 2048, 2048, 128, 64, CU_TENSOR_MAP_SWIZZLE_128B, W_PROMO);
  {
    cuuint64_t dims[5] = {1024, 2, 4, 4, 64};
    cuuint64_t strides[4] = {2048, 8 * 2048, 2 * 2048, 32 * 2048};
    cuuint32_t box[5] = {64, 2, 4, 2, 1};
    cuuint32_t es[5] = {1, 1, 1, 1, 1};
    enc(&p.tmOut, CU_TENSOR_MAP_DATA_TYPE_BFLOAT16, 5, d_out, dims, strides, box, es, CU_TENSOR_MAP_INTERLEAVE_NONE, CU_TENSOR_MAP_SWIZZLE_128B,
        CU_TENSOR_MAP_L2_PROMOTION_NONE, CU_TENSOR_MAP_FLOAT_OOB_FILL_NONE);
  }
  make_tm(enc, &p.tmG, d_in[7], 1024, 3584, 128, 32, CU_TENSOR_MAP_SWIZZLE_64B, CU_TENSOR_MAP_L2_PROMOTION_L2_128B);
  make_tm(enc, &p.tmU, d_in[8], 1024, 3584, 128, 32, CU_TENSOR_MAP_SWIZZLE_64B, CU_TENSOR_MAP_L2_PROMOTION_L2_128B);
  make_tm(enc, &p.tmDn, d_in[9], 3584, 1024, 32, 64, CU_TENSOR_MAP_SWIZZLE_128B);
  p.x = x; p.Dre = (const bf16*)d_in[3]; p.Dim = (const bf16*)d_in[4];
  p.wr = (const bf16*)d_in[6]; p.wdown = (const bf16*)d_in[9]; p.wgate = (const bf16*)d_in[7]; p.wup = (const bf16*)d_in[8];
  p.out = (bf16*)d_out; p.s = (Scratch*)abT;
  if (map == 1) fnet_moe_kernel<1><<<128, 384, SMEM_TOTAL>>>(p);
  else fnet_moe_kernel<0><<<132, 384, SMEM_TOTAL>>>(p);
}
```

```cpp
#include <cuda.h>
#include <cuda_runtime.h>
#include <cuda_bf16.h>
#include <stdint.h>
#include <type_traits>

typedef __nv_bfloat16 bf16;

constexpr int REG_C = 232, REG_P = 40;
__device__ __forceinline__ int kblock(int tau, int j) {
  int i = j - 4;
  if (i >= 19 && i < 23) i += i < 21 ? 2 : -2;
  const int c = (i * 37) >> 8;
  return j < 4 ? tau * 4 + j : ((tau + 1 + i - 7 * c) & 7) * 4 + c;
}
constexpr int AUX_AFTER = 1, AUX_AFTER2 = 1;
constexpr int PF_K0 = 8, PF_N0 = 2, PF_K1 = 24;
constexpr int WPF_K0 = 12, WPF_N = 10;
constexpr int PUB_K1 = 22;
constexpr int NREG_H = 5;
constexpr int MR_K0 = 29, MR_P = 6;
constexpr int RESET_K = 39;
constexpr int SEND_FIRST = 2;
constexpr int GATHER_NS = 400;
constexpr int MOE_PACE_CLK = 300;
constexpr int OUT_PACE_CLK = 100;
constexpr int HOP1_DELAY = 150, HOP3_DELAY = 300;
constexpr int SPEC_MIN = 10;
constexpr int IDLE_WAIT_CLK = 1200;
__host__ __device__ constexpr int mr_k(int h) { return MR_K0 + MR_P * (h >> 1) + 2 * (h & 1); }
constexpr int A_BYTES = 128 * 64 * 2;
constexpr int B_BYTES = 256 * 64 * 2;
constexpr int ST_BYTES = A_BYTES + B_BYTES;
constexpr int OFF_XCH = 4 * ST_BYTES;
constexpr int OFF_BAR = OFF_XCH + 32768;
constexpr int OFF_WR = OFF_BAR + 384;
constexpr int OFF_RS = OFF_WR + 384;
constexpr int OFF_PUB = OFF_RS + 640;
constexpr int OFF_MISC = OFF_PUB + 768;
constexpr int SMEM_TOTAL = OFF_MISC + 256;
constexpr int OFF_WSUM = OFF_MISC, OFF_TAG = OFF_MISC + 4;
constexpr int OFF_SEEN = OFF_MISC + 8;
constexpr int OFF_KV = OFF_MISC + 12;
constexpr int OFF_WKEY = OFF_MISC + 32;
constexpr int OFF_EXA = OFF_XCH;
constexpr int OFF_EXB = OFF_XCH + 4096;
__host__ __device__ constexpr int chunk_off(int c, int w) { return (c < 2 ? (c + 2) * ST_BYTES : OFF_XCH + (c - 2) * 16384) + w * 8192; }
__host__ __device__ constexpr int late_off(int i) { return i < 4 ? i * 16384 : 2 * ST_BYTES + A_BYTES + (i - 4) * 16384; }
__host__ __device__ constexpr int round_off(int h) { return h < NREG_H + 2 ? OFF_XCH + (h & 1) * 16384 : late_off(h - NREG_H - 2); }
__host__ __device__ constexpr int down_off(int i) { return late_off(6 - NREG_H + i); }
constexpr int OFF_PEER = ST_BYTES + A_BYTES;
constexpr int OFF_OUT = 3 * ST_BYTES + A_BYTES;
constexpr int OFF_XSEL = OFF_PEER;
constexpr int OFF_HSEL = OFF_PEER + 4096;
constexpr int OFF_GP = OFF_PEER + 8192;
constexpr int OFF_FIN = OFF_PEER + 9216;
__device__ __forceinline__ int slot_of(int k) { return k & 3; }
__device__ __forceinline__ int use_of(int k) { return k >> 2; }
enum { B_FULL = 0, B_EMPTY = 4, B_EPI = 8, B_STD = 12, B_EPI0B = 16, B_LATE = 17, B_STAT = 18, B_XCH = 19, B_MR = 20  , B_GU = 22,
       B_DN = 23, B_AUX = 24  , B_OUT = 26, B_KEY = 27, B_XS = 28, B_A20 = 29, B_STDA = 30, B_COUNT = 31 };
enum { NB_TURN0 = 1, NB_TURN1 = 2, NB_BOTH = 5, NB_AUX = 6 };

struct Scratch {
  bf16 abT[2048 * 2048];
  uint2 xstat[2048];
  uint2 dsum[2048];
  uint4 abflag[16 * 8 * 2];
  uint4 hstat[16 * 8 * 128];
  uint4 cand[16 * 256];
  uint4 key[8 * 16 * 2];
  uint4 ypart[128 * 256];
  uint32_t epoch;
};
__device__ __align__(1024) Scratch g_scratch;

struct Params {
  Scratch* s; bf16* out;
  const bf16* x; const bf16* Dre; const bf16* Dim; const bf16* wr; const bf16* wdown; const bf16* wgate; const bf16* wup;
  CUtensorMap tmX, tmD0, tmD1, tmXr, tmAbS, tmAbL, tmW0, tmW1, tmOut, tmG, tmU, tmDn;
};

#define SPIN_LIMIT (1u << 14)
#define MBAR_LIMIT (1u << 10)
__device__ __forceinline__ uint32_t smem_u32(const void* p) { return (uint32_t)__cvta_generic_to_shared(p); }
__device__ __forceinline__ void mbar_init(uint32_t bar, uint32_t cnt) { asm volatile("mbarrier.init.shared::cta.b64 [%0], %1;" :: "r"(bar), "r"(cnt) : "memory"); }
__device__ __forceinline__ void mbar_expect_tx(uint32_t bar, uint32_t bytes) { asm volatile("mbarrier.arrive.expect_tx.shared::cta.b64 _, [%0], %1;" :: "r"(bar), "r"(bytes) : "memory"); }
__device__ __forceinline__ void mbar_arrive(uint32_t bar) { asm volatile("mbarrier.arrive.shared::cta.b64 _, [%0];" :: "r"(bar) : "memory"); }
__device__ __forceinline__ void mbar_wait(uint32_t bar, uint32_t parity) {
  uint32_t ok, n = 0;
  do {
    asm volatile("{\n.reg .pred p;\nmbarrier.try_wait.parity.shared::cta.b64 p, [%1], %2;\nselp.u32 %0, 1, 0, p;\n}\n" : "=r"(ok) : "r"(bar), "r"(parity) : "memory");
  } while (!ok && ++n < MBAR_LIMIT);
}
__device__ __forceinline__ bool mbar_test(uint32_t bar, uint32_t parity) {
  uint32_t ok;
  asm volatile("{\n.reg .pred p;\nmbarrier.test_wait.parity.shared::cta.b64 p, [%1], %2;\nselp.u32 %0, 1, 0, p;\n}\n" : "=r"(ok) : "r"(bar), "r"(parity) : "memory");
  return ok != 0;
}
__device__ __forceinline__ void mbar_wait_cluster(uint32_t bar, uint32_t parity) {
  uint32_t ok, n = 0;
  do {
    asm volatile("{\n.reg .pred p;\nmbarrier.try_wait.parity.acquire.cluster.shared::cta.b64 p, [%1], %2;\nselp.u32 %0, 1, 0, p;\n}\n" : "=r"(ok) : "r"(bar), "r"(parity) : "memory");
  } while (!ok && ++n < MBAR_LIMIT);
}
__device__ __forceinline__ void tma_load_2d(uint32_t dst, const CUtensorMap* tm, uint32_t bar, int c0, int c1) {
  asm volatile("cp.async.bulk.tensor.2d.shared::cluster.global.mbarrier::complete_tx::bytes [%0], [%1, {%3, %4}], [%2];"
    :: "r"(dst), "l"(tm), "r"(bar), "r"(c0), "r"(c1) : "memory");
}
__device__ __forceinline__ void tma_load_2d_hint(uint32_t dst, const CUtensorMap* tm, uint32_t bar, int c0, int c1, uint64_t pol) {
  asm volatile("cp.async.bulk.tensor.2d.shared::cluster.global.mbarrier::complete_tx::bytes.L2::cache_hint [%0], [%1, {%3, %4}], [%2], %5;"
    :: "r"(dst), "l"(tm), "r"(bar), "r"(c0), "r"(c1), "l"(pol) : "memory");
}
__device__ __forceinline__ uint64_t policy_evict_first() { uint64_t p; asm volatile("createpolicy.fractional.L2::evict_first.b64 %0, 1.0;" : "=l"(p)); return p; }
__device__ __forceinline__ void tma_store_2d(const CUtensorMap* tm, uint32_t src, int c0, int c1) {
  asm volatile("cp.async.bulk.tensor.2d.global.shared::cta.bulk_group [%0, {%2, %3}], [%1];" :: "l"(tm), "r"(src), "r"(c0), "r"(c1) : "memory");
}
__device__ __forceinline__ void bulk_load(uint32_t dst, const void* src, uint32_t bytes, uint32_t bar) {
  asm volatile("cp.async.bulk.shared::cluster.global.mbarrier::complete_tx::bytes [%0], [%1], %2, [%3];" :: "r"(dst), "l"(src), "r"(bytes), "r"(bar) : "memory");
}
__device__ __forceinline__ void bulk_commit() { asm volatile("cp.async.bulk.commit_group;" ::: "memory"); }
__device__ __forceinline__ void bulk_wait_all() { asm volatile("cp.async.bulk.wait_group 0;" ::: "memory"); }
__device__ __forceinline__ void fence_async_smem() { asm volatile("fence.proxy.async.shared::cta;" ::: "memory"); }
__device__ __forceinline__ void wgmma_fence() { asm volatile("wgmma.fence.sync.aligned;" ::: "memory"); }
__device__ __forceinline__ void wgmma_commit() { asm volatile("wgmma.commit_group.sync.aligned;" ::: "memory"); }
__device__ __forceinline__ void wgmma_wait0() { asm volatile("wgmma.wait_group.sync.aligned 0;" ::: "memory"); }
__device__ __forceinline__ void bar_sync(int id, int n) { asm volatile("bar.sync %0, %1;" :: "r"(id), "r"(n) : "memory"); }
__device__ __forceinline__ void bar_arrive(int id, int n) { asm volatile("bar.arrive %0, %1;" :: "r"(id), "r"(n) : "memory"); }
template<int R> __device__ __forceinline__ void reg_inc() { asm volatile("setmaxnreg.inc.sync.aligned.u32 %0;" :: "n"(R)); }
template<int R> __device__ __forceinline__ void reg_dec() { asm volatile("setmaxnreg.dec.sync.aligned.u32 %0;" :: "n"(R)); }
__device__ __forceinline__ bool elect_one() {
  uint32_t p;
  asm volatile("{\n.reg .pred q;\nelect.sync _|q, 0xffffffff;\nselp.u32 %0, 1, 0, q;\n}\n" : "=r"(p));
  return p != 0;
}
__device__ __forceinline__ uint32_t mapa(uint32_t addr, uint32_t cta) { uint32_t r; asm volatile("mapa.shared::cluster.u32 %0, %1, %2;" : "=r"(r) : "r"(addr), "r"(cta)); return r; }
__device__ __forceinline__ void st_async_v4(uint32_t addr, uint32_t bar, uint32_t a, uint32_t b, uint32_t c, uint32_t d) {
  asm volatile("st.async.weak.shared::cluster.mbarrier::complete_tx::bytes.v4.b32 [%0], {%2, %3, %4, %5}, [%1];" :: "r"(addr), "r"(bar), "r"(a), "r"(b), "r"(c), "r"(d) : "memory");
}
__device__ __forceinline__ void stsm_x4(uint32_t addr, uint32_t a, uint32_t b, uint32_t c, uint32_t d) {
  asm volatile("stmatrix.sync.aligned.m8n8.x4.shared.b16 [%0], {%1, %2, %3, %4};" :: "r"(addr), "r"(a), "r"(b), "r"(c), "r"(d));
}
__device__ __forceinline__ uint4 lds128_v(uint32_t addr) { uint4 v; asm volatile("ld.shared.v4.b32 {%0, %1, %2, %3}, [%4];" : "=r"(v.x), "=r"(v.y), "=r"(v.z), "=r"(v.w) : "r"(addr)); return v; }
extern __shared__ __align__(1024) uint8_t smem_raw[];
template<class T> __device__ __forceinline__ T& smem_at(uint32_t addr) { return *reinterpret_cast<T*>(__cvta_shared_to_generic(addr)); }
#define SM_(T, off) smem_at<T>(sb + (off))
__device__ __forceinline__ uint4 ldg_nc128(const void* p) { uint4 v; asm volatile("ld.global.nc.v4.b32 {%0, %1, %2, %3}, [%4];" : "=r"(v.x), "=r"(v.y), "=r"(v.z), "=r"(v.w) : "l"(p)); return v; }
__device__ __forceinline__ void pkt_st128(void* p, uint32_t a, uint32_t b, uint32_t c, uint32_t d) {
  asm volatile("{\n.reg .b128 v;\n.reg .b64 lo, hi;\nmov.b64 lo, {%1, %2};\nmov.b64 hi, {%3, %4};\nmov.b128 v, {lo, hi};\nst.relaxed.gpu.global.b128 [%0], v;\n}\n"
    :: "l"(p), "r"(a), "r"(b), "r"(c), "r"(d) : "memory");
}
__device__ __forceinline__ uint4 pkt_ld128(const void* p) {
  uint4 r;
  asm volatile("{\n.reg .b128 v;\n.reg .b64 lo, hi;\nld.relaxed.gpu.global.b128 v, [%4];\nmov.b128 {lo, hi}, v;\nmov.b64 {%0, %1}, lo;\nmov.b64 {%2, %3}, hi;\n}\n"
    : "=r"(r.x), "=r"(r.y), "=r"(r.z), "=r"(r.w) : "l"(p) : "memory");
  return r;
}
__device__ __forceinline__ void pkt_ld128_if(uint4& r, const void* p, bool cond) {
  asm volatile("{\n.reg .pred q;\nsetp.ne.b32 q, %5, 0;\n@q ld.relaxed.gpu.global.v4.b32 {%0, %1, %2, %3}, [%4];\n}\n"
    : "+r"(r.x), "+r"(r.y), "+r"(r.z), "+r"(r.w) : "l"(p), "r"((uint32_t)cond) : "memory");
}
__device__ __forceinline__ void pkt_st64(void* p, uint32_t a, uint32_t b) {
  asm volatile("{\n.reg .b64 v;\nmov.b64 v, {%1, %2};\nst.relaxed.gpu.global.b64 [%0], v;\n}\n" :: "l"(p), "r"(a), "r"(b) : "memory");
}
__device__ __forceinline__ uint2 pkt_ld64(const void* p) {
  uint2 r;
  asm volatile("{\n.reg .b64 v;\nld.relaxed.gpu.global.b64 v, [%2];\nmov.b64 {%0, %1}, v;\n}\n" : "=r"(r.x), "=r"(r.y) : "l"(p) : "memory");
  return r;
}
__device__ __forceinline__ uint32_t ld_relaxed32(const void* p) { uint32_t v; asm volatile("ld.relaxed.gpu.global.b32 %0, [%1];" : "=r"(v) : "l"(p) : "memory"); return v; }
__device__ __forceinline__ void st_relaxed32(void* p, uint32_t v) { asm volatile("st.relaxed.gpu.global.b32 [%0], %1;" :: "l"(p), "r"(v) : "memory"); }
__device__ __forceinline__ uint32_t code_of(uint32_t tag) { return tag % 3u + 1u; }
__device__ __forceinline__ uint32_t with_bit(float v, uint32_t bit) { return (__float_as_uint(v) & ~1u) | (bit & 1u); }
__device__ __forceinline__ uint32_t pair_code(uint32_t a, uint32_t b) { return (a & 1u) | ((b & 1u) << 1); }
__device__ __forceinline__ uint32_t pack_bf16(float lo, float hi) { uint32_t r; asm("cvt.rn.bf16x2.f32 %0, %1, %2;" : "=r"(r) : "f"(hi), "f"(lo)); return r; }
__device__ __forceinline__ float bf_lo(uint32_t v) { return __uint_as_float(v << 16); }
__device__ __forceinline__ float bf_hi(uint32_t v) { return __uint_as_float(v & 0xFFFF0000u); }
__device__ __forceinline__ float bf16r(float x) { return __uint_as_float(pack_bf16(0.f, x)); }
__device__ __forceinline__ uint32_t badd2(uint32_t a, uint32_t b) { uint32_t r; asm("add.rn.bf16x2 %0, %1, %2;" : "=r"(r) : "r"(a), "r"(b)); return r; }
__device__ __forceinline__ uint32_t bmul2(uint32_t a, uint32_t b) { uint32_t r; asm("mul.rn.bf16x2 %0, %1, %2;" : "=r"(r) : "r"(a), "r"(b)); return r; }
__device__ __forceinline__ float warp_sum(float v) {
#pragma unroll
  for (int o = 16; o > 0; o >>= 1) v += __shfl_xor_sync(0xffffffffu, v, o);
  return v;
}
__device__ __forceinline__ uint64_t make_desc(uint32_t addr) {
  return (uint64_t)((addr & 0x3FFFF) >> 4) | ((uint64_t)1 << 16) | ((uint64_t)64 << 32) | ((uint64_t)1 << 62);
}
__device__ __forceinline__ uint64_t make_desc_noswz(uint32_t addr) {
  return (uint64_t)((addr & 0x3FFFF) >> 4) | ((uint64_t)8 << 16) | ((uint64_t)16 << 32);
}
__device__ __forceinline__ void wgmma_n256(float (&d)[128], uint64_t da, uint64_t db, int scale_d) {
  asm volatile("{\n.reg .pred p;\nsetp.ne.b32 p, %130, 0;\n"
    "wgmma.mma_async.sync.aligned.m64n256k16.f32.bf16.bf16 "
    "{%0, %1, %2, %3, %4, %5, %6, %7, %8, %9, %10, %11, %12, %13, %14, %15, %16, %17, %18, %19, %20, %21, %22, %23, %24, %25, %26, %27, %28, %29, %30, %31, "
    "%32, %33, %34, %35, %36, %37, %38, %39, %40, %41, %42, %43, %44, %45, %46, %47, %48, %49, %50, %51, %52, %53, %54, %55, %56, %57, %58, %59, %60, %61, %62, %63, "
    "%64, %65, %66, %67, %68, %69, %70, %71, %72, %73, %74, %75, %76, %77, %78, %79, %80, %81, %82, %83, %84, %85, %86, %87, %88, %89, %90, %91, %92, %93, %94, %95, "
    "%96, %97, %98, %99, %100, %101, %102, %103, %104, %105, %106, %107, %108, %109, %110, %111, %112, %113, %114, %115, %116, %117, %118, %119, %120, %121, %122, %123, %124, %125, %126, %127}, "
    "%128, %129, p, 1, 1, 0, 0;\n}\n"
    : "+f"(d[0]), "+f"(d[1]), "+f"(d[2]), "+f"(d[3]), "+f"(d[4]), "+f"(d[5]), "+f"(d[6]), "+f"(d[7]),
      "+f"(d[8]), "+f"(d[9]), "+f"(d[10]), "+f"(d[11]), "+f"(d[12]), "+f"(d[13]), "+f"(d[14]), "+f"(d[15]),
      "+f"(d[16]), "+f"(d[17]), "+f"(d[18]), "+f"(d[19]), "+f"(d[20]), "+f"(d[21]), "+f"(d[22]), "+f"(d[23]),
      "+f"(d[24]), "+f"(d[25]), "+f"(d[26]), "+f"(d[27]), "+f"(d[28]), "+f"(d[29]), "+f"(d[30]), "+f"(d[31]),
      "+f"(d[32]), "+f"(d[33]), "+f"(d[34]), "+f"(d[35]), "+f"(d[36]), "+f"(d[37]), "+f"(d[38]), "+f"(d[39]),
      "+f"(d[40]), "+f"(d[41]), "+f"(d[42]), "+f"(d[43]), "+f"(d[44]), "+f"(d[45]), "+f"(d[46]), "+f"(d[47]),
      "+f"(d[48]), "+f"(d[49]), "+f"(d[50]), "+f"(d[51]), "+f"(d[52]), "+f"(d[53]), "+f"(d[54]), "+f"(d[55]),
      "+f"(d[56]), "+f"(d[57]), "+f"(d[58]), "+f"(d[59]), "+f"(d[60]), "+f"(d[61]), "+f"(d[62]), "+f"(d[63]),
      "+f"(d[64]), "+f"(d[65]), "+f"(d[66]), "+f"(d[67]), "+f"(d[68]), "+f"(d[69]), "+f"(d[70]), "+f"(d[71]),
      "+f"(d[72]), "+f"(d[73]), "+f"(d[74]), "+f"(d[75]), "+f"(d[76]), "+f"(d[77]), "+f"(d[78]), "+f"(d[79]),
      "+f"(d[80]), "+f"(d[81]), "+f"(d[82]), "+f"(d[83]), "+f"(d[84]), "+f"(d[85]), "+f"(d[86]), "+f"(d[87]),
      "+f"(d[88]), "+f"(d[89]), "+f"(d[90]), "+f"(d[91]), "+f"(d[92]), "+f"(d[93]), "+f"(d[94]), "+f"(d[95]),
      "+f"(d[96]), "+f"(d[97]), "+f"(d[98]), "+f"(d[99]), "+f"(d[100]), "+f"(d[101]), "+f"(d[102]), "+f"(d[103]),
      "+f"(d[104]), "+f"(d[105]), "+f"(d[106]), "+f"(d[107]), "+f"(d[108]), "+f"(d[109]), "+f"(d[110]), "+f"(d[111]),
      "+f"(d[112]), "+f"(d[113]), "+f"(d[114]), "+f"(d[115]), "+f"(d[116]), "+f"(d[117]), "+f"(d[118]), "+f"(d[119]),
      "+f"(d[120]), "+f"(d[121]), "+f"(d[122]), "+f"(d[123]), "+f"(d[124]), "+f"(d[125]), "+f"(d[126]), "+f"(d[127])
    : "l"(da), "l"(db), "r"(scale_d));
}
__device__ __forceinline__ void wgmma_n256_rs(float (&d)[128], uint32_t a0, uint32_t a1, uint32_t a2, uint32_t a3, uint64_t db, int scale_d) {
  asm volatile("{\n.reg .pred p;\nsetp.ne.b32 p, %133, 0;\n"
    "wgmma.mma_async.sync.aligned.m64n256k16.f32.bf16.bf16 "
    "{%0, %1, %2, %3, %4, %5, %6, %7, %8, %9, %10, %11, %12, %13, %14, %15, %16, %17, %18, %19, %20, %21, %22, %23, %24, %25, %26, %27, %28, %29, %30, %31, "
    "%32, %33, %34, %35, %36, %37, %38, %39, %40, %41, %42, %43, %44, %45, %46, %47, %48, %49, %50, %51, %52, %53, %54, %55, %56, %57, %58, %59, %60, %61, %62, %63, "
    "%64, %65, %66, %67, %68, %69, %70, %71, %72, %73, %74, %75, %76, %77, %78, %79, %80, %81, %82, %83, %84, %85, %86, %87, %88, %89, %90, %91, %92, %93, %94, %95, "
    "%96, %97, %98, %99, %100, %101, %102, %103, %104, %105, %106, %107, %108, %109, %110, %111, %112, %113, %114, %115, %116, %117, %118, %119, %120, %121, %122, %123, %124, %125, %126, %127}, "
    "{%128, %129, %130, %131}, %132, p, 1, 1, 0;\n}\n"
    : "+f"(d[0]), "+f"(d[1]), "+f"(d[2]), "+f"(d[3]), "+f"(d[4]), "+f"(d[5]), "+f"(d[6]), "+f"(d[7]),
      "+f"(d[8]), "+f"(d[9]), "+f"(d[10]), "+f"(d[11]), "+f"(d[12]), "+f"(d[13]), "+f"(d[14]), "+f"(d[15]),
      "+f"(d[16]), "+f"(d[17]), "+f"(d[18]), "+f"(d[19]), "+f"(d[20]), "+f"(d[21]), "+f"(d[22]), "+f"(d[23]),
      "+f"(d[24]), "+f"(d[25]), "+f"(d[26]), "+f"(d[27]), "+f"(d[28]), "+f"(d[29]), "+f"(d[30]), "+f"(d[31]),
      "+f"(d[32]), "+f"(d[33]), "+f"(d[34]), "+f"(d[35]), "+f"(d[36]), "+f"(d[37]), "+f"(d[38]), "+f"(d[39]),
      "+f"(d[40]), "+f"(d[41]), "+f"(d[42]), "+f"(d[43]), "+f"(d[44]), "+f"(d[45]), "+f"(d[46]), "+f"(d[47]),
      "+f"(d[48]), "+f"(d[49]), "+f"(d[50]), "+f"(d[51]), "+f"(d[52]), "+f"(d[53]), "+f"(d[54]), "+f"(d[55]),
      "+f"(d[56]), "+f"(d[57]), "+f"(d[58]), "+f"(d[59]), "+f"(d[60]), "+f"(d[61]), "+f"(d[62]), "+f"(d[63]),
      "+f"(d[64]), "+f"(d[65]), "+f"(d[66]), "+f"(d[67]), "+f"(d[68]), "+f"(d[69]), "+f"(d[70]), "+f"(d[71]),
      "+f"(d[72]), "+f"(d[73]), "+f"(d[74]), "+f"(d[75]), "+f"(d[76]), "+f"(d[77]), "+f"(d[78]), "+f"(d[79]),
      "+f"(d[80]), "+f"(d[81]), "+f"(d[82]), "+f"(d[83]), "+f"(d[84]), "+f"(d[85]), "+f"(d[86]), "+f"(d[87]),
      "+f"(d[88]), "+f"(d[89]), "+f"(d[90]), "+f"(d[91]), "+f"(d[92]), "+f"(d[93]), "+f"(d[94]), "+f"(d[95]),
      "+f"(d[96]), "+f"(d[97]), "+f"(d[98]), "+f"(d[99]), "+f"(d[100]), "+f"(d[101]), "+f"(d[102]), "+f"(d[103]),
      "+f"(d[104]), "+f"(d[105]), "+f"(d[106]), "+f"(d[107]), "+f"(d[108]), "+f"(d[109]), "+f"(d[110]), "+f"(d[111]),
      "+f"(d[112]), "+f"(d[113]), "+f"(d[114]), "+f"(d[115]), "+f"(d[116]), "+f"(d[117]), "+f"(d[118]), "+f"(d[119]),
      "+f"(d[120]), "+f"(d[121]), "+f"(d[122]), "+f"(d[123]), "+f"(d[124]), "+f"(d[125]), "+f"(d[126]), "+f"(d[127])
    : "r"(a0), "r"(a1), "r"(a2), "r"(a3), "l"(db), "r"(scale_d));
}
__device__ __forceinline__ void wgmma_n128(float (&d)[64], uint64_t da, uint64_t db) {
  asm volatile("{\n.reg .pred p;\nsetp.ne.b32 p, 1, 0;\n"
    "wgmma.mma_async.sync.aligned.m64n128k16.f32.bf16.bf16 "
    "{%0, %1, %2, %3, %4, %5, %6, %7, %8, %9, %10, %11, %12, %13, %14, %15, %16, %17, %18, %19, %20, %21, %22, %23, %24, %25, %26, %27, %28, %29, %30, %31, %32, %33, %34, %35, %36, %37, %38, %39, %40, %41, %42, %43, %44, %45, %46, %47, %48, %49, %50, %51, %52, %53, %54, %55, %56, %57, %58, %59, %60, %61, %62, %63}, "
    "%64, %65, p, 1, 1, 0, 0;\n}\n"
    : "+f"(d[0]), "+f"(d[1]), "+f"(d[2]), "+f"(d[3]), "+f"(d[4]), "+f"(d[5]), "+f"(d[6]), "+f"(d[7]), "+f"(d[8]), "+f"(d[9]), "+f"(d[10]), "+f"(d[11]), "+f"(d[12]), "+f"(d[13]), "+f"(d[14]), "+f"(d[15]), "+f"(d[16]), "+f"(d[17]), "+f"(d[18]), "+f"(d[19]), "+f"(d[20]), "+f"(d[21]), "+f"(d[22]), "+f"(d[23]), "+f"(d[24]), "+f"(d[25]), "+f"(d[26]), "+f"(d[27]), "+f"(d[28]), "+f"(d[29]), "+f"(d[30]), "+f"(d[31]), "+f"(d[32]), "+f"(d[33]), "+f"(d[34]), "+f"(d[35]), "+f"(d[36]), "+f"(d[37]), "+f"(d[38]), "+f"(d[39]), "+f"(d[40]), "+f"(d[41]), "+f"(d[42]), "+f"(d[43]), "+f"(d[44]), "+f"(d[45]), "+f"(d[46]), "+f"(d[47]), "+f"(d[48]), "+f"(d[49]), "+f"(d[50]), "+f"(d[51]), "+f"(d[52]), "+f"(d[53]), "+f"(d[54]), "+f"(d[55]), "+f"(d[56]), "+f"(d[57]), "+f"(d[58]), "+f"(d[59]), "+f"(d[60]), "+f"(d[61]), "+f"(d[62]), "+f"(d[63])
    : "l"(da), "l"(db));
}
__device__ __forceinline__ void fence_acc64(float (&d)[64]) {
#pragma unroll
  for (int i = 0; i < 64; i++) asm volatile("" : "+f"(d[i]) :: "memory");
}
__device__ __forceinline__ void fence_acc(float (&d)[128]) {
#pragma unroll
  for (int i = 0; i < 128; i++) asm volatile("" : "+f"(d[i]) :: "memory");
}

template<int N, int I = 0, class F> __device__ __forceinline__ void static_for(F&& f) {
  if constexpr (I < N) { f(std::integral_constant<int, I>()); static_for<N, I + 1>(f); }
}

__device__ __forceinline__ void ldsm_x4_t(uint32_t addr, uint32_t& a, uint32_t& b, uint32_t& c, uint32_t& d) {
  asm volatile("ldmatrix.sync.aligned.m8n8.x4.trans.shared.b16 {%0, %1, %2, %3}, [%4];" : "=r"(a), "=r"(b), "=r"(c), "=r"(d) : "r"(addr));
}
__device__ __forceinline__ void sts128(uint32_t addr, uint32_t a, uint32_t b, uint32_t c, uint32_t d) {
  asm volatile("st.shared.v4.b32 [%0], {%1, %2, %3, %4};" :: "r"(addr), "r"(a), "r"(b), "r"(c), "r"(d));
}
__device__ __forceinline__ void mma16816(float (&c)[4], uint32_t a0, uint32_t a1, uint32_t a2, uint32_t a3, uint32_t b0, uint32_t b1) {
  asm volatile("mma.sync.aligned.m16n8k16.row.col.f32.bf16.bf16.f32 {%0, %1, %2, %3}, {%4, %5, %6, %7}, {%8, %9}, {%0, %1, %2, %3};"
      : "+f"(c[0]), "+f"(c[1]), "+f"(c[2]), "+f"(c[3]) : "r"(a0), "r"(a1), "r"(a2), "r"(a3), "r"(b0), "r"(b1));
}
__device__ __forceinline__ void mma1688(float (&c)[4], uint32_t a0, uint32_t a1, uint32_t b0) {
  asm volatile("mma.sync.aligned.m16n8k8.row.col.f32.bf16.bf16.f32 {%0, %1, %2, %3}, {%4, %5}, {%6}, {%0, %1, %2, %3};"
      : "+f"(c[0]), "+f"(c[1]), "+f"(c[2]), "+f"(c[3]) : "r"(a0), "r"(a1), "r"(b0));
}
__device__ __forceinline__ void pin(uint32_t& v) { asm volatile("shfl.sync.bfly.b32 %0, %0, 0, 0x1f, 0xffffffff;" : "+r"(v)); }
template<class T> __device__ __forceinline__ void pin(T*& v) {
  uint32_t lo = (uint32_t)(uint64_t)v, hi = (uint32_t)((uint64_t)v >> 32);
  pin(lo); pin(hi);
  v = (T*)(((uint64_t)hi << 32) | lo);
}
__device__ __forceinline__ float sel4(int q, float a, float b, float c, float d) {
  float r;
  asm("{\n.reg .pred p, o;\n.reg .f32 x, y;\n.reg .b32 t;\nand.b32 t, %1, 1;\nsetp.ne.b32 p, t, 0;\nsetp.gt.s32 o, %1, 1;\n"
      "selp.f32 x, %3, %2, p;\nselp.f32 y, %5, %4, p;\nselp.f32 %0, y, x, o;\n}\n" : "=f"(r) : "r"(q), "f"(a), "f"(b), "f"(c), "f"(d));
  return r;
}
__device__ __forceinline__ uint32_t bfma2(uint32_t a, uint32_t b, uint32_t c) { uint32_t r; asm("fma.rn.bf16x2 %0, %1, %2, %3;" : "=r"(r) : "r"(a), "r"(b), "r"(c)); return r; }
__device__ __forceinline__ void tma_store_5d(const CUtensorMap* tm, uint32_t src, int c0, int c3, int c4) {
  asm volatile("cp.async.bulk.tensor.5d.global.shared::cta.bulk_group [%0, {%2, %3, %3, %4, %5}], [%1];" :: "l"(tm), "r"(src), "r"(c0), "r"(0), "r"(c3), "r"(c4) : "memory");
}
__device__ __forceinline__ float rcp_fast(float x) { float r; asm("rcp.approx.ftz.f32 %0, %1;" : "=f"(r) : "f"(x)); return r; }
__device__ __forceinline__ float sigmoid_fast(float x) { float e; asm("ex2.approx.ftz.f32 %0, %1;" : "=f"(e) : "f"(x * -1.4426950408889634f)); return rcp_fast(1.f + e); }
__device__ __forceinline__ float sqrt_fast(float x) { float r; asm("sqrt.approx.ftz.f32 %0, %1;" : "=f"(r) : "f"(x)); return r; }
__device__ __forceinline__ float ln_sd(float var) { return bf16r(sqrt_fast(bf16r(bf16r(fmaxf(var, 0.f)) + 1e-5f))); }
__device__ __forceinline__ uint32_t norm2(uint32_t h, uint32_t neg_mean2, float inv_sd) {
  const uint32_t d = badd2(h, neg_mean2);
  return pack_bf16(bf_lo(d) * inv_sd, bf_hi(d) * inv_sd);
}
template<int N> __device__ __forceinline__ void delay_clk() {
  if constexpr (N > 0) { const uint32_t t0 = clock(); while ((uint32_t)clock() - t0 < N) {} }
}
template<int V> using IC = std::integral_constant<int, V>;

#define CT(slot) do {} while (0)
#define PT(slot) do {} while (0)

template<int MAP>
__global__ void __cluster_dims__(2, 1, 1) __launch_bounds__(384, 1)
fnet_moe_kernel(const __grid_constant__ Params p) {
  uint32_t sb;
  asm volatile("mov.u32 %0, %1;" : "=r"(sb) : "r"(smem_u32(smem_raw)));
  const int m = blockIdx.x & 1;
  int tau, eps;
  bool idle = false;
  if (MAP == 0) {
    uint32_t smid;
    asm volatile("mov.u32 %0, %%smid;" : "=r"(smid));
    const int c = smid >> 1, e7 = ((c - 32) * 37) >> 8;
    idle = c == 60 || c == 61;
    tau = c < 32 ? (c & 7) : (c < 60 ? c - 31 - 7 * e7 : 0);
    eps = c < 32 ? (c >> 3) : (c < 60 ? 4 + e7 : c - 58);
  } else {
    tau = (blockIdx.x >> 1) & 7; eps = blockIdx.x >> 4;
  }
  const int cid = tau * 16 + eps * 2 + m;
  const bool moe = tau > 0;
  auto BAR = [&](int i) { return sb + OFF_BAR + 8 * i; };
  const CUtensorMap* tmD = m ? &p.tmD1 : &p.tmD0;
  const uint64_t pol_ef = policy_evict_first();
#define LOAD_STREAM(d, tm, bar, c0, c1) tma_load_2d_hint(d, tm, bar, c0, c1, pol_ef)
  if (threadIdx.x < 32 && !idle) {
    if (elect_one()) {
#pragma unroll
      for (int k = 0; k < 4; k++) mbar_init(BAR(B_FULL + k), 1);
      asm volatile("fence.mbarrier_init.release.cluster;" ::: "memory");
#pragma unroll
      for (int k = 0; k < 4; k++) mbar_expect_tx(BAR(B_FULL + k), ST_BYTES);
    }
    PT(50);
    if (elect_one()) {
      tma_load_2d(sb + A_BYTES, &p.tmX, BAR(B_FULL), 0, tau * 256);
      LOAD_STREAM(sb, tmD, BAR(B_FULL), 0, eps * 128);
    }
    PT(52);
    if (elect_one()) {
#pragma unroll
      for (int k = 1; k < 4; k++) {
        tma_load_2d(sb + k * ST_BYTES + A_BYTES, &p.tmX, BAR(B_FULL + k), k * 64, tau * 256);
        LOAD_STREAM(sb + k * ST_BYTES, tmD, BAR(B_FULL + k), k * 64, eps * 128);
      }
    }
    PT(0);
  }
  __syncwarp();
  const int warp = __shfl_sync(0xffffffffu, threadIdx.x >> 5, 0);
  const int tid = __shfl_sync(0xffffffffu, threadIdx.x, threadIdx.x & 31), lane = tid & 31;
  if (idle) {
    __nanosleep(4000);
    const uint32_t tg = ld_relaxed32(&p.s->epoch) + 1;
    uint32_t n = 0;
    do { __nanosleep(1000); } while (!__all_sync(0xffffffffu, pkt_ld64(&p.s->xstat[(tid & 127) * 16]).y == tg) && ++n < 4096);
    return;
  }
  if (warp == 8) {
    if (elect_one()) {
#pragma unroll
      for (int b = B_EMPTY; b < B_COUNT; b++)
        mbar_init(BAR(b), b < B_EPI ? 2 : (b == B_EPI || b == B_EPI0B) ? 4 : (b < B_STD || b == B_OUT) ? 8 : (b == B_STAT || b == B_XS) ? 3 : 1);
      asm volatile("fence.mbarrier_init.release.cluster;" ::: "memory");
      mbar_expect_tx(BAR(B_XCH), 32768);
      SM_(uint32_t, OFF_SEEN) = 0;
    }
  }
  __syncthreads();

  if (warp >= 8) {
    reg_dec<REG_P>();
    asm volatile("barrier.cluster.arrive.relaxed.aligned;" ::: "memory");
    const int abrow = m * 1024 + eps * 128;
    const int f0 = (cid - 16) * 32;
    if (warp == 8) {
      const CUtensorMap* tmW = m ? &p.tmW1 : &p.tmW0;
      const int tA = tau * 256 + m * 128, tB = tau * 256 + (1 - m) * 128;
      uint32_t seen = 0;
#pragma unroll 1
      for (int k = 4; k < 48; k++) {
        const int s = slot_of(k);
        const uint32_t sa = sb + s * ST_BYTES, sbb = sa + A_BYTES;
        const int kb = kblock(tau, k - 16);
        mbar_wait(BAR(B_EMPTY + s), (use_of(k) & 1) ^ 1);
        PT(64 + k);
        if (elect_one()) {
          mbar_expect_tx(BAR(B_FULL + s), (k >> 1) == 9 ? B_BYTES : k == 20 ? ST_BYTES - 8192 : ST_BYTES);
          if (k < 16) {
            LOAD_STREAM(sa, tmD, BAR(B_FULL + s), k * 64, eps * 128);
            tma_load_2d(sbb, &p.tmX, BAR(B_FULL + s), k * 64, tau * 256);
          } else {
            LOAD_STREAM(sbb, tmW, BAR(B_FULL + s), kb * 64, tA);
            LOAD_STREAM(sbb + 16384, tmW, BAR(B_FULL + s), kb * 64, tB);
            if (k < 18) {
              tma_load_2d(sa, &p.tmXr, BAR(B_FULL + s), eps * 128, tA + s * 64);
              tma_load_2d(sa + 8192, &p.tmXr, BAR(B_FULL + s), eps * 128 + 64, tA + s * 64);
            }
          }
        }
        if (k >= 24) {
          uint32_t n = 0;
          while (!((seen >> kb) & 1) && ++n < SPIN_LIMIT * 16) seen = *(volatile uint32_t*)&SM_(uint32_t, OFF_SEEN);
          if (elect_one()) tma_load_2d(sa, &p.tmAbL, BAR(B_FULL + s), kb * 64, abrow);
        }
        if (k == PUB_K1 && elect_one()) mbar_arrive(BAR(B_LATE));
        if (k >= WPF_K0 && k < WPF_K0 + WPF_N && (eps >> 1) == ((k - WPF_K0) & 3) && elect_one())
          asm volatile("cp.async.bulk.prefetch.tensor.2d.L2.global.tile [%0, {%1, %2}];" :: "l"(tmW), "r"(kblock(tau, k - WPF_K0) * 64), "r"(tau * 256 + (eps & 1) * 128) : "memory");
        if (moe && k >= PF_K0 && !(k & 1)) {
          const int i = k < PF_K1 ? (k - PF_K0) >> 1 : PF_N0 + ((k - PF_K1) >> 1);
          if ((k >= PF_K1 || i < PF_N0) && elect_one()) {
            if (i < 8) asm volatile("cp.async.bulk.prefetch.tensor.2d.L2.global.tile [%0, {%1, %2}];" :: "l"(m ? &p.tmU : &p.tmG), "r"(f0), "r"(i * 128) : "memory");
            else if (i < 12) asm volatile("cp.async.bulk.prefetch.L2.global [%0], %1;" :: "l"(p.wdown + (size_t)f0 * 1024 + (i - 8) * 8192), "r"(16384) : "memory");
          }
        }
        if (moe && k >= MR_K0) {
          const int i = k - MR_K0, r6 = i / MR_P, u = i - MR_P * r6, h = 2 * r6 + (u >> 1);
          if (u < 4 && h < NREG_H + 2) {
            if (h < 2) mbar_wait(BAR(B_STD + 2 + h), 0);
            if (elect_one()) {
              const uint32_t bar = BAR(h < NREG_H ? B_MR + (h & 1) : B_GU);
              if (!(u & 1) && h <= NREG_H) mbar_expect_tx(bar, h < NREG_H ? 16384 : (8 - NREG_H) * 16384);
              LOAD_STREAM(sb + OFF_XCH + u * 8192, (u & 1) ? &p.tmU : &p.tmG, bar, f0, h * 128);
              if (mr_k(NREG_H + 1) == 47 && k == 47) LOAD_STREAM(sb + OFF_XCH + u * 8192 + 8192, &p.tmU, bar, f0, h * 128);
            }
          }
        }
      }
      if (moe) {
        mbar_wait(BAR(B_EMPTY + 0), 1);
        if (elect_one()) mbar_expect_tx(BAR(B_DN), 65536);
#pragma unroll 1
        for (int i = 0; i < 10 - NREG_H; i++) {
          if (i == 3) mbar_wait(BAR(B_EMPTY + 1), 1);
          if (i == 4) {
            mbar_wait(BAR(B_EMPTY + 2), 1);
            mbar_wait(BAR(B_XCH), 0);
            PT(53);
          }
          const uint32_t dst = sb + late_off(i);
          if (elect_one()) {
            if (i < 6 - NREG_H) {
              LOAD_STREAM(dst, &p.tmG, BAR(B_GU), f0, (NREG_H + 2 + i) * 128);
              LOAD_STREAM(dst + 8192, &p.tmU, BAR(B_GU), f0, (NREG_H + 2 + i) * 128);
            } else {
#pragma unroll
              for (int b = 0; b < 4; b++) LOAD_STREAM(dst + b * 4096, &p.tmDn, BAR(B_DN), (4 * (i - 6 + NREG_H) + b) * 64, f0);
            }
          }
          const long long t0 = clock64();
          while (i < 9 - NREG_H && clock64() - t0 < MOE_PACE_CLK) {}
        }
      }
    } else {
      const int a = warp - 9;
      auto stage = [&](const bf16* src, int g) {
        if (elect_one()) {
          mbar_expect_tx(BAR(B_AUX + g), 16384);
          bulk_load(sb + OFF_XCH + g * 16384, src + g * 8192, 16384, BAR(B_AUX + g));
        }
      };
      mbar_wait(BAR(B_FULL + (a == 1 ? AUX_AFTER2 : AUX_AFTER)), 0);
      if (a == 0) PT(1);
      if (a < 2) stage(p.x + (size_t)cid * 16 * 1024, a);
      const uint32_t tag = ld_relaxed32(&p.s->epoch) + 1;
      if (a == 2 && lane < 16) asm volatile("prefetch.global.L2 [%0];" :: "l"(p.wr + lane * 64));
#pragma unroll 1
      for (int it = 0; it < 4; it++) {
        const int g = it & 1;
        mbar_wait(BAR(B_AUX + g), it >> 1);
        if (a == 0) PT(2 + it);
        const uint32_t ad = sb + OFF_XCH + g * 16384 + (lane >> 2) * 2048;
        float s0 = 0.f, s1 = 0.f, q0 = 0.f, q1 = 0.f;
        auto row = [&](auto sq) {
#pragma unroll
          for (int i = 0; i < 11; i++) {
            if (i == 10 && a == 2) break;
            const uint4 v = lds128_v(ad + (((a * 44 + 4 * i + lane) & 127) << 4));
            const uint32_t ww[4] = {v.x, v.y, v.z, v.w};
#pragma unroll
            for (int z = 0; z < 4; z++) {
              const float d0 = bf_lo(ww[z]), d1 = bf_hi(ww[z]);
              s0 += d0; s1 += d1;
              if (decltype(sq)::value) { q0 = fmaf(d0, d0, q0); q1 = fmaf(d1, d1, q1); }
            }
          }
        };
        if (it < 2) row(IC<1>()); else row(IC<0>());
        s0 += s1; q0 += q1;
#pragma unroll
        for (int o = 1; o < 4; o <<= 1) { s0 += __shfl_xor_sync(0xffffffffu, s0, o); q0 += __shfl_xor_sync(0xffffffffu, q0, o); }
        if ((lane & 3) == 0) SM_(float2, OFF_PUB + a * 256 + it * 64 + (lane >> 2) * 8) = make_float2(s0, q0);
        if (it != 2) bar_sync(NB_AUX, 96);
        if (it < 2 && a == 2) stage(cid < 64 ? p.Dre + (size_t)cid * 16 * 1024 : p.Dim + (size_t)(cid - 64) * 16 * 1024, g);
      }
      if (a == 1) {
        const float2 v0 = SM_(float2, OFF_PUB + lane * 8), v1 = SM_(float2, OFF_PUB + 256 + lane * 8), v2 = SM_(float2, OFF_PUB + 512 + lane * 8);
        const float s = v0.x + v1.x + v2.x, mean = s * (1.f / 1024.f);
        const float rs = rcp_fast(ln_sd((v0.y + v1.y + v2.y) * (1.f / 1024.f) - mean * mean));
        pkt_st64((lane < 16 ? p.s->xstat : p.s->dsum) + cid * 16 + (lane & 15), lane < 16 ? pack_bf16(rs, mean) : __float_as_uint(s), tag);
        PT(6);
      }
      if (a == 2) {
        float s = 0.f;
#pragma unroll
        for (int q = 0; q < 4; q++) {
          const uint4 v = ldg_nc128(p.wr + (q * 32 + lane) * 8);
          s += ((bf_lo(v.x) + bf_hi(v.x)) + (bf_lo(v.y) + bf_hi(v.y))) + ((bf_lo(v.z) + bf_hi(v.z)) + (bf_lo(v.w) + bf_hi(v.w)));
          const int ch = q * 32 + lane - eps * 16;
          if (ch >= 0 && ch < 16) {
            SM_(uint32_t, OFF_WR + ch * 4) = v.x; SM_(uint32_t, OFF_WR + 80 + ch * 4) = v.y;
            SM_(uint32_t, OFF_WR + 160 + ch * 4) = v.z; SM_(uint32_t, OFF_WR + 240 + ch * 4) = v.w;
          }
        }
        s = warp_sum(s);
        if (lane == 0) { SM_(float, OFF_WSUM) = s; SM_(uint32_t, OFF_TAG) = tag; }
      }
      if (a < 2) __nanosleep(GATHER_NS);
      {
        const int i0 = a * 32 + lane;
        uint2 v[3], c0, c1; uint32_t n = 0;
        const uint2* dp = &p.s->dsum[abrow];
        while (true) {
#pragma unroll
          for (int q = 0; q < 3; q++) v[q] = pkt_ld64(&p.s->xstat[tau * 256 + min(i0 + 96 * q, 255)]);
          c0 = pkt_ld64(dp + i0); c1 = pkt_ld64(dp + min(i0 + 96, 127));
          if (__all_sync(0xffffffffu, v[0].y == tag && v[1].y == tag && v[2].y == tag && c0.y == tag && c1.y == tag) || ++n > SPIN_LIMIT) break;
          __nanosleep(200);
        }
#pragma unroll
        for (int q = 0; q < 3; q++) {
          const int col = min(i0 + 96 * q, 255);
          SM_(uint16_t, OFF_RS + ((col & 7) >> 1) * 144 + (col >> 3) * 4 + (col & 1) * 2) = (uint16_t)(v[q].x ^ (m << 15));
          const uint32_t nm = (v[q].x >> 16) ^ 0x8000u;
          SM_(uint4, OFF_EXB + (col >> 3) * 256 + (col & 7) * 16) = make_uint4(nm | (nm << 16), nm, 0, 0);
          SM_(uint4, OFF_EXB + (col >> 3) * 256 + 128 + (col & 7) * 16) = make_uint4(0, 0, 0, 0);
        }
#pragma unroll
        for (int q = 0; q < 2; q++) {
          const int e = min(i0 + 96 * q, 127);
          const float c = __uint_as_float(q ? c1.x : c0.x);
          const float hi = bf16r(c), mid = bf16r(c - hi), lo = bf16r((c - hi) - mid);
          SM_(uint4, OFF_EXA + (e >> 3) * 256 + (e & 7) * 16) = make_uint4((__float_as_uint(hi) >> 16) | (__float_as_uint(mid) & 0xFFFF0000u), __float_as_uint(lo) >> 16, 0, 0);
          SM_(uint4, OFF_EXA + (e >> 3) * 256 + 128 + (e & 7) * 16) = make_uint4(0, 0, 0, 0);
        }
        fence_async_smem();
      }
      __syncwarp();
      if (lane == 0) mbar_arrive(BAR(B_STAT));
      if (a == 0) PT(7);
      if (a == 0) {
        const int sg = (lane >> 2) == tau ? (tau + 1) & 7 : lane >> 2;
        const uint32_t* flg = reinterpret_cast<const uint32_t*>(&p.s->abflag[((eps * 2 + m) * 8 + sg) * 2]) + ((lane >> 2) == tau ? 4 : lane & 3);
        uint32_t seen = 0;
        mbar_wait(BAR(B_STDA), 0);
        PT(49);
#pragma unroll 1
        for (int i = 0; i < 5; i++) {
          const int s = i ? i - 1 : 0, sig = (tau + 1 + s) & 7;
          if (i == 1) mbar_wait(BAR(B_STD + 0), 0);
          uint32_t n = 0;
          while (!((seen >> (4 * (i ? sig : tau))) & 1) && ++n < SPIN_LIMIT) seen = __ballot_sync(0xffffffffu, ld_relaxed32(flg) == tag);
          if (i == 0 || i == 4) mbar_wait(BAR(i ? B_STD + 1 : B_EPI0B), 0);
          if (i != 1) mbar_wait(BAR(B_FULL + s), 0);
          PT(i ? 16 + s : 48);
          if (elect_one()) {
            if (i == 1) mbar_expect_tx(BAR(B_A20), 8192);
            tma_load_2d(sb + (i < 3 ? OFF_XCH + i * 8192 : s * ST_BYTES), i < 2 ? &p.tmAbS : &p.tmAbL, BAR(i == 1 ? B_A20 : B_FULL + s), sig * 256,
                        abrow + (i == 1 ? 64 : 0));
          }
        }
        uint32_t n = 0;
        while (true) {
          asm volatile("fence.proxy.async.global;" ::: "memory");
          *(volatile uint32_t*)&SM_(uint32_t, OFF_SEEN) = seen;
          if (seen == 0xFFFFFFFFu || ++n > SPIN_LIMIT) break;
          seen = __ballot_sync(0xffffffffu, ld_relaxed32(flg) == tag);
          __nanosleep(100);
        }
      } else {
        uint32_t* flag = reinterpret_cast<uint32_t*>(&p.s->abflag[((eps * 2 + m) * 8 + tau) * 2]);
        mbar_wait(BAR(a == 1 ? B_EPI : B_EPI0B), 0);
        if (a == 1) PT(8);
        if (lane == 0) {
          tma_store_2d(&p.tmAbS, sb + chunk_off(0, a - 1), tau * 256, abrow + (a - 1) * 64);
          bulk_commit();
          bulk_wait_all();
        }
        if (a == 2) mbar_wait(BAR(B_STDA), 0);
        if (lane == 0) {
          st_relaxed32(flag + (a == 1 ? 4 : 0), tag);
          mbar_arrive(BAR(a == 1 ? B_STDA : B_STD));
        }
        if (a == 2) PT(12);
        if (a == 1) {
          mbar_wait(BAR(B_EPI + 1), 0);
          mbar_wait(BAR(B_LATE), 0);
          PT(9);
          if (lane == 0) {
            tma_store_2d(&p.tmAbS, sb + chunk_off(1, 0), tau * 256 + 64, abrow);
            tma_store_2d(&p.tmAbS, sb + chunk_off(1, 1), tau * 256 + 64, abrow + 64);
            bulk_commit();
            bulk_wait_all();
            st_relaxed32(flag + 1, tag);
            mbar_arrive(BAR(B_STD + 1));
          }
          PT(13);
        }
        auto copy_out = [&](int c) {
          mbar_wait(BAR(B_EPI + c), 0);
          PT(8 + c);
          bf16* dst = p.s->abT + (size_t)(abrow + (lane >> 3)) * 2048 + tau * 256 + c * 64;
#pragma unroll 4
          for (int i = 0; i < 32; i++) {
            const int row = 4 * i + (lane >> 3);
            const uint4 v = lds128_v(sb + chunk_off(c, 0) + i * 512 + lane * 16);
            asm volatile("st.global.v4.b32 [%0], {%1, %2, %3, %4};" :: "l"(dst + i * 4 * 2048 + (((lane & 7) ^ (row & 7)) << 3)), "r"(v.x), "r"(v.y), "r"(v.z), "r"(v.w));
          }
          __syncwarp();
          if (lane == 0) mbar_arrive(BAR(B_STD + c));
        };
        if (a == 2) {
#pragma unroll 1
          for (int c = 2; c < 4; c++) copy_out(c);
          asm volatile("fence.acq_rel.gpu;" ::: "memory");
          __syncwarp();
          if (lane < 2) st_relaxed32(flag + 2 + lane, tag);
          PT(15);
        }
      }
      {
        mbar_wait(BAR(B_LATE), 1);
        const int grp = tau * 2 + m;
#pragma unroll 1
        for (int i = a; i < 14; i += 3) {
          uint4* dst = i < 8 ? &p.s->ypart[cid * 256 + i * 32 + lane] : i < 12 ? &p.s->hstat[(grp * 8 + eps) * 128 + (i - 8) * 32 + lane]
                     : i == 12 ? &p.s->cand[grp * 256 + eps * 32 + lane] : &p.s->key[(((lane >> 1) & 7) * 16 + grp) * 2 + (lane & 1)];
          if (i < 13 || eps == 0) pkt_st128(dst, 0, 0, 0, 0);
          __nanosleep(200);
        }
        __syncwarp();
        if (lane == 0) mbar_arrive(BAR(B_STAT));
      }
      {
        const uint4* kp = &p.s->key[(tau * 16 + (lane & 15)) * 2];
        const int i0 = a * 32 + lane;
        mbar_wait(BAR(B_KEY), 0);
        if (a == 0) PT(43);
        uint4 kq = pkt_ld128(kp), cv[3] = {};
        uint32_t n = 0, kv;
        int gspec = -1;
        while (true) {
          const bool ok = kq.y == tag && kq.w == tag;
          kv = __reduce_max_sync(0xffffffffu, ok ? kq.x : 0u);
          const int gs = (0xFFFF - (int)(kv & 0xFFFFu)) >> 7;
          const bool cok = gs == gspec && cv[0].y == tag && cv[0].w == tag && cv[1].y == tag && cv[1].w == tag && cv[2].y == tag && cv[2].w == tag;
          if (__all_sync(0xffffffffu, ok && cok) || ++n > SPIN_LIMIT) break;
          if (!ok) kq = pkt_ld128(kp);
          const bool spec = __popc(__ballot_sync(0xffffffffu, ok)) >= 2 * SPEC_MIN;
          if (!cok && spec) {
#pragma unroll
            for (int i = 0; i < 3; i++) cv[i] = pkt_ld128(&p.s->cand[gs * 256 + min(i0 + 96 * i, 255)]);
          }
          if (spec) gspec = gs;
        }
        if (a == 0) PT(45);
        const uint32_t ms = __shfl_sync(0xffffffffu, kq.z, gspec);
        const uint32_t nm = ((ms & 0xFFFFu) ^ 0x8000u) * 0x10001u;
        const float is = rcp_fast(bf_hi(ms));
#pragma unroll
        for (int i = 0; i < 3; i++) {
          const int j = min(i0 + 96 * i, 255);
          SM_(uint2, OFF_XSEL + j * 8) = make_uint2(norm2(cv[i].x, nm, is), norm2(cv[i].z, nm, is));
        }
#pragma unroll
        for (int i = 0; i < 3; i++) SM_(uint2, OFF_HSEL + min(i0 + 96 * i, 255) * 8) = make_uint2(cv[i].x, cv[i].z);
        SM_(uint32_t, OFF_KV) = kv;
        __syncwarp();
        if (lane == 0) mbar_arrive(BAR(B_XS));
      }
    }
    if (warp == 8) {
      const int lane = threadIdx.x & 31;
      mbar_wait(BAR(B_OUT), 0);
      const uint32_t km = SM_(uint32_t, OFF_WKEY + (lane & 7) * 8);
      const uint32_t bk = __reduce_max_sync(0xffffffffu, km);
      const int ww = __ffs(__ballot_sync(0xffffffffu, km == bk)) - 1;
#pragma unroll 1
      for (int i = 1; i <= 8; i++) {
        const int W = (ww + i) & 7;
        if (i == 8) {
          mbar_wait(BAR(B_XS), 0);
          if (SM_(uint32_t, OFF_KV) == bk) {
#pragma unroll 2
            for (int j = lane; j < 256; j += 32) {
              const int rho = j >> 4, row = (tau * 2 + m) * 128 + 32 * (W >> 1) + 8 * ((rho & 7) >> 1) + 4 * (W & 1) + 2 * (rho >> 3) + (rho & 1);
              const uint4 v = lds128_v(sb + OFF_OUT + (j & 8) * 2048 + (16 * W + rho) * 128 + (((j ^ rho) & 7) << 4));
              if (row != 0xFFFF - (int)(bk & 0xFFFFu))
                asm volatile("st.global.v4.b32 [%0], {%1, %2, %3, %4};" :: "l"(p.out + (size_t)row * 1024 + eps * 128 + (j & 15) * 8), "r"(v.x), "r"(v.y), "r"(v.z), "r"(v.w));
            }
            break;
          }
        }
        if (lane == 0) {
          tma_store_5d(&p.tmOut, sb + OFF_OUT + W * 2048, eps * 128, 2 * (W & 1), tau * 8 + m * 4 + (W >> 1));
          tma_store_5d(&p.tmOut, sb + OFF_OUT + 16384 + W * 2048, eps * 128 + 64, 2 * (W & 1), tau * 8 + m * 4 + (W >> 1));
        }
        const long long t0 = clock64();
        while (i < 7 && clock64() - t0 < OUT_PACE_CLK) {}
      }
      if (lane == 0) { bulk_commit(); bulk_wait_all(); }
      PT(22);
    }
    asm volatile("barrier.cluster.wait.aligned;" ::: "memory");
  } else {
    reg_inc<REG_C>();
    const int w = warp >> 2, wi = warp & 3, t = tid & 127;
    const int g = lane >> 2, q = lane & 3;
    const int turn_me = NB_TURN0 + w, turn_other = NB_TURN1 - w;
    float acc[128];
#pragma unroll
    for (int i = 0; i < 128; i++) acc[i] = 0.f;
    if (w == 1) bar_arrive(NB_TURN0, 256);
    auto kstep = [&](int k, bool first, bool a_in_xch = false) {
      const int s = slot_of(k);
      mbar_wait(BAR(B_FULL + s), use_of(k) & 1);
      CT(64 + k);
      bar_sync(turn_me, 256);
      const uint64_t da = make_desc(sb + (a_in_xch ? OFF_XCH + s * 16384 : s * ST_BYTES) + w * 8192), db = make_desc(sb + s * ST_BYTES + A_BYTES);
      wgmma_fence();
      wgmma_n256(acc, da, db, !first);
#pragma unroll
      for (int kk = 1; kk < 4; kk++) wgmma_n256(acc, da + kk * 2, db + kk * 2, 1);
      wgmma_commit();
      bar_arrive(turn_other, 256);
    };
    auto release = [&](int s) { if (t == 0) mbar_arrive(BAR(B_EMPTY + s)); };
    auto kdone = [&](int k) { wgmma_wait0(); release(slot_of(k)); };
    auto wgmma_wait1 = [&]() { asm volatile("wgmma.wait_group.sync.aligned 1;" ::: "memory"); };

#pragma unroll 1
    for (int k = 0; k < 14; k++) {
      kstep(k, k == 0);
      if (k == 0) CT(0);
      if (k == 8 && warp == 2 && lane < 2) pkt_st128(&p.s->abflag[((eps * 2 + m) * 8 + tau) * 2 + lane], 0, 0, 0, 0);
      kdone(k);
    }
    uint32_t R[64];
    uint32_t tag;
    {
      const uint32_t rsa = sb + OFF_RS + q * 144;
      const uint64_t da2 = make_desc(sb + 2 * ST_BYTES + w * 8192), db2 = make_desc(sb + 2 * ST_BYTES + A_BYTES);
      const uint64_t da3 = make_desc(sb + 3 * ST_BYTES + w * 8192), db3 = make_desc(sb + 3 * ST_BYTES + A_BYTES);
      mbar_wait(BAR(B_FULL + 2), 1);
      CT(64 + 14);
      bar_sync(turn_me, 256);
      wgmma_fence();
#pragma unroll
      for (int kk = 0; kk < 4; kk++) wgmma_n256(acc, da2 + kk * 2, db2 + kk * 2, 1);
      wgmma_commit();
      mbar_wait(BAR(B_FULL + 3), 1);
      CT(64 + 15);
      wgmma_fence();
      wgmma_n256(acc, da3, db3, 1);
      wgmma_n256(acc, da3 + 2, db3 + 2, 1);
      wgmma_commit();
      mbar_wait(BAR(B_STAT), 0);
      tag = SM_(uint32_t, OFF_TAG);
#pragma unroll
      for (int i = 0; i < 8; i++) { const uint4 v = lds128_v(rsa + i * 16); R[8 * i] = v.x; R[8 * i + 2] = v.y; R[8 * i + 4] = v.z; R[8 * i + 6] = v.w; }
      wgmma_wait1();
      release(2);
      wgmma_fence();
      wgmma_n256(acc, da3 + 4, db3 + 4, 1);
      wgmma_n256(acc, da3 + 6, db3 + 6, 1);
      wgmma_n256(acc, make_desc_noswz(sb + OFF_EXA + w * 2048), make_desc_noswz(sb + OFF_EXB), 1);
      wgmma_commit();
      bar_arrive(turn_other, 256);
      kdone(15);
      mbar_wait(BAR(B_STAT), 0);
    }
    fence_acc(acc);
    CT(1);
    auto pack = [&](auto cc) {
      constexpr int c = decltype(cc)::value;
#pragma unroll
      for (int j = 8 * c; j < 8 * c + 8; j++) {
        const uint32_t rs = R[2 * j];
        const float* ac = &acc[4 * j];
        R[2 * j] = bmul2(pack_bf16(ac[0], ac[1]), rs);
        R[2 * j + 1] = bmul2(pack_bf16(ac[2], ac[3]), rs);
      }
    };
    auto put_chunk = [&](auto cc) {
      constexpr int c = decltype(cc)::value;
      const int rho = 16 * wi + (lane & 15);
#pragma unroll
      for (int j = 8 * c; j < 8 * c + 8; j += 2) {
        const int chunk = (j & 7) + (lane >> 4);
        stsm_x4(sb + chunk_off(c, w) + rho * 128 + ((chunk ^ (lane & 7)) << 4), R[2 * j], R[2 * j + 1], R[2 * j + 2], R[2 * j + 3]);
      }
    };
    auto staged = [&](int bar) {
      fence_async_smem();
      __syncwarp();
      if (lane == 0) mbar_arrive(BAR(bar));
    };
    auto mma_rs = [&](auto cc, auto k0, auto k1) {
      constexpr int c = decltype(cc)::value;
      const uint64_t db = make_desc(sb + c * ST_BYTES + A_BYTES);
#pragma unroll
      for (int kk = decltype(k0)::value; kk < decltype(k1)::value; kk++)
        wgmma_n256_rs(acc, R[16 * c + 4 * kk], R[16 * c + 4 * kk + 1], R[16 * c + 4 * kk + 2], R[16 * c + 4 * kk + 3], db + kk * 2, c + kk > 0);
      wgmma_commit();
    };
    auto kdone_x = [&](int k, auto ic) {
      constexpr int i = decltype(ic)::value;
      uint32_t r[8];
#pragma unroll
      for (int z = 0; z < 2; z++) {
        const int tr = 32 * (i & 1) + 16 * z + 8 * (lane >> 4) + (lane & 7), chunk = 2 * wi + ((lane >> 3) & 1);
        ldsm_x4_t(sb + (i >> 1) * ST_BYTES + w * 8192 + tr * 128 + ((chunk ^ (lane & 7)) << 4), r[4 * z], r[4 * z + 1], r[4 * z + 2], r[4 * z + 3]);
      }
      float f[16];
#pragma unroll
      for (int z = 0; z < 8; z++) { f[2 * z] = bf_lo(r[z]); f[2 * z + 1] = bf_hi(r[z]); }
#pragma unroll
      for (int z = 0; z < 16; z++) asm volatile("" : "+f"(f[z]));
      kdone(k);
#pragma unroll
      for (int z = 0; z < 16; z++) asm volatile("add.f32 %0, %0, %1;" : "+f"(acc[16 * i + z]) : "f"(f[z]));
    };
    pack(IC<0>());
    put_chunk(IC<0>());
    staged(w ? B_EPI0B : B_EPI);
    mbar_wait(BAR(B_STAT), 0);
    CT(21);
    pack(IC<1>());
    pack(IC<2>());
    pack(IC<3>());
#pragma unroll
    for (int i = 16; i < 64; i++) asm volatile("" : "+r"(R[i]));
    mbar_wait(BAR(B_FULL + 0), 0);
    CT(2);
    CT(64 + 16);
    bar_sync(turn_me, 256);
    wgmma_fence();
    mma_rs(IC<0>(), IC<0>(), IC<4>());
    mbar_wait(BAR(B_FULL + 1), 0);
    CT(64 + 17);
    wgmma_fence();
    mma_rs(IC<1>(), IC<0>(), IC<2>());
    wgmma_wait1();
    release(0);
    mma_rs(IC<1>(), IC<2>(), IC<4>());
    bar_arrive(turn_other, 256);
    kdone_x(17, IC<0>());
    static_for<2>([&](auto ic) {
      constexpr int c = 2 + decltype(ic)::value;
      mbar_wait(BAR(B_FULL + c), 0);
      CT(64 + 16 + c);
      bar_sync(turn_me, 256);
      wgmma_fence();
      mma_rs(IC<c>(), IC<0>(), IC<4>());
      bar_arrive(turn_other, 256);
      if (c == 2) { put_chunk(IC<1>()); staged(B_EPI + 1); }
      kdone_x(16 + c, IC<c - 1>());
    });
#pragma unroll 1
    for (int k = 20; k < 23; k++) {
      if (w == 1) mbar_wait(BAR(B_A20), 0);
      kstep(k, false, k < 22);
      if (k == 20) {
        kdone_x(k, IC<3>());
      } else {
        if (k == 21) put_chunk(IC<2>()); else put_chunk(IC<3>());
        __syncwarp();
        if (lane == 0) mbar_arrive(BAR(B_EPI + k - 19));
        kdone(k);
      }
    }
    uint32_t wf[32][4];
    auto load_wf = [&](auto hc) {
      constexpr int h = decltype(hc)::value;
      const int d = w * 64 + (lane >> 4) * 8 + (lane & 7);
      const uint32_t ad = sb + round_off(h) + (lane & 8) * 1024 + d * 64 + ((wi ^ ((lane >> 1) & 3)) << 4);
#pragma unroll
      for (int i = 0; i < 4; i++) ldsm_x4_t(ad + i * 1024, wf[4 * h + i][0], wf[4 * h + i][1], wf[4 * h + i][2], wf[4 * h + i][3]);
    };
    auto load_wf_rest = [&]() { static_for<8 - NREG_H>([&](auto ic) { load_wf(IC<NREG_H + decltype(ic)::value>()); }); };
#pragma unroll
    for (int i = 0; i < 4 * NREG_H; i++) { wf[i][0] = 0; wf[i][1] = 0; wf[i][2] = 0; wf[i][3] = 0; }
    const int grp = tau * 2 + m;
#pragma unroll 1
    for (int k = 23; k < 46; k++) {
      kstep(k, false);
      if (moe) {
        static_for<NREG_H>([&](auto hc) {
          constexpr int h = decltype(hc)::value;
          if (k == mr_k(h) + 1) { mbar_wait(BAR(B_MR + (h & 1)), (h >> 1) & 1); load_wf(hc); }
        });
      }
      if (k == RESET_K && tid == 0) mbar_arrive(BAR(B_LATE));
      kdone(k);
    }
    asm volatile("barrier.cluster.arrive.relaxed.aligned;" ::: "memory");
    mbar_wait(BAR(B_STAT), 1);
    uint32_t wa[16][2];
    uint32_t cd = code_of(tag);
    uint4* hp_pub = &p.s->hstat[(grp * 8 + eps) * 128 + warp * 16 + g];
    const uint4* hp_poll = &p.s->hstat[(grp * 8 + 2 * q) * 128 + warp * 16 + g];
    const uint32_t vec_off = (2 * wi) * 512 + q * 128 + ((g ^ (2 * q)) << 4);
    {
      float as[64], ak[64];
      fence_acc(acc);
#pragma unroll
      for (int i = 0; i < 64; i++) asm volatile("mov.b32 %0, %1;" : "=f"(as[i]) : "f"(acc[64 + i]));
#pragma unroll
      for (int i = 0; i < 64; i++) asm volatile("mov.b32 %0, %1;" : "=f"(ak[i]) : "f"(acc[i]));
      const uint64_t da1 = make_desc(sb + 2 * ST_BYTES + w * 8192), db1 = make_desc(sb + 2 * ST_BYTES + A_BYTES);
      const uint64_t da2 = make_desc(sb + 3 * ST_BYTES + w * 8192), db2 = make_desc(sb + 3 * ST_BYTES + A_BYTES);
      mbar_wait(BAR(B_FULL + 2), 1);
      CT(64 + 46);
      mbar_wait(BAR(B_FULL + 3), 1);
      CT(64 + 47);
      bar_sync(turn_me, 256);
      wgmma_fence();
#pragma unroll
      for (int kk = 0; kk < 4; kk++) wgmma_n128(as, da1 + kk * 2, db1 + 1024 + kk * 2);
#pragma unroll
      for (int kk = 0; kk < 4; kk++) wgmma_n128(as, da2 + kk * 2, db2 + 1024 + kk * 2);
      wgmma_commit();
      bar_arrive(turn_other, 256);
      const uint32_t rx = mapa(sb + OFF_PEER + w * 4096 + vec_off, 1 - m), rb = mapa(BAR(B_XCH), 1 - m);
      asm volatile("barrier.cluster.wait.aligned;" ::: "memory");
      CT(24);
      wgmma_wait0();
      fence_acc64(as);
      CT(25);
      auto keep = [&]() {
        bar_sync(turn_me, 256);
        wgmma_fence();
#pragma unroll
        for (int kk = 0; kk < 4; kk++) wgmma_n128(ak, da1 + kk * 2, db1 + kk * 2);
        wgmma_commit();
#pragma unroll
        for (int kk = 0; kk < 4; kk++) wgmma_n128(ak, da2 + kk * 2, db2 + kk * 2);
        wgmma_commit();
        if (w == 0) bar_arrive(turn_other, 256);
      };
#pragma unroll
      for (int i = 0; i < 8; i++) {
        if (i == SEND_FIRST) keep();
        const float* ac = &as[16 * (i >> 1) + 2 * (i & 1)];
        st_async_v4(rx + (i >> 1) * 8192 + (i & 1) * 512, rb, pack_bf16(ac[0], ac[1]), pack_bf16(ac[4], ac[5]), pack_bf16(ac[8], ac[9]), pack_bf16(ac[12], ac[13]));
      }
      CT(26);
#pragma unroll
      for (int i = 0; i < 4; i++) {
        const uint4 v = lds128_v(sb + OFF_WR + q * 80 + i * 16);
        const uint32_t vv[4] = {v.x, v.y, v.z, v.w};
#pragma unroll
        for (int z = 0; z < 4; z++) {
          asm volatile("{\n.reg .pred p;\nsetp.ne.b32 p, %2, 0;\nselp.b32 %0, %1, 0x3F803F80, p;\n}" : "=r"(wa[4 * i + z][0]) : "r"(vv[z]), "r"(g & 1));
          asm volatile("{\n.reg .pred p;\nsetp.ne.b32 p, %2, 0;\nselp.b32 %0, %1, 0x3F803F80, p;\n}" : "=r"(wa[4 * i + z][1]) : "r"(vv[z]), "r"(g & 1));
        }
      }
      pin(cd); pin(hp_pub); pin(hp_poll);
      CT(27);
      wgmma_wait1();
      release(2);
      wgmma_wait0();
      fence_acc64(ak);
      CT(3);
#pragma unroll
      for (int i = 0; i < 8; i++) {
        const float* ac = &ak[16 * (i >> 1) + 2 * (i & 1)];
        sts128(sb + (2 + (i >> 2)) * ST_BYTES + w * 8192 + ((i >> 1) & 1) * 4096 + (i & 1) * 512 + vec_off,
               pack_bf16(ac[0], ac[1]), pack_bf16(ac[4], ac[5]), pack_bf16(ac[8], ac[9]), pack_bf16(ac[12], ac[13]));
      }
    }
    uint32_t h[8][4];
    {
      const int qq = 2 * (warp & 1) + ((lane >> 3) & 1);
      const uint32_t lo = (lane >> 4) * 512 + qq * 128 + (((lane & 7) ^ (2 * qq)) << 4);
      bar_sync(NB_BOTH, 256);
#pragma unroll
      for (int ks = 0; ks < 8; ks++)
        ldsm_x4_t(sb + (2 + w) * ST_BYTES + (ks >> 2) * 8192 + (wi >> 1) * 4096 + (ks & 3) * 1024 + lo, h[ks][0], h[ks][1], h[ks][2], h[ks][3]);
      CT(28);
      mbar_wait_cluster(BAR(B_XCH), 0);
      CT(4);
      uint32_t r[8][4];
#pragma unroll
      for (int ks = 0; ks < 8; ks++) ldsm_x4_t(sb + OFF_PEER + (warp >> 1) * 8192 + ks * 1024 + lo, r[ks][0], r[ks][1], r[ks][2], r[ks][3]);
      float d[4][4] = {};
#pragma unroll
      for (int ks = 0; ks < 8; ks++) {
#pragma unroll
        for (int i = 0; i < 4; i++) {
          h[ks][i] = badd2(h[ks][i], r[ks][i]);
          mma1688(d[i], h[ks][i], wa[2 * ks + (i >> 1)][i & 1], h[ks][i]);
        }
      }
#pragma unroll
      for (int i = 0; i < 2; i++) {
        const float sq = (g & 1) ? d[i][1] + d[i + 2][1] : d[i][0] + d[i + 2][0];
        const float e0 = d[i][2] + d[i + 2][2], e1 = d[i][3] + d[i + 2][3];
        const float other = __shfl_xor_sync(0xffffffffu, (g & 1) ? e0 : e1, 4);
        if (q == (g >> 1)) pkt_st128(hp_pub + 8 * i, with_bit((g & 1) ? other : e0, cd), with_bit(sq, cd >> 1), __float_as_uint((g & 1) ? e1 : other), tag);
      }
    }
    CT(5);
    if (tid == 0) mbar_arrive(BAR(B_KEY));
    delay_clk<HOP1_DELAY>();
    float m_bf, sd, inv_sd, r_bf;
    uint4* key_pub = &p.s->key[((lane & 7) * 16 + grp) * 2];
    uint4* cand_pub = &p.s->cand[grp * 256 + eps * 32 + q];
    uint32_t trow_inv = 0xFFFFu - (uint32_t)(grp * 128 + 32 * (warp >> 1) + 8 * (g >> 1) + 4 * (warp & 1) + (q & 2) + (g & 1));
    {
      uint4 u[4];
#pragma unroll
      for (int i = 0; i < 4; i++) u[i] = pkt_ld128(hp_poll + (i & 1) * 128 + (i >> 1) * 8);
      const float wsum = SM_(float, OFF_WSUM);
      pin(key_pub); pin(cand_pub); pin(trow_inv);
      uint32_t n = 0;
      while (true) {
        bool ok[4];
#pragma unroll
        for (int i = 0; i < 4; i++) ok[i] = u[i].w == tag && pair_code(u[i].x, u[i].y) == cd;
        const bool all = __all_sync(0xffffffffu, ok[0] && ok[1] && ok[2] && ok[3]);
        if (all || ++n > SPIN_LIMIT) break;
#pragma unroll
        for (int i = 0; i < 4; i++) pkt_ld128_if(u[i], hp_poll + (i & 1) * 128 + (i >> 1) * 8, !ok[i]);
      }
      CT(6);
      float a[3], b[3];
      a[0] = __uint_as_float(u[0].x & ~1u) + __uint_as_float(u[1].x & ~1u); b[0] = __uint_as_float(u[2].x & ~1u) + __uint_as_float(u[3].x & ~1u);
      a[1] = __uint_as_float(u[0].y & ~1u) + __uint_as_float(u[1].y & ~1u); b[1] = __uint_as_float(u[2].y & ~1u) + __uint_as_float(u[3].y & ~1u);
      a[2] = __uint_as_float(u[0].z) + __uint_as_float(u[1].z); b[2] = __uint_as_float(u[2].z) + __uint_as_float(u[3].z);
#pragma unroll
      for (int i = 0; i < 3; i++) {
        a[i] = ((q & 2) ? b[i] : a[i]) + __shfl_xor_sync(0xffffffffu, (q & 2) ? a[i] : b[i], 2);
        a[i] += __shfl_xor_sync(0xffffffffu, a[i], 1);
      }
      const float mu = a[0] * (1.f / 1024.f);
      m_bf = bf16r(mu);
      sd = ln_sd(a[1] * (1.f / 1024.f) - mu * mu);
      inv_sd = rcp_fast(sd);
      r_bf = bf16r((a[2] - m_bf * wsum) * inv_sd);
    }
    {
      const uint32_t u = __float_as_uint(r_bf);
      const uint32_t ord = (u & 0x80000000u) ? ~u : (u | 0x80000000u);
      const uint32_t key = (ord & 0xFFFF0000u) | trow_inv;
      const uint32_t wk = __reduce_max_sync(0xffffffffu, key);
      if (key == wk) SM_(uint2, OFF_WKEY + warp * 8) = make_uint2(wk, (__float_as_uint(m_bf) >> 16) | __float_as_uint(sd));
      const uint32_t wmask = __ballot_sync(0xffffffffu, key == wk);
      const bool hi = (wmask & 0xCCCCCCCCu) != 0;
      uint32_t c[16];
#pragma unroll
      for (int ks = 0; ks < 8; ks++) { c[2 * ks] = hi ? h[ks][1] : h[ks][0]; c[2 * ks + 1] = hi ? h[ks][3] : h[ks][2]; }
      bar_sync(NB_BOTH, 256);
      const uint2 km = SM_(uint2, OFF_WKEY + (lane & 7) * 8);
      const uint32_t bk = __reduce_max_sync(0xffffffffu, km.x);
      if (wk == bk) {
        if ((wmask >> (lane & 28)) & 15) {
#pragma unroll
          for (int ks = 0; ks < 8; ks++) pkt_st128(cand_pub + ks * 4, c[2 * ks], tag, c[2 * ks + 1], tag);
        }
      } else if (eps == 0) {
        const uint32_t kx = __shfl_sync(0xffffffffu, km.x, warp ^ 1), ms = __shfl_sync(0xffffffffu, km.y, warp ^ 1);
        if (kx == bk && lane < 8) pkt_st128(key_pub, bk, tag, ms, tag);
      }
      CT(7);
    }
    {
      const float ih = bf16r(inv_sd);
      const uint32_t nm = pack_bf16(-m_bf, -m_bf), iv = pack_bf16(ih, inv_sd - ih);
      const uint32_t nm_o = __shfl_xor_sync(0xffffffffu, nm, 2), iv_o = __shfl_xor_sync(0xffffffffu, iv, 2);
      const uint32_t nm2[2] = {(q & 2) ? nm_o : nm, (q & 2) ? nm : nm_o}, iv2[2] = {(q & 2) ? iv_o : iv, (q & 2) ? iv : iv_o};
      const uint32_t hi2[2] = {__byte_perm(iv2[0], 0, 0x1010), __byte_perm(iv2[1], 0, 0x1010)}, lo2[2] = {__byte_perm(iv2[0], 0, 0x3232), __byte_perm(iv2[1], 0, 0x3232)};
      const uint32_t oa = sb + OFF_OUT + (warp * 16 + (lane & 15)) * 128;
#pragma unroll
      for (int ks = 0; ks < 8; ks++) {
        uint32_t o[4];
#pragma unroll
        for (int i = 0; i < 4; i++) {
          const uint32_t dd = badd2(h[ks][i], nm2[i & 1]);
          o[i] = badd2(h[ks][i], bfma2(dd, hi2[i & 1], bmul2(dd, lo2[i & 1])));
        }
        stsm_x4(oa + (ks >> 2) * 16384 + (((2 * (ks & 3) + (lane >> 4)) ^ (lane & 7)) << 4), o[0], o[1], o[2], o[3]);
      }
      staged(B_OUT);
    }
    CT(8);
    uint32_t df[16][4];
    auto load_df = [&]() {
      const int frow = (lane & 7) + ((lane >> 4) << 3), hi = (lane >> 3) & 1;
      const uint32_t base = sb + down_off(warp >> 1) + (warp & 1) * 8192 + frow * 128;
#pragma unroll
      for (int mt = 0; mt < 8; mt++) {
#pragma unroll
        for (int ks = 0; ks < 2; ks++)
          ldsm_x4_t(base + (mt >> 2) * 4096 + ks * 2048 + (((2 * (mt & 3) + hi) ^ (lane & 7)) << 4),
                    df[2 * mt + ks][0], df[2 * mt + ks][1], df[2 * mt + ks][2], df[2 * mt + ks][3]);
      }
    };
    if (moe) {
      mbar_wait(BAR(B_GU), 0);
      load_wf_rest();
      mbar_wait(BAR(B_DN), 0);
      load_df();
    }
    uint4* y_pub = &p.s->ypart[cid * 256 + tid];
    uint32_t xs_ad = sb + OFF_XSEL + (8 * (g >> 2) + 4 * w + (g & 3)) * 32 + q * 8, gp_ad = sb + OFF_GP + (wi * 8 + g) * 16 + w * 8 + (q >> 1) * 4;
    pin(y_pub); pin(xs_ad); pin(gp_ad);
    mbar_wait(BAR(B_XS), 0);
    CT(9);
    if (moe) {
      float gd[8][4] = {};
      uint2 bx[4];
#pragma unroll
      for (int r = 0; r < 4; r++) bx[r] = smem_at<uint2>(xs_ad + r * 512);
#pragma unroll
      for (int r = 0; r < 4; r++) {
#pragma unroll
        for (int i = 0; i < 8; i++) mma16816(gd[i], wf[8 * r + i][0], wf[8 * r + i][1], wf[8 * r + i][2], wf[8 * r + i][3], bx[r].x, bx[r].y);
      }
      const float gs = sel4(q, gd[0][0] + gd[1][1], gd[2][0] + gd[3][1], gd[4][0] + gd[5][1], gd[6][0] + gd[7][1]);
      const float us = sel4(q, gd[0][2] + gd[1][3], gd[2][2] + gd[3][3], gd[4][2] + gd[5][3], gd[6][2] + gd[7][3]);
      float v = ((q & 2) ? us : gs) + __shfl_xor_sync(0xffffffffu, (q & 2) ? gs : us, 2);
      v += __shfl_xor_sync(0xffffffffu, v, 1);
      smem_at<float>(gp_ad) = v;
      CT(10);
      bar_sync(NB_BOTH, 256);
      uint32_t bq[4];
      {
        const float4 p0 = SM_(float4, OFF_GP + lane * 16);
        const float gt = bf16r(p0.x + p0.z), up = bf16r(p0.y + p0.w);
        const float act = bf16r(gt * sigmoid_fast(gt)) * up;
        const uint32_t pr = pack_bf16(act, __shfl_down_sync(0xffffffffu, act, 1));
#pragma unroll
        for (int i = 0; i < 4; i++) bq[i] = __shfl_sync(0xffffffffu, pr, 8 * i + 2 * q);
      }
      CT(11);
      float yd[8][4] = {};
#pragma unroll
      for (int ks = 0; ks < 2; ks++) {
#pragma unroll
        for (int mt = 0; mt < 8; mt++) mma16816(yd[mt], df[2 * mt + ks][0], df[2 * mt + ks][1], df[2 * mt + ks][2], df[2 * mt + ks][3], bq[2 * ks], bq[2 * ks + 1]);
      }
      pkt_st128(y_pub, with_bit(sel4(q, yd[0][0], yd[2][0], yd[4][0], yd[6][0]), cd), with_bit(sel4(q, yd[0][2], yd[2][2], yd[4][2], yd[6][2]), cd >> 1),
                with_bit(sel4(q, yd[1][0], yd[3][0], yd[5][0], yd[7][0]), cd), with_bit(sel4(q, yd[1][2], yd[3][2], yd[5][2], yd[7][2]), cd >> 1));
    } else {
      const long long tw = clock64();
      while (clock64() - tw < IDLE_WAIT_CLK) __nanosleep(100);
    }
    CT(12);
    const uint32_t kv = SM_(uint32_t, OFF_KV);
    const int tsel = 0xFFFF - (int)(kv & 0xFFFFu);
    const float r_sel = __uint_as_float((kv & 0x80000000u) ? (kv & 0x7FFF0000u) : (~kv & 0xFFFF0000u));
    const float sig = bf16r(sigmoid_fast(r_sel));
    const int pfin = 2 * cid + (tid & 1);
    const int col_fin = (pfin >> 5) * 128 + (pfin & 3) * 32 + ((pfin & 31) >> 2) + 8 * ((tid >> 1) & 3);
    const int sel_off = (col_fin >> 4) * 32 + ((col_fin & 7) >> 1) * 8 + ((col_fin >> 3) & 1) * 4 + (col_fin & 1) * 2;
    const float hn_fin = __uint_as_float((uint32_t)SM_(uint16_t, OFF_XSEL + sel_off) << 16), h_fin = __uint_as_float((uint32_t)SM_(uint16_t, OFF_HSEL + sel_off) << 16);
    bf16* out_fin = p.out + (size_t)tsel * 1024 + col_fin;
    {
      const uint4* src = &p.s->ypart[(16 + (tid >> 1)) * 256 + pfin];
      pin(src); pin(out_fin);
      uint4 v = make_uint4(0, 0, 0, 0);
      if (warp < 7) {
        delay_clk<HOP3_DELAY>();
        uint32_t n = 0;
        bool ok = false;
        do {
          pkt_ld128_if(v, src, !ok);
          ok = pair_code(v.x, v.y) == cd && pair_code(v.z, v.w) == cd;
        } while (!__all_sync(0xffffffffu, ok) && ++n < SPIN_LIMIT);
      }
      CT(13);
      const float y0 = __uint_as_float(v.x & ~1u), y1 = __uint_as_float(v.y & ~1u), y2 = __uint_as_float(v.z & ~1u), y3 = __uint_as_float(v.w & ~1u);
      const float a0 = ((lane & 2) ? y1 : y0) + __shfl_xor_sync(0xffffffffu, (lane & 2) ? y0 : y1, 2);
      const float a1 = ((lane & 2) ? y3 : y2) + __shfl_xor_sync(0xffffffffu, (lane & 2) ? y2 : y3, 2);
      float b = ((lane & 4) ? a1 : a0) + __shfl_xor_sync(0xffffffffu, (lane & 4) ? a0 : a1, 4);
      b += __shfl_xor_sync(0xffffffffu, b, 8);
      b += __shfl_xor_sync(0xffffffffu, b, 16);
      if (lane < 8) SM_(float, OFF_FIN + lane * 32 + warp * 4) = b;
    }
    bar_sync(NB_BOTH, 256);
    if (tid < 8) {
      const float4 y0 = SM_(float4, OFF_FIN + tid * 32), y1 = SM_(float4, OFF_FIN + tid * 32 + 16);
      const float y = ((y0.x + y0.y) + (y0.z + y0.w)) + ((y1.x + y1.y) + y1.z);
      *out_fin = __float2bfloat16_rn(h_fin + bf16r(hn_fin + bf16r(bf16r(y) * sig)));
      if (cid == 0 && tid == 0) st_relaxed32(&p.s->epoch, tag);
    }
    CT(14);
  }
}

__global__ void __launch_bounds__(384, 1) occupancy_probe_kernel() {}

typedef CUresult (*EncodeFn)(CUtensorMap*, CUtensorMapDataType, cuuint32_t, void*, const cuuint64_t*, const cuuint64_t*, const cuuint32_t*, const cuuint32_t*,
                             CUtensorMapInterleave, CUtensorMapSwizzle, CUtensorMapL2promotion, CUtensorMapFloatOOBfill);

static void make_tm(EncodeFn enc, CUtensorMap* tm, const void* ptr, uint64_t rows, uint64_t cols, uint32_t brows, uint32_t bcols, CUtensorMapSwizzle sw) {
  cuuint64_t dims[2] = {cols, rows};
  cuuint64_t strides[1] = {cols * 2};
  cuuint32_t box[2] = {bcols, brows};
  cuuint32_t es[2] = {1, 1};
  enc(tm, CU_TENSOR_MAP_DATA_TYPE_BFLOAT16, 2, const_cast<void*>(ptr), dims, strides, box, es, CU_TENSOR_MAP_INTERLEAVE_NONE, sw,
      CU_TENSOR_MAP_L2_PROMOTION_L2_128B, CU_TENSOR_MAP_FLOAT_OOB_FILL_NONE);
}

extern "C" void kernel_launch(void* const* d_in, const int* in_sizes, int n_in, void* d_out, int out_size) {
  (void)in_sizes; (void)n_in; (void)out_size;
  static EncodeFn enc = nullptr;
  static void* abT = nullptr;
  static int map = 0;
  if (!enc) {
    void* fn = nullptr; cudaDriverEntryPointQueryResult st;
    cudaGetDriverEntryPoint("cuTensorMapEncodeTiled", &fn, cudaEnableDefault, &st);
    enc = (EncodeFn)fn;
    cudaGetSymbolAddress(&abT, g_scratch);
    cudaFuncSetAttribute(fnet_moe_kernel<0>, cudaFuncAttributeMaxDynamicSharedMemorySize, SMEM_TOTAL);
    cudaFuncSetAttribute(fnet_moe_kernel<1>, cudaFuncAttributeMaxDynamicSharedMemorySize, SMEM_TOTAL);
    cudaFuncSetAttribute(occupancy_probe_kernel, cudaFuncAttributeMaxDynamicSharedMemorySize, SMEM_TOTAL);
    cudaFuncSetAttribute(occupancy_probe_kernel, cudaFuncAttributeNonPortableClusterSizeAllowed, 1);
    auto max_clusters = [&](int size) {
      cudaLaunchConfig_t cfg = {};
      cfg.gridDim = dim3(128); cfg.blockDim = dim3(384); cfg.dynamicSmemBytes = SMEM_TOTAL;
      cudaLaunchAttribute at[1];
      at[0].id = cudaLaunchAttributeClusterDimension; at[0].val.clusterDim.x = size; at[0].val.clusterDim.y = 1; at[0].val.clusterDim.z = 1;
      cfg.attrs = at; cfg.numAttrs = 1;
      int ncl = 0;
      return cudaOccupancyMaxActiveClusters(&ncl, occupancy_probe_kernel, &cfg) == cudaSuccess ? ncl : 0;
    };
    int dev = 0, sms = 0;
    cudaGetDevice(&dev);
    cudaDeviceGetAttribute(&sms, cudaDevAttrMultiProcessorCount, dev);
    map = (sms == 132 && max_clusters(2) == 66 && max_clusters(16) == 7) ? 0 : 1;
    (void)cudaGetLastError();
  }
  Params p;
  const bf16* x = (const bf16*)d_in[0];
  make_tm(enc, &p.tmD0, d_in[3], 1024, 1024, 128, 64, CU_TENSOR_MAP_SWIZZLE_128B);
  make_tm(enc, &p.tmD1, d_in[4], 1024, 1024, 128, 64, CU_TENSOR_MAP_SWIZZLE_128B);
  make_tm(enc, &p.tmX, x, 2048, 1024, 256, 64, CU_TENSOR_MAP_SWIZZLE_128B);
  make_tm(enc, &p.tmXr, x, 2048, 1024, 64, 64, CU_TENSOR_MAP_SWIZZLE_128B);
  make_tm(enc, &p.tmAbS, abT, 2048, 2048, 64, 64, CU_TENSOR_MAP_SWIZZLE_128B);
  make_tm(enc, &p.tmAbL, abT, 2048, 2048, 128, 64, CU_TENSOR_MAP_SWIZZLE_128B);
  make_tm(enc, &p.tmW0, d_in[1], 2048, 2048, 128, 64, CU_TENSOR_MAP_SWIZZLE_128B);
  make_tm(enc, &p.tmW1, d_in[2], 2048, 2048, 128, 64, CU_TENSOR_MAP_SWIZZLE_128B);
  {
    cuuint64_t dims[5] = {1024, 2, 4, 4, 64};
    cuuint64_t strides[4] = {2048, 8 * 2048, 2 * 2048, 32 * 2048};
    cuuint32_t box[5] = {64, 2, 4, 2, 1};
    cuuint32_t es[5] = {1, 1, 1, 1, 1};
    enc(&p.tmOut, CU_TENSOR_MAP_DATA_TYPE_BFLOAT16, 5, d_out, dims, strides, box, es, CU_TENSOR_MAP_INTERLEAVE_NONE, CU_TENSOR_MAP_SWIZZLE_128B,
        CU_TENSOR_MAP_L2_PROMOTION_NONE, CU_TENSOR_MAP_FLOAT_OOB_FILL_NONE);
  }
  make_tm(enc, &p.tmG, d_in[7], 1024, 3584, 128, 32, CU_TENSOR_MAP_SWIZZLE_64B);
  make_tm(enc, &p.tmU, d_in[8], 1024, 3584, 128, 32, CU_TENSOR_MAP_SWIZZLE_64B);
  make_tm(enc, &p.tmDn, d_in[9], 3584, 1024, 32, 64, CU_TENSOR_MAP_SWIZZLE_128B);
  p.x = x; p.Dre = (const bf16*)d_in[3]; p.Dim = (const bf16*)d_in[4];
  p.wr = (const bf16*)d_in[6]; p.wdown = (const bf16*)d_in[9]; p.wgate = (const bf16*)d_in[7]; p.wup = (const bf16*)d_in[8];
  p.out = (bf16*)d_out; p.s = (Scratch*)abT;
  if (map == 1) fnet_moe_kernel<1><<<128, 384, SMEM_TOTAL>>>(p);
  else fnet_moe_kernel<0><<<132, 384, SMEM_TOTAL>>>(p);
}
```

```cpp
#include <cuda.h>
#include <cuda_runtime.h>
#include <cuda_bf16.h>
#include <stdint.h>
#include <type_traits>

typedef __nv_bfloat16 bf16;

constexpr int NX0 = 240;
constexpr int REG_C = 232, REG_P = 40;
__device__ __forceinline__ int sigma_of(int tau, int r) { return r + (r >= tau); }
__device__ __forceinline__ int kblock(int tau, int j) {
  const int i = j - 4, c = (i * 37) >> 8;
  return j < 4 ? tau * 4 + j : sigma_of(tau, i - 7 * c) * 4 + c;
}
constexpr int AUX_AFTER = 1;
constexpr int PF_K0 = 8, PF_N0 = 2, PF_K1 = 24;
constexpr int WPF_K0 = 12, WPF_N = 10;
constexpr int PUB_K1 = 22;
constexpr int NREG_H = 5;
constexpr int MR_K0 = 29, MR_P = 6;
constexpr int MINI_PF_K = 39, MINI_LOAD_K = 43, MINI_K = 42;
constexpr int RESET_K = 37;
constexpr int SEND_FIRST = 2;
constexpr int HELPER_NS = 5000;
constexpr int GATHER_NS = 400;
constexpr int MOE_PACE_CLK = 300;
constexpr int OUT_PACE_CLK = 100;
constexpr int HOP1_DELAY = 150, HOP3_DELAY = 300;
constexpr int SPEC_MIN = 10;
constexpr int IDLE_WAIT_CLK = 1200;
__host__ __device__ constexpr int mr_k(int h) { return MR_K0 + MR_P * (h >> 1) + 2 * (h & 1); }
constexpr int A_BYTES = 128 * 64 * 2;
constexpr int B_BYTES = 256 * 64 * 2;
constexpr int ST_BYTES = A_BYTES + B_BYTES;
constexpr int OFF_XCH = 4 * ST_BYTES;
constexpr int OFF_BAR = OFF_XCH + 32768;
constexpr int OFF_WR = OFF_BAR + 384;
constexpr int OFF_RS = OFF_WR + 384;
constexpr int OFF_PUB = OFF_RS + 640;
constexpr int OFF_MISC = OFF_PUB + 768;
constexpr int SMEM_TOTAL = OFF_MISC + 256;
constexpr int OFF_WSUM = OFF_MISC, OFF_TAG = OFF_MISC + 4;
constexpr int OFF_SEEN = OFF_MISC + 8;
constexpr int OFF_KV = OFF_MISC + 12;
constexpr int OFF_WKEY = OFF_MISC + 32;
constexpr int OFF_MINI = OFF_XCH + 16384;
constexpr int OFF_EXA = OFF_XCH;
constexpr int OFF_EXB = OFF_XCH + 4096;
__host__ __device__ constexpr int chunk_off(int c, int w) { return (c < 2 ? (c + 2) * ST_BYTES : OFF_XCH + (c - 2) * 16384) + w * 8192; }
__host__ __device__ constexpr int late_off(int i) { return i < 4 ? i * 16384 : 2 * ST_BYTES + A_BYTES + (i - 4) * 16384; }
__host__ __device__ constexpr int round_off(int h) { return h < NREG_H + 2 ? OFF_XCH + (h & 1) * 16384 : late_off(h - NREG_H - 2); }
__host__ __device__ constexpr int down_off(int i) { return late_off(6 - NREG_H + i); }
constexpr int OFF_PEER = ST_BYTES + A_BYTES;
constexpr int OFF_OUT = 3 * ST_BYTES + A_BYTES;
constexpr int OFF_XSEL = OFF_PEER;
constexpr int OFF_HSEL = OFF_PEER + 4096;
constexpr int OFF_GP = OFF_PEER + 8192;
constexpr int OFF_FIN = OFF_PEER + 9216;
__device__ __forceinline__ int slot_of(int k) { return k & 3; }
__device__ __forceinline__ int use_of(int k) { return k >> 2; }
enum { B_FULL = 0, B_EMPTY = 4, B_EPI = 8, B_STD = 12, B_EPI0B = 16, B_LATE = 17, B_STAT = 18, B_XCH = 19, B_MR = 20  , B_GU = 22,
       B_DN = 23, B_AUX = 24  , B_OUT = 26, B_KEY = 27, B_XS = 28, B_A20 = 29, B_STDA = 30, B_COUNT = 31 };
enum { NB_TURN0 = 1, NB_TURN1 = 2, NB_WG0 = 3, NB_BOTH = 5, NB_AUX = 6 };

struct Scratch {
  bf16 abT[2048 * 2048];
  uint2 xstat[2048];
  uint2 dsum[2048];
  uint4 abflag[16 * 8 * 2];
  uint4 hflag[16 * 2];
  uint4 hstat[16 * 8 * 128];
  uint4 cand[16 * 256];
  uint4 key[8 * 16 * 2];
  uint4 ypart[128 * 256];
  uint32_t epoch;
};
__device__ __align__(1024) Scratch g_scratch;

struct Params {
  Scratch* s; bf16* out;
  const bf16* x; const bf16* Dre; const bf16* Dim; const bf16* wr; const bf16* wdown; const bf16* wgate; const bf16* wup;
  CUtensorMap tmX, tmD0, tmD1, tmXr, tmAbS, tmAbL, tmW0, tmW1, tmOut, tmG, tmU, tmDn, tmXh, tmAbM, tmWM0, tmWM1;
};

#define SPIN_LIMIT (1u << 14)
#define MBAR_LIMIT (1u << 10)
__device__ __forceinline__ uint32_t smem_u32(const void* p) { return (uint32_t)__cvta_generic_to_shared(p); }
__device__ __forceinline__ void mbar_init(uint32_t bar, uint32_t cnt) { asm volatile("mbarrier.init.shared::cta.b64 [%0], %1;" :: "r"(bar), "r"(cnt) : "memory"); }
__device__ __forceinline__ void mbar_expect_tx(uint32_t bar, uint32_t bytes) { asm volatile("mbarrier.arrive.expect_tx.shared::cta.b64 _, [%0], %1;" :: "r"(bar), "r"(bytes) : "memory"); }
__device__ __forceinline__ void mbar_arrive(uint32_t bar) { asm volatile("mbarrier.arrive.shared::cta.b64 _, [%0];" :: "r"(bar) : "memory"); }
__device__ __forceinline__ void mbar_wait(uint32_t bar, uint32_t parity) {
  uint32_t ok, n = 0;
  do {
    asm volatile("{\n.reg .pred p;\nmbarrier.try_wait.parity.shared::cta.b64 p, [%1], %2;\nselp.u32 %0, 1, 0, p;\n}\n" : "=r"(ok) : "r"(bar), "r"(parity) : "memory");
  } while (!ok && ++n < MBAR_LIMIT);
}
__device__ __forceinline__ bool mbar_test(uint32_t bar, uint32_t parity) {
  uint32_t ok;
  asm volatile("{\n.reg .pred p;\nmbarrier.test_wait.parity.shared::cta.b64 p, [%1], %2;\nselp.u32 %0, 1, 0, p;\n}\n" : "=r"(ok) : "r"(bar), "r"(parity) : "memory");
  return ok != 0;
}
__device__ __forceinline__ void mbar_wait_cluster(uint32_t bar, uint32_t parity) {
  uint32_t ok, n = 0;
  do {
    asm volatile("{\n.reg .pred p;\nmbarrier.try_wait.parity.acquire.cluster.shared::cta.b64 p, [%1], %2;\nselp.u32 %0, 1, 0, p;\n}\n" : "=r"(ok) : "r"(bar), "r"(parity) : "memory");
  } while (!ok && ++n < MBAR_LIMIT);
}
__device__ __forceinline__ void tma_load_2d(uint32_t dst, const CUtensorMap* tm, uint32_t bar, int c0, int c1) {
  asm volatile("cp.async.bulk.tensor.2d.shared::cluster.global.mbarrier::complete_tx::bytes [%0], [%1, {%3, %4}], [%2];"
    :: "r"(dst), "l"(tm), "r"(bar), "r"(c0), "r"(c1) : "memory");
}
__device__ __forceinline__ void tma_load_2d_hint(uint32_t dst, const CUtensorMap* tm, uint32_t bar, int c0, int c1, uint64_t pol) {
  asm volatile("cp.async.bulk.tensor.2d.shared::cluster.global.mbarrier::complete_tx::bytes.L2::cache_hint [%0], [%1, {%3, %4}], [%2], %5;"
    :: "r"(dst), "l"(tm), "r"(bar), "r"(c0), "r"(c1), "l"(pol) : "memory");
}
__device__ __forceinline__ uint64_t policy_evict_first() { uint64_t p; asm volatile("createpolicy.fractional.L2::evict_first.b64 %0, 1.0;" : "=l"(p)); return p; }
__device__ __forceinline__ void tma_store_2d(const CUtensorMap* tm, uint32_t src, int c0, int c1) {
  asm volatile("cp.async.bulk.tensor.2d.global.shared::cta.bulk_group [%0, {%2, %3}], [%1];" :: "l"(tm), "r"(src), "r"(c0), "r"(c1) : "memory");
}
__device__ __forceinline__ void tma_prefetch_2d(const CUtensorMap* tm, int c0, int c1) {
  asm volatile("cp.async.bulk.prefetch.tensor.2d.L2.global.tile [%0, {%1, %2}];" :: "l"(tm), "r"(c0), "r"(c1) : "memory");
}
__device__ __forceinline__ void bulk_load(uint32_t dst, const void* src, uint32_t bytes, uint32_t bar) {
  asm volatile("cp.async.bulk.shared::cluster.global.mbarrier::complete_tx::bytes [%0], [%1], %2, [%3];" :: "r"(dst), "l"(src), "r"(bytes), "r"(bar) : "memory");
}
__device__ __forceinline__ void bulk_commit() { asm volatile("cp.async.bulk.commit_group;" ::: "memory"); }
__device__ __forceinline__ void bulk_wait_all() { asm volatile("cp.async.bulk.wait_group 0;" ::: "memory"); }
__device__ __forceinline__ void fence_async_smem() { asm volatile("fence.proxy.async.shared::cta;" ::: "memory"); }
__device__ __forceinline__ void wgmma_fence() { asm volatile("wgmma.fence.sync.aligned;" ::: "memory"); }
__device__ __forceinline__ void wgmma_commit() { asm volatile("wgmma.commit_group.sync.aligned;" ::: "memory"); }
__device__ __forceinline__ void wgmma_wait0() { asm volatile("wgmma.wait_group.sync.aligned 0;" ::: "memory"); }
__device__ __forceinline__ void bar_sync(int id, int n) { asm volatile("bar.sync %0, %1;" :: "r"(id), "r"(n) : "memory"); }
__device__ __forceinline__ void bar_arrive(int id, int n) { asm volatile("bar.arrive %0, %1;" :: "r"(id), "r"(n) : "memory"); }
template<int R> __device__ __forceinline__ void reg_inc() { asm volatile("setmaxnreg.inc.sync.aligned.u32 %0;" :: "n"(R)); }
template<int R> __device__ __forceinline__ void reg_dec() { asm volatile("setmaxnreg.dec.sync.aligned.u32 %0;" :: "n"(R)); }
__device__ __forceinline__ bool elect_one() {
  uint32_t p;
  asm volatile("{\n.reg .pred q;\nelect.sync _|q, 0xffffffff;\nselp.u32 %0, 1, 0, q;\n}\n" : "=r"(p));
  return p != 0;
}
__device__ __forceinline__ uint32_t mapa(uint32_t addr, uint32_t cta) { uint32_t r; asm volatile("mapa.shared::cluster.u32 %0, %1, %2;" : "=r"(r) : "r"(addr), "r"(cta)); return r; }
__device__ __forceinline__ void st_async_v4(uint32_t addr, uint32_t bar, uint32_t a, uint32_t b, uint32_t c, uint32_t d) {
  asm volatile("st.async.weak.shared::cluster.mbarrier::complete_tx::bytes.v4.b32 [%0], {%2, %3, %4, %5}, [%1];" :: "r"(addr), "r"(bar), "r"(a), "r"(b), "r"(c), "r"(d) : "memory");
}
__device__ __forceinline__ void stsm_x4(uint32_t addr, uint32_t a, uint32_t b, uint32_t c, uint32_t d) {
  asm volatile("stmatrix.sync.aligned.m8n8.x4.shared.b16 [%0], {%1, %2, %3, %4};" :: "r"(addr), "r"(a), "r"(b), "r"(c), "r"(d));
}
__device__ __forceinline__ uint4 lds128_v(uint32_t addr) { uint4 v; asm volatile("ld.shared.v4.b32 {%0, %1, %2, %3}, [%4];" : "=r"(v.x), "=r"(v.y), "=r"(v.z), "=r"(v.w) : "r"(addr)); return v; }
extern __shared__ __align__(1024) uint8_t smem_raw[];
template<class T> __device__ __forceinline__ T& smem_at(uint32_t addr) { return *reinterpret_cast<T*>(__cvta_shared_to_generic(addr)); }
#define SM_(T, off) smem_at<T>(sb + (off))
__device__ __forceinline__ uint4 ldg_nc128(const void* p) { uint4 v; asm volatile("ld.global.nc.v4.b32 {%0, %1, %2, %3}, [%4];" : "=r"(v.x), "=r"(v.y), "=r"(v.z), "=r"(v.w) : "l"(p)); return v; }
__device__ __forceinline__ void pkt_st128(void* p, uint32_t a, uint32_t b, uint32_t c, uint32_t d) {
  asm volatile("{\n.reg .b128 v;\n.reg .b64 lo, hi;\nmov.b64 lo, {%1, %2};\nmov.b64 hi, {%3, %4};\nmov.b128 v, {lo, hi};\nst.relaxed.gpu.global.b128 [%0], v;\n}\n"
    :: "l"(p), "r"(a), "r"(b), "r"(c), "r"(d) : "memory");
}
__device__ __forceinline__ uint4 pkt_ld128(const void* p) {
  uint4 r;
  asm volatile("{\n.reg .b128 v;\n.reg .b64 lo, hi;\nld.relaxed.gpu.global.b128 v, [%4];\nmov.b128 {lo, hi}, v;\nmov.b64 {%0, %1}, lo;\nmov.b64 {%2, %3}, hi;\n}\n"
    : "=r"(r.x), "=r"(r.y), "=r"(r.z), "=r"(r.w) : "l"(p) : "memory");
  return r;
}
__device__ __forceinline__ void pkt_ld128_if(uint4& r, const void* p, bool cond) {
  asm volatile("{\n.reg .pred q;\n.reg .b64 lo, hi;\nsetp.ne.b32 q, %5, 0;\nmov.b64 lo, {%0, %1};\nmov.b64 hi, {%2, %3};\n"
               "@q ld.relaxed.gpu.global.v2.b64 {lo, hi}, [%4];\nmov.b64 {%0, %1}, lo;\nmov.b64 {%2, %3}, hi;\n}\n"
    : "+r"(r.x), "+r"(r.y), "+r"(r.z), "+r"(r.w) : "l"(p), "r"((uint32_t)cond) : "memory");
}
__device__ __forceinline__ void pkt_st64(void* p, uint32_t a, uint32_t b) {
  asm volatile("{\n.reg .b64 v;\nmov.b64 v, {%1, %2};\nst.relaxed.gpu.global.b64 [%0], v;\n}\n" :: "l"(p), "r"(a), "r"(b) : "memory");
}
__device__ __forceinline__ uint2 pkt_ld64(const void* p) {
  uint2 r;
  asm volatile("{\n.reg .b64 v;\nld.relaxed.gpu.global.b64 v, [%2];\nmov.b64 {%0, %1}, v;\n}\n" : "=r"(r.x), "=r"(r.y) : "l"(p) : "memory");
  return r;
}
__device__ __forceinline__ uint32_t ld_relaxed32(const void* p) { uint32_t v; asm volatile("ld.relaxed.gpu.global.b32 %0, [%1];" : "=r"(v) : "l"(p) : "memory"); return v; }
__device__ __forceinline__ void st_relaxed32(void* p, uint32_t v) { asm volatile("st.relaxed.gpu.global.b32 [%0], %1;" :: "l"(p), "r"(v) : "memory"); }
__device__ __forceinline__ uint32_t code_of(uint32_t tag) { return tag % 3u + 1u; }
__device__ __forceinline__ uint32_t with_bit(float v, uint32_t bit) { return (__float_as_uint(v) & ~1u) | (bit & 1u); }
__device__ __forceinline__ uint32_t pair_code(uint32_t a, uint32_t b) { return (a & 1u) | ((b & 1u) << 1); }
__device__ __forceinline__ uint32_t pack_bf16(float lo, float hi) { uint32_t r; asm("cvt.rn.bf16x2.f32 %0, %1, %2;" : "=r"(r) : "f"(hi), "f"(lo)); return r; }
__device__ __forceinline__ float bf_lo(uint32_t v) { return __uint_as_float(v << 16); }
__device__ __forceinline__ float bf_hi(uint32_t v) { return __uint_as_float(v & 0xFFFF0000u); }
__device__ __forceinline__ float bf16r(float x) { return __uint_as_float(pack_bf16(0.f, x)); }
__device__ __forceinline__ uint32_t badd2(uint32_t a, uint32_t b) { uint32_t r; asm("add.rn.bf16x2 %0, %1, %2;" : "=r"(r) : "r"(a), "r"(b)); return r; }
__device__ __forceinline__ uint32_t bmul2(uint32_t a, uint32_t b) { uint32_t r; asm("mul.rn.bf16x2 %0, %1, %2;" : "=r"(r) : "r"(a), "r"(b)); return r; }
__device__ __forceinline__ float warp_sum(float v) {
#pragma unroll
  for (int o = 16; o > 0; o >>= 1) v += __shfl_xor_sync(0xffffffffu, v, o);
  return v;
}
__device__ __forceinline__ uint64_t make_desc(uint32_t addr) {
  return (uint64_t)((addr & 0x3FFFF) >> 4) | ((uint64_t)1 << 16) | ((uint64_t)64 << 32) | ((uint64_t)1 << 62);
}
__device__ __forceinline__ uint64_t make_desc_noswz(uint32_t addr) {
  return (uint64_t)((addr & 0x3FFFF) >> 4) | ((uint64_t)8 << 16) | ((uint64_t)16 << 32);
}
__device__ __forceinline__ uint64_t make_desc_32b(uint32_t addr) {
  return (uint64_t)((addr & 0x3FFFF) >> 4) | ((uint64_t)1 << 16) | ((uint64_t)16 << 32) | ((uint64_t)3 << 62);
}
__device__ __forceinline__ void wgmma_n256(float (&d)[128], uint64_t da, uint64_t db, int scale_d) {
  asm volatile("{\n.reg .pred p;\nsetp.ne.b32 p, %130, 0;\n"
    "wgmma.mma_async.sync.aligned.m64n256k16.f32.bf16.bf16 "
    "{%0, %1, %2, %3, %4, %5, %6, %7, %8, %9, %10, %11, %12, %13, %14, %15, %16, %17, %18, %19, %20, %21, %22, %23, %24, %25, %26, %27, %28, %29, %30, %31, "
    "%32, %33, %34, %35, %36, %37, %38, %39, %40, %41, %42, %43, %44, %45, %46, %47, %48, %49, %50, %51, %52, %53, %54, %55, %56, %57, %58, %59, %60, %61, %62, %63, "
    "%64, %65, %66, %67, %68, %69, %70, %71, %72, %73, %74, %75, %76, %77, %78, %79, %80, %81, %82, %83, %84, %85, %86, %87, %88, %89, %90, %91, %92, %93, %94, %95, "
    "%96, %97, %98, %99, %100, %101, %102, %103, %104, %105, %106, %107, %108, %109, %110, %111, %112, %113, %114, %115, %116, %117, %118, %119, %120, %121, %122, %123, %124, %125, %126, %127}, "
    "%128, %129, p, 1, 1, 0, 0;\n}\n"
    : "+f"(d[0]), "+f"(d[1]), "+f"(d[2]), "+f"(d[3]), "+f"(d[4]), "+f"(d[5]), "+f"(d[6]), "+f"(d[7]),
      "+f"(d[8]), "+f"(d[9]), "+f"(d[10]), "+f"(d[11]), "+f"(d[12]), "+f"(d[13]), "+f"(d[14]), "+f"(d[15]),
      "+f"(d[16]), "+f"(d[17]), "+f"(d[18]), "+f"(d[19]), "+f"(d[20]), "+f"(d[21]), "+f"(d[22]), "+f"(d[23]),
      "+f"(d[24]), "+f"(d[25]), "+f"(d[26]), "+f"(d[27]), "+f"(d[28]), "+f"(d[29]), "+f"(d[30]), "+f"(d[31]),
      "+f"(d[32]), "+f"(d[33]), "+f"(d[34]), "+f"(d[35]), "+f"(d[36]), "+f"(d[37]), "+f"(d[38]), "+f"(d[39]),
      "+f"(d[40]), "+f"(d[41]), "+f"(d[42]), "+f"(d[43]), "+f"(d[44]), "+f"(d[45]), "+f"(d[46]), "+f"(d[47]),
      "+f"(d[48]), "+f"(d[49]), "+f"(d[50]), "+f"(d[51]), "+f"(d[52]), "+f"(d[53]), "+f"(d[54]), "+f"(d[55]),
      "+f"(d[56]), "+f"(d[57]), "+f"(d[58]), "+f"(d[59]), "+f"(d[60]), "+f"(d[61]), "+f"(d[62]), "+f"(d[63]),
      "+f"(d[64]), "+f"(d[65]), "+f"(d[66]), "+f"(d[67]), "+f"(d[68]), "+f"(d[69]), "+f"(d[70]), "+f"(d[71]),
      "+f"(d[72]), "+f"(d[73]), "+f"(d[74]), "+f"(d[75]), "+f"(d[76]), "+f"(d[77]), "+f"(d[78]), "+f"(d[79]),
      "+f"(d[80]), "+f"(d[81]), "+f"(d[82]), "+f"(d[83]), "+f"(d[84]), "+f"(d[85]), "+f"(d[86]), "+f"(d[87]),
      "+f"(d[88]), "+f"(d[89]), "+f"(d[90]), "+f"(d[91]), "+f"(d[92]), "+f"(d[93]), "+f"(d[94]), "+f"(d[95]),
      "+f"(d[96]), "+f"(d[97]), "+f"(d[98]), "+f"(d[99]), "+f"(d[100]), "+f"(d[101]), "+f"(d[102]), "+f"(d[103]),
      "+f"(d[104]), "+f"(d[105]), "+f"(d[106]), "+f"(d[107]), "+f"(d[108]), "+f"(d[109]), "+f"(d[110]), "+f"(d[111]),
      "+f"(d[112]), "+f"(d[113]), "+f"(d[114]), "+f"(d[115]), "+f"(d[116]), "+f"(d[117]), "+f"(d[118]), "+f"(d[119]),
      "+f"(d[120]), "+f"(d[121]), "+f"(d[122]), "+f"(d[123]), "+f"(d[124]), "+f"(d[125]), "+f"(d[126]), "+f"(d[127])
    : "l"(da), "l"(db), "r"(scale_d));
}
__device__ __forceinline__ void wgmma_g1(float (&d)[128], uint64_t da, uint64_t db, int scale_d) { wgmma_n256(d, da, db, scale_d); }
__device__ __forceinline__ void wgmma_g1(float (&d)[120], uint64_t da, uint64_t db, int scale_d) {
  asm volatile("{\n.reg .pred p;\nsetp.ne.b32 p, %122, 0;\n"
    "wgmma.mma_async.sync.aligned.m64n240k16.f32.bf16.bf16 "
    "{%0, %1, %2, %3, %4, %5, %6, %7, %8, %9, %10, %11, %12, %13, %14, %15, %16, %17, %18, %19, %20, %21, %22, %23, %24, %25, %26, %27, %28, %29, %30, %31, %32, %33, %34, %35, %36, %37, %38, %39, %40, %41, %42, %43, %44, %45, %46, %47, %48, %49, %50, %51, %52, %53, %54, %55, %56, %57, %58, %59, %60, %61, %62, %63, %64, %65, %66, %67, %68, %69, %70, %71, %72, %73, %74, %75, %76, %77, %78, %79, %80, %81, %82, %83, %84, %85, %86, %87, %88, %89, %90, %91, %92, %93, %94, %95, %96, %97, %98, %99, %100, %101, %102, %103, %104, %105, %106, %107, %108, %109, %110, %111, %112, %113, %114, %115, %116, %117, %118, %119}, "
    "%120, %121, p, 1, 1, 0, 0;\n}\n"
    : "+f"(d[0]), "+f"(d[1]), "+f"(d[2]), "+f"(d[3]), "+f"(d[4]), "+f"(d[5]), "+f"(d[6]), "+f"(d[7]), "+f"(d[8]), "+f"(d[9]), "+f"(d[10]), "+f"(d[11]), "+f"(d[12]), "+f"(d[13]), "+f"(d[14]), "+f"(d[15]), "+f"(d[16]), "+f"(d[17]), "+f"(d[18]), "+f"(d[19]), "+f"(d[20]), "+f"(d[21]), "+f"(d[22]), "+f"(d[23]), "+f"(d[24]), "+f"(d[25]), "+f"(d[26]), "+f"(d[27]), "+f"(d[28]), "+f"(d[29]), "+f"(d[30]), "+f"(d[31]), "+f"(d[32]), "+f"(d[33]), "+f"(d[34]), "+f"(d[35]), "+f"(d[36]), "+f"(d[37]), "+f"(d[38]), "+f"(d[39]), "+f"(d[40]), "+f"(d[41]), "+f"(d[42]), "+f"(d[43]), "+f"(d[44]), "+f"(d[45]), "+f"(d[46]), "+f"(d[47]), "+f"(d[48]), "+f"(d[49]), "+f"(d[50]), "+f"(d[51]), "+f"(d[52]), "+f"(d[53]), "+f"(d[54]), "+f"(d[55]), "+f"(d[56]), "+f"(d[57]), "+f"(d[58]), "+f"(d[59]), "+f"(d[60]), "+f"(d[61]), "+f"(d[62]), "+f"(d[63]), "+f"(d[64]), "+f"(d[65]), "+f"(d[66]), "+f"(d[67]), "+f"(d[68]), "+f"(d[69]), "+f"(d[70]), "+f"(d[71]), "+f"(d[72]), "+f"(d[73]), "+f"(d[74]), "+f"(d[75]), "+f"(d[76]), "+f"(d[77]), "+f"(d[78]), "+f"(d[79]), "+f"(d[80]), "+f"(d[81]), "+f"(d[82]), "+f"(d[83]), "+f"(d[84]), "+f"(d[85]), "+f"(d[86]), "+f"(d[87]), "+f"(d[88]), "+f"(d[89]), "+f"(d[90]), "+f"(d[91]), "+f"(d[92]), "+f"(d[93]), "+f"(d[94]), "+f"(d[95]), "+f"(d[96]), "+f"(d[97]), "+f"(d[98]), "+f"(d[99]), "+f"(d[100]), "+f"(d[101]), "+f"(d[102]), "+f"(d[103]), "+f"(d[104]), "+f"(d[105]), "+f"(d[106]), "+f"(d[107]), "+f"(d[108]), "+f"(d[109]), "+f"(d[110]), "+f"(d[111]), "+f"(d[112]), "+f"(d[113]), "+f"(d[114]), "+f"(d[115]), "+f"(d[116]), "+f"(d[117]), "+f"(d[118]), "+f"(d[119])
    : "l"(da), "l"(db), "r"(scale_d));
}
__device__ __forceinline__ void wgmma_n256_rs(float (&d)[128], uint32_t a0, uint32_t a1, uint32_t a2, uint32_t a3, uint64_t db, int scale_d) {
  asm volatile("{\n.reg .pred p;\nsetp.ne.b32 p, %133, 0;\n"
    "wgmma.mma_async.sync.aligned.m64n256k16.f32.bf16.bf16 "
    "{%0, %1, %2, %3, %4, %5, %6, %7, %8, %9, %10, %11, %12, %13, %14, %15, %16, %17, %18, %19, %20, %21, %22, %23, %24, %25, %26, %27, %28, %29, %30, %31, "
    "%32, %33, %34, %35, %36, %37, %38, %39, %40, %41, %42, %43, %44, %45, %46, %47, %48, %49, %50, %51, %52, %53, %54, %55, %56, %57, %58, %59, %60, %61, %62, %63, "
    "%64, %65, %66, %67, %68, %69, %70, %71, %72, %73, %74, %75, %76, %77, %78, %79, %80, %81, %82, %83, %84, %85, %86, %87, %88, %89, %90, %91, %92, %93, %94, %95, "
    "%96, %97, %98, %99, %100, %101, %102, %103, %104, %105, %106, %107, %108, %109, %110, %111, %112, %113, %114, %115, %116, %117, %118, %119, %120, %121, %122, %123, %124, %125, %126, %127}, "
    "{%128, %129, %130, %131}, %132, p, 1, 1, 0;\n}\n"
    : "+f"(d[0]), "+f"(d[1]), "+f"(d[2]), "+f"(d[3]), "+f"(d[4]), "+f"(d[5]), "+f"(d[6]), "+f"(d[7]),
      "+f"(d[8]), "+f"(d[9]), "+f"(d[10]), "+f"(d[11]), "+f"(d[12]), "+f"(d[13]), "+f"(d[14]), "+f"(d[15]),
      "+f"(d[16]), "+f"(d[17]), "+f"(d[18]), "+f"(d[19]), "+f"(d[20]), "+f"(d[21]), "+f"(d[22]), "+f"(d[23]),
      "+f"(d[24]), "+f"(d[25]), "+f"(d[26]), "+f"(d[27]), "+f"(d[28]), "+f"(d[29]), "+f"(d[30]), "+f"(d[31]),
      "+f"(d[32]), "+f"(d[33]), "+f"(d[34]), "+f"(d[35]), "+f"(d[36]), "+f"(d[37]), "+f"(d[38]), "+f"(d[39]),
      "+f"(d[40]), "+f"(d[41]), "+f"(d[42]), "+f"(d[43]), "+f"(d[44]), "+f"(d[45]), "+f"(d[46]), "+f"(d[47]),
      "+f"(d[48]), "+f"(d[49]), "+f"(d[50]), "+f"(d[51]), "+f"(d[52]), "+f"(d[53]), "+f"(d[54]), "+f"(d[55]),
      "+f"(d[56]), "+f"(d[57]), "+f"(d[58]), "+f"(d[59]), "+f"(d[60]), "+f"(d[61]), "+f"(d[62]), "+f"(d[63]),
      "+f"(d[64]), "+f"(d[65]), "+f"(d[66]), "+f"(d[67]), "+f"(d[68]), "+f"(d[69]), "+f"(d[70]), "+f"(d[71]),
      "+f"(d[72]), "+f"(d[73]), "+f"(d[74]), "+f"(d[75]), "+f"(d[76]), "+f"(d[77]), "+f"(d[78]), "+f"(d[79]),
      "+f"(d[80]), "+f"(d[81]), "+f"(d[82]), "+f"(d[83]), "+f"(d[84]), "+f"(d[85]), "+f"(d[86]), "+f"(d[87]),
      "+f"(d[88]), "+f"(d[89]), "+f"(d[90]), "+f"(d[91]), "+f"(d[92]), "+f"(d[93]), "+f"(d[94]), "+f"(d[95]),
      "+f"(d[96]), "+f"(d[97]), "+f"(d[98]), "+f"(d[99]), "+f"(d[100]), "+f"(d[101]), "+f"(d[102]), "+f"(d[103]),
      "+f"(d[104]), "+f"(d[105]), "+f"(d[106]), "+f"(d[107]), "+f"(d[108]), "+f"(d[109]), "+f"(d[110]), "+f"(d[111]),
      "+f"(d[112]), "+f"(d[113]), "+f"(d[114]), "+f"(d[115]), "+f"(d[116]), "+f"(d[117]), "+f"(d[118]), "+f"(d[119]),
      "+f"(d[120]), "+f"(d[121]), "+f"(d[122]), "+f"(d[123]), "+f"(d[124]), "+f"(d[125]), "+f"(d[126]), "+f"(d[127])
    : "r"(a0), "r"(a1), "r"(a2), "r"(a3), "l"(db), "r"(scale_d));
}
__device__ __forceinline__ void wgmma_n128(float (&d)[64], uint64_t da, uint64_t db, int scale_d = 1) {
  asm volatile("{\n.reg .pred p;\nsetp.ne.b32 p, %66, 0;\n"
    "wgmma.mma_async.sync.aligned.m64n128k16.f32.bf16.bf16 "
    "{%0, %1, %2, %3, %4, %5, %6, %7, %8, %9, %10, %11, %12, %13, %14, %15, %16, %17, %18, %19, %20, %21, %22, %23, %24, %25, %26, %27, %28, %29, %30, %31, %32, %33, %34, %35, %36, %37, %38, %39, %40, %41, %42, %43, %44, %45, %46, %47, %48, %49, %50, %51, %52, %53, %54, %55, %56, %57, %58, %59, %60, %61, %62, %63}, "
    "%64, %65, p, 1, 1, 0, 0;\n}\n"
    : "+f"(d[0]), "+f"(d[1]), "+f"(d[2]), "+f"(d[3]), "+f"(d[4]), "+f"(d[5]), "+f"(d[6]), "+f"(d[7]), "+f"(d[8]), "+f"(d[9]), "+f"(d[10]), "+f"(d[11]), "+f"(d[12]), "+f"(d[13]), "+f"(d[14]), "+f"(d[15]), "+f"(d[16]), "+f"(d[17]), "+f"(d[18]), "+f"(d[19]), "+f"(d[20]), "+f"(d[21]), "+f"(d[22]), "+f"(d[23]), "+f"(d[24]), "+f"(d[25]), "+f"(d[26]), "+f"(d[27]), "+f"(d[28]), "+f"(d[29]), "+f"(d[30]), "+f"(d[31]), "+f"(d[32]), "+f"(d[33]), "+f"(d[34]), "+f"(d[35]), "+f"(d[36]), "+f"(d[37]), "+f"(d[38]), "+f"(d[39]), "+f"(d[40]), "+f"(d[41]), "+f"(d[42]), "+f"(d[43]), "+f"(d[44]), "+f"(d[45]), "+f"(d[46]), "+f"(d[47]), "+f"(d[48]), "+f"(d[49]), "+f"(d[50]), "+f"(d[51]), "+f"(d[52]), "+f"(d[53]), "+f"(d[54]), "+f"(d[55]), "+f"(d[56]), "+f"(d[57]), "+f"(d[58]), "+f"(d[59]), "+f"(d[60]), "+f"(d[61]), "+f"(d[62]), "+f"(d[63])
    : "l"(da), "l"(db), "r"(scale_d));
}
__device__ __forceinline__ void fence_acc64(float (&d)[64]) {
#pragma unroll
  for (int i = 0; i < 64; i++) asm volatile("" : "+f"(d[i]) :: "memory");
}
template<int N> __device__ __forceinline__ void fence_acc(float (&d)[N]) {
#pragma unroll
  for (int i = 0; i < N; i++) asm volatile("" : "+f"(d[i]) :: "memory");
}

template<int N, int I = 0, class F> __device__ __forceinline__ void static_for(F&& f) {
  if constexpr (I < N) { f(std::integral_constant<int, I>()); static_for<N, I + 1>(f); }
}

__device__ __forceinline__ void ldsm_x4_t(uint32_t addr, uint32_t& a, uint32_t& b, uint32_t& c, uint32_t& d) {
  asm volatile("ldmatrix.sync.aligned.m8n8.x4.trans.shared.b16 {%0, %1, %2, %3}, [%4];" : "=r"(a), "=r"(b), "=r"(c), "=r"(d) : "r"(addr));
}
__device__ __forceinline__ void sts128(uint32_t addr, uint32_t a, uint32_t b, uint32_t c, uint32_t d) {
  asm volatile("st.shared.v4.b32 [%0], {%1, %2, %3, %4};" :: "r"(addr), "r"(a), "r"(b), "r"(c), "r"(d));
}
__device__ __forceinline__ void mma16816(float (&c)[4], uint32_t a0, uint32_t a1, uint32_t a2, uint32_t a3, uint32_t b0, uint32_t b1) {
  asm volatile("mma.sync.aligned.m16n8k16.row.col.f32.bf16.bf16.f32 {%0, %1, %2, %3}, {%4, %5, %6, %7}, {%8, %9}, {%0, %1, %2, %3};"
      : "+f"(c[0]), "+f"(c[1]), "+f"(c[2]), "+f"(c[3]) : "r"(a0), "r"(a1), "r"(a2), "r"(a3), "r"(b0), "r"(b1));
}
__device__ __forceinline__ void mma1688(float (&c)[4], uint32_t a0, uint32_t a1, uint32_t b0) {
  asm volatile("mma.sync.aligned.m16n8k8.row.col.f32.bf16.bf16.f32 {%0, %1, %2, %3}, {%4, %5}, {%6}, {%0, %1, %2, %3};"
      : "+f"(c[0]), "+f"(c[1]), "+f"(c[2]), "+f"(c[3]) : "r"(a0), "r"(a1), "r"(b0));
}
__device__ __forceinline__ void pin(uint32_t& v) { asm volatile("shfl.sync.bfly.b32 %0, %0, 0, 0x1f, 0xffffffff;" : "+r"(v)); }
template<class T> __device__ __forceinline__ void pin(T*& v) {
  uint32_t lo = (uint32_t)(uint64_t)v, hi = (uint32_t)((uint64_t)v >> 32);
  pin(lo); pin(hi);
  v = (T*)(((uint64_t)hi << 32) | lo);
}
__device__ __forceinline__ float sel4(int q, float a, float b, float c, float d) {
  float r;
  asm("{\n.reg .pred p, o;\n.reg .f32 x, y;\n.reg .b32 t;\nand.b32 t, %1, 1;\nsetp.ne.b32 p, t, 0;\nsetp.gt.s32 o, %1, 1;\n"
      "selp.f32 x, %3, %2, p;\nselp.f32 y, %5, %4, p;\nselp.f32 %0, y, x, o;\n}\n" : "=f"(r) : "r"(q), "f"(a), "f"(b), "f"(c), "f"(d));
  return r;
}
__device__ __forceinline__ uint32_t bfma2(uint32_t a, uint32_t b, uint32_t c) { uint32_t r; asm("fma.rn.bf16x2 %0, %1, %2, %3;" : "=r"(r) : "r"(a), "r"(b), "r"(c)); return r; }
__device__ __forceinline__ void tma_load_5d(uint32_t dst, const CUtensorMap* tm, uint32_t bar, int c0) {
  asm volatile("cp.async.bulk.tensor.5d.shared::cluster.global.mbarrier::complete_tx::bytes [%0], [%1, {%3, %4, %4, %4, %4}], [%2];"
    :: "r"(dst), "l"(tm), "r"(bar), "r"(c0), "r"(0) : "memory");
}
__device__ __forceinline__ void tma_store_5d(const CUtensorMap* tm, uint32_t src, int c0, int c3, int c4) {
  asm volatile("cp.async.bulk.tensor.5d.global.shared::cta.bulk_group [%0, {%2, %3, %3, %4, %5}], [%1];" :: "l"(tm), "r"(src), "r"(c0), "r"(0), "r"(c3), "r"(c4) : "memory");
}
__device__ __forceinline__ float rcp_fast(float x) { float r; asm("rcp.approx.ftz.f32 %0, %1;" : "=f"(r) : "f"(x)); return r; }
__device__ __forceinline__ float sigmoid_fast(float x) { float e; asm("ex2.approx.ftz.f32 %0, %1;" : "=f"(e) : "f"(x * -1.4426950408889634f)); return rcp_fast(1.f + e); }
__device__ __forceinline__ float sqrt_fast(float x) { float r; asm("sqrt.approx.ftz.f32 %0, %1;" : "=f"(r) : "f"(x)); return r; }
__device__ __forceinline__ float ln_sd(float var) { return bf16r(sqrt_fast(bf16r(bf16r(fmaxf(var, 0.f)) + 1e-5f))); }
__device__ __forceinline__ uint32_t norm2(uint32_t h, uint32_t neg_mean2, float inv_sd) {
  const uint32_t d = badd2(h, neg_mean2);
  return pack_bf16(bf_lo(d) * inv_sd, bf_hi(d) * inv_sd);
}
template<int N> __device__ __forceinline__ void delay_clk() {
  if constexpr (N > 0) { const uint32_t t0 = clock(); while ((uint32_t)clock() - t0 < N) {} }
}
__device__ __forceinline__ void put_xstat(uint32_t rs, uint32_t exb, int col, uint32_t mean_rstd, int m) {
  smem_at<uint16_t>(rs + ((col & 7) >> 1) * 144 + (col >> 3) * 4 + (col & 1) * 2) = (uint16_t)(mean_rstd ^ (m << 15));
  const uint32_t nm = (mean_rstd >> 16) ^ 0x8000u;
  smem_at<uint4>(exb + (col >> 3) * 256 + (col & 7) * 16) = make_uint4(nm | (nm << 16), nm, 0, 0);
  smem_at<uint4>(exb + (col >> 3) * 256 + 128 + (col & 7) * 16) = make_uint4(0, 0, 0, 0);
}
__device__ __forceinline__ void put_dsum(uint32_t exa, int e, float c) {
  const float hi = bf16r(c), mid = bf16r(c - hi), lo = bf16r((c - hi) - mid);
  smem_at<uint4>(exa + (e >> 3) * 256 + (e & 7) * 16) = make_uint4((__float_as_uint(hi) >> 16) | (__float_as_uint(mid) & 0xFFFF0000u), __float_as_uint(lo) >> 16, 0, 0);
  smem_at<uint4>(exa + (e >> 3) * 256 + 128 + (e & 7) * 16) = make_uint4(0, 0, 0, 0);
}
__host__ __device__ constexpr int min_c(int a, int b) { return a < b ? a : b; }
template<int V> using IC = std::integral_constant<int, V>;

#define CT(slot) do {} while (0)
#define PT(slot) do {} while (0)

template<int MAP>
__global__ void __cluster_dims__(2, 1, 1) __launch_bounds__(384, 1)
fnet_moe_kernel(const __grid_constant__ Params p) {
  constexpr int NX = MAP == 0 ? NX0 : 256;
  constexpr int G1_BYTES = A_BYTES + NX * 128;
  uint32_t sb;
  asm volatile("mov.u32 %0, %1;" : "=r"(sb) : "r"(smem_u32(smem_raw)));
  const int m = blockIdx.x & 1;
  int tau, eps;
  bool helper = false;
  if (MAP == 0) {
    uint32_t smid;
    asm volatile("mov.u32 %0, %%smid;" : "=r"(smid));
    const int c = smid >> 1, e7 = ((c - 32) * 37) >> 8;
    helper = c == 60 || c == 61;
    tau = c < 32 ? (c & 7) : (c < 60 ? c - 31 - 7 * e7 : 0);
    eps = c < 32 ? (c >> 3) : (c < 60 ? 4 + e7 : c - 58);
  } else {
    tau = (blockIdx.x >> 1) & 7; eps = blockIdx.x >> 4;
  }
  const int cid = tau * 16 + eps * 2 + m;
  const bool moe = tau > 0;
  auto BAR = [&](int i) { return sb + OFF_BAR + 8 * i; };
  const CUtensorMap* tmD = m ? &p.tmD1 : &p.tmD0;
  const uint64_t pol_ef = policy_evict_first();
#define LOAD_STREAM(d, tm, bar, c0, c1) tma_load_2d_hint(d, tm, bar, c0, c1, pol_ef)
  auto helper_load = [&](int k) {
    const uint32_t sa = sb + slot_of(k) * ST_BYTES, bar = BAR(B_FULL + slot_of(k));
    const CUtensorMap* tm = eps == 3 ? &p.tmD1 : &p.tmD0;
    tma_load_5d(sa, &p.tmXh, bar, (k & 15) * 64);
    tma_load_2d(sa + A_BYTES, tm, bar, (k & 15) * 64, m * 512 + (k >> 4) * 256);
    tma_load_2d(sa + A_BYTES + 16384, tm, bar, (k & 15) * 64, m * 512 + (k >> 4) * 256 + 128);
  };
  if (threadIdx.x < 32) {
    if (elect_one()) {
#pragma unroll
      for (int k = 0; k < 4; k++) mbar_init(BAR(B_FULL + k), 1);
      asm volatile("fence.mbarrier_init.release.cluster;" ::: "memory");
#pragma unroll
      for (int k = 0; k < 4; k++) mbar_expect_tx(BAR(B_FULL + k), helper ? ST_BYTES : G1_BYTES);
    }
    PT(50);
    if (!helper && elect_one()) {
      tma_load_2d(sb + A_BYTES, &p.tmX, BAR(B_FULL), 0, tau * 256);
      LOAD_STREAM(sb, tmD, BAR(B_FULL), 0, eps * 128);
    }
    PT(52);
    if (elect_one()) {
      if (!helper) {
#pragma unroll
        for (int k = 1; k < 4; k++) {
          tma_load_2d(sb + k * ST_BYTES + A_BYTES, &p.tmX, BAR(B_FULL + k), k * 64, tau * 256);
          LOAD_STREAM(sb + k * ST_BYTES, tmD, BAR(B_FULL + k), k * 64, eps * 128);
        }
      } else {
#pragma unroll 1
        for (int k = 0; k < 4; k++) helper_load(k);
      }
    }
    PT(0);
  }
  __syncwarp();
  const int warp = __shfl_sync(0xffffffffu, threadIdx.x >> 5, 0);
  if (warp == 8) {
    if (elect_one()) {
#pragma unroll
      for (int b = B_EMPTY; b < B_COUNT; b++)
        mbar_init(BAR(b), b < B_EPI ? 2 : (b == B_EPI || b == B_EPI0B) ? 4 : (b < B_STD || b == B_OUT) ? 8 : (b == B_STAT || b == B_XS) ? 3 : 1);
      asm volatile("fence.mbarrier_init.release.cluster;" ::: "memory");
      mbar_expect_tx(BAR(B_XCH), 32768);
      SM_(uint32_t, OFF_SEEN) = 0;
    }
  }
  __syncthreads();

  if (warp >= 8) {
    reg_dec<REG_P>();
    asm volatile("barrier.cluster.arrive.relaxed.aligned;" ::: "memory");
    const int abrow = m * 1024 + eps * 128;
    const int f0 = (cid - 16) * 32;
    const CUtensorMap* tmWM = m ? &p.tmWM1 : &p.tmWM0;
    auto side_first = [&](int k) {
      if (NX < 256 && k == MINI_LOAD_K) {
        static_assert(NX == 256 || (mr_k(NREG_H) == MINI_LOAD_K && (NREG_H & 1) == 1), "second half of the staging buffer must be free");
        mbar_wait(BAR(B_STD + 3), 0);
        uint32_t n = 0;
        while (!((*(volatile uint32_t*)&SM_(uint32_t, OFF_SEEN) >> (4 * tau + 1)) & 1) && ++n < SPIN_LIMIT * 16) {}
        if (elect_one()) {
          mbar_expect_tx(BAR(B_A20), 12288);
          tma_load_2d(sb + OFF_MINI, &p.tmAbM, BAR(B_A20), tau * 256 + 240, abrow);
          LOAD_STREAM(sb + OFF_MINI + 4096, tmWM, BAR(B_A20), tau * 256 + 240, tau * 256 + m * 128);
          LOAD_STREAM(sb + OFF_MINI + 8192, tmWM, BAR(B_A20), tau * 256 + 240, tau * 256 + (1 - m) * 128);
        }
      }
    };
    auto side = [&](int k) {
      if (NX < 256 && k == MINI_PF_K && elect_one()) tma_prefetch_2d(tmWM, tau * 256 + 240, tau * 256 + (eps & 1) * 128);
      if (!moe) return;
      const int i = k - MR_K0, r6 = i / MR_P, u = i - MR_P * r6, h = 2 * r6 + (u >> 1);
      if (i >= 0 && u < 4 && h < NREG_H) {
        if (h < 2) mbar_wait(BAR(B_STD + 2 + h), 0);
        if (elect_one()) {
          if (!(u & 1)) mbar_expect_tx(BAR(B_MR + (h & 1)), 16384);
          LOAD_STREAM(sb + OFF_XCH + u * 8192, (u & 1) ? &p.tmU : &p.tmG, BAR(B_MR + (h & 1)), f0, h * 128);
        }
      }
      if (k >= 46 && elect_one()) {
        static_assert(mr_k(NREG_H + 1) <= 47 && MINI_K + 4 <= 46, "staging buffer must be free");
        LOAD_STREAM(sb + round_off(NREG_H + k - 46), &p.tmG, BAR(B_GU), f0, (NREG_H + k - 46) * 128);
        LOAD_STREAM(sb + round_off(NREG_H + k - 46) + 8192, &p.tmU, BAR(B_GU), f0, (NREG_H + k - 46) * 128);
      }
      if (k >= PF_K1 && !(k & 1) && elect_one()) {
        const int j = PF_N0 + ((k - PF_K1) >> 1);
        if (j < 8) tma_prefetch_2d(m ? &p.tmU : &p.tmG, f0, j * 128);
        else if (j < 12) asm volatile("cp.async.bulk.prefetch.L2.global [%0], %1;" :: "l"(p.wdown + (size_t)f0 * 1024 + (j - 8) * 8192), "r"(16384) : "memory");
      }
    };
    if (MAP == 0 && helper) {
      if (warp == 8) {
#pragma unroll 1
        for (int k = 4; k < 32; k++) {
          mbar_wait(BAR(B_EMPTY + slot_of(k)), (use_of(k) & 1) ^ 1);
          if (elect_one()) { mbar_expect_tx(BAR(B_FULL + slot_of(k)), ST_BYTES); helper_load(k); }
        }
      } else {
        const int i0 = threadIdx.x - 288, lane = threadIdx.x & 31, col0 = (eps - 2) * 8 + m * 4;
        __nanosleep(HELPER_NS);
        const uint32_t tag = ld_relaxed32(&p.s->epoch) + 1;
        if (i0 < 8) pkt_st128(&p.s->hflag[col0 * 2 + i0], 0, 0, 0, 0);
        SM_(uint32_t, OFF_TAG) = tag;
#pragma unroll 1
        for (int j0 = i0; j0 < 768; j0 += 384) {
          uint2 v[4]; uint32_t n = 0;
          while (true) {
#pragma unroll
            for (int z = 0; z < 4; z++) {
              const int j = j0 + 96 * z;
              v[z] = pkt_ld64(p.s->xstat + (j < 128 ? 256 * (j >> 4) + 240 + 2 * (j & 6) + ((j >> 2) & 2) + (j & 1)
                                          : j < 640 ? 2048 + col0 * 128 + j - 128 : (j - 640) * 16));
            }
            if (__all_sync(0xffffffffu, v[0].y == tag && v[1].y == tag && v[2].y == tag && v[3].y == tag) || ++n > SPIN_LIMIT) break;
            __nanosleep(300);
          }
#pragma unroll
          for (int z = 0; z < 4; z++) {
            const int j = j0 + 96 * z;
            if (j < 128) put_xstat(sb + OFF_RS, sb + OFF_XCH + 16384, j, v[z].x, eps - 2);
            else if (j < 640) put_dsum(sb + OFF_XCH, j - 128, __uint_as_float(v[z].x));
          }
        }
        fence_async_smem();
        __syncwarp();
        if (lane == 0) mbar_arrive(BAR(B_STAT));
      }
    } else if (warp == 8) {
      const CUtensorMap* tmW = m ? &p.tmW1 : &p.tmW0;
      const int tA = tau * 256 + m * 128, tB = tau * 256 + (1 - m) * 128;
      auto wait_slot = [&](int k) {
        mbar_wait(BAR(B_EMPTY + slot_of(k)), (use_of(k) & 1) ^ 1);
        PT(64 + k);
      };
#pragma unroll 1
      for (int k = 4; k < 24; k++) {
        const int s = slot_of(k);
        const uint32_t sa = sb + s * ST_BYTES, sbb = sa + A_BYTES;
        const int kb = kblock(tau, k - 16);
        wait_slot(k);
        if (elect_one()) {
          mbar_expect_tx(BAR(B_FULL + s), k < 16 ? G1_BYTES : (k >> 1) == 9 ? B_BYTES : k == 20 ? ST_BYTES - 8192 : ST_BYTES);
          if (k < 16) {
            LOAD_STREAM(sa, tmD, BAR(B_FULL + s), k * 64, eps * 128);
            tma_load_2d(sbb, &p.tmX, BAR(B_FULL + s), k * 64, tau * 256);
          } else {
            LOAD_STREAM(sbb, tmW, BAR(B_FULL + s), kb * 64, tA);
            LOAD_STREAM(sbb + 16384, tmW, BAR(B_FULL + s), kb * 64, tB);
            if (k < 18) {
              tma_load_2d(sa, &p.tmXr, BAR(B_FULL + s), eps * 128, tA + s * 64);
              tma_load_2d(sa + 8192, &p.tmXr, BAR(B_FULL + s), eps * 128 + 64, tA + s * 64);
            }
          }
          if (k == PUB_K1) mbar_arrive(BAR(B_LATE));
          if (k >= WPF_K0 && k < WPF_K0 + WPF_N && (eps >> 1) == ((k - WPF_K0) & 3))
            tma_prefetch_2d(tmW, kblock(tau, k - WPF_K0) * 64, tau * 256 + (eps & 1) * 128);
          if (moe && k >= PF_K0 && k < PF_K0 + 2 * PF_N0 && !(k & 1)) tma_prefetch_2d(m ? &p.tmU : &p.tmG, f0, (k - PF_K0) * 64);
        }
      }
      uint32_t seen = 0;
#pragma unroll 1
      for (int k = 24; k < 48; k++) {
        const int s = slot_of(k);
        const uint32_t sa = sb + s * ST_BYTES, sbb = sa + A_BYTES;
        const int kb = kblock(tau, k - 16);
        const uint32_t need = (1u << kb) | ((kb & 3) == 3 ? 2u << (4 * tau) : 0u);
        wait_slot(k);
        side_first(k);
        if (elect_one()) {
          mbar_expect_tx(BAR(B_FULL + s), ST_BYTES);
          LOAD_STREAM(sbb, tmW, BAR(B_FULL + s), kb * 64, tA);
          LOAD_STREAM(sbb + 16384, tmW, BAR(B_FULL + s), kb * 64, tB);
        }
        uint32_t n = 0;
        while ((seen & need) != need && ++n < SPIN_LIMIT * 16) seen = *(volatile uint32_t*)&SM_(uint32_t, OFF_SEEN);
        if (elect_one()) tma_load_2d(sa, &p.tmAbL, BAR(B_FULL + s), kb * 64, abrow);
        side(k);
      }
      if (moe) {
        mbar_wait(BAR(B_EMPTY + 0), 1);
        if (elect_one()) { mbar_expect_tx(BAR(B_GU), (8 - NREG_H) * 16384); mbar_expect_tx(BAR(B_DN), 65536); }
#pragma unroll 1
        for (int i = 0; i < 10 - NREG_H; i++) {
          if (i == 3) mbar_wait(BAR(B_EMPTY + 1), 1);
          if (i == 4) {
            mbar_wait(BAR(B_EMPTY + 2), 1);
            mbar_wait(BAR(B_XCH), 0);
            PT(53);
          }
          const uint32_t dst = sb + late_off(i);
          if (elect_one()) {
            if (i < 6 - NREG_H) {
              LOAD_STREAM(dst, &p.tmG, BAR(B_GU), f0, (NREG_H + 2 + i) * 128);
              LOAD_STREAM(dst + 8192, &p.tmU, BAR(B_GU), f0, (NREG_H + 2 + i) * 128);
            } else {
#pragma unroll
              for (int b = 0; b < 4; b++) LOAD_STREAM(dst + b * 4096, &p.tmDn, BAR(B_DN), (4 * (i - 6 + NREG_H) + b) * 64, f0);
            }
          }
          const long long t0 = clock64();
          while (i < 9 - NREG_H && clock64() - t0 < MOE_PACE_CLK) {}
        }
      }
      const int lane = threadIdx.x & 31;
      mbar_wait(BAR(B_OUT), 0);
      const uint32_t km = SM_(uint32_t, OFF_WKEY + (lane & 7) * 8);
      const uint32_t bk = __reduce_max_sync(0xffffffffu, km);
      const int ww = __ffs(__ballot_sync(0xffffffffu, km == bk)) - 1;
#pragma unroll 1
      for (int i = 1; i <= 8; i++) {
        const int W = (ww + i) & 7;
        if (i == 8) {
          mbar_wait(BAR(B_XS), 0);
          if (SM_(uint32_t, OFF_KV) == bk) {
#pragma unroll 2
            for (int j = lane; j < 256; j += 32) {
              const int rho = j >> 4, row = (tau * 2 + m) * 128 + 32 * (W >> 1) + 8 * ((rho & 7) >> 1) + 4 * (W & 1) + 2 * (rho >> 3) + (rho & 1);
              const uint4 v = lds128_v(sb + OFF_OUT + (j & 8) * 2048 + (16 * W + rho) * 128 + (((j ^ rho) & 7) << 4));
              if (row != 0xFFFF - (int)(bk & 0xFFFFu))
                asm volatile("st.global.v4.b32 [%0], {%1, %2, %3, %4};" :: "l"(p.out + (size_t)row * 1024 + eps * 128 + (j & 15) * 8), "r"(v.x), "r"(v.y), "r"(v.z), "r"(v.w));
            }
            break;
          }
        }
        if (lane == 0) {
          tma_store_5d(&p.tmOut, sb + OFF_OUT + W * 2048, eps * 128, 2 * (W & 1), tau * 8 + m * 4 + (W >> 1));
          tma_store_5d(&p.tmOut, sb + OFF_OUT + 16384 + W * 2048, eps * 128 + 64, 2 * (W & 1), tau * 8 + m * 4 + (W >> 1));
        }
        const long long t0 = clock64();
        while (i < 7 && clock64() - t0 < OUT_PACE_CLK) {}
      }
      if (lane == 0) { bulk_commit(); bulk_wait_all(); }
      PT(22);
    } else {
      const int a = warp - 9;
      const int lane = threadIdx.x & 31;
      auto stage = [&](const bf16* src, int g) {
        if (elect_one()) {
          mbar_expect_tx(BAR(B_AUX + g), 16384);
          bulk_load(sb + OFF_XCH + g * 16384, src + g * 8192, 16384, BAR(B_AUX + g));
        }
      };
      mbar_wait(BAR(B_FULL + AUX_AFTER), 0);
      if (a == 0) PT(1);
      if (a < 2) stage(p.x + (size_t)cid * 16 * 1024, a);
      const uint32_t tag = ld_relaxed32(&p.s->epoch) + 1;
      if (a == 2 && lane < 16) asm volatile("prefetch.global.L2 [%0];" :: "l"(p.wr + lane * 64));
#pragma unroll 1
      for (int it = 0; it < 4; it++) {
        const int g = it & 1;
        mbar_wait(BAR(B_AUX + g), it >> 1);
        if (a == 0) PT(2 + it);
        const uint32_t ad = sb + OFF_XCH + g * 16384 + (lane >> 2) * 2048;
        float s0 = 0.f, s1 = 0.f, q0 = 0.f, q1 = 0.f;
        auto row = [&](auto sq) {
#pragma unroll
          for (int i = 0; i < 11; i++) {
            if (i == 10 && a == 2) break;
            const uint4 v = lds128_v(ad + (((a * 44 + 4 * i + lane) & 127) << 4));
            const uint32_t ww[4] = {v.x, v.y, v.z, v.w};
#pragma unroll
            for (int z = 0; z < 4; z++) {
              const float d0 = bf_lo(ww[z]), d1 = bf_hi(ww[z]);
              s0 += d0; s1 += d1;
              if (decltype(sq)::value) { q0 = fmaf(d0, d0, q0); q1 = fmaf(d1, d1, q1); }
            }
          }
        };
        if (it < 2) row(IC<1>()); else row(IC<0>());
        s0 += s1; q0 += q1;
#pragma unroll
        for (int o = 1; o < 4; o <<= 1) { s0 += __shfl_xor_sync(0xffffffffu, s0, o); q0 += __shfl_xor_sync(0xffffffffu, q0, o); }
        if ((lane & 3) == 0) SM_(float2, OFF_PUB + a * 256 + it * 64 + (lane >> 2) * 8) = make_float2(s0, q0);
        if (it != 2) bar_sync(NB_AUX, 96);
        if (it < 2 && a == 2) stage(cid < 64 ? p.Dre + (size_t)cid * 16 * 1024 : p.Dim + (size_t)(cid - 64) * 16 * 1024, g);
      }
      if (a == 1) {
        const float2 v0 = SM_(float2, OFF_PUB + lane * 8), v1 = SM_(float2, OFF_PUB + 256 + lane * 8), v2 = SM_(float2, OFF_PUB + 512 + lane * 8);
        const float s = v0.x + v1.x + v2.x, mean = s * (1.f / 1024.f);
        const float rs = rcp_fast(ln_sd((v0.y + v1.y + v2.y) * (1.f / 1024.f) - mean * mean));
        pkt_st64((lane < 16 ? p.s->xstat : p.s->dsum) + cid * 16 + (lane & 15), lane < 16 ? pack_bf16(rs, mean) : __float_as_uint(s), tag);
        PT(6);
      }
      if (a == 2) {
        float s = 0.f;
#pragma unroll
        for (int q = 0; q < 4; q++) {
          const uint4 v = ldg_nc128(p.wr + (q * 32 + lane) * 8);
          s += ((bf_lo(v.x) + bf_hi(v.x)) + (bf_lo(v.y) + bf_hi(v.y))) + ((bf_lo(v.z) + bf_hi(v.z)) + (bf_lo(v.w) + bf_hi(v.w)));
          const int ch = q * 32 + lane - eps * 16;
          if (ch >= 0 && ch < 16) {
            SM_(uint32_t, OFF_WR + ch * 4) = v.x; SM_(uint32_t, OFF_WR + 80 + ch * 4) = v.y;
            SM_(uint32_t, OFF_WR + 160 + ch * 4) = v.z; SM_(uint32_t, OFF_WR + 240 + ch * 4) = v.w;
          }
        }
        s = warp_sum(s);
        if (lane == 0) { SM_(float, OFF_WSUM) = s; SM_(uint32_t, OFF_TAG) = tag; }
      }
      if (a < 2) __nanosleep(GATHER_NS);
      {
        const int i0 = a * 32 + lane;
        uint2 v[3], c0, c1; uint32_t n = 0;
        const uint2* dp = &p.s->dsum[abrow];
        while (true) {
#pragma unroll
          for (int q = 0; q < 3; q++) v[q] = pkt_ld64(&p.s->xstat[tau * 256 + min(i0 + 96 * q, 255)]);
          c0 = pkt_ld64(dp + i0); c1 = pkt_ld64(dp + min(i0 + 96, 127));
          if (__all_sync(0xffffffffu, v[0].y == tag && v[1].y == tag && v[2].y == tag && c0.y == tag && c1.y == tag) || ++n > SPIN_LIMIT) break;
          __nanosleep(200);
        }
#pragma unroll
        for (int q = 0; q < 3; q++) put_xstat(sb + OFF_RS, sb + OFF_EXB, min(i0 + 96 * q, 255), v[q].x, m);
        put_dsum(sb + OFF_EXA, i0, __uint_as_float(c0.x));
        put_dsum(sb + OFF_EXA, min(i0 + 96, 127), __uint_as_float(c1.x));
        fence_async_smem();
      }
      __syncwarp();
      if (lane == 0) mbar_arrive(BAR(B_STAT));
      if (a == 0) PT(7);
      if (a == 0) {
        const int sg = (lane >> 2) == tau ? sigma_of(tau, 0) : lane >> 2;
        const uint32_t* flg = reinterpret_cast<const uint32_t*>(&p.s->abflag[((eps * 2 + m) * 8 + sg) * 2]) + ((lane >> 2) == tau ? 4 : lane & 3);
        if (NX < 256 && lane == 4 * tau + 1) flg = reinterpret_cast<const uint32_t*>(&p.s->hflag[(m * 8 + eps) * 2]);
        uint32_t seen = 0;
        mbar_wait(BAR(B_STDA), 0);
        PT(49);
#pragma unroll 1
        for (int i = 0; i < 5; i++) {
          const int s = i ? i - 1 : 0, sig = sigma_of(tau, s);
          if (i == 1) mbar_wait(BAR(B_STD + 0), 0);
          uint32_t n = 0;
          while (!((seen >> (4 * (i ? sig : tau))) & 1) && ++n < SPIN_LIMIT) seen = __ballot_sync(0xffffffffu, ld_relaxed32(flg) == tag);
          if (i == 0 || i == 4) mbar_wait(BAR(i ? B_STD + 1 : B_EPI0B), 0);
          if (i != 1) mbar_wait(BAR(B_FULL + s), 0);
          PT(i ? 16 + s : 48);
          if (elect_one()) {
            if (i == 1) mbar_expect_tx(BAR(B_A20), 8192);
            tma_load_2d(sb + (i < 3 ? OFF_XCH + i * 8192 : s * ST_BYTES), i < 2 ? &p.tmAbS : &p.tmAbL, BAR(i == 1 ? B_A20 : B_FULL + s), sig * 256,
                        abrow + (i == 1 ? 64 : 0));
          }
        }
        uint32_t n = 0;
        while (true) {
          asm volatile("fence.proxy.async.global;" ::: "memory");
          *(volatile uint32_t*)&SM_(uint32_t, OFF_SEEN) = seen;
          if (seen == 0xFFFFFFFFu || ++n > SPIN_LIMIT) break;
          seen = __ballot_sync(0xffffffffu, ld_relaxed32(flg) == tag);
          __nanosleep(100);
        }
      } else {
        uint32_t* flag = reinterpret_cast<uint32_t*>(&p.s->abflag[((eps * 2 + m) * 8 + tau) * 2]);
        mbar_wait(BAR(a == 1 ? B_EPI : B_EPI0B), 0);
        if (a == 1) PT(8);
        if (lane == 0) {
          tma_store_2d(&p.tmAbS, sb + chunk_off(0, a - 1), tau * 256, abrow + (a - 1) * 64);
          bulk_commit();
          bulk_wait_all();
        }
        if (a == 2) mbar_wait(BAR(B_STDA), 0);
        if (lane == 0) {
          st_relaxed32(flag + (a == 1 ? 4 : 0), tag);
          mbar_arrive(BAR(a == 1 ? B_STDA : B_STD));
        }
        if (a == 2) PT(12);
        if (a == 1) {
          mbar_wait(BAR(B_EPI + 1), 0);
          mbar_wait(BAR(B_LATE), 0);
          PT(9);
          if (lane == 0) {
            tma_store_2d(&p.tmAbS, sb + chunk_off(1, 0), tau * 256 + 64, abrow);
            tma_store_2d(&p.tmAbS, sb + chunk_off(1, 1), tau * 256 + 64, abrow + 64);
            bulk_commit();
            bulk_wait_all();
            st_relaxed32(flag + 1, tag);
            mbar_arrive(BAR(B_STD + 1));
          }
          PT(13);
        }
        auto copy_out = [&](int c) {
          mbar_wait(BAR(B_EPI + c), 0);
          PT(8 + c);
          bf16* dst = p.s->abT + (size_t)(abrow + (lane >> 3)) * 2048 + tau * 256 + c * 64 + (lane & 7) * 8;
          const uint32_t src = sb + chunk_off(c, 0) + (lane >> 3) * 128 + (((lane & 7) ^ (lane >> 3)) << 4);
          const uint32_t on = c * 64 + (lane & 7) * 8 < NX;
#pragma unroll 4
          for (int i = 0; i < 32; i++) {
            const uint4 v = lds128_v((src ^ ((i & 1) << 6)) + i * 512);
            asm volatile("{\n.reg .pred p;\nsetp.ne.b32 p, %5, 0;\n@p st.global.v4.b32 [%0], {%1, %2, %3, %4};\n}\n"
                         :: "l"(dst + i * 4 * 2048), "r"(v.x), "r"(v.y), "r"(v.z), "r"(v.w), "r"(on));
          }
          __syncwarp();
          if (lane == 0) mbar_arrive(BAR(B_STD + c));
        };
        if (a == 2) {
#pragma unroll 1
          for (int c = 2; c < 4; c++) copy_out(c);
          asm volatile("fence.acq_rel.gpu;" ::: "memory");
          __syncwarp();
          if (lane < 2) st_relaxed32(flag + 2 + lane, tag);
          PT(15);
        }
      }
      {
        mbar_wait(BAR(B_LATE), 1);
        const int grp = tau * 2 + m;
#pragma unroll 1
        for (int i = a; i < 14; i += 3) {
          uint4* dst = i < 8 ? &p.s->ypart[cid * 256 + i * 32 + lane] : i < 12 ? &p.s->hstat[(grp * 8 + eps) * 128 + (i - 8) * 32 + lane]
                     : i == 12 ? &p.s->cand[grp * 256 + eps * 32 + lane] : &p.s->key[(((lane >> 1) & 7) * 16 + grp) * 2 + (lane & 1)];
          if (i < 13 || eps == 0) pkt_st128(dst, 0, 0, 0, 0);
          __nanosleep(200);
        }
        __syncwarp();
        if (lane == 0) mbar_arrive(BAR(B_STAT));
      }
      {
        const uint4* kp = &p.s->key[(tau * 16 + (lane & 15)) * 2];
        const int i0 = a * 32 + lane;
        mbar_wait(BAR(B_KEY), 0);
        if (a == 0) PT(43);
        uint4 kq = pkt_ld128(kp), cv[3] = {};
        uint32_t n = 0, kv;
        int gspec = -1;
        while (true) {
          const bool ok = kq.y == tag && kq.w == tag;
          kv = __reduce_max_sync(0xffffffffu, ok ? kq.x : 0u);
          const int gs = (0xFFFF - (int)(kv & 0xFFFFu)) >> 7;
          const bool cok = gs == gspec && cv[0].y == tag && cv[0].w == tag && cv[1].y == tag && cv[1].w == tag && cv[2].y == tag && cv[2].w == tag;
          if (__all_sync(0xffffffffu, ok && cok) || ++n > SPIN_LIMIT) break;
          if (!ok) kq = pkt_ld128(kp);
          const bool spec = __popc(__ballot_sync(0xffffffffu, ok)) >= 2 * SPEC_MIN;
          if (!cok && spec) {
#pragma unroll
            for (int i = 0; i < 3; i++) cv[i] = pkt_ld128(&p.s->cand[gs * 256 + min(i0 + 96 * i, 255)]);
          }
          if (spec) gspec = gs;
        }
        if (a == 0) PT(45);
        const uint32_t ms = __shfl_sync(0xffffffffu, kq.z, gspec);
        const uint32_t nm = ((ms & 0xFFFFu) ^ 0x8000u) * 0x10001u;
        const float is = rcp_fast(bf_hi(ms));
#pragma unroll
        for (int i = 0; i < 3; i++) {
          const int j = min(i0 + 96 * i, 255);
          SM_(uint2, OFF_XSEL + j * 8) = make_uint2(norm2(cv[i].x, nm, is), norm2(cv[i].z, nm, is));
        }
#pragma unroll
        for (int i = 0; i < 3; i++) SM_(uint2, OFF_HSEL + min(i0 + 96 * i, 255) * 8) = make_uint2(cv[i].x, cv[i].z);
        SM_(uint32_t, OFF_KV) = kv;
        __syncwarp();
        if (lane == 0) mbar_arrive(BAR(B_XS));
      }
    }
    asm volatile("barrier.cluster.wait.aligned;" ::: "memory");
  } else {
    reg_inc<REG_C>();
    const int tid = __shfl_sync(0xffffffffu, threadIdx.x, threadIdx.x & 31), lane = tid & 31;
    const int w = warp >> 2, wi = warp & 3, t = tid & 127;
    const int g = lane >> 2, q = lane & 3;
    const int turn_me = NB_TURN0 + w, turn_other = NB_TURN1 - w;
    auto release = [&](int s) { if (t == 0) mbar_arrive(BAR(B_EMPTY + s)); };
    if (MAP == 0 && helper) {
      asm volatile("barrier.cluster.arrive.relaxed.aligned;" ::: "memory");
      float s0[64], s1[64];
#pragma unroll
      for (int i = 0; i < 64; i++) { s0[i] = 0.f; s1[i] = 0.f; }
      if (w == 1) bar_arrive(NB_TURN0, 256);
      uint32_t o[32][2] = {};
      const int col = (eps - 2) * 8 + m * 4 + w;
      auto put = [&](auto tc, uint32_t buf) {
        constexpr int tl = decltype(tc)::value;
#pragma unroll
        for (int i = 0; i < 4; i++)
          smem_at<uint2>(buf + ((i >> 1) * 64 + wi * 16 + (i & 1) * 8 + g) * 32 + ((q * 8) ^ ((g & 4) << 2))) = make_uint2(o[8 * i + tl][0], o[8 * i + tl][1]);
      };
      auto publish = [&](int c) { if (t == 0) { bulk_wait_all(); st_relaxed32(&p.s->hflag[c * 2], SM_(uint32_t, OFF_TAG)); } };
#pragma unroll 1
      for (int pass = 0; pass < 2; pass++) {
#pragma unroll 1
        for (int k = 16 * pass; k < 16 * pass + 16; k++) {
          const int s = slot_of(k);
          mbar_wait(BAR(B_FULL + s), use_of(k) & 1);
          bar_sync(turn_me, 256);
          const uint64_t da = make_desc(sb + s * ST_BYTES + A_BYTES + w * 16384), db = make_desc(sb + s * ST_BYTES);
          wgmma_fence();
#pragma unroll
          for (int kk = 0; kk < 4; kk++) {
            wgmma_n128(s0, da + kk * 2, db + kk * 2, kk > 0 || (k & 15));
            wgmma_n128(s1, da + 512 + kk * 2, db + kk * 2, kk > 0 || (k & 15));
          }
          wgmma_commit();
          if (k < 31 || w == 0) bar_arrive(turn_other, 256);
          if (pass && !(k & 1)) {
            const uint32_t buf = sb + OFF_XCH + 20480 + w * 4096;
            static_for<8>([&](auto ic) { if (k == 16 + 2 * decltype(ic)::value) put(ic, buf); });
            fence_async_smem();
            bar_sync(NB_WG0 + w, 128);
            if (t == 0) { tma_store_2d(&p.tmAbM, buf, (k - 16) * 128 + 240, col * 128); bulk_commit(); }
          }
          wgmma_wait0();
          release(s);
          if ((k & 1) && t == 0) asm volatile("cp.async.bulk.wait_group.read 0;" ::: "memory");
        }
        if (pass) publish(col);
        mbar_wait(BAR(B_STAT), 0);
        wgmma_fence();
        wgmma_n128(s0, make_desc_noswz(sb + OFF_XCH + pass * 8192 + w * 4096), make_desc_noswz(sb + OFF_XCH + 16384));
        wgmma_n128(s1, make_desc_noswz(sb + OFF_XCH + pass * 8192 + w * 4096 + 2048), make_desc_noswz(sb + OFF_XCH + 16384));
        wgmma_commit();
        uint4 rs[4];
#pragma unroll
        for (int i = 0; i < 4; i++) rs[i] = lds128_v(sb + OFF_RS + q * 144 + i * 16);
        wgmma_wait0();
        fence_acc(s0); fence_acc(s1);
#pragma unroll
        for (int i = 0; i < 32; i++) {
          const int tl = i & 7, hr = (i >> 3) & 1;
          const float* ac = (i >> 4) ? &s1[8 * tl + 2 * hr] : &s0[8 * tl + 2 * hr];
          o[i][0] = bmul2(pack_bf16(ac[0], ac[1]), (tl & 1) ? rs[tl >> 1].z : rs[tl >> 1].x);
          o[i][1] = bmul2(pack_bf16(ac[4], ac[5]), (tl & 1) ? rs[tl >> 1].w : rs[tl >> 1].y);
        }
      }
      static_for<8>([&](auto ic) { put(ic, sb + (w * 8 + decltype(ic)::value) * 4096); });
      fence_async_smem();
      bar_sync(NB_WG0 + w, 128);
      if (t == 0) {
#pragma unroll 1
        for (int i = 0; i < 8; i++) tma_store_2d(&p.tmAbM, sb + (w * 8 + i) * 4096, i * 256 + 240, (col + 2) * 128);
        bulk_commit();
      }
      publish(col + 2);
      asm volatile("barrier.cluster.wait.aligned;" ::: "memory");
      return;
    }
    float acc[128], a1[NX / 2];
#pragma unroll
    for (int i = 0; i < NX / 2; i++) a1[i] = 0.f;
    if (w == 1) bar_arrive(NB_TURN0, 256);
    auto kstep = [&](auto& d, int k, bool first, bool a_in_xch = false, bool mini = false) {
      const int s = slot_of(k);
      mbar_wait(BAR(B_FULL + s), use_of(k) & 1);
      CT(64 + k);
      bar_sync(turn_me, 256);
      const uint64_t da = make_desc(sb + (a_in_xch ? OFF_XCH + s * 16384 : s * ST_BYTES) + w * 8192), db = make_desc(sb + s * ST_BYTES + A_BYTES);
      wgmma_fence();
      wgmma_g1(d, da, db, !first);
#pragma unroll
      for (int kk = 1; kk < 4; kk++) wgmma_g1(d, da + kk * 2, db + kk * 2, 1);
      wgmma_commit();
      if (mini) {
        CT(29);
        mbar_wait(BAR(B_A20), 1);
        CT(30);
        wgmma_fence();
        wgmma_g1(d, make_desc_32b(sb + OFF_MINI + w * 2048), make_desc_32b(sb + OFF_MINI + 4096), 1);
        wgmma_commit();
      }
      bar_arrive(turn_other, 256);
    };
    auto kdone = [&](int k) { wgmma_wait0(); release(slot_of(k)); };
    auto wgmma_wait1 = [&]() { asm volatile("wgmma.wait_group.sync.aligned 1;" ::: "memory"); };

#pragma unroll 1
    for (int k = 0; k < 14; k++) {
      kstep(a1, k, k == 0);
      if (k == 0) CT(0);
      if (k == 8 && warp == 2 && lane < 2) pkt_st128(&p.s->abflag[((eps * 2 + m) * 8 + tau) * 2 + lane], 0, 0, 0, 0);
      kdone(k);
    }
    uint32_t R[64];
    uint32_t tag;
    {
      const uint32_t rsa = sb + OFF_RS + q * 144;
      const uint64_t da2 = make_desc(sb + 2 * ST_BYTES + w * 8192), db2 = make_desc(sb + 2 * ST_BYTES + A_BYTES);
      const uint64_t da3 = make_desc(sb + 3 * ST_BYTES + w * 8192), db3 = make_desc(sb + 3 * ST_BYTES + A_BYTES);
      mbar_wait(BAR(B_FULL + 2), 1);
      CT(64 + 14);
      bar_sync(turn_me, 256);
      wgmma_fence();
#pragma unroll
      for (int kk = 0; kk < 4; kk++) wgmma_g1(a1, da2 + kk * 2, db2 + kk * 2, 1);
      wgmma_commit();
      mbar_wait(BAR(B_FULL + 3), 1);
      CT(64 + 15);
      wgmma_fence();
      wgmma_g1(a1, da3, db3, 1);
      wgmma_g1(a1, da3 + 2, db3 + 2, 1);
      wgmma_commit();
      mbar_wait(BAR(B_STAT), 0);
      tag = SM_(uint32_t, OFF_TAG);
#pragma unroll
      for (int i = 0; i < 8; i++) { const uint4 v = lds128_v(rsa + i * 16); R[8 * i] = v.x; R[8 * i + 2] = v.y; R[8 * i + 4] = v.z; R[8 * i + 6] = v.w; }
      wgmma_wait1();
      release(2);
      wgmma_fence();
      wgmma_g1(a1, da3 + 4, db3 + 4, 1);
      wgmma_g1(a1, da3 + 6, db3 + 6, 1);
      wgmma_g1(a1, make_desc_noswz(sb + OFF_EXA + w * 2048), make_desc_noswz(sb + OFF_EXB), 1);
      wgmma_commit();
      bar_arrive(turn_other, 256);
      kdone(15);
      mbar_wait(BAR(B_STAT), 0);
    }
    fence_acc(a1);
    CT(1);
    auto pack = [&](auto cc) {
      constexpr int c = decltype(cc)::value;
#pragma unroll
      for (int j = 8 * c; j < min_c(8 * c + 8, NX / 8); j++) {
        const uint32_t rs = R[2 * j];
        const float* ac = &a1[4 * j];
        R[2 * j] = bmul2(pack_bf16(ac[0], ac[1]), rs);
        R[2 * j + 1] = bmul2(pack_bf16(ac[2], ac[3]), rs);
      }
    };
    auto put_chunk = [&](auto cc) {
      constexpr int c = decltype(cc)::value;
      const int rho = 16 * wi + (lane & 15);
#pragma unroll
      for (int j = 8 * c; j < min_c(8 * c + 8, NX / 8); j += 2) {
        const int chunk = (j & 7) + (lane >> 4);
        stsm_x4(sb + chunk_off(c, w) + rho * 128 + ((chunk ^ (lane & 7)) << 4), R[2 * j], R[2 * j + 1], R[2 * j + 2], R[2 * j + 3]);
      }
    };
    auto staged = [&](int bar) {
      fence_async_smem();
      __syncwarp();
      if (lane == 0) mbar_arrive(BAR(bar));
    };
    auto mma_rs = [&](auto cc, auto k0, auto k1) {
      constexpr int c = decltype(cc)::value;
      const uint64_t db = make_desc(sb + c * ST_BYTES + A_BYTES);
#pragma unroll
      for (int kk = decltype(k0)::value; kk < decltype(k1)::value; kk++)
        wgmma_n256_rs(acc, R[16 * c + 4 * kk], R[16 * c + 4 * kk + 1], R[16 * c + 4 * kk + 2], R[16 * c + 4 * kk + 3], db + kk * 2, c + kk > 0);
      wgmma_commit();
    };
    auto kdone_x = [&](int k, auto ic) {
      constexpr int i = decltype(ic)::value;
      uint32_t r[8];
#pragma unroll
      for (int z = 0; z < 2; z++) {
        const int tr = 32 * (i & 1) + 16 * z + 8 * (lane >> 4) + (lane & 7), chunk = 2 * wi + ((lane >> 3) & 1);
        ldsm_x4_t(sb + (i >> 1) * ST_BYTES + w * 8192 + tr * 128 + ((chunk ^ (lane & 7)) << 4), r[4 * z], r[4 * z + 1], r[4 * z + 2], r[4 * z + 3]);
      }
      float f[16];
#pragma unroll
      for (int z = 0; z < 8; z++) { f[2 * z] = bf_lo(r[z]); f[2 * z + 1] = bf_hi(r[z]); }
#pragma unroll
      for (int z = 0; z < 16; z++) asm volatile("" : "+f"(f[z]));
      kdone(k);
#pragma unroll
      for (int z = 0; z < 16; z++) asm volatile("add.f32 %0, %0, %1;" : "+f"(acc[16 * i + z]) : "f"(f[z]));
    };
    pack(IC<0>());
    put_chunk(IC<0>());
    staged(w ? B_EPI0B : B_EPI);
    mbar_wait(BAR(B_STAT), 0);
    CT(21);
    pack(IC<1>());
    pack(IC<2>());
    pack(IC<3>());
#pragma unroll
    for (int i = 16; i < NX / 4; i++) asm volatile("" : "+r"(R[i]));
#pragma unroll
    for (int i = 0; i < 128; i++) asm volatile("" : "=f"(acc[i]));
    mbar_wait(BAR(B_FULL + 0), 0);
    CT(2);
    CT(64 + 16);
    bar_sync(turn_me, 256);
    wgmma_fence();
    mma_rs(IC<0>(), IC<0>(), IC<4>());
    mbar_wait(BAR(B_FULL + 1), 0);
    CT(64 + 17);
    wgmma_fence();
    mma_rs(IC<1>(), IC<0>(), IC<2>());
    wgmma_wait1();
    release(0);
    mma_rs(IC<1>(), IC<2>(), IC<4>());
    bar_arrive(turn_other, 256);
    kdone_x(17, IC<0>());
    static_for<2>([&](auto ic) {
      constexpr int c = 2 + decltype(ic)::value;
      mbar_wait(BAR(B_FULL + c), 0);
      CT(64 + 16 + c);
      bar_sync(turn_me, 256);
      wgmma_fence();
      mma_rs(IC<c>(), IC<0>(), IC<min_c(4, NX / 16 - 4 * c)>());
      bar_arrive(turn_other, 256);
      if (c == 2) { put_chunk(IC<1>()); staged(B_EPI + 1); }
      kdone_x(16 + c, IC<c - 1>());
    });
#pragma unroll 1
    for (int k = 20; k < 23; k++) {
      if (w == 1) mbar_wait(BAR(B_A20), 0);
      kstep(acc, k, false, k < 22);
      if (k == 20) {
        kdone_x(k, IC<3>());
      } else {
        if (k == 21) put_chunk(IC<2>()); else put_chunk(IC<3>());
        __syncwarp();
        if (lane == 0) mbar_arrive(BAR(B_EPI + k - 19));
        kdone(k);
      }
    }
    uint32_t wf[32][4];
    auto load_wf = [&](auto hc) {
      constexpr int h = decltype(hc)::value;
      const int d = w * 64 + (lane >> 4) * 8 + (lane & 7);
      const uint32_t ad = sb + round_off(h) + (lane & 8) * 1024 + d * 64 + ((wi ^ ((lane >> 1) & 3)) << 4);
#pragma unroll
      for (int i = 0; i < 4; i++) ldsm_x4_t(ad + i * 1024, wf[4 * h + i][0], wf[4 * h + i][1], wf[4 * h + i][2], wf[4 * h + i][3]);
    };
    auto load_wf_rest = [&]() { static_for<8 - NREG_H>([&](auto ic) { load_wf(IC<NREG_H + decltype(ic)::value>()); }); };
#pragma unroll
    for (int i = 0; i < 4 * NREG_H; i++) { wf[i][0] = 0; wf[i][1] = 0; wf[i][2] = 0; wf[i][3] = 0; }
    const int grp = tau * 2 + m;
#pragma unroll 1
    for (int k = 23; k < 46; k++) {
      kstep(acc, k, false, false, NX < 256 && k == MINI_K);
      if (moe) {
        static_for<NREG_H>([&](auto hc) {
          constexpr int h = decltype(hc)::value;
          if (k == mr_k(h) + 1) { mbar_wait(BAR(B_MR + (h & 1)), (h >> 1) & 1); CT(32 + h); load_wf(hc); }
        });
      }
      if (k == RESET_K && tid == 0) mbar_arrive(BAR(B_LATE));
      kdone(k);
    }
    asm volatile("barrier.cluster.arrive.relaxed.aligned;" ::: "memory");
    mbar_wait(BAR(B_STAT), 1);
    uint32_t wa[16][2];
    uint32_t cd = code_of(tag);
    uint4* hp_pub = &p.s->hstat[(grp * 8 + eps) * 128 + warp * 16 + g];
    const uint4* hp_poll = &p.s->hstat[(grp * 8 + 2 * q) * 128 + warp * 16 + g];
    const uint32_t vec_off = (2 * wi) * 512 + q * 128 + ((g ^ (2 * q)) << 4);
    {
      float as[64], ak[64];
      fence_acc(acc);
#pragma unroll
      for (int i = 0; i < 64; i++) asm volatile("mov.b32 %0, %1;" : "=f"(as[i]) : "f"(acc[64 + i]));
#pragma unroll
      for (int i = 0; i < 64; i++) asm volatile("mov.b32 %0, %1;" : "=f"(ak[i]) : "f"(acc[i]));
      const uint64_t da1 = make_desc(sb + 2 * ST_BYTES + w * 8192), db1 = make_desc(sb + 2 * ST_BYTES + A_BYTES);
      const uint64_t da2 = make_desc(sb + 3 * ST_BYTES + w * 8192), db2 = make_desc(sb + 3 * ST_BYTES + A_BYTES);
      mbar_wait(BAR(B_FULL + 2), 1);
      CT(64 + 46);
      mbar_wait(BAR(B_FULL + 3), 1);
      CT(64 + 47);
      bar_sync(turn_me, 256);
      wgmma_fence();
#pragma unroll
      for (int kk = 0; kk < 4; kk++) wgmma_n128(as, da1 + kk * 2, db1 + 1024 + kk * 2);
#pragma unroll
      for (int kk = 0; kk < 4; kk++) wgmma_n128(as, da2 + kk * 2, db2 + 1024 + kk * 2);
      wgmma_commit();
      bar_arrive(turn_other, 256);
      const uint32_t rx = mapa(sb + OFF_PEER + w * 4096 + vec_off, 1 - m), rb = mapa(BAR(B_XCH), 1 - m);
      asm volatile("barrier.cluster.wait.aligned;" ::: "memory");
      CT(24);
      wgmma_wait0();
      fence_acc64(as);
      CT(25);
      auto keep = [&]() {
        bar_sync(turn_me, 256);
        wgmma_fence();
#pragma unroll
        for (int kk = 0; kk < 4; kk++) wgmma_n128(ak, da1 + kk * 2, db1 + kk * 2);
        wgmma_commit();
#pragma unroll
        for (int kk = 0; kk < 4; kk++) wgmma_n128(ak, da2 + kk * 2, db2 + kk * 2);
        wgmma_commit();
        if (w == 0) bar_arrive(turn_other, 256);
      };
#pragma unroll
      for (int i = 0; i < 8; i++) {
        if (i == SEND_FIRST) keep();
        const float* ac = &as[16 * (i >> 1) + 2 * (i & 1)];
        st_async_v4(rx + (i >> 1) * 8192 + (i & 1) * 512, rb, pack_bf16(ac[0], ac[1]), pack_bf16(ac[4], ac[5]), pack_bf16(ac[8], ac[9]), pack_bf16(ac[12], ac[13]));
      }
      CT(26);
#pragma unroll
      for (int i = 0; i < 4; i++) {
        const uint4 v = lds128_v(sb + OFF_WR + q * 80 + i * 16);
        const uint32_t vv[4] = {v.x, v.y, v.z, v.w};
#pragma unroll
        for (int z = 0; z < 4; z++) {
          asm volatile("{\n.reg .pred p;\nsetp.ne.b32 p, %2, 0;\nselp.b32 %0, %1, 0x3F803F80, p;\n}" : "=r"(wa[4 * i + z][0]) : "r"(vv[z]), "r"(g & 1));
          asm volatile("{\n.reg .pred p;\nsetp.ne.b32 p, %2, 0;\nselp.b32 %0, %1, 0x3F803F80, p;\n}" : "=r"(wa[4 * i + z][1]) : "r"(vv[z]), "r"(g & 1));
        }
      }
      pin(cd); pin(hp_pub); pin(hp_poll);
      CT(27);
      wgmma_wait1();
      release(2);
      wgmma_wait0();
      fence_acc64(ak);
      CT(3);
#pragma unroll
      for (int i = 0; i < 8; i++) {
        const float* ac = &ak[16 * (i >> 1) + 2 * (i & 1)];
        sts128(sb + (2 + (i >> 2)) * ST_BYTES + w * 8192 + ((i >> 1) & 1) * 4096 + (i & 1) * 512 + vec_off,
               pack_bf16(ac[0], ac[1]), pack_bf16(ac[4], ac[5]), pack_bf16(ac[8], ac[9]), pack_bf16(ac[12], ac[13]));
      }
    }
    uint32_t h[8][4];
    {
      const int qq = 2 * (warp & 1) + ((lane >> 3) & 1);
      const uint32_t lo = (lane >> 4) * 512 + qq * 128 + (((lane & 7) ^ (2 * qq)) << 4);
      bar_sync(NB_BOTH, 256);
#pragma unroll
      for (int ks = 0; ks < 8; ks++)
        ldsm_x4_t(sb + (2 + w) * ST_BYTES + (ks >> 2) * 8192 + (wi >> 1) * 4096 + (ks & 3) * 1024 + lo, h[ks][0], h[ks][1], h[ks][2], h[ks][3]);
      CT(28);
      mbar_wait_cluster(BAR(B_XCH), 0);
      CT(4);
      uint32_t r[8][4];
#pragma unroll
      for (int ks = 0; ks < 8; ks++) ldsm_x4_t(sb + OFF_PEER + (warp >> 1) * 8192 + ks * 1024 + lo, r[ks][0], r[ks][1], r[ks][2], r[ks][3]);
      float d[4][4] = {};
#pragma unroll
      for (int ks = 0; ks < 8; ks++) {
#pragma unroll
        for (int i = 0; i < 4; i++) {
          h[ks][i] = badd2(h[ks][i], r[ks][i]);
          mma1688(d[i], h[ks][i], wa[2 * ks + (i >> 1)][i & 1], h[ks][i]);
        }
      }
#pragma unroll
      for (int i = 0; i < 2; i++) {
        const float sq = (g & 1) ? d[i][1] + d[i + 2][1] : d[i][0] + d[i + 2][0];
        const float e0 = d[i][2] + d[i + 2][2], e1 = d[i][3] + d[i + 2][3];
        const float other = __shfl_xor_sync(0xffffffffu, (g & 1) ? e0 : e1, 4);
        if (q == (g >> 1)) pkt_st128(hp_pub + 8 * i, with_bit((g & 1) ? other : e0, cd), with_bit(sq, cd >> 1), __float_as_uint((g & 1) ? e1 : other), tag);
      }
    }
    CT(5);
    if (tid == 0) mbar_arrive(BAR(B_KEY));
    delay_clk<HOP1_DELAY>();
    float m_bf, sd, inv_sd, r_bf;
    uint4* key_pub = &p.s->key[((lane & 7) * 16 + grp) * 2];
    uint4* cand_pub = &p.s->cand[grp * 256 + eps * 32 + q];
    uint32_t trow_inv = 0xFFFFu - (uint32_t)(grp * 128 + 32 * (warp >> 1) + 8 * (g >> 1) + 4 * (warp & 1) + (q & 2) + (g & 1));
    {
      uint4 u[4];
#pragma unroll
      for (int i = 0; i < 4; i++) u[i] = pkt_ld128(hp_poll + (i & 1) * 128 + (i >> 1) * 8);
      const float wsum = SM_(float, OFF_WSUM);
      pin(key_pub); pin(cand_pub); pin(trow_inv);
      uint32_t n = 0;
      while (true) {
        bool ok[4];
#pragma unroll
        for (int i = 0; i < 4; i++) ok[i] = u[i].w == tag && pair_code(u[i].x, u[i].y) == cd;
        const bool all = __all_sync(0xffffffffu, ok[0] && ok[1] && ok[2] && ok[3]);
        if (all || ++n > SPIN_LIMIT) break;
#pragma unroll
        for (int i = 0; i < 4; i++) pkt_ld128_if(u[i], hp_poll + (i & 1) * 128 + (i >> 1) * 8, !ok[i]);
      }
      CT(6);
      float a[3], b[3];
      a[0] = __uint_as_float(u[0].x & ~1u) + __uint_as_float(u[1].x & ~1u); b[0] = __uint_as_float(u[2].x & ~1u) + __uint_as_float(u[3].x & ~1u);
      a[1] = __uint_as_float(u[0].y & ~1u) + __uint_as_float(u[1].y & ~1u); b[1] = __uint_as_float(u[2].y & ~1u) + __uint_as_float(u[3].y & ~1u);
      a[2] = __uint_as_float(u[0].z) + __uint_as_float(u[1].z); b[2] = __uint_as_float(u[2].z) + __uint_as_float(u[3].z);
#pragma unroll
      for (int i = 0; i < 3; i++) {
        a[i] = ((q & 2) ? b[i] : a[i]) + __shfl_xor_sync(0xffffffffu, (q & 2) ? a[i] : b[i], 2);
        a[i] += __shfl_xor_sync(0xffffffffu, a[i], 1);
      }
      const float mu = a[0] * (1.f / 1024.f);
      m_bf = bf16r(mu);
      sd = ln_sd(a[1] * (1.f / 1024.f) - mu * mu);
      inv_sd = rcp_fast(sd);
      r_bf = bf16r((a[2] - m_bf * wsum) * inv_sd);
    }
    {
      const uint32_t u = __float_as_uint(r_bf);
      const uint32_t ord = (u & 0x80000000u) ? ~u : (u | 0x80000000u);
      const uint32_t key = (ord & 0xFFFF0000u) | trow_inv;
      const uint32_t wk = __reduce_max_sync(0xffffffffu, key);
      if (key == wk) SM_(uint2, OFF_WKEY + warp * 8) = make_uint2(wk, (__float_as_uint(m_bf) >> 16) | __float_as_uint(sd));
      const uint32_t wmask = __ballot_sync(0xffffffffu, key == wk);
      const bool hi = (wmask & 0xCCCCCCCCu) != 0;
      uint32_t c[16];
#pragma unroll
      for (int ks = 0; ks < 8; ks++) { c[2 * ks] = hi ? h[ks][1] : h[ks][0]; c[2 * ks + 1] = hi ? h[ks][3] : h[ks][2]; }
      bar_sync(NB_BOTH, 256);
      const uint2 km = SM_(uint2, OFF_WKEY + (lane & 7) * 8);
      const uint32_t bk = __reduce_max_sync(0xffffffffu, km.x);
      if (wk == bk) {
        if ((wmask >> (lane & 28)) & 15) {
#pragma unroll
          for (int ks = 0; ks < 8; ks++) pkt_st128(cand_pub + ks * 4, c[2 * ks], tag, c[2 * ks + 1], tag);
        }
      } else if (eps == 0) {
        const uint32_t kx = __shfl_sync(0xffffffffu, km.x, warp ^ 1), ms = __shfl_sync(0xffffffffu, km.y, warp ^ 1);
        if (kx == bk && lane < 8) pkt_st128(key_pub, bk, tag, ms, tag);
      }
      CT(7);
    }
    {
      const float ih = bf16r(inv_sd);
      const uint32_t nm = pack_bf16(-m_bf, -m_bf), iv = pack_bf16(ih, inv_sd - ih);
      const uint32_t nm_o = __shfl_xor_sync(0xffffffffu, nm, 2), iv_o = __shfl_xor_sync(0xffffffffu, iv, 2);
      const uint32_t nm2[2] = {(q & 2) ? nm_o : nm, (q & 2) ? nm : nm_o}, iv2[2] = {(q & 2) ? iv_o : iv, (q & 2) ? iv : iv_o};
      const uint32_t hi2[2] = {__byte_perm(iv2[0], 0, 0x1010), __byte_perm(iv2[1], 0, 0x1010)}, lo2[2] = {__byte_perm(iv2[0], 0, 0x3232), __byte_perm(iv2[1], 0, 0x3232)};
      const uint32_t oa = sb + OFF_OUT + (warp * 16 + (lane & 15)) * 128;
#pragma unroll
      for (int ks = 0; ks < 8; ks++) {
        uint32_t o[4];
#pragma unroll
        for (int i = 0; i < 4; i++) {
          const uint32_t dd = badd2(h[ks][i], nm2[i & 1]);
          o[i] = badd2(h[ks][i], bfma2(dd, hi2[i & 1], bmul2(dd, lo2[i & 1])));
        }
        stsm_x4(oa + (ks >> 2) * 16384 + (((2 * (ks & 3) + (lane >> 4)) ^ (lane & 7)) << 4), o[0], o[1], o[2], o[3]);
      }
      staged(B_OUT);
    }
    CT(8);
    uint32_t df[16][4];
    auto load_df = [&]() {
      const int frow = (lane & 7) + ((lane >> 4) << 3), hi = (lane >> 3) & 1;
      const uint32_t base = sb + down_off(warp >> 1) + (warp & 1) * 8192 + frow * 128;
#pragma unroll
      for (int mt = 0; mt < 8; mt++) {
#pragma unroll
        for (int ks = 0; ks < 2; ks++)
          ldsm_x4_t(base + (mt >> 2) * 4096 + ks * 2048 + (((2 * (mt & 3) + hi) ^ (lane & 7)) << 4),
                    df[2 * mt + ks][0], df[2 * mt + ks][1], df[2 * mt + ks][2], df[2 * mt + ks][3]);
      }
    };
    if (moe) {
      mbar_wait(BAR(B_GU), 0);
      load_wf_rest();
      mbar_wait(BAR(B_DN), 0);
      load_df();
    }
    uint4* y_pub = &p.s->ypart[cid * 256 + tid];
    uint32_t xs_ad = sb + OFF_XSEL + (8 * (g >> 2) + 4 * w + (g & 3)) * 32 + q * 8, gp_ad = sb + OFF_GP + (wi * 8 + g) * 16 + w * 8 + (q >> 1) * 4;
    pin(y_pub); pin(xs_ad); pin(gp_ad);
    mbar_wait(BAR(B_XS), 0);
    CT(9);
    if (moe) {
      float gd[8][4] = {};
      uint2 bx[4];
#pragma unroll
      for (int r = 0; r < 4; r++) bx[r] = smem_at<uint2>(xs_ad + r * 512);
#pragma unroll
      for (int r = 0; r < 4; r++) {
#pragma unroll
        for (int i = 0; i < 8; i++) mma16816(gd[i], wf[8 * r + i][0], wf[8 * r + i][1], wf[8 * r + i][2], wf[8 * r + i][3], bx[r].x, bx[r].y);
      }
      const float gs = sel4(q, gd[0][0] + gd[1][1], gd[2][0] + gd[3][1], gd[4][0] + gd[5][1], gd[6][0] + gd[7][1]);
      const float us = sel4(q, gd[0][2] + gd[1][3], gd[2][2] + gd[3][3], gd[4][2] + gd[5][3], gd[6][2] + gd[7][3]);
      float v = ((q & 2) ? us : gs) + __shfl_xor_sync(0xffffffffu, (q & 2) ? gs : us, 2);
      v += __shfl_xor_sync(0xffffffffu, v, 1);
      smem_at<float>(gp_ad) = v;
      CT(10);
      bar_sync(NB_BOTH, 256);
      uint32_t bq[4];
      {
        const float4 p0 = SM_(float4, OFF_GP + lane * 16);
        const float gt = bf16r(p0.x + p0.z), up = bf16r(p0.y + p0.w);
        const float act = bf16r(gt * sigmoid_fast(gt)) * up;
        const uint32_t pr = pack_bf16(act, __shfl_down_sync(0xffffffffu, act, 1));
#pragma unroll
        for (int i = 0; i < 4; i++) bq[i] = __shfl_sync(0xffffffffu, pr, 8 * i + 2 * q);
      }
      CT(11);
      float yd[8][4] = {};
#pragma unroll
      for (int ks = 0; ks < 2; ks++) {
#pragma unroll
        for (int mt = 0; mt < 8; mt++) mma16816(yd[mt], df[2 * mt + ks][0], df[2 * mt + ks][1], df[2 * mt + ks][2], df[2 * mt + ks][3], bq[2 * ks], bq[2 * ks + 1]);
      }
      pkt_st128(y_pub, with_bit(sel4(q, yd[0][0], yd[2][0], yd[4][0], yd[6][0]), cd), with_bit(sel4(q, yd[0][2], yd[2][2], yd[4][2], yd[6][2]), cd >> 1),
                with_bit(sel4(q, yd[1][0], yd[3][0], yd[5][0], yd[7][0]), cd), with_bit(sel4(q, yd[1][2], yd[3][2], yd[5][2], yd[7][2]), cd >> 1));
    } else {
      const long long tw = clock64();
      while (clock64() - tw < IDLE_WAIT_CLK) __nanosleep(100);
    }
    CT(12);
    const uint32_t kv = SM_(uint32_t, OFF_KV);
    const int tsel = 0xFFFF - (int)(kv & 0xFFFFu);
    const float r_sel = __uint_as_float((kv & 0x80000000u) ? (kv & 0x7FFF0000u) : (~kv & 0xFFFF0000u));
    const float sig = bf16r(sigmoid_fast(r_sel));
    const int pfin = 2 * cid + (tid & 1);
    const int col_fin = (pfin >> 5) * 128 + (pfin & 3) * 32 + ((pfin & 31) >> 2) + 8 * ((tid >> 1) & 3);
    const int sel_off = (col_fin >> 4) * 32 + ((col_fin & 7) >> 1) * 8 + ((col_fin >> 3) & 1) * 4 + (col_fin & 1) * 2;
    const float hn_fin = __uint_as_float((uint32_t)SM_(uint16_t, OFF_XSEL + sel_off) << 16), h_fin = __uint_as_float((uint32_t)SM_(uint16_t, OFF_HSEL + sel_off) << 16);
    bf16* out_fin = p.out + (size_t)tsel * 1024 + col_fin;
    {
      const uint4* src = &p.s->ypart[(16 + (tid >> 1)) * 256 + pfin];
      pin(src); pin(out_fin);
      uint4 v = make_uint4(0, 0, 0, 0);
      if (warp < 7) {
        delay_clk<HOP3_DELAY>();
        uint32_t n = 0;
        bool ok = false;
        do {
          pkt_ld128_if(v, src, !ok);
          ok = pair_code(v.x, v.y) == cd && pair_code(v.z, v.w) == cd;
        } while (!__all_sync(0xffffffffu, ok) && ++n < SPIN_LIMIT);
      }
      CT(13);
      const float y0 = __uint_as_float(v.x & ~1u), y1 = __uint_as_float(v.y & ~1u), y2 = __uint_as_float(v.z & ~1u), y3 = __uint_as_float(v.w & ~1u);
      const float a0 = ((lane & 2) ? y1 : y0) + __shfl_xor_sync(0xffffffffu, (lane & 2) ? y0 : y1, 2);
      const float a1 = ((lane & 2) ? y3 : y2) + __shfl_xor_sync(0xffffffffu, (lane & 2) ? y2 : y3, 2);
      float b = ((lane & 4) ? a1 : a0) + __shfl_xor_sync(0xffffffffu, (lane & 4) ? a0 : a1, 4);
      b += __shfl_xor_sync(0xffffffffu, b, 8);
      b += __shfl_xor_sync(0xffffffffu, b, 16);
      if (lane < 8) SM_(float, OFF_FIN + lane * 32 + warp * 4) = b;
    }
    bar_sync(NB_BOTH, 256);
    if (tid < 8) {
      const float4 y0 = SM_(float4, OFF_FIN + tid * 32), y1 = SM_(float4, OFF_FIN + tid * 32 + 16);
      const float y = ((y0.x + y0.y) + (y0.z + y0.w)) + ((y1.x + y1.y) + y1.z);
      *out_fin = __float2bfloat16_rn(h_fin + bf16r(hn_fin + bf16r(bf16r(y) * sig)));
      if (cid == 0 && tid == 0) st_relaxed32(&p.s->epoch, tag);
    }
    CT(14);
  }
}

__global__ void __launch_bounds__(384, 1) occupancy_probe_kernel() {}

typedef CUresult (*EncodeFn)(CUtensorMap*, CUtensorMapDataType, cuuint32_t, void*, const cuuint64_t*, const cuuint64_t*, const cuuint32_t*, const cuuint32_t*,
                             CUtensorMapInterleave, CUtensorMapSwizzle, CUtensorMapL2promotion, CUtensorMapFloatOOBfill);

static void make_tm(EncodeFn enc, CUtensorMap* tm, const void* ptr, uint64_t rows, uint64_t cols, uint32_t brows, uint32_t bcols, CUtensorMapSwizzle sw,
                    CUtensorMapL2promotion promo = CU_TENSOR_MAP_L2_PROMOTION_L2_128B) {
  cuuint64_t dims[2] = {cols, rows};
  cuuint64_t strides[1] = {cols * 2};
  cuuint32_t box[2] = {bcols, brows};
  cuuint32_t es[2] = {1, 1};
  enc(tm, CU_TENSOR_MAP_DATA_TYPE_BFLOAT16, 2, const_cast<void*>(ptr), dims, strides, box, es, CU_TENSOR_MAP_INTERLEAVE_NONE, sw,
      promo, CU_TENSOR_MAP_FLOAT_OOB_FILL_NONE);
}

extern "C" void kernel_launch(void* const* d_in, const int* in_sizes, int n_in, void* d_out, int out_size) {
  (void)in_sizes; (void)n_in; (void)out_size;
  static EncodeFn enc = nullptr;
  static void* abT = nullptr;
  static int map = 0;
  if (!enc) {
    void* fn = nullptr; cudaDriverEntryPointQueryResult st;
    cudaGetDriverEntryPoint("cuTensorMapEncodeTiled", &fn, cudaEnableDefault, &st);
    enc = (EncodeFn)fn;
    cudaGetSymbolAddress(&abT, g_scratch);
    cudaFuncSetAttribute(fnet_moe_kernel<0>, cudaFuncAttributeMaxDynamicSharedMemorySize, SMEM_TOTAL);
    cudaFuncSetAttribute(fnet_moe_kernel<1>, cudaFuncAttributeMaxDynamicSharedMemorySize, SMEM_TOTAL);
    cudaFuncSetAttribute(occupancy_probe_kernel, cudaFuncAttributeMaxDynamicSharedMemorySize, SMEM_TOTAL);
    cudaFuncSetAttribute(occupancy_probe_kernel, cudaFuncAttributeNonPortableClusterSizeAllowed, 1);
    auto max_clusters = [&](int size) {
      cudaLaunchConfig_t cfg = {};
      cfg.gridDim = dim3(128); cfg.blockDim = dim3(384); cfg.dynamicSmemBytes = SMEM_TOTAL;
      cudaLaunchAttribute at[1];
      at[0].id = cudaLaunchAttributeClusterDimension; at[0].val.clusterDim.x = size; at[0].val.clusterDim.y = 1; at[0].val.clusterDim.z = 1;
      cfg.attrs = at; cfg.numAttrs = 1;
      int ncl = 0;
      return cudaOccupancyMaxActiveClusters(&ncl, occupancy_probe_kernel, &cfg) == cudaSuccess ? ncl : 0;
    };
    int dev = 0, sms = 0;
    cudaGetDevice(&dev);
    cudaDeviceGetAttribute(&sms, cudaDevAttrMultiProcessorCount, dev);
    map = (sms == 132 && max_clusters(2) == 66 && max_clusters(16) == 7) ? 0 : 1;
    (void)cudaGetLastError();
  }
  Params p;
  const bf16* x = (const bf16*)d_in[0];
  make_tm(enc, &p.tmD0, d_in[3], 1024, 1024, 128, 64, CU_TENSOR_MAP_SWIZZLE_128B);
  make_tm(enc, &p.tmD1, d_in[4], 1024, 1024, 128, 64, CU_TENSOR_MAP_SWIZZLE_128B);
  make_tm(enc, &p.tmX, x, 2048, 1024, map == 0 ? NX0 : 256, 64, CU_TENSOR_MAP_SWIZZLE_128B);
  make_tm(enc, &p.tmXr, x, 2048, 1024, 64, 64, CU_TENSOR_MAP_SWIZZLE_128B);
  make_tm(enc, &p.tmAbS, abT, 2048, 2048, 64, 64, CU_TENSOR_MAP_SWIZZLE_128B);
  make_tm(enc, &p.tmAbL, abT, 2048, 2048, 128, 64, CU_TENSOR_MAP_SWIZZLE_128B);
  make_tm(enc, &p.tmW0, d_in[1], 2048, 2048, 128, 64, CU_TENSOR_MAP_SWIZZLE_128B);
  make_tm(enc, &p.tmW1, d_in[2], 2048, 2048, 128, 64, CU_TENSOR_MAP_SWIZZLE_128B);
  {
    cuuint64_t dims[5] = {1024, 2, 4, 4, 64};
    cuuint64_t strides[4] = {2048, 8 * 2048, 2 * 2048, 32 * 2048};
    cuuint32_t box[5] = {64, 2, 4, 2, 1};
    cuuint32_t es[5] = {1, 1, 1, 1, 1};
    enc(&p.tmOut, CU_TENSOR_MAP_DATA_TYPE_BFLOAT16, 5, d_out, dims, strides, box, es, CU_TENSOR_MAP_INTERLEAVE_NONE, CU_TENSOR_MAP_SWIZZLE_128B,
        CU_TENSOR_MAP_L2_PROMOTION_NONE, CU_TENSOR_MAP_FLOAT_OOB_FILL_NONE);
  }
  {
    cuuint64_t dims[5] = {1024, 2, 4, 2, 8};
    cuuint64_t strides[4] = {2048, 4 * 2048, 2 * 2048, 256 * 2048};
    cuuint32_t box[5] = {64, 2, 4, 2, 8};
    cuuint32_t es[5] = {1, 1, 1, 1, 1};
    enc(&p.tmXh, CU_TENSOR_MAP_DATA_TYPE_BFLOAT16, 5, const_cast<bf16*>(x) + 240 * 1024, dims, strides, box, es, CU_TENSOR_MAP_INTERLEAVE_NONE,
        CU_TENSOR_MAP_SWIZZLE_128B, CU_TENSOR_MAP_L2_PROMOTION_L2_128B, CU_TENSOR_MAP_FLOAT_OOB_FILL_NONE);
  }
  make_tm(enc, &p.tmAbM, abT, 2048, 2048, 128, 16, CU_TENSOR_MAP_SWIZZLE_32B, CU_TENSOR_MAP_L2_PROMOTION_NONE);
  make_tm(enc, &p.tmWM0, d_in[1], 2048, 2048, 128, 16, CU_TENSOR_MAP_SWIZZLE_32B, CU_TENSOR_MAP_L2_PROMOTION_NONE);
  make_tm(enc, &p.tmWM1, d_in[2], 2048, 2048, 128, 16, CU_TENSOR_MAP_SWIZZLE_32B, CU_TENSOR_MAP_L2_PROMOTION_NONE);
  make_tm(enc, &p.tmG, d_in[7], 1024, 3584, 128, 32, CU_TENSOR_MAP_SWIZZLE_64B);
  make_tm(enc, &p.tmU, d_in[8], 1024, 3584, 128, 32, CU_TENSOR_MAP_SWIZZLE_64B);
  make_tm(enc, &p.tmDn, d_in[9], 3584, 1024, 32, 64, CU_TENSOR_MAP_SWIZZLE_128B);
  p.x = x; p.Dre = (const bf16*)d_in[3]; p.Dim = (const bf16*)d_in[4];
  p.wr = (const bf16*)d_in[6]; p.wdown = (const bf16*)d_in[9]; p.wgate = (const bf16*)d_in[7]; p.wup = (const bf16*)d_in[8];
  p.out = (bf16*)d_out; p.s = (Scratch*)abT;
  if (map == 1) fnet_moe_kernel<1><<<128, 384, SMEM_TOTAL>>>(p);
  else fnet_moe_kernel<0><<<132, 384, SMEM_TOTAL>>>(p);
}
```

```cpp
#include <cuda.h>
#include <cuda_runtime.h>
#include <cuda_bf16.h>
#include <stdint.h>
#include <type_traits>

typedef __nv_bfloat16 bf16;

constexpr int NX0 = 240;
constexpr int REG_C = 232, REG_P = 40;
__device__ __forceinline__ int sigma_of(int tau, int r) { return r + (r >= tau); }
__device__ __forceinline__ int kblock(int tau, int j) {
  const int i = j - 4, c = (i * 37) >> 8;
  return j < 4 ? tau * 4 + j : sigma_of(tau, i - 7 * c) * 4 + c;
}
constexpr int AUX_AFTER = 1;
constexpr int PF_K0 = 8, PF_N0 = 2, PF_K1 = 24;
constexpr int WPF_K0 = 12, WPF_N = 10;
constexpr int PUB_K1 = 22;
constexpr int NREG_H = 5;
constexpr int MR_K0 = 29, MR_P = 6;
constexpr int MINI_PF_K = 39, MINI_LOAD_K = 43, MINI_K = 42;
constexpr int RESET_K = 37;
constexpr int SEND_FIRST = 2;
constexpr int HELPER_NS = 5000;
constexpr int GATHER_NS = 400;
constexpr int MOE_PACE_CLK = 300;
constexpr int OUT_PACE_CLK = 100;
constexpr int HOP1_DELAY = 150, HOP3_DELAY = 300;
constexpr int SPEC_MIN = 10;
constexpr int IDLE_WAIT_CLK = 1200;
__host__ __device__ constexpr int mr_k(int h) { return MR_K0 + MR_P * (h >> 1) + 2 * (h & 1); }
constexpr int A_BYTES = 128 * 64 * 2;
constexpr int B_BYTES = 256 * 64 * 2;
constexpr int ST_BYTES = A_BYTES + B_BYTES;
constexpr int OFF_XCH = 4 * ST_BYTES;
constexpr int OFF_BAR = OFF_XCH + 32768;
constexpr int OFF_WR = OFF_BAR + 384;
constexpr int OFF_RS = OFF_WR + 384;
constexpr int OFF_PUB = OFF_RS + 640;
constexpr int OFF_MISC = OFF_PUB + 768;
constexpr int SMEM_TOTAL = OFF_MISC + 256;
constexpr int OFF_WSUM = OFF_MISC, OFF_TAG = OFF_MISC + 4;
constexpr int OFF_SEEN = OFF_MISC + 8;
constexpr int OFF_KV = OFF_MISC + 12;
constexpr int OFF_WKEY = OFF_MISC + 32;
constexpr int OFF_MINI = OFF_XCH + 16384;
constexpr int OFF_EXA = OFF_XCH;
constexpr int OFF_EXB = OFF_XCH + 4096;
__host__ __device__ constexpr int chunk_off(int c, int w) { return (c < 2 ? (c + 2) * ST_BYTES : OFF_XCH + (c - 2) * 16384) + w * 8192; }
__host__ __device__ constexpr int late_off(int i) { return i < 4 ? i * 16384 : 2 * ST_BYTES + A_BYTES + (i - 4) * 16384; }
__host__ __device__ constexpr int round_off(int h) { return h < NREG_H + 2 ? OFF_XCH + (h & 1) * 16384 : late_off(h - NREG_H - 2); }
__host__ __device__ constexpr int down_off(int i) { return late_off(6 - NREG_H + i); }
constexpr int OFF_PEER = ST_BYTES + A_BYTES;
constexpr int OFF_OUT = 3 * ST_BYTES + A_BYTES;
constexpr int OFF_XSEL = OFF_PEER;
constexpr int OFF_HSEL = OFF_PEER + 4096;
constexpr int OFF_GP = OFF_PEER + 8192;
constexpr int OFF_FIN = OFF_PEER + 9216;
__device__ __forceinline__ int slot_of(int k) { return k & 3; }
__device__ __forceinline__ int use_of(int k) { return k >> 2; }
enum { B_FULL = 0, B_EMPTY = 4, B_EPI = 8, B_STD = 12, B_EPI0B = 16, B_LATE = 17, B_STAT = 18, B_XCH = 19, B_MR = 20  , B_GU = 22,
       B_DN = 23, B_AUX = 24  , B_OUT = 26, B_KEY = 27, B_XS = 28, B_A20 = 29, B_STDA = 30, B_COUNT = 31 };
enum { NB_TURN0 = 1, NB_TURN1 = 2, NB_WG0 = 3, NB_BOTH = 5, NB_AUX = 6 };

struct Scratch {
  bf16 abT[2048 * 2048];
  uint2 xstat[2048];
  uint2 dsum[2048];
  uint4 abflag[16 * 8 * 2];
  uint4 hflag[16 * 2];
  uint4 hstat[16 * 8 * 128];
  uint4 cand[16 * 256];
  uint4 key[8 * 16 * 2];
  uint4 ypart[128 * 256];
  uint32_t epoch;
};
__device__ __align__(1024) Scratch g_scratch;

struct Params {
  Scratch* s; bf16* out;
  const bf16* x; const bf16* Dre; const bf16* Dim; const bf16* wr; const bf16* wdown; const bf16* wgate; const bf16* wup;
  CUtensorMap tmX, tmD0, tmD1, tmXr, tmAbS, tmAbL, tmW0, tmW1, tmOut, tmG, tmU, tmDn, tmXh, tmAbM, tmWM0, tmWM1;
};

#define SPIN_LIMIT (1u << 14)
#define MBAR_LIMIT (1u << 10)
__device__ __forceinline__ uint32_t smem_u32(const void* p) { return (uint32_t)__cvta_generic_to_shared(p); }
__device__ __forceinline__ void mbar_init(uint32_t bar, uint32_t cnt) { asm volatile("mbarrier.init.shared::cta.b64 [%0], %1;" :: "r"(bar), "r"(cnt) : "memory"); }
__device__ __forceinline__ void mbar_expect_tx(uint32_t bar, uint32_t bytes) { asm volatile("mbarrier.arrive.expect_tx.shared::cta.b64 _, [%0], %1;" :: "r"(bar), "r"(bytes) : "memory"); }
__device__ __forceinline__ void mbar_arrive(uint32_t bar) { asm volatile("mbarrier.arrive.shared::cta.b64 _, [%0];" :: "r"(bar) : "memory"); }
__device__ __forceinline__ void mbar_wait(uint32_t bar, uint32_t parity) {
  uint32_t ok, n = 0;
  do {
    asm volatile("{\n.reg .pred p;\nmbarrier.try_wait.parity.shared::cta.b64 p, [%1], %2;\nselp.u32 %0, 1, 0, p;\n}\n" : "=r"(ok) : "r"(bar), "r"(parity) : "memory");
  } while (!ok && ++n < MBAR_LIMIT);
}
__device__ __forceinline__ bool mbar_test(uint32_t bar, uint32_t parity) {
  uint32_t ok;
  asm volatile("{\n.reg .pred p;\nmbarrier.test_wait.parity.shared::cta.b64 p, [%1], %2;\nselp.u32 %0, 1, 0, p;\n}\n" : "=r"(ok) : "r"(bar), "r"(parity) : "memory");
  return ok != 0;
}
__device__ __forceinline__ void mbar_wait_cluster(uint32_t bar, uint32_t parity) {
  uint32_t ok, n = 0;
  do {
    asm volatile("{\n.reg .pred p;\nmbarrier.try_wait.parity.acquire.cluster.shared::cta.b64 p, [%1], %2;\nselp.u32 %0, 1, 0, p;\n}\n" : "=r"(ok) : "r"(bar), "r"(parity) : "memory");
  } while (!ok && ++n < MBAR_LIMIT);
}
__device__ __forceinline__ void tma_load_2d(uint32_t dst, const CUtensorMap* tm, uint32_t bar, int c0, int c1) {
  asm volatile("cp.async.bulk.tensor.2d.shared::cluster.global.mbarrier::complete_tx::bytes [%0], [%1, {%3, %4}], [%2];"
    :: "r"(dst), "l"(tm), "r"(bar), "r"(c0), "r"(c1) : "memory");
}
__device__ __forceinline__ void tma_load_2d_hint(uint32_t dst, const CUtensorMap* tm, uint32_t bar, int c0, int c1, uint64_t pol) {
  asm volatile("cp.async.bulk.tensor.2d.shared::cluster.global.mbarrier::complete_tx::bytes.L2::cache_hint [%0], [%1, {%3, %4}], [%2], %5;"
    :: "r"(dst), "l"(tm), "r"(bar), "r"(c0), "r"(c1), "l"(pol) : "memory");
}
__device__ __forceinline__ uint64_t policy_evict_first() { uint64_t p; asm volatile("createpolicy.fractional.L2::evict_first.b64 %0, 1.0;" : "=l"(p)); return p; }
__device__ __forceinline__ void tma_store_2d(const CUtensorMap* tm, uint32_t src, int c0, int c1) {
  asm volatile("cp.async.bulk.tensor.2d.global.shared::cta.bulk_group [%0, {%2, %3}], [%1];" :: "l"(tm), "r"(src), "r"(c0), "r"(c1) : "memory");
}
__device__ __forceinline__ void tma_prefetch_2d(const CUtensorMap* tm, int c0, int c1) {
  asm volatile("cp.async.bulk.prefetch.tensor.2d.L2.global.tile [%0, {%1, %2}];" :: "l"(tm), "r"(c0), "r"(c1) : "memory");
}
__device__ __forceinline__ void bulk_load(uint32_t dst, const void* src, uint32_t bytes, uint32_t bar) {
  asm volatile("cp.async.bulk.shared::cluster.global.mbarrier::complete_tx::bytes [%0], [%1], %2, [%3];" :: "r"(dst), "l"(src), "r"(bytes), "r"(bar) : "memory");
}
__device__ __forceinline__ void bulk_commit() { asm volatile("cp.async.bulk.commit_group;" ::: "memory"); }
__device__ __forceinline__ void bulk_wait_all() { asm volatile("cp.async.bulk.wait_group 0;" ::: "memory"); }
__device__ __forceinline__ void fence_async_smem() { asm volatile("fence.proxy.async.shared::cta;" ::: "memory"); }
__device__ __forceinline__ void wgmma_fence() { asm volatile("wgmma.fence.sync.aligned;" ::: "memory"); }
__device__ __forceinline__ void wgmma_commit() { asm volatile("wgmma.commit_group.sync.aligned;" ::: "memory"); }
__device__ __forceinline__ void wgmma_wait0() { asm volatile("wgmma.wait_group.sync.aligned 0;" ::: "memory"); }
__device__ __forceinline__ void bar_sync(int id, int n) { asm volatile("bar.sync %0, %1;" :: "r"(id), "r"(n) : "memory"); }
__device__ __forceinline__ void bar_arrive(int id, int n) { asm volatile("bar.arrive %0, %1;" :: "r"(id), "r"(n) : "memory"); }
template<int R> __device__ __forceinline__ void reg_inc() { asm volatile("setmaxnreg.inc.sync.aligned.u32 %0;" :: "n"(R)); }
template<int R> __device__ __forceinline__ void reg_dec() { asm volatile("setmaxnreg.dec.sync.aligned.u32 %0;" :: "n"(R)); }
__device__ __forceinline__ bool elect_one() {
  uint32_t p;
  asm volatile("{\n.reg .pred q;\nelect.sync _|q, 0xffffffff;\nselp.u32 %0, 1, 0, q;\n}\n" : "=r"(p));
  return p != 0;
}
__device__ __forceinline__ uint32_t mapa(uint32_t addr, uint32_t cta) { uint32_t r; asm volatile("mapa.shared::cluster.u32 %0, %1, %2;" : "=r"(r) : "r"(addr), "r"(cta)); return r; }
__device__ __forceinline__ void st_async_v4(uint32_t addr, uint32_t bar, uint32_t a, uint32_t b, uint32_t c, uint32_t d) {
  asm volatile("st.async.weak.shared::cluster.mbarrier::complete_tx::bytes.v4.b32 [%0], {%2, %3, %4, %5}, [%1];" :: "r"(addr), "r"(bar), "r"(a), "r"(b), "r"(c), "r"(d) : "memory");
}
__device__ __forceinline__ void stsm_x4(uint32_t addr, uint32_t a, uint32_t b, uint32_t c, uint32_t d) {
  asm volatile("stmatrix.sync.aligned.m8n8.x4.shared.b16 [%0], {%1, %2, %3, %4};" :: "r"(addr), "r"(a), "r"(b), "r"(c), "r"(d));
}
__device__ __forceinline__ uint4 lds128_v(uint32_t addr) { uint4 v; asm volatile("ld.shared.v4.b32 {%0, %1, %2, %3}, [%4];" : "=r"(v.x), "=r"(v.y), "=r"(v.z), "=r"(v.w) : "r"(addr)); return v; }
extern __shared__ __align__(1024) uint8_t smem_raw[];
template<class T> __device__ __forceinline__ T& smem_at(uint32_t addr) { return *reinterpret_cast<T*>(__cvta_shared_to_generic(addr)); }
#define SM_(T, off) smem_at<T>(sb + (off))
__device__ __forceinline__ uint4 ldg_nc128(const void* p) { uint4 v; asm volatile("ld.global.nc.v4.b32 {%0, %1, %2, %3}, [%4];" : "=r"(v.x), "=r"(v.y), "=r"(v.z), "=r"(v.w) : "l"(p)); return v; }
__device__ __forceinline__ void pkt_st128(void* p, uint32_t a, uint32_t b, uint32_t c, uint32_t d) {
  asm volatile("{\n.reg .b128 v;\n.reg .b64 lo, hi;\nmov.b64 lo, {%1, %2};\nmov.b64 hi, {%3, %4};\nmov.b128 v, {lo, hi};\nst.relaxed.gpu.global.b128 [%0], v;\n}\n"
    :: "l"(p), "r"(a), "r"(b), "r"(c), "r"(d) : "memory");
}
__device__ __forceinline__ uint4 pkt_ld128(const void* p) {
  uint4 r;
  asm volatile("{\n.reg .b128 v;\n.reg .b64 lo, hi;\nld.relaxed.gpu.global.b128 v, [%4];\nmov.b128 {lo, hi}, v;\nmov.b64 {%0, %1}, lo;\nmov.b64 {%2, %3}, hi;\n}\n"
    : "=r"(r.x), "=r"(r.y), "=r"(r.z), "=r"(r.w) : "l"(p) : "memory");
  return r;
}
__device__ __forceinline__ void pkt_ld128_if(uint4& r, const void* p, bool cond) {
  asm volatile("{\n.reg .pred q;\n.reg .b64 lo, hi;\nsetp.ne.b32 q, %5, 0;\nmov.b64 lo, {%0, %1};\nmov.b64 hi, {%2, %3};\n"
               "@q ld.relaxed.gpu.global.v2.b64 {lo, hi}, [%4];\nmov.b64 {%0, %1}, lo;\nmov.b64 {%2, %3}, hi;\n}\n"
    : "+r"(r.x), "+r"(r.y), "+r"(r.z), "+r"(r.w) : "l"(p), "r"((uint32_t)cond) : "memory");
}
__device__ __forceinline__ void pkt_st64(void* p, uint32_t a, uint32_t b) {
  asm volatile("{\n.reg .b64 v;\nmov.b64 v, {%1, %2};\nst.relaxed.gpu.global.b64 [%0], v;\n}\n" :: "l"(p), "r"(a), "r"(b) : "memory");
}
__device__ __forceinline__ uint2 pkt_ld64(const void* p) {
  uint2 r;
  asm volatile("{\n.reg .b64 v;\nld.relaxed.gpu.global.b64 v, [%2];\nmov.b64 {%0, %1}, v;\n}\n" : "=r"(r.x), "=r"(r.y) : "l"(p) : "memory");
  return r;
}
__device__ __forceinline__ uint32_t ld_relaxed32(const void* p) { uint32_t v; asm volatile("ld.relaxed.gpu.global.b32 %0, [%1];" : "=r"(v) : "l"(p) : "memory"); return v; }
__device__ __forceinline__ void st_relaxed32(void* p, uint32_t v) { asm volatile("st.relaxed.gpu.global.b32 [%0], %1;" :: "l"(p), "r"(v) : "memory"); }
__device__ __forceinline__ uint32_t code_of(uint32_t tag) { return tag % 3u + 1u; }
__device__ __forceinline__ uint32_t with_bit(float v, uint32_t bit) { return (__float_as_uint(v) & ~1u) | (bit & 1u); }
__device__ __forceinline__ uint32_t pair_code(uint32_t a, uint32_t b) { return (a & 1u) | ((b & 1u) << 1); }
__device__ __forceinline__ uint32_t pack_bf16(float lo, float hi) { uint32_t r; asm("cvt.rn.bf16x2.f32 %0, %1, %2;" : "=r"(r) : "f"(hi), "f"(lo)); return r; }
__device__ __forceinline__ float bf_lo(uint32_t v) { return __uint_as_float(v << 16); }
__device__ __forceinline__ float bf_hi(uint32_t v) { return __uint_as_float(v & 0xFFFF0000u); }
__device__ __forceinline__ float bf16r(float x) { return __uint_as_float(pack_bf16(0.f, x)); }
__device__ __forceinline__ uint32_t badd2(uint32_t a, uint32_t b) { uint32_t r; asm("add.rn.bf16x2 %0, %1, %2;" : "=r"(r) : "r"(a), "r"(b)); return r; }
__device__ __forceinline__ uint32_t bmul2(uint32_t a, uint32_t b) { uint32_t r; asm("mul.rn.bf16x2 %0, %1, %2;" : "=r"(r) : "r"(a), "r"(b)); return r; }
__device__ __forceinline__ float warp_sum(float v) {
#pragma unroll
  for (int o = 16; o > 0; o >>= 1) v += __shfl_xor_sync(0xffffffffu, v, o);
  return v;
}
__device__ __forceinline__ uint64_t make_desc(uint32_t addr) {
  return (uint64_t)((addr & 0x3FFFF) >> 4) | ((uint64_t)1 << 16) | ((uint64_t)64 << 32) | ((uint64_t)1 << 62);
}
__device__ __forceinline__ uint64_t make_desc_noswz(uint32_t addr) {
  return (uint64_t)((addr & 0x3FFFF) >> 4) | ((uint64_t)8 << 16) | ((uint64_t)16 << 32);
}
__device__ __forceinline__ uint64_t make_desc_32b(uint32_t addr) {
  return (uint64_t)((addr & 0x3FFFF) >> 4) | ((uint64_t)1 << 16) | ((uint64_t)16 << 32) | ((uint64_t)3 << 62);
}
__device__ __forceinline__ void wgmma_n256(float (&d)[128], uint64_t da, uint64_t db, int scale_d) {
  asm volatile("{\n.reg .pred p;\nsetp.ne.b32 p, %130, 0;\n"
    "wgmma.mma_async.sync.aligned.m64n256k16.f32.bf16.bf16 "
    "{%0, %1, %2, %3, %4, %5, %6, %7, %8, %9, %10, %11, %12, %13, %14, %15, %16, %17, %18, %19, %20, %21, %22, %23, %24, %25, %26, %27, %28, %29, %30, %31, "
    "%32, %33, %34, %35, %36, %37, %38, %39, %40, %41, %42, %43, %44, %45, %46, %47, %48, %49, %50, %51, %52, %53, %54, %55, %56, %57, %58, %59, %60, %61, %62, %63, "
    "%64, %65, %66, %67, %68, %69, %70, %71, %72, %73, %74, %75, %76, %77, %78, %79, %80, %81, %82, %83, %84, %85, %86, %87, %88, %89, %90, %91, %92, %93, %94, %95, "
    "%96, %97, %98, %99, %100, %101, %102, %103, %104, %105, %106, %107, %108, %109, %110, %111, %112, %113, %114, %115, %116, %117, %118, %119, %120, %121, %122, %123, %124, %125, %126, %127}, "
    "%128, %129, p, 1, 1, 0, 0;\n}\n"
    : "+f"(d[0]), "+f"(d[1]), "+f"(d[2]), "+f"(d[3]), "+f"(d[4]), "+f"(d[5]), "+f"(d[6]), "+f"(d[7]),
      "+f"(d[8]), "+f"(d[9]), "+f"(d[10]), "+f"(d[11]), "+f"(d[12]), "+f"(d[13]), "+f"(d[14]), "+f"(d[15]),
      "+f"(d[16]), "+f"(d[17]), "+f"(d[18]), "+f"(d[19]), "+f"(d[20]), "+f"(d[21]), "+f"(d[22]), "+f"(d[23]),
      "+f"(d[24]), "+f"(d[25]), "+f"(d[26]), "+f"(d[27]), "+f"(d[28]), "+f"(d[29]), "+f"(d[30]), "+f"(d[31]),
      "+f"(d[32]), "+f"(d[33]), "+f"(d[34]), "+f"(d[35]), "+f"(d[36]), "+f"(d[37]), "+f"(d[38]), "+f"(d[39]),
      "+f"(d[40]), "+f"(d[41]), "+f"(d[42]), "+f"(d[43]), "+f"(d[44]), "+f"(d[45]), "+f"(d[46]), "+f"(d[47]),
      "+f"(d[48]), "+f"(d[49]), "+f"(d[50]), "+f"(d[51]), "+f"(d[52]), "+f"(d[53]), "+f"(d[54]), "+f"(d[55]),
      "+f"(d[56]), "+f"(d[57]), "+f"(d[58]), "+f"(d[59]), "+f"(d[60]), "+f"(d[61]), "+f"(d[62]), "+f"(d[63]),
      "+f"(d[64]), "+f"(d[65]), "+f"(d[66]), "+f"(d[67]), "+f"(d[68]), "+f"(d[69]), "+f"(d[70]), "+f"(d[71]),
      "+f"(d[72]), "+f"(d[73]), "+f"(d[74]), "+f"(d[75]), "+f"(d[76]), "+f"(d[77]), "+f"(d[78]), "+f"(d[79]),
      "+f"(d[80]), "+f"(d[81]), "+f"(d[82]), "+f"(d[83]), "+f"(d[84]), "+f"(d[85]), "+f"(d[86]), "+f"(d[87]),
      "+f"(d[88]), "+f"(d[89]), "+f"(d[90]), "+f"(d[91]), "+f"(d[92]), "+f"(d[93]), "+f"(d[94]), "+f"(d[95]),
      "+f"(d[96]), "+f"(d[97]), "+f"(d[98]), "+f"(d[99]), "+f"(d[100]), "+f"(d[101]), "+f"(d[102]), "+f"(d[103]),
      "+f"(d[104]), "+f"(d[105]), "+f"(d[106]), "+f"(d[107]), "+f"(d[108]), "+f"(d[109]), "+f"(d[110]), "+f"(d[111]),
      "+f"(d[112]), "+f"(d[113]), "+f"(d[114]), "+f"(d[115]), "+f"(d[116]), "+f"(d[117]), "+f"(d[118]), "+f"(d[119]),
      "+f"(d[120]), "+f"(d[121]), "+f"(d[122]), "+f"(d[123]), "+f"(d[124]), "+f"(d[125]), "+f"(d[126]), "+f"(d[127])
    : "l"(da), "l"(db), "r"(scale_d));
}
__device__ __forceinline__ void wgmma_g1(float (&d)[128], uint64_t da, uint64_t db, int scale_d) { wgmma_n256(d, da, db, scale_d); }
__device__ __forceinline__ void wgmma_g1(float (&d)[120], uint64_t da, uint64_t db, int scale_d) {
  asm volatile("{\n.reg .pred p;\nsetp.ne.b32 p, %122, 0;\n"
    "wgmma.mma_async.sync.aligned.m64n240k16.f32.bf16.bf16 "
    "{%0, %1, %2, %3, %4, %5, %6, %7, %8, %9, %10, %11, %12, %13, %14, %15, %16, %17, %18, %19, %20, %21, %22, %23, %24, %25, %26, %27, %28, %29, %30, %31, %32, %33, %34, %35, %36, %37, %38, %39, %40, %41, %42, %43, %44, %45, %46, %47, %48, %49, %50, %51, %52, %53, %54, %55, %56, %57, %58, %59, %60, %61, %62, %63, %64, %65, %66, %67, %68, %69, %70, %71, %72, %73, %74, %75, %76, %77, %78, %79, %80, %81, %82, %83, %84, %85, %86, %87, %88, %89, %90, %91, %92, %93, %94, %95, %96, %97, %98, %99, %100, %101, %102, %103, %104, %105, %106, %107, %108, %109, %110, %111, %112, %113, %114, %115, %116, %117, %118, %119}, "
    "%120, %121, p, 1, 1, 0, 0;\n}\n"
    : "+f"(d[0]), "+f"(d[1]), "+f"(d[2]), "+f"(d[3]), "+f"(d[4]), "+f"(d[5]), "+f"(d[6]), "+f"(d[7]), "+f"(d[8]), "+f"(d[9]), "+f"(d[10]), "+f"(d[11]), "+f"(d[12]), "+f"(d[13]), "+f"(d[14]), "+f"(d[15]), "+f"(d[16]), "+f"(d[17]), "+f"(d[18]), "+f"(d[19]), "+f"(d[20]), "+f"(d[21]), "+f"(d[22]), "+f"(d[23]), "+f"(d[24]), "+f"(d[25]), "+f"(d[26]), "+f"(d[27]), "+f"(d[28]), "+f"(d[29]), "+f"(d[30]), "+f"(d[31]), "+f"(d[32]), "+f"(d[33]), "+f"(d[34]), "+f"(d[35]), "+f"(d[36]), "+f"(d[37]), "+f"(d[38]), "+f"(d[39]), "+f"(d[40]), "+f"(d[41]), "+f"(d[42]), "+f"(d[43]), "+f"(d[44]), "+f"(d[45]), "+f"(d[46]), "+f"(d[47]), "+f"(d[48]), "+f"(d[49]), "+f"(d[50]), "+f"(d[51]), "+f"(d[52]), "+f"(d[53]), "+f"(d[54]), "+f"(d[55]), "+f"(d[56]), "+f"(d[57]), "+f"(d[58]), "+f"(d[59]), "+f"(d[60]), "+f"(d[61]), "+f"(d[62]), "+f"(d[63]), "+f"(d[64]), "+f"(d[65]), "+f"(d[66]), "+f"(d[67]), "+f"(d[68]), "+f"(d[69]), "+f"(d[70]), "+f"(d[71]), "+f"(d[72]), "+f"(d[73]), "+f"(d[74]), "+f"(d[75]), "+f"(d[76]), "+f"(d[77]), "+f"(d[78]), "+f"(d[79]), "+f"(d[80]), "+f"(d[81]), "+f"(d[82]), "+f"(d[83]), "+f"(d[84]), "+f"(d[85]), "+f"(d[86]), "+f"(d[87]), "+f"(d[88]), "+f"(d[89]), "+f"(d[90]), "+f"(d[91]), "+f"(d[92]), "+f"(d[93]), "+f"(d[94]), "+f"(d[95]), "+f"(d[96]), "+f"(d[97]), "+f"(d[98]), "+f"(d[99]), "+f"(d[100]), "+f"(d[101]), "+f"(d[102]), "+f"(d[103]), "+f"(d[104]), "+f"(d[105]), "+f"(d[106]), "+f"(d[107]), "+f"(d[108]), "+f"(d[109]), "+f"(d[110]), "+f"(d[111]), "+f"(d[112]), "+f"(d[113]), "+f"(d[114]), "+f"(d[115]), "+f"(d[116]), "+f"(d[117]), "+f"(d[118]), "+f"(d[119])
    : "l"(da), "l"(db), "r"(scale_d));
}
__device__ __forceinline__ void wgmma_n256_rs(float (&d)[128], uint32_t a0, uint32_t a1, uint32_t a2, uint32_t a3, uint64_t db, int scale_d) {
  asm volatile("{\n.reg .pred p;\nsetp.ne.b32 p, %133, 0;\n"
    "wgmma.mma_async.sync.aligned.m64n256k16.f32.bf16.bf16 "
    "{%0, %1, %2, %3, %4, %5, %6, %7, %8, %9, %10, %11, %12, %13, %14, %15, %16, %17, %18, %19, %20, %21, %22, %23, %24, %25, %26, %27, %28, %29, %30, %31, "
    "%32, %33, %34, %35, %36, %37, %38, %39, %40, %41, %42, %43, %44, %45, %46, %47, %48, %49, %50, %51, %52, %53, %54, %55, %56, %57, %58, %59, %60, %61, %62, %63, "
    "%64, %65, %66, %67, %68, %69, %70, %71, %72, %73, %74, %75, %76, %77, %78, %79, %80, %81, %82, %83, %84, %85, %86, %87, %88, %89, %90, %91, %92, %93, %94, %95, "
    "%96, %97, %98, %99, %100, %101, %102, %103, %104, %105, %106, %107, %108, %109, %110, %111, %112, %113, %114, %115, %116, %117, %118, %119, %120, %121, %122, %123, %124, %125, %126, %127}, "
    "{%128, %129, %130, %131}, %132, p, 1, 1, 0;\n}\n"
    : "+f"(d[0]), "+f"(d[1]), "+f"(d[2]), "+f"(d[3]), "+f"(d[4]), "+f"(d[5]), "+f"(d[6]), "+f"(d[7]),
      "+f"(d[8]), "+f"(d[9]), "+f"(d[10]), "+f"(d[11]), "+f"(d[12]), "+f"(d[13]), "+f"(d[14]), "+f"(d[15]),
      "+f"(d[16]), "+f"(d[17]), "+f"(d[18]), "+f"(d[19]), "+f"(d[20]), "+f"(d[21]), "+f"(d[22]), "+f"(d[23]),
      "+f"(d[24]), "+f"(d[25]), "+f"(d[26]), "+f"(d[27]), "+f"(d[28]), "+f"(d[29]), "+f"(d[30]), "+f"(d[31]),
      "+f"(d[32]), "+f"(d[33]), "+f"(d[34]), "+f"(d[35]), "+f"(d[36]), "+f"(d[37]), "+f"(d[38]), "+f"(d[39]),
      "+f"(d[40]), "+f"(d[41]), "+f"(d[42]), "+f"(d[43]), "+f"(d[44]), "+f"(d[45]), "+f"(d[46]), "+f"(d[47]),
      "+f"(d[48]), "+f"(d[49]), "+f"(d[50]), "+f"(d[51]), "+f"(d[52]), "+f"(d[53]), "+f"(d[54]), "+f"(d[55]),
      "+f"(d[56]), "+f"(d[57]), "+f"(d[58]), "+f"(d[59]), "+f"(d[60]), "+f"(d[61]), "+f"(d[62]), "+f"(d[63]),
      "+f"(d[64]), "+f"(d[65]), "+f"(d[66]), "+f"(d[67]), "+f"(d[68]), "+f"(d[69]), "+f"(d[70]), "+f"(d[71]),
      "+f"(d[72]), "+f"(d[73]), "+f"(d[74]), "+f"(d[75]), "+f"(d[76]), "+f"(d[77]), "+f"(d[78]), "+f"(d[79]),
      "+f"(d[80]), "+f"(d[81]), "+f"(d[82]), "+f"(d[83]), "+f"(d[84]), "+f"(d[85]), "+f"(d[86]), "+f"(d[87]),
      "+f"(d[88]), "+f"(d[89]), "+f"(d[90]), "+f"(d[91]), "+f"(d[92]), "+f"(d[93]), "+f"(d[94]), "+f"(d[95]),
      "+f"(d[96]), "+f"(d[97]), "+f"(d[98]), "+f"(d[99]), "+f"(d[100]), "+f"(d[101]), "+f"(d[102]), "+f"(d[103]),
      "+f"(d[104]), "+f"(d[105]), "+f"(d[106]), "+f"(d[107]), "+f"(d[108]), "+f"(d[109]), "+f"(d[110]), "+f"(d[111]),
      "+f"(d[112]), "+f"(d[113]), "+f"(d[114]), "+f"(d[115]), "+f"(d[116]), "+f"(d[117]), "+f"(d[118]), "+f"(d[119]),
      "+f"(d[120]), "+f"(d[121]), "+f"(d[122]), "+f"(d[123]), "+f"(d[124]), "+f"(d[125]), "+f"(d[126]), "+f"(d[127])
    : "r"(a0), "r"(a1), "r"(a2), "r"(a3), "l"(db), "r"(scale_d));
}
__device__ __forceinline__ void wgmma_n128(float (&d)[64], uint64_t da, uint64_t db, int scale_d = 1) {
  asm volatile("{\n.reg .pred p;\nsetp.ne.b32 p, %66, 0;\n"
    "wgmma.mma_async.sync.aligned.m64n128k16.f32.bf16.bf16 "
    "{%0, %1, %2, %3, %4, %5, %6, %7, %8, %9, %10, %11, %12, %13, %14, %15, %16, %17, %18, %19, %20, %21, %22, %23, %24, %25, %26, %27, %28, %29, %30, %31, %32, %33, %34, %35, %36, %37, %38, %39, %40, %41, %42, %43, %44, %45, %46, %47, %48, %49, %50, %51, %52, %53, %54, %55, %56, %57, %58, %59, %60, %61, %62, %63}, "
    "%64, %65, p, 1, 1, 0, 0;\n}\n"
    : "+f"(d[0]), "+f"(d[1]), "+f"(d[2]), "+f"(d[3]), "+f"(d[4]), "+f"(d[5]), "+f"(d[6]), "+f"(d[7]), "+f"(d[8]), "+f"(d[9]), "+f"(d[10]), "+f"(d[11]), "+f"(d[12]), "+f"(d[13]), "+f"(d[14]), "+f"(d[15]), "+f"(d[16]), "+f"(d[17]), "+f"(d[18]), "+f"(d[19]), "+f"(d[20]), "+f"(d[21]), "+f"(d[22]), "+f"(d[23]), "+f"(d[24]), "+f"(d[25]), "+f"(d[26]), "+f"(d[27]), "+f"(d[28]), "+f"(d[29]), "+f"(d[30]), "+f"(d[31]), "+f"(d[32]), "+f"(d[33]), "+f"(d[34]), "+f"(d[35]), "+f"(d[36]), "+f"(d[37]), "+f"(d[38]), "+f"(d[39]), "+f"(d[40]), "+f"(d[41]), "+f"(d[42]), "+f"(d[43]), "+f"(d[44]), "+f"(d[45]), "+f"(d[46]), "+f"(d[47]), "+f"(d[48]), "+f"(d[49]), "+f"(d[50]), "+f"(d[51]), "+f"(d[52]), "+f"(d[53]), "+f"(d[54]), "+f"(d[55]), "+f"(d[56]), "+f"(d[57]), "+f"(d[58]), "+f"(d[59]), "+f"(d[60]), "+f"(d[61]), "+f"(d[62]), "+f"(d[63])
    : "l"(da), "l"(db), "r"(scale_d));
}
__device__ __forceinline__ void fence_acc64(float (&d)[64]) {
#pragma unroll
  for (int i = 0; i < 64; i++) asm volatile("" : "+f"(d[i]) :: "memory");
}
template<int N> __device__ __forceinline__ void fence_acc(float (&d)[N]) {
#pragma unroll
  for (int i = 0; i < N; i++) asm volatile("" : "+f"(d[i]) :: "memory");
}

template<int N, int I = 0, class F> __device__ __forceinline__ void static_for(F&& f) {
  if constexpr (I < N) { f(std::integral_constant<int, I>()); static_for<N, I + 1>(f); }
}

__device__ __forceinline__ void ldsm_x4_t(uint32_t addr, uint32_t& a, uint32_t& b, uint32_t& c, uint32_t& d) {
  asm volatile("ldmatrix.sync.aligned.m8n8.x4.trans.shared.b16 {%0, %1, %2, %3}, [%4];" : "=r"(a), "=r"(b), "=r"(c), "=r"(d) : "r"(addr));
}
__device__ __forceinline__ void sts128(uint32_t addr, uint32_t a, uint32_t b, uint32_t c, uint32_t d) {
  asm volatile("st.shared.v4.b32 [%0], {%1, %2, %3, %4};" :: "r"(addr), "r"(a), "r"(b), "r"(c), "r"(d));
}
__device__ __forceinline__ void mma16816(float (&c)[4], uint32_t a0, uint32_t a1, uint32_t a2, uint32_t a3, uint32_t b0, uint32_t b1) {
  asm volatile("mma.sync.aligned.m16n8k16.row.col.f32.bf16.bf16.f32 {%0, %1, %2, %3}, {%4, %5, %6, %7}, {%8, %9}, {%0, %1, %2, %3};"
      : "+f"(c[0]), "+f"(c[1]), "+f"(c[2]), "+f"(c[3]) : "r"(a0), "r"(a1), "r"(a2), "r"(a3), "r"(b0), "r"(b1));
}
__device__ __forceinline__ void mma1688(float (&c)[4], uint32_t a0, uint32_t a1, uint32_t b0) {
  asm volatile("mma.sync.aligned.m16n8k8.row.col.f32.bf16.bf16.f32 {%0, %1, %2, %3}, {%4, %5}, {%6}, {%0, %1, %2, %3};"
      : "+f"(c[0]), "+f"(c[1]), "+f"(c[2]), "+f"(c[3]) : "r"(a0), "r"(a1), "r"(b0));
}
__device__ __forceinline__ void pin(uint32_t& v) { asm volatile("shfl.sync.bfly.b32 %0, %0, 0, 0x1f, 0xffffffff;" : "+r"(v)); }
template<class T> __device__ __forceinline__ void pin(T*& v) {
  uint32_t lo = (uint32_t)(uint64_t)v, hi = (uint32_t)((uint64_t)v >> 32);
  pin(lo); pin(hi);
  v = (T*)(((uint64_t)hi << 32) | lo);
}
__device__ __forceinline__ float sel4(int q, float a, float b, float c, float d) {
  float r;
  asm("{\n.reg .pred p, o;\n.reg .f32 x, y;\n.reg .b32 t;\nand.b32 t, %1, 1;\nsetp.ne.b32 p, t, 0;\nsetp.gt.s32 o, %1, 1;\n"
      "selp.f32 x, %3, %2, p;\nselp.f32 y, %5, %4, p;\nselp.f32 %0, y, x, o;\n}\n" : "=f"(r) : "r"(q), "f"(a), "f"(b), "f"(c), "f"(d));
  return r;
}
__device__ __forceinline__ uint32_t bfma2(uint32_t a, uint32_t b, uint32_t c) { uint32_t r; asm("fma.rn.bf16x2 %0, %1, %2, %3;" : "=r"(r) : "r"(a), "r"(b), "r"(c)); return r; }
__device__ __forceinline__ void tma_load_5d(uint32_t dst, const CUtensorMap* tm, uint32_t bar, int c0) {
  asm volatile("cp.async.bulk.tensor.5d.shared::cluster.global.mbarrier::complete_tx::bytes [%0], [%1, {%3, %4, %4, %4, %4}], [%2];"
    :: "r"(dst), "l"(tm), "r"(bar), "r"(c0), "r"(0) : "memory");
}
__device__ __forceinline__ void tma_store_5d(const CUtensorMap* tm, uint32_t src, int c0, int c3, int c4) {
  asm volatile("cp.async.bulk.tensor.5d.global.shared::cta.bulk_group [%0, {%2, %3, %3, %4, %5}], [%1];" :: "l"(tm), "r"(src), "r"(c0), "r"(0), "r"(c3), "r"(c4) : "memory");
}
__device__ __forceinline__ float rcp_fast(float x) { float r; asm("rcp.approx.ftz.f32 %0, %1;" : "=f"(r) : "f"(x)); return r; }
__device__ __forceinline__ float sigmoid_fast(float x) { float e; asm("ex2.approx.ftz.f32 %0, %1;" : "=f"(e) : "f"(x * -1.4426950408889634f)); return rcp_fast(1.f + e); }
__device__ __forceinline__ float sqrt_fast(float x) { float r; asm("sqrt.approx.ftz.f32 %0, %1;" : "=f"(r) : "f"(x)); return r; }
__device__ __forceinline__ float ln_sd(float var) { return bf16r(sqrt_fast(bf16r(bf16r(fmaxf(var, 0.f)) + 1e-5f))); }
__device__ __forceinline__ uint32_t norm2(uint32_t h, uint32_t neg_mean2, float inv_sd) {
  const uint32_t d = badd2(h, neg_mean2);
  return pack_bf16(bf_lo(d) * inv_sd, bf_hi(d) * inv_sd);
}
template<int N> __device__ __forceinline__ void delay_clk() {
  if constexpr (N > 0) { const uint32_t t0 = clock(); while ((uint32_t)clock() - t0 < N) {} }
}
__device__ __forceinline__ void put_xstat(uint32_t rs, uint32_t exb, int col, uint32_t mean_rstd, int m) {
  smem_at<uint16_t>(rs + ((col & 7) >> 1) * 144 + (col >> 3) * 4 + (col & 1) * 2) = (uint16_t)(mean_rstd ^ (m << 15));
  const uint32_t nm = (mean_rstd >> 16) ^ 0x8000u;
  smem_at<uint4>(exb + (col >> 3) * 256 + (col & 7) * 16) = make_uint4(nm | (nm << 16), nm, 0, 0);
  smem_at<uint4>(exb + (col >> 3) * 256 + 128 + (col & 7) * 16) = make_uint4(0, 0, 0, 0);
}
__device__ __forceinline__ void put_dsum(uint32_t exa, int e, float c) {
  const float hi = bf16r(c), mid = bf16r(c - hi), lo = bf16r((c - hi) - mid);
  smem_at<uint4>(exa + (e >> 3) * 256 + (e & 7) * 16) = make_uint4((__float_as_uint(hi) >> 16) | (__float_as_uint(mid) & 0xFFFF0000u), __float_as_uint(lo) >> 16, 0, 0);
  smem_at<uint4>(exa + (e >> 3) * 256 + 128 + (e & 7) * 16) = make_uint4(0, 0, 0, 0);
}
__host__ __device__ constexpr int min_c(int a, int b) { return a < b ? a : b; }
template<int V> using IC = std::integral_constant<int, V>;

#define CT(slot) do {} while (0)
#define PT(slot) do {} while (0)

template<int MAP>
__global__ void __cluster_dims__(2, 1, 1) __launch_bounds__(384, 1)
fnet_moe_kernel(const __grid_constant__ Params p) {
  constexpr int NX = MAP == 0 ? NX0 : 256;
  constexpr int G1_BYTES = A_BYTES + NX * 128;
  uint32_t sb;
  asm volatile("mov.u32 %0, %1;" : "=r"(sb) : "r"(smem_u32(smem_raw)));
  const int m = blockIdx.x & 1;
  int tau, eps;
  bool helper = false;
  if (MAP == 0) {
    uint32_t smid;
    asm volatile("mov.u32 %0, %%smid;" : "=r"(smid));
    const int c = smid >> 1, e7 = ((c - 32) * 37) >> 8;
    helper = c == 60 || c == 61;
    tau = c < 32 ? (c & 7) : (c < 60 ? c - 31 - 7 * e7 : 0);
    eps = c < 32 ? (c >> 3) : (c < 60 ? 4 + e7 : c - 58);
  } else {
    tau = (blockIdx.x >> 1) & 7; eps = blockIdx.x >> 4;
  }
  const int cid = tau * 16 + eps * 2 + m;
  const bool moe = tau > 0;
  auto BAR = [&](int i) { return sb + OFF_BAR + 8 * i; };
  const CUtensorMap* tmD = m ? &p.tmD1 : &p.tmD0;
  const uint64_t pol_ef = policy_evict_first();
#define LOAD_STREAM(d, tm, bar, c0, c1) tma_load_2d_hint(d, tm, bar, c0, c1, pol_ef)
  auto helper_load = [&](int k) {
    const uint32_t sa = sb + slot_of(k) * ST_BYTES, bar = BAR(B_FULL + slot_of(k));
    const CUtensorMap* tm = eps == 3 ? &p.tmD1 : &p.tmD0;
    tma_load_5d(sa, &p.tmXh, bar, (k & 15) * 64);
    tma_load_2d(sa + A_BYTES, tm, bar, (k & 15) * 64, m * 512 + (k >> 4) * 256);
    tma_load_2d(sa + A_BYTES + 16384, tm, bar, (k & 15) * 64, m * 512 + (k >> 4) * 256 + 128);
  };
  if (threadIdx.x < 32 && elect_one()) {
    mbar_init(BAR(B_FULL), 1);
    asm volatile("fence.mbarrier_init.release.cluster;" ::: "memory");
    if (!helper) {
      tma_load_2d(sb + A_BYTES, &p.tmX, BAR(B_FULL), 0, tau * 256);
      tma_load_2d(sb, tmD, BAR(B_FULL), 0, eps * 128);
    }
    PT(52);
#pragma unroll
    for (int k = 1; k < 4; k++) mbar_init(BAR(B_FULL + k), 1);
    asm volatile("fence.mbarrier_init.release.cluster;" ::: "memory");
#pragma unroll
    for (int k = 0; k < 4; k++) mbar_expect_tx(BAR(B_FULL + k), helper ? ST_BYTES : G1_BYTES);
    if (!helper) {
#pragma unroll
      for (int k = 1; k < 4; k++) {
        tma_load_2d(sb + k * ST_BYTES + A_BYTES, &p.tmX, BAR(B_FULL + k), k * 64, tau * 256);
        LOAD_STREAM(sb + k * ST_BYTES, tmD, BAR(B_FULL + k), k * 64, eps * 128);
      }
    } else {
#pragma unroll 1
      for (int k = 0; k < 4; k++) helper_load(k);
    }
    PT(0);
  }
  __syncwarp();
  const int warp = __shfl_sync(0xffffffffu, threadIdx.x >> 5, 0);
  if (warp == 8) {
    if (elect_one()) {
#pragma unroll
      for (int b = B_EMPTY; b < B_COUNT; b++)
        mbar_init(BAR(b), b < B_EPI ? 2 : (b == B_EPI || b == B_EPI0B) ? 4 : (b < B_STD || b == B_OUT) ? 8 : (b == B_STAT || b == B_XS) ? 3 : 1);
      asm volatile("fence.mbarrier_init.release.cluster;" ::: "memory");
      mbar_expect_tx(BAR(B_XCH), 32768);
      SM_(uint32_t, OFF_SEEN) = 0;
    }
  }
  __syncthreads();

  if (warp >= 8) {
    reg_dec<REG_P>();
    asm volatile("barrier.cluster.arrive.relaxed.aligned;" ::: "memory");
    const int abrow = m * 1024 + eps * 128;
    const int f0 = (cid - 16) * 32;
    const CUtensorMap* tmWM = m ? &p.tmWM1 : &p.tmWM0;
    auto side_first = [&](int k) {
      if (NX < 256 && k == MINI_LOAD_K) {
        static_assert(NX == 256 || (mr_k(NREG_H) == MINI_LOAD_K && (NREG_H & 1) == 1), "second half of the staging buffer must be free");
        mbar_wait(BAR(B_STD + 3), 0);
        uint32_t n = 0;
        while (!((*(volatile uint32_t*)&SM_(uint32_t, OFF_SEEN) >> (4 * tau + 1)) & 1) && ++n < SPIN_LIMIT * 16) {}
        if (elect_one()) {
          mbar_expect_tx(BAR(B_A20), 12288);
          tma_load_2d(sb + OFF_MINI, &p.tmAbM, BAR(B_A20), tau * 256 + 240, abrow);
          LOAD_STREAM(sb + OFF_MINI + 4096, tmWM, BAR(B_A20), tau * 256 + 240, tau * 256 + m * 128);
          LOAD_STREAM(sb + OFF_MINI + 8192, tmWM, BAR(B_A20), tau * 256 + 240, tau * 256 + (1 - m) * 128);
        }
      }
    };
    auto side = [&](int k) {
      if (NX < 256 && k == MINI_PF_K && elect_one()) tma_prefetch_2d(tmWM, tau * 256 + 240, tau * 256 + (eps & 1) * 128);
      if (!moe) return;
      const int i = k - MR_K0, r6 = i / MR_P, u = i - MR_P * r6, h = 2 * r6 + (u >> 1);
      if (i >= 0 && u < 4 && h < NREG_H) {
        if (h < 2) mbar_wait(BAR(B_STD + 2 + h), 0);
        if (elect_one()) {
          if (!(u & 1)) mbar_expect_tx(BAR(B_MR + (h & 1)), 16384);
          LOAD_STREAM(sb + OFF_XCH + u * 8192, (u & 1) ? &p.tmU : &p.tmG, BAR(B_MR + (h & 1)), f0, h * 128);
        }
      }
      if (k >= 46 && elect_one()) {
        static_assert(mr_k(NREG_H + 1) <= 47 && MINI_K + 4 <= 46, "staging buffer must be free");
        LOAD_STREAM(sb + round_off(NREG_H + k - 46), &p.tmG, BAR(B_GU), f0, (NREG_H + k - 46) * 128);
        LOAD_STREAM(sb + round_off(NREG_H + k - 46) + 8192, &p.tmU, BAR(B_GU), f0, (NREG_H + k - 46) * 128);
      }
      if (k >= PF_K1 && !(k & 1) && elect_one()) {
        const int j = PF_N0 + ((k - PF_K1) >> 1);
        if (j < 8) tma_prefetch_2d(m ? &p.tmU : &p.tmG, f0, j * 128);
        else if (j < 12) asm volatile("cp.async.bulk.prefetch.L2.global [%0], %1;" :: "l"(p.wdown + (size_t)f0 * 1024 + (j - 8) * 8192), "r"(16384) : "memory");
      }
    };
    if (MAP == 0 && helper) {
      if (warp == 8) {
#pragma unroll 1
        for (int k = 4; k < 32; k++) {
          mbar_wait(BAR(B_EMPTY + slot_of(k)), (use_of(k) & 1) ^ 1);
          if (elect_one()) { mbar_expect_tx(BAR(B_FULL + slot_of(k)), ST_BYTES); helper_load(k); }
        }
      } else {
        const int i0 = threadIdx.x - 288, lane = threadIdx.x & 31, col0 = (eps - 2) * 8 + m * 4;
        __nanosleep(HELPER_NS);
        const uint32_t tag = ld_relaxed32(&p.s->epoch) + 1;
        if (i0 < 8) pkt_st128(&p.s->hflag[col0 * 2 + i0], 0, 0, 0, 0);
        SM_(uint32_t, OFF_TAG) = tag;
#pragma unroll 1
        for (int j0 = i0; j0 < 768; j0 += 384) {
          uint2 v[4]; uint32_t n = 0;
          while (true) {
#pragma unroll
            for (int z = 0; z < 4; z++) {
              const int j = j0 + 96 * z;
              v[z] = pkt_ld64(p.s->xstat + (j < 128 ? 256 * (j >> 4) + 240 + 2 * (j & 6) + ((j >> 2) & 2) + (j & 1)
                                          : j < 640 ? 2048 + col0 * 128 + j - 128 : (j - 640) * 16));
            }
            if (__all_sync(0xffffffffu, v[0].y == tag && v[1].y == tag && v[2].y == tag && v[3].y == tag) || ++n > SPIN_LIMIT) break;
            __nanosleep(300);
          }
#pragma unroll
          for (int z = 0; z < 4; z++) {
            const int j = j0 + 96 * z;
            if (j < 128) put_xstat(sb + OFF_RS, sb + OFF_XCH + 16384, j, v[z].x, eps - 2);
            else if (j < 640) put_dsum(sb + OFF_XCH, j - 128, __uint_as_float(v[z].x));
          }
        }
        fence_async_smem();
        __syncwarp();
        if (lane == 0) mbar_arrive(BAR(B_STAT));
      }
    } else if (warp == 8) {
      const CUtensorMap* tmW = m ? &p.tmW1 : &p.tmW0;
      const int tA = tau * 256 + m * 128, tB = tau * 256 + (1 - m) * 128;
      auto wait_slot = [&](int k) {
        mbar_wait(BAR(B_EMPTY + slot_of(k)), (use_of(k) & 1) ^ 1);
        PT(64 + k);
      };
#pragma unroll 1
      for (int k = 4; k < 24; k++) {
        const int s = slot_of(k);
        const uint32_t sa = sb + s * ST_BYTES, sbb = sa + A_BYTES;
        const int kb = kblock(tau, k - 16);
        wait_slot(k);
        if (elect_one()) {
          mbar_expect_tx(BAR(B_FULL + s), k < 16 ? G1_BYTES : (k >> 1) == 9 ? B_BYTES : k == 20 ? ST_BYTES - 8192 : ST_BYTES);
          if (k < 16) {
            LOAD_STREAM(sa, tmD, BAR(B_FULL + s), k * 64, eps * 128);
            tma_load_2d(sbb, &p.tmX, BAR(B_FULL + s), k * 64, tau * 256);
          } else {
            LOAD_STREAM(sbb, tmW, BAR(B_FULL + s), kb * 64, tA);
            LOAD_STREAM(sbb + 16384, tmW, BAR(B_FULL + s), kb * 64, tB);
            if (k < 18) {
              tma_load_2d(sa, &p.tmXr, BAR(B_FULL + s), eps * 128, tA + s * 64);
              tma_load_2d(sa + 8192, &p.tmXr, BAR(B_FULL + s), eps * 128 + 64, tA + s * 64);
            }
          }
          if (k == PUB_K1) mbar_arrive(BAR(B_LATE));
          if (k >= WPF_K0 && k < WPF_K0 + WPF_N && (eps >> 1) == ((k - WPF_K0) & 3))
            tma_prefetch_2d(tmW, kblock(tau, k - WPF_K0) * 64, tau * 256 + (eps & 1) * 128);
          if (moe && k >= PF_K0 && k < PF_K0 + 2 * PF_N0 && !(k & 1)) tma_prefetch_2d(m ? &p.tmU : &p.tmG, f0, (k - PF_K0) * 64);
        }
      }
      uint32_t seen = 0;
#pragma unroll 1
      for (int k = 24; k < 48; k++) {
        const int s = slot_of(k);
        const uint32_t sa = sb + s * ST_BYTES, sbb = sa + A_BYTES;
        const int kb = kblock(tau, k - 16);
        const uint32_t need = (1u << kb) | ((kb & 3) == 3 ? 2u << (4 * tau) : 0u);
        wait_slot(k);
        side_first(k);
        if (elect_one()) {
          mbar_expect_tx(BAR(B_FULL + s), ST_BYTES);
          LOAD_STREAM(sbb, tmW, BAR(B_FULL + s), kb * 64, tA);
          LOAD_STREAM(sbb + 16384, tmW, BAR(B_FULL + s), kb * 64, tB);
        }
        uint32_t n = 0;
        while ((seen & need) != need && ++n < SPIN_LIMIT * 16) seen = *(volatile uint32_t*)&SM_(uint32_t, OFF_SEEN);
        if (elect_one()) tma_load_2d(sa, &p.tmAbL, BAR(B_FULL + s), kb * 64, abrow);
        side(k);
      }
      if (moe) {
        mbar_wait(BAR(B_EMPTY + 0), 1);
        if (elect_one()) { mbar_expect_tx(BAR(B_GU), (8 - NREG_H) * 16384); mbar_expect_tx(BAR(B_DN), 65536); }
#pragma unroll 1
        for (int i = 0; i < 10 - NREG_H; i++) {
          if (i == 3) mbar_wait(BAR(B_EMPTY + 1), 1);
          if (i == 4) {
            mbar_wait(BAR(B_EMPTY + 2), 1);
            mbar_wait(BAR(B_XCH), 0);
            PT(53);
          }
          const uint32_t dst = sb + late_off(i);
          if (elect_one()) {
            if (i < 6 - NREG_H) {
              LOAD_STREAM(dst, &p.tmG, BAR(B_GU), f0, (NREG_H + 2 + i) * 128);
              LOAD_STREAM(dst + 8192, &p.tmU, BAR(B_GU), f0, (NREG_H + 2 + i) * 128);
            } else {
#pragma unroll
              for (int b = 0; b < 4; b++) LOAD_STREAM(dst + b * 4096, &p.tmDn, BAR(B_DN), (4 * (i - 6 + NREG_H) + b) * 64, f0);
            }
          }
          const long long t0 = clock64();
          while (i < 9 - NREG_H && clock64() - t0 < MOE_PACE_CLK) {}
        }
      }
      const int lane = threadIdx.x & 31;
      mbar_wait(BAR(B_OUT), 0);
      const uint32_t km = SM_(uint32_t, OFF_WKEY + (lane & 7) * 8);
      const uint32_t bk = __reduce_max_sync(0xffffffffu, km);
      const int ww = __ffs(__ballot_sync(0xffffffffu, km == bk)) - 1;
#pragma unroll 1
      for (int i = 1; i <= 8; i++) {
        const int W = (ww + i) & 7;
        if (i == 8) {
          mbar_wait(BAR(B_XS), 0);
          if (SM_(uint32_t, OFF_KV) == bk) {
#pragma unroll 2
            for (int j = lane; j < 256; j += 32) {
              const int rho = j >> 4, row = (tau * 2 + m) * 128 + 32 * (W >> 1) + 8 * ((rho & 7) >> 1) + 4 * (W & 1) + 2 * (rho >> 3) + (rho & 1);
              const uint4 v = lds128_v(sb + OFF_OUT + (j & 8) * 2048 + (16 * W + rho) * 128 + (((j ^ rho) & 7) << 4));
              if (row != 0xFFFF - (int)(bk & 0xFFFFu))
                asm volatile("st.global.v4.b32 [%0], {%1, %2, %3, %4};" :: "l"(p.out + (size_t)row * 1024 + eps * 128 + (j & 15) * 8), "r"(v.x), "r"(v.y), "r"(v.z), "r"(v.w));
            }
            break;
          }
        }
        if (lane == 0) {
          tma_store_5d(&p.tmOut, sb + OFF_OUT + W * 2048, eps * 128, 2 * (W & 1), tau * 8 + m * 4 + (W >> 1));
          tma_store_5d(&p.tmOut, sb + OFF_OUT + 16384 + W * 2048, eps * 128 + 64, 2 * (W & 1), tau * 8 + m * 4 + (W >> 1));
        }
        const long long t0 = clock64();
        while (i < 7 && clock64() - t0 < OUT_PACE_CLK) {}
      }
      if (lane == 0) { bulk_commit(); bulk_wait_all(); }
      PT(22);
    } else {
      const int a = warp - 9;
      const int lane = threadIdx.x & 31;
      auto stage = [&](const bf16* src, int g) {
        if (elect_one()) {
          mbar_expect_tx(BAR(B_AUX + g), 16384);
          bulk_load(sb + OFF_XCH + g * 16384, src + g * 8192, 16384, BAR(B_AUX + g));
        }
      };
      mbar_wait(BAR(B_FULL + AUX_AFTER), 0);
      if (a == 0) PT(1);
      if (a < 2) stage(p.x + (size_t)cid * 16 * 1024, a);
      const uint32_t tag = ld_relaxed32(&p.s->epoch) + 1;
      if (a == 2 && lane < 16) asm volatile("prefetch.global.L2 [%0];" :: "l"(p.wr + lane * 64));
#pragma unroll 1
      for (int it = 0; it < 4; it++) {
        const int g = it & 1;
        mbar_wait(BAR(B_AUX + g), it >> 1);
        if (a == 0) PT(2 + it);
        const uint32_t ad = sb + OFF_XCH + g * 16384 + (lane >> 2) * 2048;
        float s0 = 0.f, s1 = 0.f, q0 = 0.f, q1 = 0.f;
        auto row = [&](auto sq) {
#pragma unroll
          for (int i = 0; i < 11; i++) {
            if (i == 10 && a == 2) break;
            const uint4 v = lds128_v(ad + (((a * 44 + 4 * i + lane) & 127) << 4));
            const uint32_t ww[4] = {v.x, v.y, v.z, v.w};
#pragma unroll
            for (int z = 0; z < 4; z++) {
              const float d0 = bf_lo(ww[z]), d1 = bf_hi(ww[z]);
              s0 += d0; s1 += d1;
              if (decltype(sq)::value) { q0 = fmaf(d0, d0, q0); q1 = fmaf(d1, d1, q1); }
            }
          }
        };
        if (it < 2) row(IC<1>()); else row(IC<0>());
        s0 += s1; q0 += q1;
#pragma unroll
        for (int o = 1; o < 4; o <<= 1) { s0 += __shfl_xor_sync(0xffffffffu, s0, o); q0 += __shfl_xor_sync(0xffffffffu, q0, o); }
        if ((lane & 3) == 0) SM_(float2, OFF_PUB + a * 256 + it * 64 + (lane >> 2) * 8) = make_float2(s0, q0);
        if (it != 2) bar_sync(NB_AUX, 96);
        if (it < 2 && a == 2) stage(cid < 64 ? p.Dre + (size_t)cid * 16 * 1024 : p.Dim + (size_t)(cid - 64) * 16 * 1024, g);
      }
      if (a == 1) {
        const float2 v0 = SM_(float2, OFF_PUB + lane * 8), v1 = SM_(float2, OFF_PUB + 256 + lane * 8), v2 = SM_(float2, OFF_PUB + 512 + lane * 8);
        const float s = v0.x + v1.x + v2.x, mean = s * (1.f / 1024.f);
        const float rs = rcp_fast(ln_sd((v0.y + v1.y + v2.y) * (1.f / 1024.f) - mean * mean));
        pkt_st64((lane < 16 ? p.s->xstat : p.s->dsum) + cid * 16 + (lane & 15), lane < 16 ? pack_bf16(rs, mean) : __float_as_uint(s), tag);
        PT(6);
      }
      if (a == 2) {
        float s = 0.f;
#pragma unroll
        for (int q = 0; q < 4; q++) {
          const uint4 v = ldg_nc128(p.wr + (q * 32 + lane) * 8);
          s += ((bf_lo(v.x) + bf_hi(v.x)) + (bf_lo(v.y) + bf_hi(v.y))) + ((bf_lo(v.z) + bf_hi(v.z)) + (bf_lo(v.w) + bf_hi(v.w)));
          const int ch = q * 32 + lane - eps * 16;
          if (ch >= 0 && ch < 16) {
            SM_(uint32_t, OFF_WR + ch * 4) = v.x; SM_(uint32_t, OFF_WR + 80 + ch * 4) = v.y;
            SM_(uint32_t, OFF_WR + 160 + ch * 4) = v.z; SM_(uint32_t, OFF_WR + 240 + ch * 4) = v.w;
          }
        }
        s = warp_sum(s);
        if (lane == 0) { SM_(float, OFF_WSUM) = s; SM_(uint32_t, OFF_TAG) = tag; }
      }
      if (a < 2) __nanosleep(GATHER_NS);
      {
        const int i0 = a * 32 + lane;
        uint2 v[3], c0, c1; uint32_t n = 0;
        const uint2* dp = &p.s->dsum[abrow];
        while (true) {
#pragma unroll
          for (int q = 0; q < 3; q++) v[q] = pkt_ld64(&p.s->xstat[tau * 256 + min(i0 + 96 * q, 255)]);
          c0 = pkt_ld64(dp + i0); c1 = pkt_ld64(dp + min(i0 + 96, 127));
          if (__all_sync(0xffffffffu, v[0].y == tag && v[1].y == tag && v[2].y == tag && c0.y == tag && c1.y == tag) || ++n > SPIN_LIMIT) break;
          __nanosleep(200);
        }
#pragma unroll
        for (int q = 0; q < 3; q++) put_xstat(sb + OFF_RS, sb + OFF_EXB, min(i0 + 96 * q, 255), v[q].x, m);
        put_dsum(sb + OFF_EXA, i0, __uint_as_float(c0.x));
        put_dsum(sb + OFF_EXA, min(i0 + 96, 127), __uint_as_float(c1.x));
        fence_async_smem();
      }
      __syncwarp();
      if (lane == 0) mbar_arrive(BAR(B_STAT));
      if (a == 0) PT(7);
      if (a == 0) {
        const int sg = (lane >> 2) == tau ? sigma_of(tau, 0) : lane >> 2;
        const uint32_t* flg = reinterpret_cast<const uint32_t*>(&p.s->abflag[((eps * 2 + m) * 8 + sg) * 2]) + ((lane >> 2) == tau ? 4 : lane & 3);
        if (NX < 256 && lane == 4 * tau + 1) flg = reinterpret_cast<const uint32_t*>(&p.s->hflag[(m * 8 + eps) * 2]);
        uint32_t seen = 0;
        mbar_wait(BAR(B_STDA), 0);
        PT(49);
#pragma unroll 1
        for (int i = 0; i < 5; i++) {
          const int s = i ? i - 1 : 0, sig = sigma_of(tau, s);
          if (i == 1) mbar_wait(BAR(B_STD + 0), 0);
          uint32_t n = 0;
          while (!((seen >> (4 * (i ? sig : tau))) & 1) && ++n < SPIN_LIMIT) seen = __ballot_sync(0xffffffffu, ld_relaxed32(flg) == tag);
          if (i == 0 || i == 4) mbar_wait(BAR(i ? B_STD + 1 : B_EPI0B), 0);
          if (i != 1) mbar_wait(BAR(B_FULL + s), 0);
          PT(i ? 16 + s : 48);
          if (elect_one()) {
            if (i == 1) mbar_expect_tx(BAR(B_A20), 8192);
            tma_load_2d(sb + (i < 3 ? OFF_XCH + i * 8192 : s * ST_BYTES), i < 2 ? &p.tmAbS : &p.tmAbL, BAR(i == 1 ? B_A20 : B_FULL + s), sig * 256,
                        abrow + (i == 1 ? 64 : 0));
          }
        }
        uint32_t n = 0;
        while (true) {
          asm volatile("fence.proxy.async.global;" ::: "memory");
          *(volatile uint32_t*)&SM_(uint32_t, OFF_SEEN) = seen;
          if (seen == 0xFFFFFFFFu || ++n > SPIN_LIMIT) break;
          seen = __ballot_sync(0xffffffffu, ld_relaxed32(flg) == tag);
          __nanosleep(100);
        }
      } else {
        uint32_t* flag = reinterpret_cast<uint32_t*>(&p.s->abflag[((eps * 2 + m) * 8 + tau) * 2]);
        mbar_wait(BAR(a == 1 ? B_EPI : B_EPI0B), 0);
        if (a == 1) PT(8);
        if (lane == 0) {
          tma_store_2d(&p.tmAbS, sb + chunk_off(0, a - 1), tau * 256, abrow + (a - 1) * 64);
          bulk_commit();
          bulk_wait_all();
        }
        if (a == 2) mbar_wait(BAR(B_STDA), 0);
        if (lane == 0) {
          st_relaxed32(flag + (a == 1 ? 4 : 0), tag);
          mbar_arrive(BAR(a == 1 ? B_STDA : B_STD));
        }
        if (a == 2) PT(12);
        if (a == 1) {
          mbar_wait(BAR(B_EPI + 1), 0);
          mbar_wait(BAR(B_LATE), 0);
          PT(9);
          if (lane == 0) {
            tma_store_2d(&p.tmAbS, sb + chunk_off(1, 0), tau * 256 + 64, abrow);
            tma_store_2d(&p.tmAbS, sb + chunk_off(1, 1), tau * 256 + 64, abrow + 64);
            bulk_commit();
            bulk_wait_all();
            st_relaxed32(flag + 1, tag);
            mbar_arrive(BAR(B_STD + 1));
          }
          PT(13);
        }
        auto copy_out = [&](int c) {
          mbar_wait(BAR(B_EPI + c), 0);
          PT(8 + c);
          bf16* dst = p.s->abT + (size_t)(abrow + (lane >> 3)) * 2048 + tau * 256 + c * 64 + (lane & 7) * 8;
          const uint32_t src = sb + chunk_off(c, 0) + (lane >> 3) * 128 + (((lane & 7) ^ (lane >> 3)) << 4);
          const uint32_t on = c * 64 + (lane & 7) * 8 < NX;
#pragma unroll 4
          for (int i = 0; i < 32; i++) {
            const uint4 v = lds128_v((src ^ ((i & 1) << 6)) + i * 512);
            asm volatile("{\n.reg .pred p;\nsetp.ne.b32 p, %5, 0;\n@p st.global.v4.b32 [%0], {%1, %2, %3, %4};\n}\n"
                         :: "l"(dst + i * 4 * 2048), "r"(v.x), "r"(v.y), "r"(v.z), "r"(v.w), "r"(on));
          }
          __syncwarp();
          if (lane == 0) mbar_arrive(BAR(B_STD + c));
        };
        if (a == 2) {
#pragma unroll 1
          for (int c = 2; c < 4; c++) copy_out(c);
          asm volatile("fence.acq_rel.gpu;" ::: "memory");
          __syncwarp();
          if (lane < 2) st_relaxed32(flag + 2 + lane, tag);
          PT(15);
        }
      }
      {
        mbar_wait(BAR(B_LATE), 1);
        const int grp = tau * 2 + m;
#pragma unroll 1
        for (int i = a; i < 14; i += 3) {
          uint4* dst = i < 8 ? &p.s->ypart[cid * 256 + i * 32 + lane] : i < 12 ? &p.s->hstat[(grp * 8 + eps) * 128 + (i - 8) * 32 + lane]
                     : i == 12 ? &p.s->cand[grp * 256 + eps * 32 + lane] : &p.s->key[(((lane >> 1) & 7) * 16 + grp) * 2 + (lane & 1)];
          if (i < 13 || eps == 0) pkt_st128(dst, 0, 0, 0, 0);
          __nanosleep(200);
        }
        __syncwarp();
        if (lane == 0) mbar_arrive(BAR(B_STAT));
      }
      {
        const uint4* kp = &p.s->key[(tau * 16 + (lane & 15)) * 2];
        const int i0 = a * 32 + lane;
        mbar_wait(BAR(B_KEY), 0);
        if (a == 0) PT(43);
        uint4 kq = pkt_ld128(kp), cv[3] = {};
        uint32_t n = 0, kv;
        int gspec = -1;
        while (true) {
          const bool ok = kq.y == tag && kq.w == tag;
          kv = __reduce_max_sync(0xffffffffu, ok ? kq.x : 0u);
          const int gs = (0xFFFF - (int)(kv & 0xFFFFu)) >> 7;
          const bool cok = gs == gspec && cv[0].y == tag && cv[0].w == tag && cv[1].y == tag && cv[1].w == tag && cv[2].y == tag && cv[2].w == tag;
          if (__all_sync(0xffffffffu, ok && cok) || ++n > SPIN_LIMIT) break;
          if (!ok) kq = pkt_ld128(kp);
          const bool spec = __popc(__ballot_sync(0xffffffffu, ok)) >= 2 * SPEC_MIN;
          if (!cok && spec) {
#pragma unroll
            for (int i = 0; i < 3; i++) cv[i] = pkt_ld128(&p.s->cand[gs * 256 + min(i0 + 96 * i, 255)]);
          }
          if (spec) gspec = gs;
        }
        if (a == 0) PT(45);
        const uint32_t ms = __shfl_sync(0xffffffffu, kq.z, gspec);
        const uint32_t nm = ((ms & 0xFFFFu) ^ 0x8000u) * 0x10001u;
        const float is = rcp_fast(bf_hi(ms));
#pragma unroll
        for (int i = 0; i < 3; i++) {
          const int j = min(i0 + 96 * i, 255);
          SM_(uint2, OFF_XSEL + j * 8) = make_uint2(norm2(cv[i].x, nm, is), norm2(cv[i].z, nm, is));
        }
#pragma unroll
        for (int i = 0; i < 3; i++) SM_(uint2, OFF_HSEL + min(i0 + 96 * i, 255) * 8) = make_uint2(cv[i].x, cv[i].z);
        SM_(uint32_t, OFF_KV) = kv;
        __syncwarp();
        if (lane == 0) mbar_arrive(BAR(B_XS));
      }
    }
    asm volatile("barrier.cluster.wait.aligned;" ::: "memory");
  } else {
    reg_inc<REG_C>();
    const int tid = __shfl_sync(0xffffffffu, threadIdx.x, threadIdx.x & 31), lane = tid & 31;
    const int w = warp >> 2, wi = warp & 3, t = tid & 127;
    const int g = lane >> 2, q = lane & 3;
    const int turn_me = NB_TURN0 + w, turn_other = NB_TURN1 - w;
    auto release = [&](int s) { if (t == 0) mbar_arrive(BAR(B_EMPTY + s)); };
    if (MAP == 0 && helper) {
      asm volatile("barrier.cluster.arrive.relaxed.aligned;" ::: "memory");
      float s0[64], s1[64];
#pragma unroll
      for (int i = 0; i < 64; i++) { s0[i] = 0.f; s1[i] = 0.f; }
      if (w == 1) bar_arrive(NB_TURN0, 256);
      uint32_t o[32][2] = {};
      const int col = (eps - 2) * 8 + m * 4 + w;
      auto put = [&](auto tc, uint32_t buf) {
        constexpr int tl = decltype(tc)::value;
#pragma unroll
        for (int i = 0; i < 4; i++)
          smem_at<uint2>(buf + ((i >> 1) * 64 + wi * 16 + (i & 1) * 8 + g) * 32 + ((q * 8) ^ ((g & 4) << 2))) = make_uint2(o[8 * i + tl][0], o[8 * i + tl][1]);
      };
      auto publish = [&](int c) { if (t == 0) { bulk_wait_all(); st_relaxed32(&p.s->hflag[c * 2], SM_(uint32_t, OFF_TAG)); } };
#pragma unroll 1
      for (int pass = 0; pass < 2; pass++) {
#pragma unroll 1
        for (int k = 16 * pass; k < 16 * pass + 16; k++) {
          const int s = slot_of(k);
          mbar_wait(BAR(B_FULL + s), use_of(k) & 1);
          bar_sync(turn_me, 256);
          const uint64_t da = make_desc(sb + s * ST_BYTES + A_BYTES + w * 16384), db = make_desc(sb + s * ST_BYTES);
          wgmma_fence();
#pragma unroll
          for (int kk = 0; kk < 4; kk++) {
            wgmma_n128(s0, da + kk * 2, db + kk * 2, kk > 0 || (k & 15));
            wgmma_n128(s1, da + 512 + kk * 2, db + kk * 2, kk > 0 || (k & 15));
          }
          wgmma_commit();
          if (k < 31 || w == 0) bar_arrive(turn_other, 256);
          if (pass && !(k & 1)) {
            const uint32_t buf = sb + OFF_XCH + 20480 + w * 4096;
            static_for<8>([&](auto ic) { if (k == 16 + 2 * decltype(ic)::value) put(ic, buf); });
            fence_async_smem();
            bar_sync(NB_WG0 + w, 128);
            if (t == 0) { tma_store_2d(&p.tmAbM, buf, (k - 16) * 128 + 240, col * 128); bulk_commit(); }
          }
          wgmma_wait0();
          release(s);
          if ((k & 1) && t == 0) asm volatile("cp.async.bulk.wait_group.read 0;" ::: "memory");
        }
        if (pass) publish(col);
        mbar_wait(BAR(B_STAT), 0);
        wgmma_fence();
        wgmma_n128(s0, make_desc_noswz(sb + OFF_XCH + pass * 8192 + w * 4096), make_desc_noswz(sb + OFF_XCH + 16384));
        wgmma_n128(s1, make_desc_noswz(sb + OFF_XCH + pass * 8192 + w * 4096 + 2048), make_desc_noswz(sb + OFF_XCH + 16384));
        wgmma_commit();
        uint4 rs[4];
#pragma unroll
        for (int i = 0; i < 4; i++) rs[i] = lds128_v(sb + OFF_RS + q * 144 + i * 16);
        wgmma_wait0();
        fence_acc(s0); fence_acc(s1);
#pragma unroll
        for (int i = 0; i < 32; i++) {
          const int tl = i & 7, hr = (i >> 3) & 1;
          const float* ac = (i >> 4) ? &s1[8 * tl + 2 * hr] : &s0[8 * tl + 2 * hr];
          o[i][0] = bmul2(pack_bf16(ac[0], ac[1]), (tl & 1) ? rs[tl >> 1].z : rs[tl >> 1].x);
          o[i][1] = bmul2(pack_bf16(ac[4], ac[5]), (tl & 1) ? rs[tl >> 1].w : rs[tl >> 1].y);
        }
      }
      static_for<8>([&](auto ic) { put(ic, sb + (w * 8 + decltype(ic)::value) * 4096); });
      fence_async_smem();
      bar_sync(NB_WG0 + w, 128);
      if (t == 0) {
#pragma unroll 1
        for (int i = 0; i < 8; i++) tma_store_2d(&p.tmAbM, sb + (w * 8 + i) * 4096, i * 256 + 240, (col + 2) * 128);
        bulk_commit();
      }
      publish(col + 2);
      asm volatile("barrier.cluster.wait.aligned;" ::: "memory");
      return;
    }
    float acc[128], a1[NX / 2];
#pragma unroll
    for (int i = 0; i < NX / 2; i++) a1[i] = 0.f;
    if (w == 1) bar_arrive(NB_TURN0, 256);
    auto kstep = [&](auto& d, int k, bool first, bool a_in_xch = false, bool mini = false) {
      const int s = slot_of(k);
      mbar_wait(BAR(B_FULL + s), use_of(k) & 1);
      CT(64 + k);
      bar_sync(turn_me, 256);
      const uint64_t da = make_desc(sb + (a_in_xch ? OFF_XCH + s * 16384 : s * ST_BYTES) + w * 8192), db = make_desc(sb + s * ST_BYTES + A_BYTES);
      wgmma_fence();
      wgmma_g1(d, da, db, !first);
#pragma unroll
      for (int kk = 1; kk < 4; kk++) wgmma_g1(d, da + kk * 2, db + kk * 2, 1);
      wgmma_commit();
      if (mini) {
        CT(29);
        mbar_wait(BAR(B_A20), 1);
        CT(30);
        wgmma_fence();
        wgmma_g1(d, make_desc_32b(sb + OFF_MINI + w * 2048), make_desc_32b(sb + OFF_MINI + 4096), 1);
        wgmma_commit();
      }
      bar_arrive(turn_other, 256);
    };
    auto kdone = [&](int k) { wgmma_wait0(); release(slot_of(k)); };
    auto wgmma_wait1 = [&]() { asm volatile("wgmma.wait_group.sync.aligned 1;" ::: "memory"); };

#pragma unroll 1
    for (int k = 0; k < 14; k++) {
      kstep(a1, k, k == 0);
      if (k == 0) CT(0);
      if (k == 8 && warp == 2 && lane < 2) pkt_st128(&p.s->abflag[((eps * 2 + m) * 8 + tau) * 2 + lane], 0, 0, 0, 0);
      kdone(k);
    }
    uint32_t R[64];
    uint32_t tag;
    {
      const uint32_t rsa = sb + OFF_RS + q * 144;
      const uint64_t da2 = make_desc(sb + 2 * ST_BYTES + w * 8192), db2 = make_desc(sb + 2 * ST_BYTES + A_BYTES);
      const uint64_t da3 = make_desc(sb + 3 * ST_BYTES + w * 8192), db3 = make_desc(sb + 3 * ST_BYTES + A_BYTES);
      mbar_wait(BAR(B_FULL + 2), 1);
      CT(64 + 14);
      bar_sync(turn_me, 256);
      wgmma_fence();
#pragma unroll
      for (int kk = 0; kk < 4; kk++) wgmma_g1(a1, da2 + kk * 2, db2 + kk * 2, 1);
      wgmma_commit();
      mbar_wait(BAR(B_FULL + 3), 1);
      CT(64 + 15);
      wgmma_fence();
      wgmma_g1(a1, da3, db3, 1);
      wgmma_g1(a1, da3 + 2, db3 + 2, 1);
      wgmma_commit();
      mbar_wait(BAR(B_STAT), 0);
      tag = SM_(uint32_t, OFF_TAG);
#pragma unroll
      for (int i = 0; i < 8; i++) { const uint4 v = lds128_v(rsa + i * 16); R[8 * i] = v.x; R[8 * i + 2] = v.y; R[8 * i + 4] = v.z; R[8 * i + 6] = v.w; }
      wgmma_wait1();
      release(2);
      wgmma_fence();
      wgmma_g1(a1, da3 + 4, db3 + 4, 1);
      wgmma_g1(a1, da3 + 6, db3 + 6, 1);
      wgmma_g1(a1, make_desc_noswz(sb + OFF_EXA + w * 2048), make_desc_noswz(sb + OFF_EXB), 1);
      wgmma_commit();
      bar_arrive(turn_other, 256);
      kdone(15);
      mbar_wait(BAR(B_STAT), 0);
    }
    fence_acc(a1);
    CT(1);
    auto pack = [&](auto cc) {
      constexpr int c = decltype(cc)::value;
#pragma unroll
      for (int j = 8 * c; j < min_c(8 * c + 8, NX / 8); j++) {
        const uint32_t rs = R[2 * j];
        const float* ac = &a1[4 * j];
        R[2 * j] = bmul2(pack_bf16(ac[0], ac[1]), rs);
        R[2 * j + 1] = bmul2(pack_bf16(ac[2], ac[3]), rs);
      }
    };
    auto put_chunk = [&](auto cc) {
      constexpr int c = decltype(cc)::value;
      const int rho = 16 * wi + (lane & 15);
#pragma unroll
      for (int j = 8 * c; j < min_c(8 * c + 8, NX / 8); j += 2) {
        const int chunk = (j & 7) + (lane >> 4);
        stsm_x4(sb + chunk_off(c, w) + rho * 128 + ((chunk ^ (lane & 7)) << 4), R[2 * j], R[2 * j + 1], R[2 * j + 2], R[2 * j + 3]);
      }
    };
    auto staged = [&](int bar) {
      fence_async_smem();
      __syncwarp();
      if (lane == 0) mbar_arrive(BAR(bar));
    };
    auto mma_rs = [&](auto cc, auto k0, auto k1) {
      constexpr int c = decltype(cc)::value;
      const uint64_t db = make_desc(sb + c * ST_BYTES + A_BYTES);
#pragma unroll
      for (int kk = decltype(k0)::value; kk < decltype(k1)::value; kk++)
        wgmma_n256_rs(acc, R[16 * c + 4 * kk], R[16 * c + 4 * kk + 1], R[16 * c + 4 * kk + 2], R[16 * c + 4 * kk + 3], db + kk * 2, c + kk > 0);
      wgmma_commit();
    };
    auto kdone_x = [&](int k, auto ic) {
      constexpr int i = decltype(ic)::value;
      uint32_t r[8];
#pragma unroll
      for (int z = 0; z < 2; z++) {
        const int tr = 32 * (i & 1) + 16 * z + 8 * (lane >> 4) + (lane & 7), chunk = 2 * wi + ((lane >> 3) & 1);
        ldsm_x4_t(sb + (i >> 1) * ST_BYTES + w * 8192 + tr * 128 + ((chunk ^ (lane & 7)) << 4), r[4 * z], r[4 * z + 1], r[4 * z + 2], r[4 * z + 3]);
      }
      float f[16];
#pragma unroll
      for (int z = 0; z < 8; z++) { f[2 * z] = bf_lo(r[z]); f[2 * z + 1] = bf_hi(r[z]); }
#pragma unroll
      for (int z = 0; z < 16; z++) asm volatile("" : "+f"(f[z]));
      kdone(k);
#pragma unroll
      for (int z = 0; z < 16; z++) asm volatile("add.f32 %0, %0, %1;" : "+f"(acc[16 * i + z]) : "f"(f[z]));
    };
    pack(IC<0>());
    put_chunk(IC<0>());
    staged(w ? B_EPI0B : B_EPI);
    mbar_wait(BAR(B_STAT), 0);
    CT(21);
    pack(IC<1>());
    pack(IC<2>());
    pack(IC<3>());
#pragma unroll
    for (int i = 16; i < NX / 4; i++) asm volatile("" : "+r"(R[i]));
#pragma unroll
    for (int i = 0; i < 128; i++) asm volatile("" : "=f"(acc[i]));
    mbar_wait(BAR(B_FULL + 0), 0);
    CT(2);
    CT(64 + 16);
    bar_sync(turn_me, 256);
    wgmma_fence();
    mma_rs(IC<0>(), IC<0>(), IC<4>());
    mbar_wait(BAR(B_FULL + 1), 0);
    CT(64 + 17);
    wgmma_fence();
    mma_rs(IC<1>(), IC<0>(), IC<2>());
    wgmma_wait1();
    release(0);
    mma_rs(IC<1>(), IC<2>(), IC<4>());
    bar_arrive(turn_other, 256);
    kdone_x(17, IC<0>());
    static_for<2>([&](auto ic) {
      constexpr int c = 2 + decltype(ic)::value;
      mbar_wait(BAR(B_FULL + c), 0);
      CT(64 + 16 + c);
      bar_sync(turn_me, 256);
      wgmma_fence();
      mma_rs(IC<c>(), IC<0>(), IC<min_c(4, NX / 16 - 4 * c)>());
      bar_arrive(turn_other, 256);
      if (c == 2) { put_chunk(IC<1>()); staged(B_EPI + 1); }
      kdone_x(16 + c, IC<c - 1>());
    });
#pragma unroll 1
    for (int k = 20; k < 23; k++) {
      if (w == 1) mbar_wait(BAR(B_A20), 0);
      kstep(acc, k, false, k < 22);
      if (k == 20) {
        kdone_x(k, IC<3>());
      } else {
        if (k == 21) put_chunk(IC<2>()); else put_chunk(IC<3>());
        __syncwarp();
        if (lane == 0) mbar_arrive(BAR(B_EPI + k - 19));
        kdone(k);
      }
    }
    uint32_t wf[32][4];
    auto load_wf = [&](auto hc) {
      constexpr int h = decltype(hc)::value;
      const int d = w * 64 + (lane >> 4) * 8 + (lane & 7);
      const uint32_t ad = sb + round_off(h) + (lane & 8) * 1024 + d * 64 + ((wi ^ ((lane >> 1) & 3)) << 4);
#pragma unroll
      for (int i = 0; i < 4; i++) ldsm_x4_t(ad + i * 1024, wf[4 * h + i][0], wf[4 * h + i][1], wf[4 * h + i][2], wf[4 * h + i][3]);
    };
    auto load_wf_rest = [&]() { static_for<8 - NREG_H>([&](auto ic) { load_wf(IC<NREG_H + decltype(ic)::value>()); }); };
#pragma unroll
    for (int i = 0; i < 4 * NREG_H; i++) { wf[i][0] = 0; wf[i][1] = 0; wf[i][2] = 0; wf[i][3] = 0; }
    const int grp = tau * 2 + m;
#pragma unroll 1
    for (int k = 23; k < 46; k++) {
      kstep(acc, k, false, false, NX < 256 && k == MINI_K);
      if (moe) {
        static_for<NREG_H>([&](auto hc) {
          constexpr int h = decltype(hc)::value;
          if (k == mr_k(h) + 1) { mbar_wait(BAR(B_MR + (h & 1)), (h >> 1) & 1); CT(32 + h); load_wf(hc); }
        });
      }
      if (k == RESET_K && tid == 0) mbar_arrive(BAR(B_LATE));
      kdone(k);
    }
    asm volatile("barrier.cluster.arrive.relaxed.aligned;" ::: "memory");
    mbar_wait(BAR(B_STAT), 1);
    uint32_t wa[16][2];
    uint32_t cd = code_of(tag);
    uint4* hp_pub = &p.s->hstat[(grp * 8 + eps) * 128 + warp * 16 + g];
    const uint4* hp_poll = &p.s->hstat[(grp * 8 + 2 * q) * 128 + warp * 16 + g];
    const uint32_t vec_off = (2 * wi) * 512 + q * 128 + ((g ^ (2 * q)) << 4);
    {
      float as[64], ak[64];
      fence_acc(acc);
#pragma unroll
      for (int i = 0; i < 64; i++) asm volatile("mov.b32 %0, %1;" : "=f"(as[i]) : "f"(acc[64 + i]));
#pragma unroll
      for (int i = 0; i < 64; i++) asm volatile("mov.b32 %0, %1;" : "=f"(ak[i]) : "f"(acc[i]));
      const uint64_t da1 = make_desc(sb + 2 * ST_BYTES + w * 8192), db1 = make_desc(sb + 2 * ST_BYTES + A_BYTES);
      const uint64_t da2 = make_desc(sb + 3 * ST_BYTES + w * 8192), db2 = make_desc(sb + 3 * ST_BYTES + A_BYTES);
      mbar_wait(BAR(B_FULL + 2), 1);
      CT(64 + 46);
      mbar_wait(BAR(B_FULL + 3), 1);
      CT(64 + 47);
      bar_sync(turn_me, 256);
      wgmma_fence();
#pragma unroll
      for (int kk = 0; kk < 4; kk++) wgmma_n128(as, da1 + kk * 2, db1 + 1024 + kk * 2);
#pragma unroll
      for (int kk = 0; kk < 4; kk++) wgmma_n128(as, da2 + kk * 2, db2 + 1024 + kk * 2);
      wgmma_commit();
      bar_arrive(turn_other, 256);
      const uint32_t rx = mapa(sb + OFF_PEER + w * 4096 + vec_off, 1 - m), rb = mapa(BAR(B_XCH), 1 - m);
      asm volatile("barrier.cluster.wait.aligned;" ::: "memory");
      CT(24);
      wgmma_wait0();
      fence_acc64(as);
      CT(25);
      auto keep = [&]() {
        bar_sync(turn_me, 256);
        wgmma_fence();
#pragma unroll
        for (int kk = 0; kk < 4; kk++) wgmma_n128(ak, da1 + kk * 2, db1 + kk * 2);
        wgmma_commit();
#pragma unroll
        for (int kk = 0; kk < 4; kk++) wgmma_n128(ak, da2 + kk * 2, db2 + kk * 2);
        wgmma_commit();
        if (w == 0) bar_arrive(turn_other, 256);
      };
#pragma unroll
      for (int i = 0; i < 8; i++) {
        if (i == SEND_FIRST) keep();
        const float* ac = &as[16 * (i >> 1) + 2 * (i & 1)];
        st_async_v4(rx + (i >> 1) * 8192 + (i & 1) * 512, rb, pack_bf16(ac[0], ac[1]), pack_bf16(ac[4], ac[5]), pack_bf16(ac[8], ac[9]), pack_bf16(ac[12], ac[13]));
      }
      CT(26);
#pragma unroll
      for (int i = 0; i < 4; i++) {
        const uint4 v = lds128_v(sb + OFF_WR + q * 80 + i * 16);
        const uint32_t vv[4] = {v.x, v.y, v.z, v.w};
#pragma unroll
        for (int z = 0; z < 4; z++) {
          asm volatile("{\n.reg .pred p;\nsetp.ne.b32 p, %2, 0;\nselp.b32 %0, %1, 0x3F803F80, p;\n}" : "=r"(wa[4 * i + z][0]) : "r"(vv[z]), "r"(g & 1));
          asm volatile("{\n.reg .pred p;\nsetp.ne.b32 p, %2, 0;\nselp.b32 %0, %1, 0x3F803F80, p;\n}" : "=r"(wa[4 * i + z][1]) : "r"(vv[z]), "r"(g & 1));
        }
      }
      pin(cd); pin(hp_pub); pin(hp_poll);
      CT(27);
      wgmma_wait1();
      release(2);
      wgmma_wait0();
      fence_acc64(ak);
      CT(3);
#pragma unroll
      for (int i = 0; i < 8; i++) {
        const float* ac = &ak[16 * (i >> 1) + 2 * (i & 1)];
        sts128(sb + (2 + (i >> 2)) * ST_BYTES + w * 8192 + ((i >> 1) & 1) * 4096 + (i & 1) * 512 + vec_off,
               pack_bf16(ac[0], ac[1]), pack_bf16(ac[4], ac[5]), pack_bf16(ac[8], ac[9]), pack_bf16(ac[12], ac[13]));
      }
    }
    uint32_t h[8][4];
    {
      const int qq = 2 * (warp & 1) + ((lane >> 3) & 1);
      const uint32_t lo = (lane >> 4) * 512 + qq * 128 + (((lane & 7) ^ (2 * qq)) << 4);
      bar_sync(NB_BOTH, 256);
#pragma unroll
      for (int ks = 0; ks < 8; ks++)
        ldsm_x4_t(sb + (2 + w) * ST_BYTES + (ks >> 2) * 8192 + (wi >> 1) * 4096 + (ks & 3) * 1024 + lo, h[ks][0], h[ks][1], h[ks][2], h[ks][3]);
      CT(28);
      mbar_wait_cluster(BAR(B_XCH), 0);
      CT(4);
      uint32_t r[8][4];
#pragma unroll
      for (int ks = 0; ks < 8; ks++) ldsm_x4_t(sb + OFF_PEER + (warp >> 1) * 8192 + ks * 1024 + lo, r[ks][0], r[ks][1], r[ks][2], r[ks][3]);
      float d[4][4] = {};
#pragma unroll
      for (int ks = 0; ks < 8; ks++) {
#pragma unroll
        for (int i = 0; i < 4; i++) {
          h[ks][i] = badd2(h[ks][i], r[ks][i]);
          mma1688(d[i], h[ks][i], wa[2 * ks + (i >> 1)][i & 1], h[ks][i]);
        }
      }
#pragma unroll
      for (int i = 0; i < 2; i++) {
        const float sq = (g & 1) ? d[i][1] + d[i + 2][1] : d[i][0] + d[i + 2][0];
        const float e0 = d[i][2] + d[i + 2][2], e1 = d[i][3] + d[i + 2][3];
        const float other = __shfl_xor_sync(0xffffffffu, (g & 1) ? e0 : e1, 4);
        if (q == (g >> 1)) pkt_st128(hp_pub + 8 * i, with_bit((g & 1) ? other : e0, cd), with_bit(sq, cd >> 1), __float_as_uint((g & 1) ? e1 : other), tag);
      }
    }
    CT(5);
    if (tid == 0) mbar_arrive(BAR(B_KEY));
    delay_clk<HOP1_DELAY>();
    float m_bf, sd, inv_sd, r_bf;
    uint4* key_pub = &p.s->key[((lane & 7) * 16 + grp) * 2];
    uint4* cand_pub = &p.s->cand[grp * 256 + eps * 32 + q];
    uint32_t trow_inv = 0xFFFFu - (uint32_t)(grp * 128 + 32 * (warp >> 1) + 8 * (g >> 1) + 4 * (warp & 1) + (q & 2) + (g & 1));
    {
      uint4 u[4];
#pragma unroll
      for (int i = 0; i < 4; i++) u[i] = pkt_ld128(hp_poll + (i & 1) * 128 + (i >> 1) * 8);
      const float wsum = SM_(float, OFF_WSUM);
      pin(key_pub); pin(cand_pub); pin(trow_inv);
      uint32_t n = 0;
      while (true) {
        bool ok[4];
#pragma unroll
        for (int i = 0; i < 4; i++) ok[i] = u[i].w == tag && pair_code(u[i].x, u[i].y) == cd;
        const bool all = __all_sync(0xffffffffu, ok[0] && ok[1] && ok[2] && ok[3]);
        if (all || ++n > SPIN_LIMIT) break;
#pragma unroll
        for (int i = 0; i < 4; i++) pkt_ld128_if(u[i], hp_poll + (i & 1) * 128 + (i >> 1) * 8, !ok[i]);
      }
      CT(6);
      float a[3], b[3];
      a[0] = __uint_as_float(u[0].x & ~1u) + __uint_as_float(u[1].x & ~1u); b[0] = __uint_as_float(u[2].x & ~1u) + __uint_as_float(u[3].x & ~1u);
      a[1] = __uint_as_float(u[0].y & ~1u) + __uint_as_float(u[1].y & ~1u); b[1] = __uint_as_float(u[2].y & ~1u) + __uint_as_float(u[3].y & ~1u);
      a[2] = __uint_as_float(u[0].z) + __uint_as_float(u[1].z); b[2] = __uint_as_float(u[2].z) + __uint_as_float(u[3].z);
#pragma unroll
      for (int i = 0; i < 3; i++) {
        a[i] = ((q & 2) ? b[i] : a[i]) + __shfl_xor_sync(0xffffffffu, (q & 2) ? a[i] : b[i], 2);
        a[i] += __shfl_xor_sync(0xffffffffu, a[i], 1);
      }
      const float mu = a[0] * (1.f / 1024.f);
      m_bf = bf16r(mu);
      sd = ln_sd(a[1] * (1.f / 1024.f) - mu * mu);
      inv_sd = rcp_fast(sd);
      r_bf = bf16r((a[2] - m_bf * wsum) * inv_sd);
    }
    {
      const uint32_t u = __float_as_uint(r_bf);
      const uint32_t ord = (u & 0x80000000u) ? ~u : (u | 0x80000000u);
      const uint32_t key = (ord & 0xFFFF0000u) | trow_inv;
      const uint32_t wk = __reduce_max_sync(0xffffffffu, key);
      if (key == wk) SM_(uint2, OFF_WKEY + warp * 8) = make_uint2(wk, (__float_as_uint(m_bf) >> 16) | __float_as_uint(sd));
      const uint32_t wmask = __ballot_sync(0xffffffffu, key == wk);
      const bool hi = (wmask & 0xCCCCCCCCu) != 0;
      uint32_t c[16];
#pragma unroll
      for (int ks = 0; ks < 8; ks++) { c[2 * ks] = hi ? h[ks][1] : h[ks][0]; c[2 * ks + 1] = hi ? h[ks][3] : h[ks][2]; }
      bar_sync(NB_BOTH, 256);
      const uint2 km = SM_(uint2, OFF_WKEY + (lane & 7) * 8);
      const uint32_t bk = __reduce_max_sync(0xffffffffu, km.x);
      if (wk == bk) {
        if ((wmask >> (lane & 28)) & 15) {
#pragma unroll
          for (int ks = 0; ks < 8; ks++) pkt_st128(cand_pub + ks * 4, c[2 * ks], tag, c[2 * ks + 1], tag);
        }
      } else if (eps == 0) {
        const uint32_t kx = __shfl_sync(0xffffffffu, km.x, warp ^ 1), ms = __shfl_sync(0xffffffffu, km.y, warp ^ 1);
        if (kx == bk && lane < 8) pkt_st128(key_pub, bk, tag, ms, tag);
      }
      CT(7);
    }
    {
      const float ih = bf16r(inv_sd);
      const uint32_t nm = pack_bf16(-m_bf, -m_bf), iv = pack_bf16(ih, inv_sd - ih);
      const uint32_t nm_o = __shfl_xor_sync(0xffffffffu, nm, 2), iv_o = __shfl_xor_sync(0xffffffffu, iv, 2);
      const uint32_t nm2[2] = {(q & 2) ? nm_o : nm, (q & 2) ? nm : nm_o}, iv2[2] = {(q & 2) ? iv_o : iv, (q & 2) ? iv : iv_o};
      const uint32_t hi2[2] = {__byte_perm(iv2[0], 0, 0x1010), __byte_perm(iv2[1], 0, 0x1010)}, lo2[2] = {__byte_perm(iv2[0], 0, 0x3232), __byte_perm(iv2[1], 0, 0x3232)};
      const uint32_t oa = sb + OFF_OUT + (warp * 16 + (lane & 15)) * 128;
#pragma unroll
      for (int ks = 0; ks < 8; ks++) {
        uint32_t o[4];
#pragma unroll
        for (int i = 0; i < 4; i++) {
          const uint32_t dd = badd2(h[ks][i], nm2[i & 1]);
          o[i] = badd2(h[ks][i], bfma2(dd, hi2[i & 1], bmul2(dd, lo2[i & 1])));
        }
        stsm_x4(oa + (ks >> 2) * 16384 + (((2 * (ks & 3) + (lane >> 4)) ^ (lane & 7)) << 4), o[0], o[1], o[2], o[3]);
      }
      staged(B_OUT);
    }
    CT(8);
    uint32_t df[16][4];
    auto load_df = [&]() {
      const int frow = (lane & 7) + ((lane >> 4) << 3), hi = (lane >> 3) & 1;
      const uint32_t base = sb + down_off(warp >> 1) + (warp & 1) * 8192 + frow * 128;
#pragma unroll
      for (int mt = 0; mt < 8; mt++) {
#pragma unroll
        for (int ks = 0; ks < 2; ks++)
          ldsm_x4_t(base + (mt >> 2) * 4096 + ks * 2048 + (((2 * (mt & 3) + hi) ^ (lane & 7)) << 4),
                    df[2 * mt + ks][0], df[2 * mt + ks][1], df[2 * mt + ks][2], df[2 * mt + ks][3]);
      }
    };
    if (moe) {
      mbar_wait(BAR(B_GU), 0);
      load_wf_rest();
      mbar_wait(BAR(B_DN), 0);
      load_df();
    }
    uint4* y_pub = &p.s->ypart[cid * 256 + tid];
    uint32_t xs_ad = sb + OFF_XSEL + (8 * (g >> 2) + 4 * w + (g & 3)) * 32 + q * 8, gp_ad = sb + OFF_GP + (wi * 8 + g) * 16 + w * 8 + (q >> 1) * 4;
    pin(y_pub); pin(xs_ad); pin(gp_ad);
    mbar_wait(BAR(B_XS), 0);
    CT(9);
    if (moe) {
      float gd[8][4] = {};
      uint2 bx[4];
#pragma unroll
      for (int r = 0; r < 4; r++) bx[r] = smem_at<uint2>(xs_ad + r * 512);
#pragma unroll
      for (int r = 0; r < 4; r++) {
#pragma unroll
        for (int i = 0; i < 8; i++) mma16816(gd[i], wf[8 * r + i][0], wf[8 * r + i][1], wf[8 * r + i][2], wf[8 * r + i][3], bx[r].x, bx[r].y);
      }
      const float gs = sel4(q, gd[0][0] + gd[1][1], gd[2][0] + gd[3][1], gd[4][0] + gd[5][1], gd[6][0] + gd[7][1]);
      const float us = sel4(q, gd[0][2] + gd[1][3], gd[2][2] + gd[3][3], gd[4][2] + gd[5][3], gd[6][2] + gd[7][3]);
      float v = ((q & 2) ? us : gs) + __shfl_xor_sync(0xffffffffu, (q & 2) ? gs : us, 2);
      v += __shfl_xor_sync(0xffffffffu, v, 1);
      smem_at<float>(gp_ad) = v;
      CT(10);
      bar_sync(NB_BOTH, 256);
      uint32_t bq[4];
      {
        const float4 p0 = SM_(float4, OFF_GP + lane * 16);
        const float gt = bf16r(p0.x + p0.z), up = bf16r(p0.y + p0.w);
        const float act = bf16r(gt * sigmoid_fast(gt)) * up;
        const uint32_t pr = pack_bf16(act, __shfl_down_sync(0xffffffffu, act, 1));
#pragma unroll
        for (int i = 0; i < 4; i++) bq[i] = __shfl_sync(0xffffffffu, pr, 8 * i + 2 * q);
      }
      CT(11);
      float yd[8][4] = {};
#pragma unroll
      for (int ks = 0; ks < 2; ks++) {
#pragma unroll
        for (int mt = 0; mt < 8; mt++) mma16816(yd[mt], df[2 * mt + ks][0], df[2 * mt + ks][1], df[2 * mt + ks][2], df[2 * mt + ks][3], bq[2 * ks], bq[2 * ks + 1]);
      }
      pkt_st128(y_pub, with_bit(sel4(q, yd[0][0], yd[2][0], yd[4][0], yd[6][0]), cd), with_bit(sel4(q, yd[0][2], yd[2][2], yd[4][2], yd[6][2]), cd >> 1),
                with_bit(sel4(q, yd[1][0], yd[3][0], yd[5][0], yd[7][0]), cd), with_bit(sel4(q, yd[1][2], yd[3][2], yd[5][2], yd[7][2]), cd >> 1));
    } else {
      const long long tw = clock64();
      while (clock64() - tw < IDLE_WAIT_CLK) __nanosleep(100);
    }
    CT(12);
    const uint32_t kv = SM_(uint32_t, OFF_KV);
    const int tsel = 0xFFFF - (int)(kv & 0xFFFFu);
    const float r_sel = __uint_as_float((kv & 0x80000000u) ? (kv & 0x7FFF0000u) : (~kv & 0xFFFF0000u));
    const float sig = bf16r(sigmoid_fast(r_sel));
    const int pfin = 2 * cid + (tid & 1);
    const int col_fin = (pfin >> 5) * 128 + (pfin & 3) * 32 + ((pfin & 31) >> 2) + 8 * ((tid >> 1) & 3);
    const int sel_off = (col_fin >> 4) * 32 + ((col_fin & 7) >> 1) * 8 + ((col_fin >> 3) & 1) * 4 + (col_fin & 1) * 2;
    const float hn_fin = __uint_as_float((uint32_t)SM_(uint16_t, OFF_XSEL + sel_off) << 16), h_fin = __uint_as_float((uint32_t)SM_(uint16_t, OFF_HSEL + sel_off) << 16);
    bf16* out_fin = p.out + (size_t)tsel * 1024 + col_fin;
    {
      const uint4* src = &p.s->ypart[(16 + (tid >> 1)) * 256 + pfin];
      pin(src); pin(out_fin);
      uint4 v = make_uint4(0, 0, 0, 0);
      if (warp < 7) {
        delay_clk<HOP3_DELAY>();
        uint32_t n = 0;
        bool ok = false;
        do {
          pkt_ld128_if(v, src, !ok);
          ok = pair_code(v.x, v.y) == cd && pair_code(v.z, v.w) == cd;
        } while (!__all_sync(0xffffffffu, ok) && ++n < SPIN_LIMIT);
      }
      CT(13);
      const float y0 = __uint_as_float(v.x & ~1u), y1 = __uint_as_float(v.y & ~1u), y2 = __uint_as_float(v.z & ~1u), y3 = __uint_as_float(v.w & ~1u);
      const float a0 = ((lane & 2) ? y1 : y0) + __shfl_xor_sync(0xffffffffu, (lane & 2) ? y0 : y1, 2);
      const float a1 = ((lane & 2) ? y3 : y2) + __shfl_xor_sync(0xffffffffu, (lane & 2) ? y2 : y3, 2);
      float b = ((lane & 4) ? a1 : a0) + __shfl_xor_sync(0xffffffffu, (lane & 4) ? a0 : a1, 4);
      b += __shfl_xor_sync(0xffffffffu, b, 8);
      b += __shfl_xor_sync(0xffffffffu, b, 16);
      if (lane < 8) SM_(float, OFF_FIN + lane * 32 + warp * 4) = b;
    }
    bar_sync(NB_BOTH, 256);
    if (tid < 8) {
      const float4 y0 = SM_(float4, OFF_FIN + tid * 32), y1 = SM_(float4, OFF_FIN + tid * 32 + 16);
      const float y = ((y0.x + y0.y) + (y0.z + y0.w)) + ((y1.x + y1.y) + y1.z);
      *out_fin = __float2bfloat16_rn(h_fin + bf16r(hn_fin + bf16r(bf16r(y) * sig)));
      if (cid == 0 && tid == 0) st_relaxed32(&p.s->epoch, tag);
    }
    CT(14);
  }
}

__global__ void __launch_bounds__(384, 1) occupancy_probe_kernel() {}

typedef CUresult (*EncodeFn)(CUtensorMap*, CUtensorMapDataType, cuuint32_t, void*, const cuuint64_t*, const cuuint64_t*, const cuuint32_t*, const cuuint32_t*,
                             CUtensorMapInterleave, CUtensorMapSwizzle, CUtensorMapL2promotion, CUtensorMapFloatOOBfill);

static void make_tm(EncodeFn enc, CUtensorMap* tm, const void* ptr, uint64_t rows, uint64_t cols, uint32_t brows, uint32_t bcols, CUtensorMapSwizzle sw,
                    CUtensorMapL2promotion promo = CU_TENSOR_MAP_L2_PROMOTION_L2_128B) {
  cuuint64_t dims[2] = {cols, rows};
  cuuint64_t strides[1] = {cols * 2};
  cuuint32_t box[2] = {bcols, brows};
  cuuint32_t es[2] = {1, 1};
  enc(tm, CU_TENSOR_MAP_DATA_TYPE_BFLOAT16, 2, const_cast<void*>(ptr), dims, strides, box, es, CU_TENSOR_MAP_INTERLEAVE_NONE, sw,
      promo, CU_TENSOR_MAP_FLOAT_OOB_FILL_NONE);
}

extern "C" void kernel_launch(void* const* d_in, const int* in_sizes, int n_in, void* d_out, int out_size) {
  (void)in_sizes; (void)n_in; (void)out_size;
  static EncodeFn enc = nullptr;
  static void* abT = nullptr;
  static int map = 0;
  if (!enc) {
    void* fn = nullptr; cudaDriverEntryPointQueryResult st;
    cudaGetDriverEntryPoint("cuTensorMapEncodeTiled", &fn, cudaEnableDefault, &st);
    enc = (EncodeFn)fn;
    cudaGetSymbolAddress(&abT, g_scratch);
    cudaFuncSetAttribute(fnet_moe_kernel<0>, cudaFuncAttributeMaxDynamicSharedMemorySize, SMEM_TOTAL);
    cudaFuncSetAttribute(fnet_moe_kernel<1>, cudaFuncAttributeMaxDynamicSharedMemorySize, SMEM_TOTAL);
    cudaFuncSetAttribute(occupancy_probe_kernel, cudaFuncAttributeMaxDynamicSharedMemorySize, SMEM_TOTAL);
    cudaFuncSetAttribute(occupancy_probe_kernel, cudaFuncAttributeNonPortableClusterSizeAllowed, 1);
    auto max_clusters = [&](int size) {
      cudaLaunchConfig_t cfg = {};
      cfg.gridDim = dim3(128); cfg.blockDim = dim3(384); cfg.dynamicSmemBytes = SMEM_TOTAL;
      cudaLaunchAttribute at[1];
      at[0].id = cudaLaunchAttributeClusterDimension; at[0].val.clusterDim.x = size; at[0].val.clusterDim.y = 1; at[0].val.clusterDim.z = 1;
      cfg.attrs = at; cfg.numAttrs = 1;
      int ncl = 0;
      return cudaOccupancyMaxActiveClusters(&ncl, occupancy_probe_kernel, &cfg) == cudaSuccess ? ncl : 0;
    };
    int dev = 0, sms = 0;
    cudaGetDevice(&dev);
    cudaDeviceGetAttribute(&sms, cudaDevAttrMultiProcessorCount, dev);
    map = (sms == 132 && max_clusters(2) == 66 && max_clusters(16) == 7) ? 0 : 1;
    (void)cudaGetLastError();
  }
  Params p;
  const bf16* x = (const bf16*)d_in[0];
  make_tm(enc, &p.tmD0, d_in[3], 1024, 1024, 128, 64, CU_TENSOR_MAP_SWIZZLE_128B);
  make_tm(enc, &p.tmD1, d_in[4], 1024, 1024, 128, 64, CU_TENSOR_MAP_SWIZZLE_128B);
  make_tm(enc, &p.tmX, x, 2048, 1024, map == 0 ? NX0 : 256, 64, CU_TENSOR_MAP_SWIZZLE_128B);
  make_tm(enc, &p.tmXr, x, 2048, 1024, 64, 64, CU_TENSOR_MAP_SWIZZLE_128B);
  make_tm(enc, &p.tmAbS, abT, 2048, 2048, 64, 64, CU_TENSOR_MAP_SWIZZLE_128B);
  make_tm(enc, &p.tmAbL, abT, 2048, 2048, 128, 64, CU_TENSOR_MAP_SWIZZLE_128B);
  make_tm(enc, &p.tmW0, d_in[1], 2048, 2048, 128, 64, CU_TENSOR_MAP_SWIZZLE_128B);
  make_tm(enc, &p.tmW1, d_in[2], 2048, 2048, 128, 64, CU_TENSOR_MAP_SWIZZLE_128B);
  {
    cuuint64_t dims[5] = {1024, 2, 4, 4, 64};
    cuuint64_t strides[4] = {2048, 8 * 2048, 2 * 2048, 32 * 2048};
    cuuint32_t box[5] = {64, 2, 4, 2, 1};
    cuuint32_t es[5] = {1, 1, 1, 1, 1};
    enc(&p.tmOut, CU_TENSOR_MAP_DATA_TYPE_BFLOAT16, 5, d_out, dims, strides, box, es, CU_TENSOR_MAP_INTERLEAVE_NONE, CU_TENSOR_MAP_SWIZZLE_128B,
        CU_TENSOR_MAP_L2_PROMOTION_NONE, CU_TENSOR_MAP_FLOAT_OOB_FILL_NONE);
  }
  {
    cuuint64_t dims[5] = {1024, 2, 4, 2, 8};
    cuuint64_t strides[4] = {2048, 4 * 2048, 2 * 2048, 256 * 2048};
    cuuint32_t box[5] = {64, 2, 4, 2, 8};
    cuuint32_t es[5] = {1, 1, 1, 1, 1};
    enc(&p.tmXh, CU_TENSOR_MAP_DATA_TYPE_BFLOAT16, 5, const_cast<bf16*>(x) + 240 * 1024, dims, strides, box, es, CU_TENSOR_MAP_INTERLEAVE_NONE,
        CU_TENSOR_MAP_SWIZZLE_128B, CU_TENSOR_MAP_L2_PROMOTION_L2_128B, CU_TENSOR_MAP_FLOAT_OOB_FILL_NONE);
  }
  make_tm(enc, &p.tmAbM, abT, 2048, 2048, 128, 16, CU_TENSOR_MAP_SWIZZLE_32B, CU_TENSOR_MAP_L2_PROMOTION_NONE);
  make_tm(enc, &p.tmWM0, d_in[1], 2048, 2048, 128, 16, CU_TENSOR_MAP_SWIZZLE_32B, CU_TENSOR_MAP_L2_PROMOTION_NONE);
  make_tm(enc, &p.tmWM1, d_in[2], 2048, 2048, 128, 16, CU_TENSOR_MAP_SWIZZLE_32B, CU_TENSOR_MAP_L2_PROMOTION_NONE);
  make_tm(enc, &p.tmG, d_in[7], 1024, 3584, 128, 32, CU_TENSOR_MAP_SWIZZLE_64B);
  make_tm(enc, &p.tmU, d_in[8], 1024, 3584, 128, 32, CU_TENSOR_MAP_SWIZZLE_64B);
  make_tm(enc, &p.tmDn, d_in[9], 3584, 1024, 32, 64, CU_TENSOR_MAP_SWIZZLE_128B);
  p.x = x; p.Dre = (const bf16*)d_in[3]; p.Dim = (const bf16*)d_in[4];
  p.wr = (const bf16*)d_in[6]; p.wdown = (const bf16*)d_in[9]; p.wgate = (const bf16*)d_in[7]; p.wup = (const bf16*)d_in[8];
  p.out = (bf16*)d_out; p.s = (Scratch*)abT;
  if (map == 1) fnet_moe_kernel<1><<<128, 384, SMEM_TOTAL>>>(p);
  else fnet_moe_kernel<0><<<132, 384, SMEM_TOTAL>>>(p);
}
```

```cpp
#include <cuda.h>
#include <cuda_runtime.h>
#include <cuda_bf16.h>
#include <stdint.h>
#include <type_traits>

typedef __nv_bfloat16 bf16;

constexpr int NX0 = 240;
constexpr int REG_C = 232, REG_P = 40;
__device__ __forceinline__ int sigma_of(int tau, int r) { return r + (r >= tau); }
__device__ __forceinline__ int kblock(int tau, int j) {
  const int i = j - 4, c = (i * 37) >> 8;
  return j < 4 ? tau * 4 + j : sigma_of(tau, i - 7 * c) * 4 + c;
}
constexpr int AUX_AFTER = 1;
constexpr int PF_K0 = 8, PF_N0 = 2, PF_K1 = 24;
constexpr int WPF_K0 = 12, WPF_N = 10;
constexpr int PUB_K1 = 22;
constexpr int NREG_H = 5;
constexpr int MR_K0 = 29, MR_P = 6;
constexpr int MINI_PF_K = 39, MINI_LOAD_K = 43, MINI_K = 42;
constexpr int RESET_K = 37;
constexpr int SEND_FIRST = 2;
constexpr int HELPER_NS = 5000;
constexpr int GATHER_NS = 400;
constexpr int MOE_PACE_CLK = 300;
constexpr int OUT_PACE_CLK = 70;
constexpr int HOP1_DELAY = 150, HOP3_DELAY = 450;
constexpr int SPEC_MIN = 10;
constexpr int IDLE_WAIT_CLK = 1200;
__host__ __device__ constexpr int mr_k(int h) { return MR_K0 + MR_P * (h >> 1) + 2 * (h & 1); }
constexpr int A_BYTES = 128 * 64 * 2;
constexpr int B_BYTES = 256 * 64 * 2;
constexpr int ST_BYTES = A_BYTES + B_BYTES;
constexpr int OFF_XCH = 4 * ST_BYTES;
constexpr int OFF_BAR = OFF_XCH + 32768;
constexpr int OFF_WR = OFF_BAR + 384;
constexpr int OFF_RS = OFF_WR + 384;
constexpr int OFF_PUB = OFF_RS + 640;
constexpr int OFF_MISC = OFF_PUB + 768;
constexpr int SMEM_TOTAL = OFF_MISC + 256;
constexpr int OFF_WSUM = OFF_MISC, OFF_TAG = OFF_MISC + 4;
constexpr int OFF_SEEN = OFF_MISC + 8;
constexpr int OFF_KV = OFF_MISC + 12;
constexpr int OFF_WKEY = OFF_MISC + 32;
constexpr int OFF_MINI = OFF_XCH + 16384;
constexpr int OFF_EXA = OFF_XCH;
constexpr int OFF_EXB = OFF_XCH + 4096;
__host__ __device__ constexpr int chunk_off(int c, int w) { return (c < 2 ? (c + 2) * ST_BYTES : OFF_XCH + (c - 2) * 16384) + w * 8192; }
__host__ __device__ constexpr int late_off(int i) { return i < 4 ? i * 16384 : 2 * ST_BYTES + A_BYTES + (i - 4) * 16384; }
__host__ __device__ constexpr int round_off(int h) { return h < NREG_H + 2 ? OFF_XCH + (h & 1) * 16384 : late_off(h - NREG_H - 2); }
__host__ __device__ constexpr int down_off(int i) { return late_off(6 - NREG_H + i); }
constexpr int OFF_PEER = ST_BYTES + A_BYTES;
constexpr int OFF_OUT = 3 * ST_BYTES + A_BYTES;
constexpr int OFF_XSEL = OFF_PEER;
constexpr int OFF_HSEL = OFF_PEER + 4096;
constexpr int OFF_GP = OFF_PEER + 8192;
constexpr int OFF_FIN = OFF_PEER + 9216;
__device__ __forceinline__ int slot_of(int k) { return k & 3; }
__device__ __forceinline__ int use_of(int k) { return k >> 2; }
enum { B_FULL = 0, B_EMPTY = 4, B_EPI = 8, B_STD = 12, B_EPI0B = 16, B_LATE = 17, B_STAT = 18, B_XCH = 19, B_MR = 20  , B_GU = 22,
       B_DN = 23, B_AUX = 24  , B_OUT = 26, B_KEY = 27, B_XS = 28, B_A20 = 29, B_STDA = 30, B_PUB1 = 31, B_COUNT = 32 };
enum { NB_TURN0 = 1, NB_TURN1 = 2, NB_WG0 = 3, NB_BOTH = 5, NB_AUX = 6 };

struct Scratch {
  bf16 abT[2048 * 2048];
  uint2 xstat[2048];
  uint2 dsum[2048];
  uint4 abflag[16 * 8 * 2];
  uint4 hflag[16 * 2];
  uint4 hstat[16 * 8 * 128];
  uint4 cand[16 * 256];
  uint4 key[8 * 16 * 2];
  uint4 ypart[128 * 256];
  uint32_t epoch;
};
__device__ __align__(1024) Scratch g_scratch;

struct Params {
  Scratch* s; bf16* out;
  const bf16* x; const bf16* Dre; const bf16* Dim; const bf16* wr; const bf16* wdown; const bf16* wgate; const bf16* wup;
  CUtensorMap tmX, tmD0, tmD1, tmXr, tmAbS, tmAbL, tmW0, tmW1, tmOut, tmG, tmU, tmDn, tmXh, tmAbM, tmWM0, tmWM1;
};

#define SPIN_LIMIT (1u << 14)
#define MBAR_LIMIT (1u << 10)
__device__ __forceinline__ uint32_t smem_u32(const void* p) { return (uint32_t)__cvta_generic_to_shared(p); }
__device__ __forceinline__ void mbar_init(uint32_t bar, uint32_t cnt) { asm volatile("mbarrier.init.shared::cta.b64 [%0], %1;" :: "r"(bar), "r"(cnt) : "memory"); }
__device__ __forceinline__ void mbar_expect_tx(uint32_t bar, uint32_t bytes) { asm volatile("mbarrier.arrive.expect_tx.shared::cta.b64 _, [%0], %1;" :: "r"(bar), "r"(bytes) : "memory"); }
__device__ __forceinline__ void mbar_arrive(uint32_t bar) { asm volatile("mbarrier.arrive.shared::cta.b64 _, [%0];" :: "r"(bar) : "memory"); }
__device__ __forceinline__ void mbar_wait(uint32_t bar, uint32_t parity) {
  uint32_t ok, n = 0;
  do {
    asm volatile("{\n.reg .pred p;\nmbarrier.try_wait.parity.shared::cta.b64 p, [%1], %2;\nselp.u32 %0, 1, 0, p;\n}\n" : "=r"(ok) : "r"(bar), "r"(parity) : "memory");
  } while (!ok && ++n < MBAR_LIMIT);
}
__device__ __forceinline__ void mbar_wait_cluster(uint32_t bar, uint32_t parity) {
  uint32_t ok, n = 0;
  do {
    asm volatile("{\n.reg .pred p;\nmbarrier.try_wait.parity.acquire.cluster.shared::cta.b64 p, [%1], %2;\nselp.u32 %0, 1, 0, p;\n}\n" : "=r"(ok) : "r"(bar), "r"(parity) : "memory");
  } while (!ok && ++n < MBAR_LIMIT);
}
__device__ __forceinline__ void tma_load_2d(uint32_t dst, const CUtensorMap* tm, uint32_t bar, int c0, int c1) {
  asm volatile("cp.async.bulk.tensor.2d.shared::cluster.global.mbarrier::complete_tx::bytes [%0], [%1, {%3, %4}], [%2];"
    :: "r"(dst), "l"(tm), "r"(bar), "r"(c0), "r"(c1) : "memory");
}
__device__ __forceinline__ void tma_load_2d_hint(uint32_t dst, const CUtensorMap* tm, uint32_t bar, int c0, int c1, uint64_t pol) {
  asm volatile("cp.async.bulk.tensor.2d.shared::cluster.global.mbarrier::complete_tx::bytes.L2::cache_hint [%0], [%1, {%3, %4}], [%2], %5;"
    :: "r"(dst), "l"(tm), "r"(bar), "r"(c0), "r"(c1), "l"(pol) : "memory");
}
__device__ __forceinline__ uint64_t policy_evict_first() { uint64_t p; asm volatile("createpolicy.fractional.L2::evict_first.b64 %0, 1.0;" : "=l"(p)); return p; }
__device__ __forceinline__ void tma_store_2d(const CUtensorMap* tm, uint32_t src, int c0, int c1) {
  asm volatile("cp.async.bulk.tensor.2d.global.shared::cta.bulk_group [%0, {%2, %3}], [%1];" :: "l"(tm), "r"(src), "r"(c0), "r"(c1) : "memory");
}
__device__ __forceinline__ void tma_prefetch_2d(const CUtensorMap* tm, int c0, int c1) {
  asm volatile("cp.async.bulk.prefetch.tensor.2d.L2.global.tile [%0, {%1, %2}];" :: "l"(tm), "r"(c0), "r"(c1) : "memory");
}
__device__ __forceinline__ void bulk_load(uint32_t dst, const void* src, uint32_t bytes, uint32_t bar) {
  asm volatile("cp.async.bulk.shared::cluster.global.mbarrier::complete_tx::bytes [%0], [%1], %2, [%3];" :: "r"(dst), "l"(src), "r"(bytes), "r"(bar) : "memory");
}
__device__ __forceinline__ void bulk_commit() { asm volatile("cp.async.bulk.commit_group;" ::: "memory"); }
__device__ __forceinline__ void bulk_wait_all() { asm volatile("cp.async.bulk.wait_group 0;" ::: "memory"); }
__device__ __forceinline__ void fence_async_smem() { asm volatile("fence.proxy.async.shared::cta;" ::: "memory"); }
__device__ __forceinline__ void wgmma_fence() { asm volatile("wgmma.fence.sync.aligned;" ::: "memory"); }
__device__ __forceinline__ void wgmma_commit() { asm volatile("wgmma.commit_group.sync.aligned;" ::: "memory"); }
__device__ __forceinline__ void wgmma_wait0() { asm volatile("wgmma.wait_group.sync.aligned 0;" ::: "memory"); }
__device__ __forceinline__ void bar_sync(int id, int n) { asm volatile("bar.sync %0, %1;" :: "r"(id), "r"(n) : "memory"); }
__device__ __forceinline__ void bar_arrive(int id, int n) { asm volatile("bar.arrive %0, %1;" :: "r"(id), "r"(n) : "memory"); }
template<int R> __device__ __forceinline__ void reg_inc() { asm volatile("setmaxnreg.inc.sync.aligned.u32 %0;" :: "n"(R)); }
template<int R> __device__ __forceinline__ void reg_dec() { asm volatile("setmaxnreg.dec.sync.aligned.u32 %0;" :: "n"(R)); }
__device__ __forceinline__ bool elect_one() {
  uint32_t p;
  asm volatile("{\n.reg .pred q;\nelect.sync _|q, 0xffffffff;\nselp.u32 %0, 1, 0, q;\n}\n" : "=r"(p));
  return p != 0;
}
__device__ __forceinline__ uint32_t mapa(uint32_t addr, uint32_t cta) { uint32_t r; asm volatile("mapa.shared::cluster.u32 %0, %1, %2;" : "=r"(r) : "r"(addr), "r"(cta)); return r; }
__device__ __forceinline__ void st_async_v4(uint32_t addr, uint32_t bar, uint32_t a, uint32_t b, uint32_t c, uint32_t d) {
  asm volatile("st.async.weak.shared::cluster.mbarrier::complete_tx::bytes.v4.b32 [%0], {%2, %3, %4, %5}, [%1];" :: "r"(addr), "r"(bar), "r"(a), "r"(b), "r"(c), "r"(d) : "memory");
}
__device__ __forceinline__ void stsm_x4(uint32_t addr, uint32_t a, uint32_t b, uint32_t c, uint32_t d) {
  asm volatile("stmatrix.sync.aligned.m8n8.x4.shared.b16 [%0], {%1, %2, %3, %4};" :: "r"(addr), "r"(a), "r"(b), "r"(c), "r"(d));
}
__device__ __forceinline__ uint4 lds128_v(uint32_t addr) { uint4 v; asm volatile("ld.shared.v4.b32 {%0, %1, %2, %3}, [%4];" : "=r"(v.x), "=r"(v.y), "=r"(v.z), "=r"(v.w) : "r"(addr)); return v; }
extern __shared__ __align__(1024) uint8_t smem_raw[];
template<class T> __device__ __forceinline__ T& smem_at(uint32_t addr) { return *reinterpret_cast<T*>(__cvta_shared_to_generic(addr)); }
#define SM_(T, off) smem_at<T>(sb + (off))
__device__ __forceinline__ uint4 ldg_nc128(const void* p) { uint4 v; asm volatile("ld.global.nc.v4.b32 {%0, %1, %2, %3}, [%4];" : "=r"(v.x), "=r"(v.y), "=r"(v.z), "=r"(v.w) : "l"(p)); return v; }
__device__ __forceinline__ void pkt_st128(void* p, uint32_t a, uint32_t b, uint32_t c, uint32_t d) {
  asm volatile("{\n.reg .b128 v;\n.reg .b64 lo, hi;\nmov.b64 lo, {%1, %2};\nmov.b64 hi, {%3, %4};\nmov.b128 v, {lo, hi};\nst.relaxed.gpu.global.b128 [%0], v;\n}\n"
    :: "l"(p), "r"(a), "r"(b), "r"(c), "r"(d) : "memory");
}
__device__ __forceinline__ uint4 pkt_ld128(const void* p) {
  uint4 r;
  asm volatile("{\n.reg .b128 v;\n.reg .b64 lo, hi;\nld.relaxed.gpu.global.b128 v, [%4];\nmov.b128 {lo, hi}, v;\nmov.b64 {%0, %1}, lo;\nmov.b64 {%2, %3}, hi;\n}\n"
    : "=r"(r.x), "=r"(r.y), "=r"(r.z), "=r"(r.w) : "l"(p) : "memory");
  return r;
}
__device__ __forceinline__ void pkt_ld128_if(uint4& r, const void* p, bool cond) {
  asm volatile("{\n.reg .pred q;\n.reg .b64 lo, hi;\nsetp.ne.b32 q, %5, 0;\nmov.b64 lo, {%0, %1};\nmov.b64 hi, {%2, %3};\n"
               "@q ld.relaxed.gpu.global.v2.b64 {lo, hi}, [%4];\nmov.b64 {%0, %1}, lo;\nmov.b64 {%2, %3}, hi;\n}\n"
    : "+r"(r.x), "+r"(r.y), "+r"(r.z), "+r"(r.w) : "l"(p), "r"((uint32_t)cond) : "memory");
}
__device__ __forceinline__ void pkt_st64(void* p, uint32_t a, uint32_t b) {
  asm volatile("{\n.reg .b64 v;\nmov.b64 v, {%1, %2};\nst.relaxed.gpu.global.b64 [%0], v;\n}\n" :: "l"(p), "r"(a), "r"(b) : "memory");
}
__device__ __forceinline__ uint2 pkt_ld64(const void* p) {
  uint2 r;
  asm volatile("{\n.reg .b64 v;\nld.relaxed.gpu.global.b64 v, [%2];\nmov.b64 {%0, %1}, v;\n}\n" : "=r"(r.x), "=r"(r.y) : "l"(p) : "memory");
  return r;
}
__device__ __forceinline__ uint32_t ld_relaxed32(const void* p) { uint32_t v; asm volatile("ld.relaxed.gpu.global.b32 %0, [%1];" : "=r"(v) : "l"(p) : "memory"); return v; }
__device__ __forceinline__ void st_relaxed32(void* p, uint32_t v) { asm volatile("st.relaxed.gpu.global.b32 [%0], %1;" :: "l"(p), "r"(v) : "memory"); }
__device__ __forceinline__ uint32_t code_of(uint32_t tag) { return tag % 3u + 1u; }
__device__ __forceinline__ uint32_t with_bit(float v, uint32_t bit) { return (__float_as_uint(v) & ~1u) | (bit & 1u); }
__device__ __forceinline__ uint32_t pair_code(uint32_t a, uint32_t b) { return (a & 1u) | ((b & 1u) << 1); }
__device__ __forceinline__ uint32_t pack_bf16(float lo, float hi) { uint32_t r; asm("cvt.rn.bf16x2.f32 %0, %1, %2;" : "=r"(r) : "f"(hi), "f"(lo)); return r; }
__device__ __forceinline__ float bf_lo(uint32_t v) { return __uint_as_float(v << 16); }
__device__ __forceinline__ float bf_hi(uint32_t v) { return __uint_as_float(v & 0xFFFF0000u); }
__device__ __forceinline__ float bf16r(float x) { return __uint_as_float(pack_bf16(0.f, x)); }
__device__ __forceinline__ uint32_t badd2(uint32_t a, uint32_t b) { uint32_t r; asm("add.rn.bf16x2 %0, %1, %2;" : "=r"(r) : "r"(a), "r"(b)); return r; }
__device__ __forceinline__ uint32_t bmul2(uint32_t a, uint32_t b) { uint32_t r; asm("mul.rn.bf16x2 %0, %1, %2;" : "=r"(r) : "r"(a), "r"(b)); return r; }
__device__ __forceinline__ float warp_sum(float v) {
#pragma unroll
  for (int o = 16; o > 0; o >>= 1) v += __shfl_xor_sync(0xffffffffu, v, o);
  return v;
}
__device__ __forceinline__ uint64_t make_desc(uint32_t addr) {
  return (uint64_t)((addr & 0x3FFFF) >> 4) | ((uint64_t)1 << 16) | ((uint64_t)64 << 32) | ((uint64_t)1 << 62);
}
__device__ __forceinline__ uint64_t make_desc_noswz(uint32_t addr) {
  return (uint64_t)((addr & 0x3FFFF) >> 4) | ((uint64_t)8 << 16) | ((uint64_t)16 << 32);
}
__device__ __forceinline__ uint64_t make_desc_32b(uint32_t addr) {
  return (uint64_t)((addr & 0x3FFFF) >> 4) | ((uint64_t)1 << 16) | ((uint64_t)16 << 32) | ((uint64_t)3 << 62);
}
__device__ __forceinline__ void wgmma_n256(float (&d)[128], uint64_t da, uint64_t db, int scale_d) {
  asm volatile("{\n.reg .pred p;\nsetp.ne.b32 p, %130, 0;\n"
    "wgmma.mma_async.sync.aligned.m64n256k16.f32.bf16.bf16 "
    "{%0, %1, %2, %3, %4, %5, %6, %7, %8, %9, %10, %11, %12, %13, %14, %15, %16, %17, %18, %19, %20, %21, %22, %23, %24, %25, %26, %27, %28, %29, %30, %31, "
    "%32, %33, %34, %35, %36, %37, %38, %39, %40, %41, %42, %43, %44, %45, %46, %47, %48, %49, %50, %51, %52, %53, %54, %55, %56, %57, %58, %59, %60, %61, %62, %63, "
    "%64, %65, %66, %67, %68, %69, %70, %71, %72, %73, %74, %75, %76, %77, %78, %79, %80, %81, %82, %83, %84, %85, %86, %87, %88, %89, %90, %91, %92, %93, %94, %95, "
    "%96, %97, %98, %99, %100, %101, %102, %103, %104, %105, %106, %107, %108, %109, %110, %111, %112, %113, %114, %115, %116, %117, %118, %119, %120, %121, %122, %123, %124, %125, %126, %127}, "
    "%128, %129, p, 1, 1, 0, 0;\n}\n"
    : "+f"(d[0]), "+f"(d[1]), "+f"(d[2]), "+f"(d[3]), "+f"(d[4]), "+f"(d[5]), "+f"(d[6]), "+f"(d[7]),
      "+f"(d[8]), "+f"(d[9]), "+f"(d[10]), "+f"(d[11]), "+f"(d[12]), "+f"(d[13]), "+f"(d[14]), "+f"(d[15]),
      "+f"(d[16]), "+f"(d[17]), "+f"(d[18]), "+f"(d[19]), "+f"(d[20]), "+f"(d[21]), "+f"(d[22]), "+f"(d[23]),
      "+f"(d[24]), "+f"(d[25]), "+f"(d[26]), "+f"(d[27]), "+f"(d[28]), "+f"(d[29]), "+f"(d[30]), "+f"(d[31]),
      "+f"(d[32]), "+f"(d[33]), "+f"(d[34]), "+f"(d[35]), "+f"(d[36]), "+f"(d[37]), "+f"(d[38]), "+f"(d[39]),
      "+f"(d[40]), "+f"(d[41]), "+f"(d[42]), "+f"(d[43]), "+f"(d[44]), "+f"(d[45]), "+f"(d[46]), "+f"(d[47]),
      "+f"(d[48]), "+f"(d[49]), "+f"(d[50]), "+f"(d[51]), "+f"(d[52]), "+f"(d[53]), "+f"(d[54]), "+f"(d[55]),
      "+f"(d[56]), "+f"(d[57]), "+f"(d[58]), "+f"(d[59]), "+f"(d[60]), "+f"(d[61]), "+f"(d[62]), "+f"(d[63]),
      "+f"(d[64]), "+f"(d[65]), "+f"(d[66]), "+f"(d[67]), "+f"(d[68]), "+f"(d[69]), "+f"(d[70]), "+f"(d[71]),
      "+f"(d[72]), "+f"(d[73]), "+f"(d[74]), "+f"(d[75]), "+f"(d[76]), "+f"(d[77]), "+f"(d[78]), "+f"(d[79]),
      "+f"(d[80]), "+f"(d[81]), "+f"(d[82]), "+f"(d[83]), "+f"(d[84]), "+f"(d[85]), "+f"(d[86]), "+f"(d[87]),
      "+f"(d[88]), "+f"(d[89]), "+f"(d[90]), "+f"(d[91]), "+f"(d[92]), "+f"(d[93]), "+f"(d[94]), "+f"(d[95]),
      "+f"(d[96]), "+f"(d[97]), "+f"(d[98]), "+f"(d[99]), "+f"(d[100]), "+f"(d[101]), "+f"(d[102]), "+f"(d[103]),
      "+f"(d[104]), "+f"(d[105]), "+f"(d[106]), "+f"(d[107]), "+f"(d[108]), "+f"(d[109]), "+f"(d[110]), "+f"(d[111]),
      "+f"(d[112]), "+f"(d[113]), "+f"(d[114]), "+f"(d[115]), "+f"(d[116]), "+f"(d[117]), "+f"(d[118]), "+f"(d[119]),
      "+f"(d[120]), "+f"(d[121]), "+f"(d[122]), "+f"(d[123]), "+f"(d[124]), "+f"(d[125]), "+f"(d[126]), "+f"(d[127])
    : "l"(da), "l"(db), "r"(scale_d));
}
__device__ __forceinline__ void wgmma_g1(float (&d)[128], uint64_t da, uint64_t db, int scale_d) { wgmma_n256(d, da, db, scale_d); }
__device__ __forceinline__ void wgmma_g1(float (&d)[120], uint64_t da, uint64_t db, int scale_d) {
  asm volatile("{\n.reg .pred p;\nsetp.ne.b32 p, %122, 0;\n"
    "wgmma.mma_async.sync.aligned.m64n240k16.f32.bf16.bf16 "
    "{%0, %1, %2, %3, %4, %5, %6, %7, %8, %9, %10, %11, %12, %13, %14, %15, %16, %17, %18, %19, %20, %21, %22, %23, %24, %25, %26, %27, %28, %29, %30, %31, %32, %33, %34, %35, %36, %37, %38, %39, %40, %41, %42, %43, %44, %45, %46, %47, %48, %49, %50, %51, %52, %53, %54, %55, %56, %57, %58, %59, %60, %61, %62, %63, %64, %65, %66, %67, %68, %69, %70, %71, %72, %73, %74, %75, %76, %77, %78, %79, %80, %81, %82, %83, %84, %85, %86, %87, %88, %89, %90, %91, %92, %93, %94, %95, %96, %97, %98, %99, %100, %101, %102, %103, %104, %105, %106, %107, %108, %109, %110, %111, %112, %113, %114, %115, %116, %117, %118, %119}, "
    "%120, %121, p, 1, 1, 0, 0;\n}\n"
    : "+f"(d[0]), "+f"(d[1]), "+f"(d[2]), "+f"(d[3]), "+f"(d[4]), "+f"(d[5]), "+f"(d[6]), "+f"(d[7]), "+f"(d[8]), "+f"(d[9]), "+f"(d[10]), "+f"(d[11]), "+f"(d[12]), "+f"(d[13]), "+f"(d[14]), "+f"(d[15]), "+f"(d[16]), "+f"(d[17]), "+f"(d[18]), "+f"(d[19]), "+f"(d[20]), "+f"(d[21]), "+f"(d[22]), "+f"(d[23]), "+f"(d[24]), "+f"(d[25]), "+f"(d[26]), "+f"(d[27]), "+f"(d[28]), "+f"(d[29]), "+f"(d[30]), "+f"(d[31]), "+f"(d[32]), "+f"(d[33]), "+f"(d[34]), "+f"(d[35]), "+f"(d[36]), "+f"(d[37]), "+f"(d[38]), "+f"(d[39]), "+f"(d[40]), "+f"(d[41]), "+f"(d[42]), "+f"(d[43]), "+f"(d[44]), "+f"(d[45]), "+f"(d[46]), "+f"(d[47]), "+f"(d[48]), "+f"(d[49]), "+f"(d[50]), "+f"(d[51]), "+f"(d[52]), "+f"(d[53]), "+f"(d[54]), "+f"(d[55]), "+f"(d[56]), "+f"(d[57]), "+f"(d[58]), "+f"(d[59]), "+f"(d[60]), "+f"(d[61]), "+f"(d[62]), "+f"(d[63]), "+f"(d[64]), "+f"(d[65]), "+f"(d[66]), "+f"(d[67]), "+f"(d[68]), "+f"(d[69]), "+f"(d[70]), "+f"(d[71]), "+f"(d[72]), "+f"(d[73]), "+f"(d[74]), "+f"(d[75]), "+f"(d[76]), "+f"(d[77]), "+f"(d[78]), "+f"(d[79]), "+f"(d[80]), "+f"(d[81]), "+f"(d[82]), "+f"(d[83]), "+f"(d[84]), "+f"(d[85]), "+f"(d[86]), "+f"(d[87]), "+f"(d[88]), "+f"(d[89]), "+f"(d[90]), "+f"(d[91]), "+f"(d[92]), "+f"(d[93]), "+f"(d[94]), "+f"(d[95]), "+f"(d[96]), "+f"(d[97]), "+f"(d[98]), "+f"(d[99]), "+f"(d[100]), "+f"(d[101]), "+f"(d[102]), "+f"(d[103]), "+f"(d[104]), "+f"(d[105]), "+f"(d[106]), "+f"(d[107]), "+f"(d[108]), "+f"(d[109]), "+f"(d[110]), "+f"(d[111]), "+f"(d[112]), "+f"(d[113]), "+f"(d[114]), "+f"(d[115]), "+f"(d[116]), "+f"(d[117]), "+f"(d[118]), "+f"(d[119])
    : "l"(da), "l"(db), "r"(scale_d));
}
__device__ __forceinline__ void wgmma_n256_rs(float (&d)[128], uint32_t a0, uint32_t a1, uint32_t a2, uint32_t a3, uint64_t db, int scale_d) {
  asm volatile("{\n.reg .pred p;\nsetp.ne.b32 p, %133, 0;\n"
    "wgmma.mma_async.sync.aligned.m64n256k16.f32.bf16.bf16 "
    "{%0, %1, %2, %3, %4, %5, %6, %7, %8, %9, %10, %11, %12, %13, %14, %15, %16, %17, %18, %19, %20, %21, %22, %23, %24, %25, %26, %27, %28, %29, %30, %31, "
    "%32, %33, %34, %35, %36, %37, %38, %39, %40, %41, %42, %43, %44, %45, %46, %47, %48, %49, %50, %51, %52, %53, %54, %55, %56, %57, %58, %59, %60, %61, %62, %63, "
    "%64, %65, %66, %67, %68, %69, %70, %71, %72, %73, %74, %75, %76, %77, %78, %79, %80, %81, %82, %83, %84, %85, %86, %87, %88, %89, %90, %91, %92, %93, %94, %95, "
    "%96, %97, %98, %99, %100, %101, %102, %103, %104, %105, %106, %107, %108, %109, %110, %111, %112, %113, %114, %115, %116, %117, %118, %119, %120, %121, %122, %123, %124, %125, %126, %127}, "
    "{%128, %129, %130, %131}, %132, p, 1, 1, 0;\n}\n"
    : "+f"(d[0]), "+f"(d[1]), "+f"(d[2]), "+f"(d[3]), "+f"(d[4]), "+f"(d[5]), "+f"(d[6]), "+f"(d[7]),
      "+f"(d[8]), "+f"(d[9]), "+f"(d[10]), "+f"(d[11]), "+f"(d[12]), "+f"(d[13]), "+f"(d[14]), "+f"(d[15]),
      "+f"(d[16]), "+f"(d[17]), "+f"(d[18]), "+f"(d[19]), "+f"(d[20]), "+f"(d[21]), "+f"(d[22]), "+f"(d[23]),
      "+f"(d[24]), "+f"(d[25]), "+f"(d[26]), "+f"(d[27]), "+f"(d[28]), "+f"(d[29]), "+f"(d[30]), "+f"(d[31]),
      "+f"(d[32]), "+f"(d[33]), "+f"(d[34]), "+f"(d[35]), "+f"(d[36]), "+f"(d[37]), "+f"(d[38]), "+f"(d[39]),
      "+f"(d[40]), "+f"(d[41]), "+f"(d[42]), "+f"(d[43]), "+f"(d[44]), "+f"(d[45]), "+f"(d[46]), "+f"(d[47]),
      "+f"(d[48]), "+f"(d[49]), "+f"(d[50]), "+f"(d[51]), "+f"(d[52]), "+f"(d[53]), "+f"(d[54]), "+f"(d[55]),
      "+f"(d[56]), "+f"(d[57]), "+f"(d[58]), "+f"(d[59]), "+f"(d[60]), "+f"(d[61]), "+f"(d[62]), "+f"(d[63]),
      "+f"(d[64]), "+f"(d[65]), "+f"(d[66]), "+f"(d[67]), "+f"(d[68]), "+f"(d[69]), "+f"(d[70]), "+f"(d[71]),
      "+f"(d[72]), "+f"(d[73]), "+f"(d[74]), "+f"(d[75]), "+f"(d[76]), "+f"(d[77]), "+f"(d[78]), "+f"(d[79]),
      "+f"(d[80]), "+f"(d[81]), "+f"(d[82]), "+f"(d[83]), "+f"(d[84]), "+f"(d[85]), "+f"(d[86]), "+f"(d[87]),
      "+f"(d[88]), "+f"(d[89]), "+f"(d[90]), "+f"(d[91]), "+f"(d[92]), "+f"(d[93]), "+f"(d[94]), "+f"(d[95]),
      "+f"(d[96]), "+f"(d[97]), "+f"(d[98]), "+f"(d[99]), "+f"(d[100]), "+f"(d[101]), "+f"(d[102]), "+f"(d[103]),
      "+f"(d[104]), "+f"(d[105]), "+f"(d[106]), "+f"(d[107]), "+f"(d[108]), "+f"(d[109]), "+f"(d[110]), "+f"(d[111]),
      "+f"(d[112]), "+f"(d[113]), "+f"(d[114]), "+f"(d[115]), "+f"(d[116]), "+f"(d[117]), "+f"(d[118]), "+f"(d[119]),
      "+f"(d[120]), "+f"(d[121]), "+f"(d[122]), "+f"(d[123]), "+f"(d[124]), "+f"(d[125]), "+f"(d[126]), "+f"(d[127])
    : "r"(a0), "r"(a1), "r"(a2), "r"(a3), "l"(db), "r"(scale_d));
}
__device__ __forceinline__ void wgmma_n128(float (&d)[64], uint64_t da, uint64_t db, int scale_d = 1) {
  asm volatile("{\n.reg .pred p;\nsetp.ne.b32 p, %66, 0;\n"
    "wgmma.mma_async.sync.aligned.m64n128k16.f32.bf16.bf16 "
    "{%0, %1, %2, %3, %4, %5, %6, %7, %8, %9, %10, %11, %12, %13, %14, %15, %16, %17, %18, %19, %20, %21, %22, %23, %24, %25, %26, %27, %28, %29, %30, %31, %32, %33, %34, %35, %36, %37, %38, %39, %40, %41, %42, %43, %44, %45, %46, %47, %48, %49, %50, %51, %52, %53, %54, %55, %56, %57, %58, %59, %60, %61, %62, %63}, "
    "%64, %65, p, 1, 1, 0, 0;\n}\n"
    : "+f"(d[0]), "+f"(d[1]), "+f"(d[2]), "+f"(d[3]), "+f"(d[4]), "+f"(d[5]), "+f"(d[6]), "+f"(d[7]), "+f"(d[8]), "+f"(d[9]), "+f"(d[10]), "+f"(d[11]), "+f"(d[12]), "+f"(d[13]), "+f"(d[14]), "+f"(d[15]), "+f"(d[16]), "+f"(d[17]), "+f"(d[18]), "+f"(d[19]), "+f"(d[20]), "+f"(d[21]), "+f"(d[22]), "+f"(d[23]), "+f"(d[24]), "+f"(d[25]), "+f"(d[26]), "+f"(d[27]), "+f"(d[28]), "+f"(d[29]), "+f"(d[30]), "+f"(d[31]), "+f"(d[32]), "+f"(d[33]), "+f"(d[34]), "+f"(d[35]), "+f"(d[36]), "+f"(d[37]), "+f"(d[38]), "+f"(d[39]), "+f"(d[40]), "+f"(d[41]), "+f"(d[42]), "+f"(d[43]), "+f"(d[44]), "+f"(d[45]), "+f"(d[46]), "+f"(d[47]), "+f"(d[48]), "+f"(d[49]), "+f"(d[50]), "+f"(d[51]), "+f"(d[52]), "+f"(d[53]), "+f"(d[54]), "+f"(d[55]), "+f"(d[56]), "+f"(d[57]), "+f"(d[58]), "+f"(d[59]), "+f"(d[60]), "+f"(d[61]), "+f"(d[62]), "+f"(d[63])
    : "l"(da), "l"(db), "r"(scale_d));
}
template<int N> __device__ __forceinline__ void fence_acc(float (&d)[N]) {
#pragma unroll
  for (int i = 0; i < N; i++) asm volatile("" : "+f"(d[i]) :: "memory");
}

template<int N, int I = 0, class F> __device__ __forceinline__ void static_for(F&& f) {
  if constexpr (I < N) { f(std::integral_constant<int, I>()); static_for<N, I + 1>(f); }
}

__device__ __forceinline__ void ldsm_x4_t(uint32_t addr, uint32_t& a, uint32_t& b, uint32_t& c, uint32_t& d) {
  asm volatile("ldmatrix.sync.aligned.m8n8.x4.trans.shared.b16 {%0, %1, %2, %3}, [%4];" : "=r"(a), "=r"(b), "=r"(c), "=r"(d) : "r"(addr));
}
__device__ __forceinline__ void sts128(uint32_t addr, uint32_t a, uint32_t b, uint32_t c, uint32_t d) {
  asm volatile("st.shared.v4.b32 [%0], {%1, %2, %3, %4};" :: "r"(addr), "r"(a), "r"(b), "r"(c), "r"(d));
}
__device__ __forceinline__ void mma16816(float (&c)[4], uint32_t a0, uint32_t a1, uint32_t a2, uint32_t a3, uint32_t b0, uint32_t b1) {
  asm volatile("mma.sync.aligned.m16n8k16.row.col.f32.bf16.bf16.f32 {%0, %1, %2, %3}, {%4, %5, %6, %7}, {%8, %9}, {%0, %1, %2, %3};"
      : "+f"(c[0]), "+f"(c[1]), "+f"(c[2]), "+f"(c[3]) : "r"(a0), "r"(a1), "r"(a2), "r"(a3), "r"(b0), "r"(b1));
}
__device__ __forceinline__ void mma1688(float (&c)[4], uint32_t a0, uint32_t a1, uint32_t b0) {
  asm volatile("mma.sync.aligned.m16n8k8.row.col.f32.bf16.bf16.f32 {%0, %1, %2, %3}, {%4, %5}, {%6}, {%0, %1, %2, %3};"
      : "+f"(c[0]), "+f"(c[1]), "+f"(c[2]), "+f"(c[3]) : "r"(a0), "r"(a1), "r"(b0));
}
__device__ __forceinline__ void pin(uint32_t& v) { asm volatile("shfl.sync.bfly.b32 %0, %0, 0, 0x1f, 0xffffffff;" : "+r"(v)); }
template<class T> __device__ __forceinline__ void pin(T*& v) {
  uint32_t lo = (uint32_t)(uint64_t)v, hi = (uint32_t)((uint64_t)v >> 32);
  pin(lo); pin(hi);
  v = (T*)(((uint64_t)hi << 32) | lo);
}
__device__ __forceinline__ float sel4(int q, float a, float b, float c, float d) {
  float r;
  asm("{\n.reg .pred p, o;\n.reg .f32 x, y;\n.reg .b32 t;\nand.b32 t, %1, 1;\nsetp.ne.b32 p, t, 0;\nsetp.gt.s32 o, %1, 1;\n"
      "selp.f32 x, %3, %2, p;\nselp.f32 y, %5, %4, p;\nselp.f32 %0, y, x, o;\n}\n" : "=f"(r) : "r"(q), "f"(a), "f"(b), "f"(c), "f"(d));
  return r;
}
__device__ __forceinline__ uint32_t bfma2(uint32_t a, uint32_t b, uint32_t c) { uint32_t r; asm("fma.rn.bf16x2 %0, %1, %2, %3;" : "=r"(r) : "r"(a), "r"(b), "r"(c)); return r; }
__device__ __forceinline__ void tma_load_5d(uint32_t dst, const CUtensorMap* tm, uint32_t bar, int c0) {
  asm volatile("cp.async.bulk.tensor.5d.shared::cluster.global.mbarrier::complete_tx::bytes [%0], [%1, {%3, %4, %4, %4, %4}], [%2];"
    :: "r"(dst), "l"(tm), "r"(bar), "r"(c0), "r"(0) : "memory");
}
__device__ __forceinline__ void tma_store_5d(const CUtensorMap* tm, uint32_t src, int c0, int c3, int c4) {
  asm volatile("cp.async.bulk.tensor.5d.global.shared::cta.bulk_group [%0, {%2, %3, %3, %4, %5}], [%1];" :: "l"(tm), "r"(src), "r"(c0), "r"(0), "r"(c3), "r"(c4) : "memory");
}
__device__ __forceinline__ float rcp_fast(float x) { float r; asm("rcp.approx.ftz.f32 %0, %1;" : "=f"(r) : "f"(x)); return r; }
__device__ __forceinline__ float sigmoid_fast(float x) { float e; asm("ex2.approx.ftz.f32 %0, %1;" : "=f"(e) : "f"(x * -1.4426950408889634f)); return rcp_fast(1.f + e); }
__device__ __forceinline__ float sqrt_fast(float x) { float r; asm("sqrt.approx.ftz.f32 %0, %1;" : "=f"(r) : "f"(x)); return r; }
__device__ __forceinline__ float ln_sd(float var) { return bf16r(sqrt_fast(bf16r(bf16r(fmaxf(var, 0.f)) + 1e-5f))); }
__device__ __forceinline__ uint32_t norm2(uint32_t h, uint32_t neg_mean2, float inv_sd) {
  const uint32_t d = badd2(h, neg_mean2);
  return pack_bf16(bf_lo(d) * inv_sd, bf_hi(d) * inv_sd);
}
template<int N> __device__ __forceinline__ void delay_clk() {
  if constexpr (N > 0) { const uint32_t t0 = clock(); while ((uint32_t)clock() - t0 < N) {} }
}
__device__ __forceinline__ void put_xstat(uint32_t rs, uint32_t exb, int col, uint32_t mean_rstd, int m) {
  smem_at<uint16_t>(rs + ((col & 7) >> 1) * 144 + (col >> 3) * 4 + (col & 1) * 2) = (uint16_t)(mean_rstd ^ (m << 15));
  const uint32_t nm = (mean_rstd >> 16) ^ 0x8000u;
  smem_at<uint4>(exb + (col >> 3) * 256 + (col & 7) * 16) = make_uint4(nm | (nm << 16), nm, 0, 0);
  smem_at<uint4>(exb + (col >> 3) * 256 + 128 + (col & 7) * 16) = make_uint4(0, 0, 0, 0);
}
__device__ __forceinline__ void put_dsum(uint32_t exa, int e, float c) {
  const float hi = bf16r(c), mid = bf16r(c - hi), lo = bf16r((c - hi) - mid);
  smem_at<uint4>(exa + (e >> 3) * 256 + (e & 7) * 16) = make_uint4((__float_as_uint(hi) >> 16) | (__float_as_uint(mid) & 0xFFFF0000u), __float_as_uint(lo) >> 16, 0, 0);
  smem_at<uint4>(exa + (e >> 3) * 256 + 128 + (e & 7) * 16) = make_uint4(0, 0, 0, 0);
}
__host__ __device__ constexpr int min_c(int a, int b) { return a < b ? a : b; }
template<int V> using IC = std::integral_constant<int, V>;

#define CT(slot) do {} while (0)
#define PT(slot) do {} while (0)

template<int MAP>
__global__ void __cluster_dims__(2, 1, 1) __launch_bounds__(384, 1)
fnet_moe_kernel(const __grid_constant__ Params p) {
  constexpr int NX = MAP == 0 ? NX0 : 256;
  constexpr int G1_BYTES = A_BYTES + NX * 128;
  uint32_t sb;
  asm volatile("mov.u32 %0, %1;" : "=r"(sb) : "r"(smem_u32(smem_raw)));
  const int m = blockIdx.x & 1;
  int tau, eps;
  bool helper = false;
  if (MAP == 0) {
    uint32_t smid;
    asm volatile("mov.u32 %0, %%smid;" : "=r"(smid));
    const int c = smid >> 1, e7 = ((c - 32) * 37) >> 8;
    helper = c == 60 || c == 61;
    tau = c < 32 ? (c & 7) : (c < 60 ? c - 31 - 7 * e7 : 0);
    eps = c < 32 ? (c >> 3) : (c < 60 ? 4 + e7 : c - 58);
  } else {
    tau = (blockIdx.x >> 1) & 7; eps = blockIdx.x >> 4;
  }
  const int cid = tau * 16 + eps * 2 + m;
  const bool moe = tau > 0;
  auto BAR = [&](int i) { return sb + OFF_BAR + 8 * i; };
  const CUtensorMap* tmD = m ? &p.tmD1 : &p.tmD0;
  const uint64_t pol_ef = policy_evict_first();
#define LOAD_STREAM(d, tm, bar, c0, c1) tma_load_2d_hint(d, tm, bar, c0, c1, pol_ef)
  auto helper_load = [&](int k) {
    const uint32_t sa = sb + slot_of(k) * ST_BYTES, bar = BAR(B_FULL + slot_of(k));
    const CUtensorMap* tm = eps == 3 ? &p.tmD1 : &p.tmD0;
    tma_load_5d(sa, &p.tmXh, bar, (k & 15) * 64);
    tma_load_2d(sa + A_BYTES, tm, bar, (k & 15) * 64, m * 512 + (k >> 4) * 256);
    tma_load_2d(sa + A_BYTES + 16384, tm, bar, (k & 15) * 64, m * 512 + (k >> 4) * 256 + 128);
  };
  if (threadIdx.x < 32 && elect_one()) {
    mbar_init(BAR(B_FULL), 1);
    asm volatile("fence.mbarrier_init.release.cluster;" ::: "memory");
    if (!helper) {
      tma_load_2d(sb + A_BYTES, &p.tmX, BAR(B_FULL), 0, tau * 256);
      tma_load_2d(sb, tmD, BAR(B_FULL), 0, eps * 128);
    }
    PT(52);
#pragma unroll
    for (int k = 1; k < 4; k++) mbar_init(BAR(B_FULL + k), 1);
    asm volatile("fence.mbarrier_init.release.cluster;" ::: "memory");
#pragma unroll
    for (int k = 0; k < 4; k++) mbar_expect_tx(BAR(B_FULL + k), helper ? ST_BYTES : G1_BYTES);
    if (!helper) {
#pragma unroll
      for (int k = 1; k < 4; k++) {
        tma_load_2d(sb + k * ST_BYTES + A_BYTES, &p.tmX, BAR(B_FULL + k), k * 64, tau * 256);
        LOAD_STREAM(sb + k * ST_BYTES, tmD, BAR(B_FULL + k), k * 64, eps * 128);
      }
    } else {
#pragma unroll 1
      for (int k = 0; k < 4; k++) helper_load(k);
    }
    PT(0);
  }
  __syncwarp();
  const int warp = __shfl_sync(0xffffffffu, threadIdx.x >> 5, 0);
  if (warp == 8) {
    if (elect_one()) {
#pragma unroll
      for (int b = B_EMPTY; b < B_COUNT; b++)
        mbar_init(BAR(b), b < B_EPI ? 2 : (b == B_EPI || b == B_EPI0B) ? 4 : (b < B_STD || b == B_OUT) ? 8 : (b == B_STAT || b == B_XS) ? 3 : 1);
      asm volatile("fence.mbarrier_init.release.cluster;" ::: "memory");
      mbar_expect_tx(BAR(B_XCH), 32768);
      SM_(uint32_t, OFF_SEEN) = 0;
    }
  }
  __syncthreads();

  if (warp >= 8) {
    reg_dec<REG_P>();
    asm volatile("barrier.cluster.arrive.relaxed.aligned;" ::: "memory");
    const int abrow = m * 1024 + eps * 128;
    const int f0 = (cid - 16) * 32;
    const CUtensorMap* tmWM = m ? &p.tmWM1 : &p.tmWM0;
    auto side_first = [&](int k) {
      if (NX < 256 && k == MINI_LOAD_K) {
        static_assert(NX == 256 || (mr_k(NREG_H) == MINI_LOAD_K && (NREG_H & 1) == 1), "second half of the staging buffer must be free");
        mbar_wait(BAR(B_STD + 3), 0);
        uint32_t n = 0;
        while (!((*(volatile uint32_t*)&SM_(uint32_t, OFF_SEEN) >> (4 * tau + 1)) & 1) && ++n < SPIN_LIMIT * 16) {}
        if (elect_one()) {
          mbar_expect_tx(BAR(B_A20), 12288);
          tma_load_2d(sb + OFF_MINI, &p.tmAbM, BAR(B_A20), tau * 256 + 240, abrow);
          LOAD_STREAM(sb + OFF_MINI + 4096, tmWM, BAR(B_A20), tau * 256 + 240, tau * 256 + m * 128);
          LOAD_STREAM(sb + OFF_MINI + 8192, tmWM, BAR(B_A20), tau * 256 + 240, tau * 256 + (1 - m) * 128);
        }
      }
    };
    auto side = [&](int k) {
      if (NX < 256 && k == MINI_PF_K && elect_one()) tma_prefetch_2d(tmWM, tau * 256 + 240, tau * 256 + (eps & 1) * 128);
      if (!moe) return;
      const int i = k - MR_K0, r6 = i / MR_P, u = i - MR_P * r6, h = 2 * r6 + (u >> 1);
      if (i >= 0 && u < 4 && h < NREG_H) {
        if (h < 2) mbar_wait(BAR(B_STD + 2 + h), 0);
        if (elect_one()) {
          if (!(u & 1)) mbar_expect_tx(BAR(B_MR + (h & 1)), 16384);
          LOAD_STREAM(sb + OFF_XCH + u * 8192, (u & 1) ? &p.tmU : &p.tmG, BAR(B_MR + (h & 1)), f0, h * 128);
        }
      }
      if (k >= 46 && elect_one()) {
        static_assert(mr_k(NREG_H + 1) <= 47 && MINI_K + 4 <= 46, "staging buffer must be free");
        LOAD_STREAM(sb + round_off(NREG_H + k - 46), &p.tmG, BAR(B_GU), f0, (NREG_H + k - 46) * 128);
        LOAD_STREAM(sb + round_off(NREG_H + k - 46) + 8192, &p.tmU, BAR(B_GU), f0, (NREG_H + k - 46) * 128);
      }
      if (k >= PF_K1 && !(k & 1) && elect_one()) {
        const int j = PF_N0 + ((k - PF_K1) >> 1);
        if (j < 8) tma_prefetch_2d(m ? &p.tmU : &p.tmG, f0, j * 128);
        else if (j < 12) asm volatile("cp.async.bulk.prefetch.L2.global [%0], %1;" :: "l"(p.wdown + (size_t)f0 * 1024 + (j - 8) * 8192), "r"(16384) : "memory");
      }
    };
    if (MAP == 0 && helper) {
      if (warp == 8) {
#pragma unroll 1
        for (int k = 4; k < 32; k++) {
          mbar_wait(BAR(B_EMPTY + slot_of(k)), (use_of(k) & 1) ^ 1);
          if (elect_one()) { mbar_expect_tx(BAR(B_FULL + slot_of(k)), ST_BYTES); helper_load(k); }
        }
      } else {
        const int i0 = threadIdx.x - 288, lane = threadIdx.x & 31, col0 = (eps - 2) * 8 + m * 4;
        __nanosleep(HELPER_NS);
        const uint32_t tag = ld_relaxed32(&p.s->epoch) + 1;
        if (i0 < 8) pkt_st128(&p.s->hflag[col0 * 2 + i0], 0, 0, 0, 0);
        SM_(uint32_t, OFF_TAG) = tag;
#pragma unroll 1
        for (int j0 = i0; j0 < 768; j0 += 384) {
          uint2 v[4]; uint32_t n = 0;
          while (true) {
#pragma unroll
            for (int z = 0; z < 4; z++) {
              const int j = j0 + 96 * z;
              v[z] = pkt_ld64(p.s->xstat + (j < 128 ? 256 * (j >> 4) + 240 + 2 * (j & 6) + ((j >> 2) & 2) + (j & 1)
                                          : j < 640 ? 2048 + col0 * 128 + j - 128 : (j - 640) * 16));
            }
            if (__all_sync(0xffffffffu, v[0].y == tag && v[1].y == tag && v[2].y == tag && v[3].y == tag) || ++n > SPIN_LIMIT) break;
            __nanosleep(300);
          }
#pragma unroll
          for (int z = 0; z < 4; z++) {
            const int j = j0 + 96 * z;
            if (j < 128) put_xstat(sb + OFF_RS, sb + OFF_XCH + 16384, j, v[z].x, eps - 2);
            else if (j < 640) put_dsum(sb + OFF_XCH, j - 128, __uint_as_float(v[z].x));
          }
        }
        fence_async_smem();
        __syncwarp();
        if (lane == 0) mbar_arrive(BAR(B_STAT));
      }
    } else if (warp == 8) {
      const CUtensorMap* tmW = m ? &p.tmW1 : &p.tmW0;
      const int tA = tau * 256 + m * 128, tB = tau * 256 + (1 - m) * 128;
      auto wait_slot = [&](int k) {
        mbar_wait(BAR(B_EMPTY + slot_of(k)), (use_of(k) & 1) ^ 1);
        PT(64 + k);
      };
#pragma unroll 1
      for (int k = 4; k < 24; k++) {
        const int s = slot_of(k);
        const uint32_t sa = sb + s * ST_BYTES, sbb = sa + A_BYTES;
        const int kb = kblock(tau, k - 16);
        wait_slot(k);
        if (elect_one()) {
          mbar_expect_tx(BAR(B_FULL + s), k < 16 ? G1_BYTES : (k >> 1) == 9 ? B_BYTES : k == 20 ? ST_BYTES - 8192 : ST_BYTES);
          if (k < 16) {
            LOAD_STREAM(sa, tmD, BAR(B_FULL + s), k * 64, eps * 128);
            tma_load_2d(sbb, &p.tmX, BAR(B_FULL + s), k * 64, tau * 256);
          } else {
            LOAD_STREAM(sbb, tmW, BAR(B_FULL + s), kb * 64, tA);
            LOAD_STREAM(sbb + 16384, tmW, BAR(B_FULL + s), kb * 64, tB);
            if (k < 18) {
              tma_load_2d(sa, &p.tmXr, BAR(B_FULL + s), eps * 128, tA + s * 64);
              tma_load_2d(sa + 8192, &p.tmXr, BAR(B_FULL + s), eps * 128 + 64, tA + s * 64);
            }
          }
          if (k == PUB_K1) mbar_arrive(BAR(B_LATE));
          if (k >= WPF_K0 && k < WPF_K0 + WPF_N && (eps >> 1) == ((k - WPF_K0) & 3))
            tma_prefetch_2d(tmW, kblock(tau, k - WPF_K0) * 64, tau * 256 + (eps & 1) * 128);
          if (moe && k >= PF_K0 && k < PF_K0 + 2 * PF_N0 && !(k & 1)) tma_prefetch_2d(m ? &p.tmU : &p.tmG, f0, (k - PF_K0) * 64);
        }
      }
      uint32_t seen = 0;
#pragma unroll 1
      for (int k = 24; k < 48; k++) {
        const int s = slot_of(k);
        const uint32_t sa = sb + s * ST_BYTES, sbb = sa + A_BYTES;
        const int kb = kblock(tau, k - 16);
        const uint32_t need = (1u << kb) | ((kb & 3) == 3 ? 2u << (4 * tau) : 0u);
        wait_slot(k);
        side_first(k);
        if (elect_one()) {
          mbar_expect_tx(BAR(B_FULL + s), ST_BYTES);
          LOAD_STREAM(sbb, tmW, BAR(B_FULL + s), kb * 64, tA);
          LOAD_STREAM(sbb + 16384, tmW, BAR(B_FULL + s), kb * 64, tB);
        }
        uint32_t n = 0;
        while ((seen & need) != need && ++n < SPIN_LIMIT * 16) seen = *(volatile uint32_t*)&SM_(uint32_t, OFF_SEEN);
        if (elect_one()) tma_load_2d(sa, &p.tmAbL, BAR(B_FULL + s), kb * 64, abrow);
        side(k);
      }
      if (moe) {
        mbar_wait(BAR(B_EMPTY + 0), 1);
        if (elect_one()) { mbar_expect_tx(BAR(B_GU), (8 - NREG_H) * 16384); mbar_expect_tx(BAR(B_DN), 65536); }
#pragma unroll 1
        for (int i = 0; i < 10 - NREG_H; i++) {
          if (i == 3) mbar_wait(BAR(B_EMPTY + 1), 1);
          if (i == 4) {
            mbar_wait(BAR(B_EMPTY + 2), 1);
            mbar_wait(BAR(B_XCH), 0);
            PT(53);
          }
          const uint32_t dst = sb + late_off(i);
          if (elect_one()) {
            if (i < 6 - NREG_H) {
              LOAD_STREAM(dst, &p.tmG, BAR(B_GU), f0, (NREG_H + 2 + i) * 128);
              LOAD_STREAM(dst + 8192, &p.tmU, BAR(B_GU), f0, (NREG_H + 2 + i) * 128);
            } else {
#pragma unroll
              for (int b = 0; b < 4; b++) LOAD_STREAM(dst + b * 4096, &p.tmDn, BAR(B_DN), (4 * (i - 6 + NREG_H) + b) * 64, f0);
            }
          }
          const long long t0 = clock64();
          while (i < 9 - NREG_H && clock64() - t0 < MOE_PACE_CLK) {}
        }
      }
      const int lane = threadIdx.x & 31;
      mbar_wait(BAR(B_OUT), 0);
      const uint32_t km = SM_(uint32_t, OFF_WKEY + (lane & 7) * 8);
      const uint32_t bk = __reduce_max_sync(0xffffffffu, km);
      const int ww = __ffs(__ballot_sync(0xffffffffu, km == bk)) - 1;
#pragma unroll 1
      for (int i = 1; i <= 8; i++) {
        const int W = (ww + i) & 7;
        if (i == 8) {
          mbar_wait(BAR(B_XS), 0);
          if (SM_(uint32_t, OFF_KV) == bk) {
#pragma unroll 2
            for (int j = lane; j < 256; j += 32) {
              const int rho = j >> 4, row = (tau * 2 + m) * 128 + 32 * (W >> 1) + 8 * ((rho & 7) >> 1) + 4 * (W & 1) + 2 * (rho >> 3) + (rho & 1);
              const uint4 v = lds128_v(sb + OFF_OUT + (j & 8) * 2048 + (16 * W + rho) * 128 + (((j ^ rho) & 7) << 4));
              if (row != 0xFFFF - (int)(bk & 0xFFFFu))
                asm volatile("st.global.v4.b32 [%0], {%1, %2, %3, %4};" :: "l"(p.out + (size_t)row * 1024 + eps * 128 + (j & 15) * 8), "r"(v.x), "r"(v.y), "r"(v.z), "r"(v.w));
            }
            break;
          }
        }
        if (lane == 0) {
          tma_store_5d(&p.tmOut, sb + OFF_OUT + W * 2048, eps * 128, 2 * (W & 1), tau * 8 + m * 4 + (W >> 1));
          tma_store_5d(&p.tmOut, sb + OFF_OUT + 16384 + W * 2048, eps * 128 + 64, 2 * (W & 1), tau * 8 + m * 4 + (W >> 1));
        }
        const long long t0 = clock64();
        while (i < 7 && clock64() - t0 < OUT_PACE_CLK) {}
      }
      if (lane == 0) { bulk_commit(); bulk_wait_all(); }
      PT(22);
    } else {
      const int a = warp - 9;
      const int lane = threadIdx.x & 31;
      auto stage = [&](const bf16* src, int g) {
        if (elect_one()) {
          mbar_expect_tx(BAR(B_AUX + g), 16384);
          bulk_load(sb + OFF_XCH + g * 16384, src + g * 8192, 16384, BAR(B_AUX + g));
        }
      };
      mbar_wait(BAR(B_FULL + AUX_AFTER), 0);
      if (a == 0) PT(1);
      if (a < 2) stage(p.x + (size_t)cid * 16 * 1024, a);
      const uint32_t tag = ld_relaxed32(&p.s->epoch) + 1;
      if (a == 2 && lane < 16) asm volatile("prefetch.global.L2 [%0];" :: "l"(p.wr + lane * 64));
#pragma unroll 1
      for (int it = 0; it < 4; it++) {
        const int g = it & 1;
        mbar_wait(BAR(B_AUX + g), it >> 1);
        if (a == 0) PT(2 + it);
        const uint32_t ad = sb + OFF_XCH + g * 16384 + (lane >> 2) * 2048;
        float s0 = 0.f, s1 = 0.f, q0 = 0.f, q1 = 0.f;
        auto row = [&](auto sq) {
#pragma unroll
          for (int i = 0; i < 11; i++) {
            if (i == 10 && a == 2) break;
            const uint4 v = lds128_v(ad + (((a * 44 + 4 * i + lane) & 127) << 4));
            const uint32_t ww[4] = {v.x, v.y, v.z, v.w};
#pragma unroll
            for (int z = 0; z < 4; z++) {
              const float d0 = bf_lo(ww[z]), d1 = bf_hi(ww[z]);
              s0 += d0; s1 += d1;
              if (decltype(sq)::value) { q0 = fmaf(d0, d0, q0); q1 = fmaf(d1, d1, q1); }
            }
          }
        };
        if (it < 2) row(IC<1>()); else row(IC<0>());
        s0 += s1; q0 += q1;
#pragma unroll
        for (int o = 1; o < 4; o <<= 1) { s0 += __shfl_xor_sync(0xffffffffu, s0, o); q0 += __shfl_xor_sync(0xffffffffu, q0, o); }
        if ((lane & 3) == 0) SM_(float2, OFF_PUB + a * 256 + it * 64 + (lane >> 2) * 8) = make_float2(s0, q0);
        if (it != 2) bar_sync(NB_AUX, 96);
        if (it < 2 && a == 2) stage(cid < 64 ? p.Dre + (size_t)cid * 16 * 1024 : p.Dim + (size_t)(cid - 64) * 16 * 1024, g);
      }
      if (a == 1) {
        const float2 v0 = SM_(float2, OFF_PUB + lane * 8), v1 = SM_(float2, OFF_PUB + 256 + lane * 8), v2 = SM_(float2, OFF_PUB + 512 + lane * 8);
        const float s = v0.x + v1.x + v2.x, mean = s * (1.f / 1024.f);
        const float rs = rcp_fast(ln_sd((v0.y + v1.y + v2.y) * (1.f / 1024.f) - mean * mean));
        pkt_st64((lane < 16 ? p.s->xstat : p.s->dsum) + cid * 16 + (lane & 15), lane < 16 ? pack_bf16(rs, mean) : __float_as_uint(s), tag);
        PT(6);
      }
      if (a == 2) {
        float s = 0.f;
#pragma unroll
        for (int q = 0; q < 4; q++) {
          const uint4 v = ldg_nc128(p.wr + (q * 32 + lane) * 8);
          s += ((bf_lo(v.x) + bf_hi(v.x)) + (bf_lo(v.y) + bf_hi(v.y))) + ((bf_lo(v.z) + bf_hi(v.z)) + (bf_lo(v.w) + bf_hi(v.w)));
          const int ch = q * 32 + lane - eps * 16;
          if (ch >= 0 && ch < 16) {
            SM_(uint32_t, OFF_WR + ch * 4) = v.x; SM_(uint32_t, OFF_WR + 80 + ch * 4) = v.y;
            SM_(uint32_t, OFF_WR + 160 + ch * 4) = v.z; SM_(uint32_t, OFF_WR + 240 + ch * 4) = v.w;
          }
        }
        s = warp_sum(s);
        if (lane == 0) { SM_(float, OFF_WSUM) = s; SM_(uint32_t, OFF_TAG) = tag; }
      }
      if (a < 2) __nanosleep(GATHER_NS);
      {
        const int i0 = a * 32 + lane;
        uint2 v[3], c0, c1; uint32_t n = 0;
        const uint2* dp = &p.s->dsum[abrow];
        while (true) {
#pragma unroll
          for (int q = 0; q < 3; q++) v[q] = pkt_ld64(&p.s->xstat[tau * 256 + min(i0 + 96 * q, 255)]);
          c0 = pkt_ld64(dp + i0); c1 = pkt_ld64(dp + min(i0 + 96, 127));
          if (__all_sync(0xffffffffu, v[0].y == tag && v[1].y == tag && v[2].y == tag && c0.y == tag && c1.y == tag) || ++n > SPIN_LIMIT) break;
          __nanosleep(200);
        }
#pragma unroll
        for (int q = 0; q < 3; q++) put_xstat(sb + OFF_RS, sb + OFF_EXB, min(i0 + 96 * q, 255), v[q].x, m);
        put_dsum(sb + OFF_EXA, i0, __uint_as_float(c0.x));
        put_dsum(sb + OFF_EXA, min(i0 + 96, 127), __uint_as_float(c1.x));
        fence_async_smem();
      }
      __syncwarp();
      if (lane == 0) mbar_arrive(BAR(B_STAT));
      if (a == 0) PT(7);
      if (a == 0) {
        const int sg = (lane >> 2) == tau ? sigma_of(tau, 0) : lane >> 2;
        const uint32_t* flg = reinterpret_cast<const uint32_t*>(&p.s->abflag[((eps * 2 + m) * 8 + sg) * 2]) + ((lane >> 2) == tau ? 4 : lane & 3);
        if (NX < 256 && lane == 4 * tau + 1) flg = reinterpret_cast<const uint32_t*>(&p.s->hflag[(m * 8 + eps) * 2]);
        uint32_t seen = 0;
        auto until = [&](int tile) {
          uint32_t n = 0;
          while (!((seen >> (4 * tile)) & 1) && ++n < SPIN_LIMIT) seen = __ballot_sync(0xffffffffu, ld_relaxed32(flg) == tag);
        };
        const int s0 = sigma_of(tau, 0), s1 = sigma_of(tau, 1), s2 = sigma_of(tau, 2), s3 = sigma_of(tau, 3);
        mbar_wait(BAR(B_EPI), 0);
        mbar_wait(BAR(B_FULL + 0), 0);
        mbar_wait(BAR(B_FULL + 1), 0);
        if (elect_one()) mbar_expect_tx(BAR(B_A20), 8192);
        mbar_wait(BAR(B_STDA), 0);
        PT(49);
        until(tau);
        mbar_wait(BAR(B_EPI0B), 0);
        PT(48);
        if (elect_one()) tma_load_2d(sb + OFF_XCH, &p.tmAbS, BAR(B_FULL + 0), s0 * 256, abrow);
        mbar_wait(BAR(B_FULL + 2), 0);
        mbar_wait(BAR(B_STD + 0), 0);
        until(s0);
        PT(16);
        if (elect_one()) tma_load_2d(sb + OFF_XCH + 8192, &p.tmAbS, BAR(B_A20), s0 * 256, abrow + 64);
        until(s1);
        PT(17);
        if (elect_one()) tma_load_2d(sb + OFF_XCH + 16384, &p.tmAbL, BAR(B_FULL + 1), s1 * 256, abrow);
        until(s2);
        PT(18);
        if (elect_one()) {
          tma_load_2d(sb + 2 * ST_BYTES, &p.tmAbL, BAR(B_FULL + 2), s2 * 256, abrow);
          mbar_arrive(BAR(B_PUB1));
        }
        until(s3);
        mbar_wait(BAR(B_FULL + 3), 0);
        mbar_wait(BAR(B_STD + 1), 0);
        PT(19);
        if (elect_one()) tma_load_2d(sb + 3 * ST_BYTES, &p.tmAbL, BAR(B_FULL + 3), s3 * 256, abrow);
        uint32_t n = 0;
        while (true) {
          asm volatile("fence.proxy.async.global;" ::: "memory");
          *(volatile uint32_t*)&SM_(uint32_t, OFF_SEEN) = seen;
          if (seen == 0xFFFFFFFFu || ++n > SPIN_LIMIT) break;
          seen = __ballot_sync(0xffffffffu, ld_relaxed32(flg) == tag);
          __nanosleep(100);
        }
      } else {
        uint32_t* flag = reinterpret_cast<uint32_t*>(&p.s->abflag[((eps * 2 + m) * 8 + tau) * 2]);
        mbar_wait(BAR(a == 1 ? B_EPI : B_EPI0B), 0);
        if (a == 1) PT(8);
        if (lane == 0) {
          tma_store_2d(&p.tmAbS, sb + chunk_off(0, a - 1), tau * 256, abrow + (a - 1) * 64);
          bulk_commit();
          bulk_wait_all();
        }
        if (a == 2) mbar_wait(BAR(B_STDA), 0);
        if (lane == 0) {
          st_relaxed32(flag + (a == 1 ? 4 : 0), tag);
          mbar_arrive(BAR(a == 1 ? B_STDA : B_STD));
        }
        if (a == 2) PT(12);
        if (a == 1) {
          mbar_wait(BAR(B_EPI + 1), 0);
          mbar_wait(BAR(B_LATE), 0);
          mbar_wait(BAR(B_PUB1), 0);
          PT(9);
          if (lane == 0) {
            tma_store_2d(&p.tmAbS, sb + chunk_off(1, 0), tau * 256 + 64, abrow);
            tma_store_2d(&p.tmAbS, sb + chunk_off(1, 1), tau * 256 + 64, abrow + 64);
            bulk_commit();
            bulk_wait_all();
            st_relaxed32(flag + 1, tag);
            mbar_arrive(BAR(B_STD + 1));
          }
          PT(13);
        }
        auto copy_out = [&](int c) {
          mbar_wait(BAR(B_EPI + c), 0);
          PT(8 + c);
          bf16* dst = p.s->abT + (size_t)(abrow + (lane >> 3)) * 2048 + tau * 256 + c * 64 + (lane & 7) * 8;
          const uint32_t src = sb + chunk_off(c, 0) + (lane >> 3) * 128 + (((lane & 7) ^ (lane >> 3)) << 4);
          const uint32_t on = c * 64 + (lane & 7) * 8 < NX;
#pragma unroll 4
          for (int i = 0; i < 32; i++) {
            const uint4 v = lds128_v((src ^ ((i & 1) << 6)) + i * 512);
            asm volatile("{\n.reg .pred p;\nsetp.ne.b32 p, %5, 0;\n@p st.global.v4.b32 [%0], {%1, %2, %3, %4};\n}\n"
                         :: "l"(dst + i * 4 * 2048), "r"(v.x), "r"(v.y), "r"(v.z), "r"(v.w), "r"(on));
          }
          __syncwarp();
          if (lane == 0) mbar_arrive(BAR(B_STD + c));
        };
        if (a == 2) {
#pragma unroll 1
          for (int c = 2; c < 4; c++) copy_out(c);
          asm volatile("fence.acq_rel.gpu;" ::: "memory");
          __syncwarp();
          if (lane < 2) st_relaxed32(flag + 2 + lane, tag);
          PT(15);
        }
      }
      {
        mbar_wait(BAR(B_LATE), 1);
        const int grp = tau * 2 + m;
#pragma unroll 1
        for (int i = a; i < 14; i += 3) {
          uint4* dst = i < 8 ? &p.s->ypart[cid * 256 + i * 32 + lane] : i < 12 ? &p.s->hstat[(grp * 8 + eps) * 128 + (i - 8) * 32 + lane]
                     : i == 12 ? &p.s->cand[grp * 256 + eps * 32 + lane] : &p.s->key[(((lane >> 1) & 7) * 16 + grp) * 2 + (lane & 1)];
          if (i < 13 || eps == 0) pkt_st128(dst, 0, 0, 0, 0);
          __nanosleep(200);
        }
        __syncwarp();
        if (lane == 0) mbar_arrive(BAR(B_STAT));
      }
      {
        const uint4* kp = &p.s->key[(tau * 16 + (lane & 15)) * 2];
        const int i0 = a * 32 + lane;
        mbar_wait(BAR(B_KEY), 0);
        if (a == 0) PT(43);
        uint4 kq = pkt_ld128(kp), cv[3] = {};
        uint32_t n = 0, kv;
        int gspec = -1;
        while (true) {
          const bool ok = kq.y == tag && kq.w == tag;
          kv = __reduce_max_sync(0xffffffffu, ok ? kq.x : 0u);
          const int gs = (0xFFFF - (int)(kv & 0xFFFFu)) >> 7;
          const bool cok = gs == gspec && cv[0].y == tag && cv[0].w == tag && cv[1].y == tag && cv[1].w == tag && cv[2].y == tag && cv[2].w == tag;
          if (__all_sync(0xffffffffu, ok && cok) || ++n > SPIN_LIMIT) break;
          if (!ok) kq = pkt_ld128(kp);
          const bool spec = __popc(__ballot_sync(0xffffffffu, ok)) >= 2 * SPEC_MIN;
          if (!cok && spec) {
#pragma unroll
            for (int i = 0; i < 3; i++) cv[i] = pkt_ld128(&p.s->cand[gs * 256 + min(i0 + 96 * i, 255)]);
          }
          if (spec) gspec = gs;
        }
        if (a == 0) PT(45);
        const uint32_t ms = __shfl_sync(0xffffffffu, kq.z, gspec);
        const uint32_t nm = ((ms & 0xFFFFu) ^ 0x8000u) * 0x10001u;
        const float is = rcp_fast(bf_hi(ms));
#pragma unroll
        for (int i = 0; i < 3; i++) {
          const int j = min(i0 + 96 * i, 255);
          SM_(uint2, OFF_XSEL + j * 8) = make_uint2(norm2(cv[i].x, nm, is), norm2(cv[i].z, nm, is));
        }
#pragma unroll
        for (int i = 0; i < 3; i++) SM_(uint2, OFF_HSEL + min(i0 + 96 * i, 255) * 8) = make_uint2(cv[i].x, cv[i].z);
        SM_(uint32_t, OFF_KV) = kv;
        __syncwarp();
        if (lane == 0) mbar_arrive(BAR(B_XS));
      }
    }
    asm volatile("barrier.cluster.wait.aligned;" ::: "memory");
  } else {
    reg_inc<REG_C>();
    const int tid = __shfl_sync(0xffffffffu, threadIdx.x, threadIdx.x & 31), lane = tid & 31;
    const int w = warp >> 2, wi = warp & 3, t = tid & 127;
    const int g = lane >> 2, q = lane & 3;
    const int turn_me = NB_TURN0 + w, turn_other = NB_TURN1 - w;
    auto release = [&](int s) { if (t == 0) mbar_arrive(BAR(B_EMPTY + s)); };
    if (MAP == 0 && helper) {
      asm volatile("barrier.cluster.arrive.relaxed.aligned;" ::: "memory");
      float s0[64], s1[64];
#pragma unroll
      for (int i = 0; i < 64; i++) { s0[i] = 0.f; s1[i] = 0.f; }
      if (w == 1) bar_arrive(NB_TURN0, 256);
      uint32_t o[32][2] = {};
      const int col = (eps - 2) * 8 + m * 4 + w;
      auto put = [&](auto tc, uint32_t buf) {
        constexpr int tl = decltype(tc)::value;
#pragma unroll
        for (int i = 0; i < 4; i++)
          smem_at<uint2>(buf + ((i >> 1) * 64 + wi * 16 + (i & 1) * 8 + g) * 32 + ((q * 8) ^ ((g & 4) << 2))) = make_uint2(o[8 * i + tl][0], o[8 * i + tl][1]);
      };
      auto publish = [&](int c) { if (t == 0) { bulk_wait_all(); st_relaxed32(&p.s->hflag[c * 2], SM_(uint32_t, OFF_TAG)); } };
#pragma unroll 1
      for (int pass = 0; pass < 2; pass++) {
#pragma unroll 1
        for (int k = 16 * pass; k < 16 * pass + 16; k++) {
          const int s = slot_of(k);
          mbar_wait(BAR(B_FULL + s), use_of(k) & 1);
          bar_sync(turn_me, 256);
          const uint64_t da = make_desc(sb + s * ST_BYTES + A_BYTES + w * 16384), db = make_desc(sb + s * ST_BYTES);
          wgmma_fence();
#pragma unroll
          for (int kk = 0; kk < 4; kk++) {
            wgmma_n128(s0, da + kk * 2, db + kk * 2, kk > 0 || (k & 15));
            wgmma_n128(s1, da + 512 + kk * 2, db + kk * 2, kk > 0 || (k & 15));
          }
          wgmma_commit();
          if (k < 31 || w == 0) bar_arrive(turn_other, 256);
          if (pass && !(k & 1)) {
            const uint32_t buf = sb + OFF_XCH + 20480 + w * 4096;
            static_for<8>([&](auto ic) { if (k == 16 + 2 * decltype(ic)::value) put(ic, buf); });
            fence_async_smem();
            bar_sync(NB_WG0 + w, 128);
            if (t == 0) { tma_store_2d(&p.tmAbM, buf, (k - 16) * 128 + 240, col * 128); bulk_commit(); }
          }
          wgmma_wait0();
          release(s);
          if ((k & 1) && t == 0) asm volatile("cp.async.bulk.wait_group.read 0;" ::: "memory");
        }
        if (pass) publish(col);
        mbar_wait(BAR(B_STAT), 0);
        wgmma_fence();
        wgmma_n128(s0, make_desc_noswz(sb + OFF_XCH + pass * 8192 + w * 4096), make_desc_noswz(sb + OFF_XCH + 16384));
        wgmma_n128(s1, make_desc_noswz(sb + OFF_XCH + pass * 8192 + w * 4096 + 2048), make_desc_noswz(sb + OFF_XCH + 16384));
        wgmma_commit();
        uint4 rs[4];
#pragma unroll
        for (int i = 0; i < 4; i++) rs[i] = lds128_v(sb + OFF_RS + q * 144 + i * 16);
        wgmma_wait0();
        fence_acc(s0); fence_acc(s1);
#pragma unroll
        for (int i = 0; i < 32; i++) {
          const int tl = i & 7, hr = (i >> 3) & 1;
          const float* ac = (i >> 4) ? &s1[8 * tl + 2 * hr] : &s0[8 * tl + 2 * hr];
          o[i][0] = bmul2(pack_bf16(ac[0], ac[1]), (tl & 1) ? rs[tl >> 1].z : rs[tl >> 1].x);
          o[i][1] = bmul2(pack_bf16(ac[4], ac[5]), (tl & 1) ? rs[tl >> 1].w : rs[tl >> 1].y);
        }
      }
      static_for<8>([&](auto ic) { put(ic, sb + (w * 8 + decltype(ic)::value) * 4096); });
      fence_async_smem();
      bar_sync(NB_WG0 + w, 128);
      if (t == 0) {
#pragma unroll 1
        for (int i = 0; i < 8; i++) tma_store_2d(&p.tmAbM, sb + (w * 8 + i) * 4096, i * 256 + 240, (col + 2) * 128);
        bulk_commit();
      }
      publish(col + 2);
      asm volatile("barrier.cluster.wait.aligned;" ::: "memory");
      return;
    }
    float acc[128], a1[NX / 2];
#pragma unroll
    for (int i = 0; i < NX / 2; i++) a1[i] = 0.f;
    if (w == 1) bar_arrive(NB_TURN0, 256);
    auto kstep = [&](auto& d, int k, bool first, bool a_in_xch = false, bool mini = false) {
      const int s = slot_of(k);
      mbar_wait(BAR(B_FULL + s), use_of(k) & 1);
      CT(64 + k);
      bar_sync(turn_me, 256);
      const uint64_t da = make_desc(sb + (a_in_xch ? OFF_XCH + s * 16384 : s * ST_BYTES) + w * 8192), db = make_desc(sb + s * ST_BYTES + A_BYTES);
      wgmma_fence();
      wgmma_g1(d, da, db, !first);
#pragma unroll
      for (int kk = 1; kk < 4; kk++) wgmma_g1(d, da + kk * 2, db + kk * 2, 1);
      wgmma_commit();
      if (mini) {
        CT(29);
        mbar_wait(BAR(B_A20), 1);
        CT(30);
        wgmma_fence();
        wgmma_g1(d, make_desc_32b(sb + OFF_MINI + w * 2048), make_desc_32b(sb + OFF_MINI + 4096), 1);
        wgmma_commit();
      }
      bar_arrive(turn_other, 256);
    };
    auto kdone = [&](int k) { wgmma_wait0(); release(slot_of(k)); };
    auto wgmma_wait1 = [&]() { asm volatile("wgmma.wait_group.sync.aligned 1;" ::: "memory"); };

#pragma unroll 1
    for (int k = 0; k < 14; k++) {
      kstep(a1, k, k == 0);
      if (k == 0) CT(0);
      if (k == 8 && warp == 2 && lane < 2) pkt_st128(&p.s->abflag[((eps * 2 + m) * 8 + tau) * 2 + lane], 0, 0, 0, 0);
      kdone(k);
    }
    uint32_t R[64];
    uint32_t tag;
    {
      const uint32_t rsa = sb + OFF_RS + q * 144;
      const uint64_t da2 = make_desc(sb + 2 * ST_BYTES + w * 8192), db2 = make_desc(sb + 2 * ST_BYTES + A_BYTES);
      const uint64_t da3 = make_desc(sb + 3 * ST_BYTES + w * 8192), db3 = make_desc(sb + 3 * ST_BYTES + A_BYTES);
      mbar_wait(BAR(B_FULL + 2), 1);
      CT(64 + 14);
      bar_sync(turn_me, 256);
      wgmma_fence();
#pragma unroll
      for (int kk = 0; kk < 4; kk++) wgmma_g1(a1, da2 + kk * 2, db2 + kk * 2, 1);
      wgmma_commit();
      mbar_wait(BAR(B_FULL + 3), 1);
      CT(64 + 15);
      wgmma_fence();
      wgmma_g1(a1, da3, db3, 1);
      wgmma_g1(a1, da3 + 2, db3 + 2, 1);
      wgmma_commit();
      mbar_wait(BAR(B_STAT), 0);
      tag = SM_(uint32_t, OFF_TAG);
#pragma unroll
      for (int i = 0; i < 8; i++) { const uint4 v = lds128_v(rsa + i * 16); R[8 * i] = v.x; R[8 * i + 2] = v.y; R[8 * i + 4] = v.z; R[8 * i + 6] = v.w; }
      wgmma_wait1();
      release(2);
      wgmma_fence();
      wgmma_g1(a1, da3 + 4, db3 + 4, 1);
      wgmma_g1(a1, da3 + 6, db3 + 6, 1);
      wgmma_g1(a1, make_desc_noswz(sb + OFF_EXA + w * 2048), make_desc_noswz(sb + OFF_EXB), 1);
      wgmma_commit();
      bar_arrive(turn_other, 256);
      kdone(15);
      mbar_wait(BAR(B_STAT), 0);
    }
    fence_acc(a1);
    CT(1);
    auto pack = [&](auto cc) {
      constexpr int c = decltype(cc)::value;
#pragma unroll
      for (int j = 8 * c; j < min_c(8 * c + 8, NX / 8); j++) {
        const uint32_t rs = R[2 * j];
        const float* ac = &a1[4 * j];
        R[2 * j] = bmul2(pack_bf16(ac[0], ac[1]), rs);
        R[2 * j + 1] = bmul2(pack_bf16(ac[2], ac[3]), rs);
      }
    };
    auto put_chunk = [&](auto cc) {
      constexpr int c = decltype(cc)::value;
      const int rho = 16 * wi + (lane & 15);
#pragma unroll
      for (int j = 8 * c; j < min_c(8 * c + 8, NX / 8); j += 2) {
        const int chunk = (j & 7) + (lane >> 4);
        stsm_x4(sb + chunk_off(c, w) + rho * 128 + ((chunk ^ (lane & 7)) << 4), R[2 * j], R[2 * j + 1], R[2 * j + 2], R[2 * j + 3]);
      }
    };
    auto staged = [&](int bar) {
      fence_async_smem();
      __syncwarp();
      if (lane == 0) mbar_arrive(BAR(bar));
    };
    auto mma_rs = [&](auto cc, auto k0, auto k1) {
      constexpr int c = decltype(cc)::value;
      const uint64_t db = make_desc(sb + c * ST_BYTES + A_BYTES);
#pragma unroll
      for (int kk = decltype(k0)::value; kk < decltype(k1)::value; kk++)
        wgmma_n256_rs(acc, R[16 * c + 4 * kk], R[16 * c + 4 * kk + 1], R[16 * c + 4 * kk + 2], R[16 * c + 4 * kk + 3], db + kk * 2, c + kk > 0);
      wgmma_commit();
    };
    auto kdone_x = [&](int k, auto ic) {
      constexpr int i = decltype(ic)::value;
      uint32_t r[8];
#pragma unroll
      for (int z = 0; z < 2; z++) {
        const int tr = 32 * (i & 1) + 16 * z + 8 * (lane >> 4) + (lane & 7), chunk = 2 * wi + ((lane >> 3) & 1);
        ldsm_x4_t(sb + (i >> 1) * ST_BYTES + w * 8192 + tr * 128 + ((chunk ^ (lane & 7)) << 4), r[4 * z], r[4 * z + 1], r[4 * z + 2], r[4 * z + 3]);
      }
      float f[16];
#pragma unroll
      for (int z = 0; z < 8; z++) { f[2 * z] = bf_lo(r[z]); f[2 * z + 1] = bf_hi(r[z]); }
#pragma unroll
      for (int z = 0; z < 16; z++) asm volatile("" : "+f"(f[z]));
      kdone(k);
#pragma unroll
      for (int z = 0; z < 16; z++) asm volatile("add.f32 %0, %0, %1;" : "+f"(acc[16 * i + z]) : "f"(f[z]));
    };
    pack(IC<0>());
    put_chunk(IC<0>());
    staged(w ? B_EPI0B : B_EPI);
    mbar_wait(BAR(B_STAT), 0);
    CT(21);
    pack(IC<1>());
    pack(IC<2>());
    pack(IC<3>());
#pragma unroll
    for (int i = 16; i < NX / 4; i++) asm volatile("" : "+r"(R[i]));
#pragma unroll
    for (int i = 0; i < 128; i++) asm volatile("" : "=f"(acc[i]));
    mbar_wait(BAR(B_FULL + 0), 0);
    CT(2);
    CT(64 + 16);
    bar_sync(turn_me, 256);
    wgmma_fence();
    mma_rs(IC<0>(), IC<0>(), IC<4>());
    mbar_wait(BAR(B_FULL + 1), 0);
    CT(64 + 17);
    wgmma_fence();
    mma_rs(IC<1>(), IC<0>(), IC<2>());
    wgmma_wait1();
    release(0);
    mma_rs(IC<1>(), IC<2>(), IC<4>());
    bar_arrive(turn_other, 256);
    kdone_x(17, IC<0>());
    static_for<2>([&](auto ic) {
      constexpr int c = 2 + decltype(ic)::value;
      mbar_wait(BAR(B_FULL + c), 0);
      CT(64 + 16 + c);
      bar_sync(turn_me, 256);
      wgmma_fence();
      mma_rs(IC<c>(), IC<0>(), IC<min_c(4, NX / 16 - 4 * c)>());
      bar_arrive(turn_other, 256);
      if (c == 2) { put_chunk(IC<1>()); staged(B_EPI + 1); }
      kdone_x(16 + c, IC<c - 1>());
    });
#pragma unroll 1
    for (int k = 20; k < 23; k++) {
      if (w == 1) mbar_wait(BAR(B_A20), 0);
      kstep(acc, k, false, k < 22);
      if (k == 20) {
        kdone_x(k, IC<3>());
      } else {
        if (k == 21) put_chunk(IC<2>()); else put_chunk(IC<3>());
        __syncwarp();
        if (lane == 0) mbar_arrive(BAR(B_EPI + k - 19));
        kdone(k);
      }
    }
    uint32_t wf[32][4];
    auto load_wf = [&](auto hc) {
      constexpr int h = decltype(hc)::value;
      const int d = w * 64 + (lane >> 4) * 8 + (lane & 7);
      const uint32_t ad = sb + round_off(h) + (lane & 8) * 1024 + d * 64 + ((wi ^ ((lane >> 1) & 3)) << 4);
#pragma unroll
      for (int i = 0; i < 4; i++) ldsm_x4_t(ad + i * 1024, wf[4 * h + i][0], wf[4 * h + i][1], wf[4 * h + i][2], wf[4 * h + i][3]);
    };
    auto load_wf_rest = [&]() { static_for<8 - NREG_H>([&](auto ic) { load_wf(IC<NREG_H + decltype(ic)::value>()); }); };
#pragma unroll
    for (int i = 0; i < 4 * NREG_H; i++) { wf[i][0] = 0; wf[i][1] = 0; wf[i][2] = 0; wf[i][3] = 0; }
    const int grp = tau * 2 + m;
#pragma unroll 1
    for (int k = 23; k < 46; k++) {
      kstep(acc, k, false, false, NX < 256 && k == MINI_K);
      if (moe) {
        static_for<NREG_H>([&](auto hc) {
          constexpr int h = decltype(hc)::value;
          if (k == mr_k(h) + 1) { mbar_wait(BAR(B_MR + (h & 1)), (h >> 1) & 1); CT(32 + h); load_wf(hc); }
        });
      }
      if (k == RESET_K && tid == 0) mbar_arrive(BAR(B_LATE));
      kdone(k);
    }
    asm volatile("barrier.cluster.arrive.relaxed.aligned;" ::: "memory");
    mbar_wait(BAR(B_STAT), 1);
    uint32_t wa[16][2];
    uint32_t cd = code_of(tag);
    uint4* hp_pub = &p.s->hstat[(grp * 8 + eps) * 128 + warp * 16 + g];
    const uint4* hp_poll = &p.s->hstat[(grp * 8 + 2 * q) * 128 + warp * 16 + g];
    const uint32_t vec_off = (2 * wi) * 512 + q * 128 + ((g ^ (2 * q)) << 4);
    {
      float as[64], ak[64];
      fence_acc(acc);
#pragma unroll
      for (int i = 0; i < 64; i++) asm volatile("mov.b32 %0, %1;" : "=f"(as[i]) : "f"(acc[64 + i]));
#pragma unroll
      for (int i = 0; i < 64; i++) asm volatile("mov.b32 %0, %1;" : "=f"(ak[i]) : "f"(acc[i]));
      const uint64_t da1 = make_desc(sb + 2 * ST_BYTES + w * 8192), db1 = make_desc(sb + 2 * ST_BYTES + A_BYTES);
      const uint64_t da2 = make_desc(sb + 3 * ST_BYTES + w * 8192), db2 = make_desc(sb + 3 * ST_BYTES + A_BYTES);
      mbar_wait(BAR(B_FULL + 2), 1);
      CT(64 + 46);
      mbar_wait(BAR(B_FULL + 3), 1);
      CT(64 + 47);
      bar_sync(turn_me, 256);
      wgmma_fence();
#pragma unroll
      for (int kk = 0; kk < 4; kk++) wgmma_n128(as, da1 + kk * 2, db1 + 1024 + kk * 2);
#pragma unroll
      for (int kk = 0; kk < 4; kk++) wgmma_n128(as, da2 + kk * 2, db2 + 1024 + kk * 2);
      wgmma_commit();
      bar_arrive(turn_other, 256);
      const uint32_t rx = mapa(sb + OFF_PEER + w * 4096 + vec_off, 1 - m), rb = mapa(BAR(B_XCH), 1 - m);
      asm volatile("barrier.cluster.wait.aligned;" ::: "memory");
      CT(24);
      wgmma_wait0();
      fence_acc(as);
      CT(25);
      auto keep = [&]() {
        bar_sync(turn_me, 256);
        wgmma_fence();
#pragma unroll
        for (int kk = 0; kk < 4; kk++) wgmma_n128(ak, da1 + kk * 2, db1 + kk * 2);
        wgmma_commit();
#pragma unroll
        for (int kk = 0; kk < 4; kk++) wgmma_n128(ak, da2 + kk * 2, db2 + kk * 2);
        wgmma_commit();
        if (w == 0) bar_arrive(turn_other, 256);
      };
#pragma unroll
      for (int i = 0; i < 8; i++) {
        if (i == SEND_FIRST) keep();
        const float* ac = &as[16 * (i >> 1) + 2 * (i & 1)];
        st_async_v4(rx + (i >> 1) * 8192 + (i & 1) * 512, rb, pack_bf16(ac[0], ac[1]), pack_bf16(ac[4], ac[5]), pack_bf16(ac[8], ac[9]), pack_bf16(ac[12], ac[13]));
      }
      CT(26);
#pragma unroll
      for (int i = 0; i < 4; i++) {
        const uint4 v = lds128_v(sb + OFF_WR + q * 80 + i * 16);
        const uint32_t vv[4] = {v.x, v.y, v.z, v.w};
#pragma unroll
        for (int z = 0; z < 4; z++) {
          asm volatile("{\n.reg .pred p;\nsetp.ne.b32 p, %2, 0;\nselp.b32 %0, %1, 0x3F803F80, p;\n}" : "=r"(wa[4 * i + z][0]) : "r"(vv[z]), "r"(g & 1));
          asm volatile("{\n.reg .pred p;\nsetp.ne.b32 p, %2, 0;\nselp.b32 %0, %1, 0x3F803F80, p;\n}" : "=r"(wa[4 * i + z][1]) : "r"(vv[z]), "r"(g & 1));
        }
      }
      pin(cd); pin(hp_pub); pin(hp_poll);
      CT(27);
      wgmma_wait1();
      release(2);
      wgmma_wait0();
      fence_acc(ak);
      CT(3);
#pragma unroll
      for (int i = 0; i < 8; i++) {
        const float* ac = &ak[16 * (i >> 1) + 2 * (i & 1)];
        sts128(sb + (2 + (i >> 2)) * ST_BYTES + w * 8192 + ((i >> 1) & 1) * 4096 + (i & 1) * 512 + vec_off,
               pack_bf16(ac[0], ac[1]), pack_bf16(ac[4], ac[5]), pack_bf16(ac[8], ac[9]), pack_bf16(ac[12], ac[13]));
      }
    }
    uint32_t h[8][4];
    {
      const int qq = 2 * (warp & 1) + ((lane >> 3) & 1);
      const uint32_t lo = (lane >> 4) * 512 + qq * 128 + (((lane & 7) ^ (2 * qq)) << 4);
      bar_sync(NB_BOTH, 256);
#pragma unroll
      for (int ks = 0; ks < 8; ks++)
        ldsm_x4_t(sb + (2 + w) * ST_BYTES + (ks >> 2) * 8192 + (wi >> 1) * 4096 + (ks & 3) * 1024 + lo, h[ks][0], h[ks][1], h[ks][2], h[ks][3]);
      CT(28);
      mbar_wait_cluster(BAR(B_XCH), 0);
      CT(4);
      uint32_t r[8][4];
#pragma unroll
      for (int ks = 0; ks < 8; ks++) ldsm_x4_t(sb + OFF_PEER + (warp >> 1) * 8192 + ks * 1024 + lo, r[ks][0], r[ks][1], r[ks][2], r[ks][3]);
      float d[4][4] = {};
#pragma unroll
      for (int ks = 0; ks < 8; ks++) {
#pragma unroll
        for (int i = 0; i < 4; i++) {
          h[ks][i] = badd2(h[ks][i], r[ks][i]);
          mma1688(d[i], h[ks][i], wa[2 * ks + (i >> 1)][i & 1], h[ks][i]);
        }
      }
#pragma unroll
      for (int i = 0; i < 2; i++) {
        const float sq = (g & 1) ? d[i][1] + d[i + 2][1] : d[i][0] + d[i + 2][0];
        const float e0 = d[i][2] + d[i + 2][2], e1 = d[i][3] + d[i + 2][3];
        const float other = __shfl_xor_sync(0xffffffffu, (g & 1) ? e0 : e1, 4);
        if (q == (g >> 1)) pkt_st128(hp_pub + 8 * i, with_bit((g & 1) ? other : e0, cd), with_bit(sq, cd >> 1), __float_as_uint((g & 1) ? e1 : other), tag);
      }
    }
    CT(5);
    if (tid == 0) mbar_arrive(BAR(B_KEY));
    delay_clk<HOP1_DELAY>();
    float m_bf, sd, inv_sd, r_bf;
    uint4* key_pub = &p.s->key[((lane & 7) * 16 + grp) * 2];
    uint4* cand_pub = &p.s->cand[grp * 256 + eps * 32 + q];
    uint32_t trow_inv = 0xFFFFu - (uint32_t)(grp * 128 + 32 * (warp >> 1) + 8 * (g >> 1) + 4 * (warp & 1) + (q & 2) + (g & 1));
    {
      uint4 u[4];
#pragma unroll
      for (int i = 0; i < 4; i++) u[i] = pkt_ld128(hp_poll + (i & 1) * 128 + (i >> 1) * 8);
      const float wsum = SM_(float, OFF_WSUM);
      pin(key_pub); pin(cand_pub); pin(trow_inv);
      uint32_t n = 0;
      while (true) {
        bool ok[4];
#pragma unroll
        for (int i = 0; i < 4; i++) ok[i] = u[i].w == tag && pair_code(u[i].x, u[i].y) == cd;
        const bool all = __all_sync(0xffffffffu, ok[0] && ok[1] && ok[2] && ok[3]);
        if (all || ++n > SPIN_LIMIT) break;
#pragma unroll
        for (int i = 0; i < 4; i++) pkt_ld128_if(u[i], hp_poll + (i & 1) * 128 + (i >> 1) * 8, !ok[i]);
      }
      CT(6);
      float a[3], b[3];
      a[0] = __uint_as_float(u[0].x & ~1u) + __uint_as_float(u[1].x & ~1u); b[0] = __uint_as_float(u[2].x & ~1u) + __uint_as_float(u[3].x & ~1u);
      a[1] = __uint_as_float(u[0].y & ~1u) + __uint_as_float(u[1].y & ~1u); b[1] = __uint_as_float(u[2].y & ~1u) + __uint_as_float(u[3].y & ~1u);
      a[2] = __uint_as_float(u[0].z) + __uint_as_float(u[1].z); b[2] = __uint_as_float(u[2].z) + __uint_as_float(u[3].z);
#pragma unroll
      for (int i = 0; i < 3; i++) {
        a[i] = ((q & 2) ? b[i] : a[i]) + __shfl_xor_sync(0xffffffffu, (q & 2) ? a[i] : b[i], 2);
        a[i] += __shfl_xor_sync(0xffffffffu, a[i], 1);
      }
      const float mu = a[0] * (1.f / 1024.f);
      m_bf = bf16r(mu);
      sd = ln_sd(a[1] * (1.f / 1024.f) - mu * mu);
      inv_sd = rcp_fast(sd);
      r_bf = bf16r((a[2] - m_bf * wsum) * inv_sd);
    }
    {
      const uint32_t u = __float_as_uint(r_bf);
      const uint32_t ord = (u & 0x80000000u) ? ~u : (u | 0x80000000u);
      const uint32_t key = (ord & 0xFFFF0000u) | trow_inv;
      const uint32_t wk = __reduce_max_sync(0xffffffffu, key);
      if (key == wk) SM_(uint2, OFF_WKEY + warp * 8) = make_uint2(wk, (__float_as_uint(m_bf) >> 16) | __float_as_uint(sd));
      const uint32_t wmask = __ballot_sync(0xffffffffu, key == wk);
      const bool hi = (wmask & 0xCCCCCCCCu) != 0;
      uint32_t c[16];
#pragma unroll
      for (int ks = 0; ks < 8; ks++) { c[2 * ks] = hi ? h[ks][1] : h[ks][0]; c[2 * ks + 1] = hi ? h[ks][3] : h[ks][2]; }
      bar_sync(NB_BOTH, 256);
      const uint2 km = SM_(uint2, OFF_WKEY + (lane & 7) * 8);
      const uint32_t bk = __reduce_max_sync(0xffffffffu, km.x);
      if (wk == bk) {
        if ((wmask >> (lane & 28)) & 15) {
#pragma unroll
          for (int ks = 0; ks < 8; ks++) pkt_st128(cand_pub + ks * 4, c[2 * ks], tag, c[2 * ks + 1], tag);
        }
      } else if (eps == 0) {
        const uint32_t kx = __shfl_sync(0xffffffffu, km.x, warp ^ 1), ms = __shfl_sync(0xffffffffu, km.y, warp ^ 1);
        if (kx == bk && lane < 8) pkt_st128(key_pub, bk, tag, ms, tag);
      }
      CT(7);
    }
    {
      const float ih = bf16r(inv_sd);
      const uint32_t nm = pack_bf16(-m_bf, -m_bf), iv = pack_bf16(ih, inv_sd - ih);
      const uint32_t nm_o = __shfl_xor_sync(0xffffffffu, nm, 2), iv_o = __shfl_xor_sync(0xffffffffu, iv, 2);
      const uint32_t nm2[2] = {(q & 2) ? nm_o : nm, (q & 2) ? nm : nm_o}, iv2[2] = {(q & 2) ? iv_o : iv, (q & 2) ? iv : iv_o};
      const uint32_t hi2[2] = {__byte_perm(iv2[0], 0, 0x1010), __byte_perm(iv2[1], 0, 0x1010)}, lo2[2] = {__byte_perm(iv2[0], 0, 0x3232), __byte_perm(iv2[1], 0, 0x3232)};
      const uint32_t oa = sb + OFF_OUT + (warp * 16 + (lane & 15)) * 128;
#pragma unroll
      for (int ks = 0; ks < 8; ks++) {
        uint32_t o[4];
#pragma unroll
        for (int i = 0; i < 4; i++) {
          const uint32_t dd = badd2(h[ks][i], nm2[i & 1]);
          o[i] = badd2(h[ks][i], bfma2(dd, hi2[i & 1], bmul2(dd, lo2[i & 1])));
        }
        stsm_x4(oa + (ks >> 2) * 16384 + (((2 * (ks & 3) + (lane >> 4)) ^ (lane & 7)) << 4), o[0], o[1], o[2], o[3]);
      }
      staged(B_OUT);
    }
    CT(8);
    uint32_t df[16][4];
    auto load_df = [&]() {
      const int frow = (lane & 7) + ((lane >> 4) << 3), hi = (lane >> 3) & 1;
      const uint32_t base = sb + down_off(warp >> 1) + (warp & 1) * 8192 + frow * 128;
#pragma unroll
      for (int mt = 0; mt < 8; mt++) {
#pragma unroll
        for (int ks = 0; ks < 2; ks++)
          ldsm_x4_t(base + (mt >> 2) * 4096 + ks * 2048 + (((2 * (mt & 3) + hi) ^ (lane & 7)) << 4),
                    df[2 * mt + ks][0], df[2 * mt + ks][1], df[2 * mt + ks][2], df[2 * mt + ks][3]);
      }
    };
    if (moe) {
      mbar_wait(BAR(B_GU), 0);
      load_wf_rest();
      mbar_wait(BAR(B_DN), 0);
      load_df();
    }
    uint4* y_pub = &p.s->ypart[cid * 256 + tid];
    uint32_t xs_ad = sb + OFF_XSEL + (8 * (g >> 2) + 4 * w + (g & 3)) * 32 + q * 8, gp_ad = sb + OFF_GP + (wi * 8 + g) * 16 + w * 8 + (q >> 1) * 4;
    pin(y_pub); pin(xs_ad); pin(gp_ad);
    mbar_wait(BAR(B_XS), 0);
    CT(9);
    if (moe) {
      float gd[8][4] = {};
      uint2 bx[4];
#pragma unroll
      for (int r = 0; r < 4; r++) bx[r] = smem_at<uint2>(xs_ad + r * 512);
#pragma unroll
      for (int r = 0; r < 4; r++) {
#pragma unroll
        for (int i = 0; i < 8; i++) mma16816(gd[i], wf[8 * r + i][0], wf[8 * r + i][1], wf[8 * r + i][2], wf[8 * r + i][3], bx[r].x, bx[r].y);
      }
      const float gs = sel4(q, gd[0][0] + gd[1][1], gd[2][0] + gd[3][1], gd[4][0] + gd[5][1], gd[6][0] + gd[7][1]);
      const float us = sel4(q, gd[0][2] + gd[1][3], gd[2][2] + gd[3][3], gd[4][2] + gd[5][3], gd[6][2] + gd[7][3]);
      float v = ((q & 2) ? us : gs) + __shfl_xor_sync(0xffffffffu, (q & 2) ? gs : us, 2);
      v += __shfl_xor_sync(0xffffffffu, v, 1);
      smem_at<float>(gp_ad) = v;
      CT(10);
      bar_sync(NB_BOTH, 256);
      uint32_t bq[4];
      {
        const float4 p0 = SM_(float4, OFF_GP + lane * 16);
        const float gt = bf16r(p0.x + p0.z), up = bf16r(p0.y + p0.w);
        const float act = bf16r(gt * sigmoid_fast(gt)) * up;
        const uint32_t pr = pack_bf16(act, __shfl_down_sync(0xffffffffu, act, 1));
#pragma unroll
        for (int i = 0; i < 4; i++) bq[i] = __shfl_sync(0xffffffffu, pr, 8 * i + 2 * q);
      }
      CT(11);
      float yd[8][4] = {};
#pragma unroll
      for (int ks = 0; ks < 2; ks++) {
#pragma unroll
        for (int mt = 0; mt < 8; mt++) mma16816(yd[mt], df[2 * mt + ks][0], df[2 * mt + ks][1], df[2 * mt + ks][2], df[2 * mt + ks][3], bq[2 * ks], bq[2 * ks + 1]);
      }
      pkt_st128(y_pub, with_bit(sel4(q, yd[0][0], yd[2][0], yd[4][0], yd[6][0]), cd), with_bit(sel4(q, yd[0][2], yd[2][2], yd[4][2], yd[6][2]), cd >> 1),
                with_bit(sel4(q, yd[1][0], yd[3][0], yd[5][0], yd[7][0]), cd), with_bit(sel4(q, yd[1][2], yd[3][2], yd[5][2], yd[7][2]), cd >> 1));
    } else {
      const long long tw = clock64();
      while (clock64() - tw < IDLE_WAIT_CLK) __nanosleep(100);
    }
    CT(12);
    const uint32_t kv = SM_(uint32_t, OFF_KV);
    const int tsel = 0xFFFF - (int)(kv & 0xFFFFu);
    const float r_sel = __uint_as_float((kv & 0x80000000u) ? (kv & 0x7FFF0000u) : (~kv & 0xFFFF0000u));
    const float sig = bf16r(sigmoid_fast(r_sel));
    const int pfin = 2 * cid + (tid & 1);
    const int col_fin = (pfin >> 5) * 128 + (pfin & 3) * 32 + ((pfin & 31) >> 2) + 8 * ((tid >> 1) & 3);
    const int sel_off = (col_fin >> 4) * 32 + ((col_fin & 7) >> 1) * 8 + ((col_fin >> 3) & 1) * 4 + (col_fin & 1) * 2;
    const float hn_fin = __uint_as_float((uint32_t)SM_(uint16_t, OFF_XSEL + sel_off) << 16), h_fin = __uint_as_float((uint32_t)SM_(uint16_t, OFF_HSEL + sel_off) << 16);
    bf16* out_fin = p.out + (size_t)tsel * 1024 + col_fin;
    {
      const uint4* src = &p.s->ypart[(16 + (tid >> 1)) * 256 + pfin];
      pin(src); pin(out_fin);
      uint4 v = make_uint4(0, 0, 0, 0);
      if (warp < 7) {
        delay_clk<HOP3_DELAY>();
        uint32_t n = 0;
        bool ok = false;
        do {
          pkt_ld128_if(v, src, !ok);
          ok = pair_code(v.x, v.y) == cd && pair_code(v.z, v.w) == cd;
        } while (!__all_sync(0xffffffffu, ok) && ++n < SPIN_LIMIT);
      }
      CT(13);
      const float y0 = __uint_as_float(v.x & ~1u), y1 = __uint_as_float(v.y & ~1u), y2 = __uint_as_float(v.z & ~1u), y3 = __uint_as_float(v.w & ~1u);
      const float a0 = ((lane & 2) ? y1 : y0) + __shfl_xor_sync(0xffffffffu, (lane & 2) ? y0 : y1, 2);
      const float a1 = ((lane & 2) ? y3 : y2) + __shfl_xor_sync(0xffffffffu, (lane & 2) ? y2 : y3, 2);
      float b = ((lane & 4) ? a1 : a0) + __shfl_xor_sync(0xffffffffu, (lane & 4) ? a0 : a1, 4);
      b += __shfl_xor_sync(0xffffffffu, b, 8);
      b += __shfl_xor_sync(0xffffffffu, b, 16);
      if (lane < 8) SM_(float, OFF_FIN + lane * 32 + warp * 4) = b;
    }
    bar_sync(NB_BOTH, 256);
    if (tid < 8) {
      const float4 y0 = SM_(float4, OFF_FIN + tid * 32), y1 = SM_(float4, OFF_FIN + tid * 32 + 16);
      const float y = ((y0.x + y0.y) + (y0.z + y0.w)) + ((y1.x + y1.y) + y1.z);
      *out_fin = __float2bfloat16_rn(h_fin + bf16r(hn_fin + bf16r(bf16r(y) * sig)));
      if (cid == 0 && tid == 0) st_relaxed32(&p.s->epoch, tag);
    }
    CT(14);
  }
}

__global__ void __launch_bounds__(384, 1) occupancy_probe_kernel() {}

typedef CUresult (*EncodeFn)(CUtensorMap*, CUtensorMapDataType, cuuint32_t, void*, const cuuint64_t*, const cuuint64_t*, const cuuint32_t*, const cuuint32_t*,
                             CUtensorMapInterleave, CUtensorMapSwizzle, CUtensorMapL2promotion, CUtensorMapFloatOOBfill);

static void make_tm(EncodeFn enc, CUtensorMap* tm, const void* ptr, uint64_t rows, uint64_t cols, uint32_t brows, uint32_t bcols, CUtensorMapSwizzle sw,
                    CUtensorMapL2promotion promo = CU_TENSOR_MAP_L2_PROMOTION_L2_128B) {
  cuuint64_t dims[2] = {cols, rows};
  cuuint64_t strides[1] = {cols * 2};
  cuuint32_t box[2] = {bcols, brows};
  cuuint32_t es[2] = {1, 1};
  enc(tm, CU_TENSOR_MAP_DATA_TYPE_BFLOAT16, 2, const_cast<void*>(ptr), dims, strides, box, es, CU_TENSOR_MAP_INTERLEAVE_NONE, sw,
      promo, CU_TENSOR_MAP_FLOAT_OOB_FILL_NONE);
}

extern "C" void kernel_launch(void* const* d_in, const int* in_sizes, int n_in, void* d_out, int out_size) {
  (void)in_sizes; (void)n_in; (void)out_size;
  static EncodeFn enc = nullptr;
  static void* abT = nullptr;
  static int map = 0;
  if (!enc) {
    void* fn = nullptr; cudaDriverEntryPointQueryResult st;
    cudaGetDriverEntryPoint("cuTensorMapEncodeTiled", &fn, cudaEnableDefault, &st);
    enc = (EncodeFn)fn;
    cudaGetSymbolAddress(&abT, g_scratch);
    cudaFuncSetAttribute(fnet_moe_kernel<0>, cudaFuncAttributeMaxDynamicSharedMemorySize, SMEM_TOTAL);
    cudaFuncSetAttribute(fnet_moe_kernel<1>, cudaFuncAttributeMaxDynamicSharedMemorySize, SMEM_TOTAL);
    cudaFuncSetAttribute(occupancy_probe_kernel, cudaFuncAttributeMaxDynamicSharedMemorySize, SMEM_TOTAL);
    cudaFuncSetAttribute(occupancy_probe_kernel, cudaFuncAttributeNonPortableClusterSizeAllowed, 1);
    auto max_clusters = [&](int size) {
      cudaLaunchConfig_t cfg = {};
      cfg.gridDim = dim3(128); cfg.blockDim = dim3(384); cfg.dynamicSmemBytes = SMEM_TOTAL;
      cudaLaunchAttribute at[1];
      at[0].id = cudaLaunchAttributeClusterDimension; at[0].val.clusterDim.x = size; at[0].val.clusterDim.y = 1; at[0].val.clusterDim.z = 1;
      cfg.attrs = at; cfg.numAttrs = 1;
      int ncl = 0;
      return cudaOccupancyMaxActiveClusters(&ncl, occupancy_probe_kernel, &cfg) == cudaSuccess ? ncl : 0;
    };
    int dev = 0, sms = 0;
    cudaGetDevice(&dev);
    cudaDeviceGetAttribute(&sms, cudaDevAttrMultiProcessorCount, dev);
    map = (sms == 132 && max_clusters(2) == 66 && max_clusters(16) == 7) ? 0 : 1;
    (void)cudaGetLastError();
  }
  Params p;
  const bf16* x = (const bf16*)d_in[0];
  make_tm(enc, &p.tmD0, d_in[3], 1024, 1024, 128, 64, CU_TENSOR_MAP_SWIZZLE_128B);
  make_tm(enc, &p.tmD1, d_in[4], 1024, 1024, 128, 64, CU_TENSOR_MAP_SWIZZLE_128B);
  make_tm(enc, &p.tmX, x, 2048, 1024, map == 0 ? NX0 : 256, 64, CU_TENSOR_MAP_SWIZZLE_128B);
  make_tm(enc, &p.tmXr, x, 2048, 1024, 64, 64, CU_TENSOR_MAP_SWIZZLE_128B);
  make_tm(enc, &p.tmAbS, abT, 2048, 2048, 64, 64, CU_TENSOR_MAP_SWIZZLE_128B);
  make_tm(enc, &p.tmAbL, abT, 2048, 2048, 128, 64, CU_TENSOR_MAP_SWIZZLE_128B);
  make_tm(enc, &p.tmW0, d_in[1], 2048, 2048, 128, 64, CU_TENSOR_MAP_SWIZZLE_128B);
  make_tm(enc, &p.tmW1, d_in[2], 2048, 2048, 128, 64, CU_TENSOR_MAP_SWIZZLE_128B);
  {
    cuuint64_t dims[5] = {1024, 2, 4, 4, 64};
    cuuint64_t strides[4] = {2048, 8 * 2048, 2 * 2048, 32 * 2048};
    cuuint32_t box[5] = {64, 2, 4, 2, 1};
    cuuint32_t es[5] = {1, 1, 1, 1, 1};
    enc(&p.tmOut, CU_TENSOR_MAP_DATA_TYPE_BFLOAT16, 5, d_out, dims, strides, box, es, CU_TENSOR_MAP_INTERLEAVE_NONE, CU_TENSOR_MAP_SWIZZLE_128B,
        CU_TENSOR_MAP_L2_PROMOTION_NONE, CU_TENSOR_MAP_FLOAT_OOB_FILL_NONE);
  }
  {
    cuuint64_t dims[5] = {1024, 2, 4, 2, 8};
    cuuint64_t strides[4] = {2048, 4 * 2048, 2 * 2048, 256 * 2048};
    cuuint32_t box[5] = {64, 2, 4, 2, 8};
    cuuint32_t es[5] = {1, 1, 1, 1, 1};
    enc(&p.tmXh, CU_TENSOR_MAP_DATA_TYPE_BFLOAT16, 5, const_cast<bf16*>(x) + 240 * 1024, dims, strides, box, es, CU_TENSOR_MAP_INTERLEAVE_NONE,
        CU_TENSOR_MAP_SWIZZLE_128B, CU_TENSOR_MAP_L2_PROMOTION_L2_128B, CU_TENSOR_MAP_FLOAT_OOB_FILL_NONE);
  }
  make_tm(enc, &p.tmAbM, abT, 2048, 2048, 128, 16, CU_TENSOR_MAP_SWIZZLE_32B, CU_TENSOR_MAP_L2_PROMOTION_NONE);
  make_tm(enc, &p.tmWM0, d_in[1], 2048, 2048, 128, 16, CU_TENSOR_MAP_SWIZZLE_32B, CU_TENSOR_MAP_L2_PROMOTION_NONE);
  make_tm(enc, &p.tmWM1, d_in[2], 2048, 2048, 128, 16, CU_TENSOR_MAP_SWIZZLE_32B, CU_TENSOR_MAP_L2_PROMOTION_NONE);
  make_tm(enc, &p.tmG, d_in[7], 1024, 3584, 128, 32, CU_TENSOR_MAP_SWIZZLE_64B);
  make_tm(enc, &p.tmU, d_in[8], 1024, 3584, 128, 32, CU_TENSOR_MAP_SWIZZLE_64B);
  make_tm(enc, &p.tmDn, d_in[9], 3584, 1024, 32, 64, CU_TENSOR_MAP_SWIZZLE_128B);
  p.x = x; p.Dre = (const bf16*)d_in[3]; p.Dim = (const bf16*)d_in[4];
  p.wr = (const bf16*)d_in[6]; p.wdown = (const bf16*)d_in[9]; p.wgate = (const bf16*)d_in[7]; p.wup = (const bf16*)d_in[8];
  p.out = (bf16*)d_out; p.s = (Scratch*)abT;
  if (map == 1) fnet_moe_kernel<1><<<128, 384, SMEM_TOTAL>>>(p);
  else fnet_moe_kernel<0><<<132, 384, SMEM_TOTAL>>>(p);
}
```

```cpp
#include <cuda.h>
#include <cuda_runtime.h>
#include <cuda_bf16.h>
#include <stdint.h>
#include <type_traits>

typedef __nv_bfloat16 bf16;

constexpr int NX0 = 240;
constexpr int REG_C = 232, REG_P = 40;
__device__ __forceinline__ int sigma_of(int tau, int r) { return r + (r >= tau); }
__device__ __forceinline__ int kblock(int tau, int j) {
  const int i = j - 4, c = (i * 37) >> 8;
  return j < 4 ? tau * 4 + j : sigma_of(tau, i - 7 * c) * 4 + c;
}
constexpr int AUX_AFTER = 1;
constexpr int PF_K0 = 8, PF_N0 = 2, PF_K1 = 24;
constexpr int WPF_K0 = 12, WPF_N = 10;
constexpr int PUB_K1 = 22;
constexpr int NREG_H = 5;
constexpr int MR_K0 = 29, MR_P = 6;
constexpr int MINI_PF_K = 39, MINI_LOAD_K = 43, MINI_K = 42;
constexpr int RESET_K = 37;
constexpr int SEND_FIRST = 2;
constexpr int HELPER_NS = 5000;
constexpr int GATHER_NS = 400;
constexpr int MOE_PACE_CLK = 300;
constexpr int OUT_PACE_CLK = 70;
constexpr int HOP1_DELAY = 150, HOP3_DELAY = 450;
constexpr int SPEC_MIN = 10;
constexpr int IDLE_WAIT_CLK = 1200;
__host__ __device__ constexpr int mr_k(int h) { return MR_K0 + MR_P * (h >> 1) + 2 * (h & 1); }
constexpr int A_BYTES = 128 * 64 * 2;
constexpr int B_BYTES = 256 * 64 * 2;
constexpr int ST_BYTES = A_BYTES + B_BYTES;
constexpr int OFF_XCH = 4 * ST_BYTES;
constexpr int OFF_BAR = OFF_XCH + 32768;
constexpr int OFF_WR = OFF_BAR + 384;
constexpr int OFF_RS = OFF_WR + 384;
constexpr int OFF_PUB = OFF_RS + 640;
constexpr int OFF_MISC = OFF_PUB + 768;
constexpr int SMEM_TOTAL = OFF_MISC + 256;
constexpr int OFF_WSUM = OFF_MISC, OFF_TAG = OFF_MISC + 4;
constexpr int OFF_SEEN = OFF_MISC + 8;
constexpr int OFF_KV = OFF_MISC + 12;
constexpr int OFF_WKEY = OFF_MISC + 32;
constexpr int OFF_MINI = OFF_XCH + 16384;
constexpr int OFF_EXA = OFF_XCH;
constexpr int OFF_EXB = OFF_XCH + 4096;
__host__ __device__ constexpr int chunk_off(int c, int w) { return (c < 2 ? (c + 2) * ST_BYTES : OFF_XCH + (c - 2) * 16384) + w * 8192; }
__host__ __device__ constexpr int late_off(int i) { return i < 4 ? i * 16384 : 2 * ST_BYTES + A_BYTES + (i - 4) * 16384; }
__host__ __device__ constexpr int round_off(int h) { return h < NREG_H + 2 ? OFF_XCH + (h & 1) * 16384 : late_off(h - NREG_H - 2); }
__host__ __device__ constexpr int down_off(int i) { return late_off(6 - NREG_H + i); }
constexpr int OFF_PEER = ST_BYTES + A_BYTES;
constexpr int OFF_OUT = 3 * ST_BYTES + A_BYTES;
constexpr int OFF_XSEL = OFF_PEER;
constexpr int OFF_HSEL = OFF_PEER + 4096;
constexpr int OFF_GP = OFF_PEER + 8192;
constexpr int OFF_FIN = OFF_PEER + 9216;
__device__ __forceinline__ int slot_of(int k) { return k & 3; }
__device__ __forceinline__ int use_of(int k) { return k >> 2; }
enum { B_FULL = 0, B_EMPTY = 4, B_EPI = 8, B_STD = 12, B_EPI0B = 16, B_LATE = 17, B_STAT = 18, B_XCH = 19, B_MR = 20  , B_GU = 22,
       B_DN = 23, B_AUX = 24  , B_OUT = 26, B_KEY = 27, B_XS = 28, B_A20 = 29, B_STDA = 30, B_PUB1 = 31, B_COUNT = 32 };
enum { NB_TURN0 = 1, NB_TURN1 = 2, NB_WG0 = 3, NB_BOTH = 5, NB_AUX = 6 };

struct Scratch {
  bf16 abT[2048 * 2048];
  uint2 xstat[2048];
  uint2 dsum[2048];
  uint4 abflag[16 * 8 * 2];
  uint4 hflag[16 * 2];
  uint4 hstat[16 * 8 * 128];
  uint4 cand[16 * 256];
  uint4 key[8 * 16 * 2];
  uint4 ypart[128 * 256];
  uint32_t epoch;
};
__device__ __align__(1024) Scratch g_scratch;

struct Params {
  Scratch* s; bf16* out;
  const bf16* x; const bf16* Dre; const bf16* Dim; const bf16* wr; const bf16* wdown; const bf16* wgate; const bf16* wup;
  CUtensorMap tmX, tmD0, tmD1, tmXr, tmAbS, tmAbL, tmW0, tmW1, tmOut, tmG, tmU, tmDn, tmXh, tmAbM, tmWM0, tmWM1;
};

#define SPIN_LIMIT (1u << 14)
#define MBAR_LIMIT (1u << 10)
__device__ __forceinline__ uint32_t smem_u32(const void* p) { return (uint32_t)__cvta_generic_to_shared(p); }
__device__ __forceinline__ void mbar_init(uint32_t bar, uint32_t cnt) { asm volatile("mbarrier.init.shared::cta.b64 [%0], %1;" :: "r"(bar), "r"(cnt) : "memory"); }
__device__ __forceinline__ void mbar_expect_tx(uint32_t bar, uint32_t bytes) { asm volatile("mbarrier.arrive.expect_tx.shared::cta.b64 _, [%0], %1;" :: "r"(bar), "r"(bytes) : "memory"); }
__device__ __forceinline__ void mbar_arrive(uint32_t bar) { asm volatile("mbarrier.arrive.shared::cta.b64 _, [%0];" :: "r"(bar) : "memory"); }
__device__ __forceinline__ void mbar_wait(uint32_t bar, uint32_t parity) {
  uint32_t ok, n = 0;
  do {
    asm volatile("{\n.reg .pred p;\nmbarrier.try_wait.parity.shared::cta.b64 p, [%1], %2;\nselp.u32 %0, 1, 0, p;\n}\n" : "=r"(ok) : "r"(bar), "r"(parity) : "memory");
  } while (!ok && ++n < MBAR_LIMIT);
}
__device__ __forceinline__ void mbar_wait_cluster(uint32_t bar, uint32_t parity) {
  uint32_t ok, n = 0;
  do {
    asm volatile("{\n.reg .pred p;\nmbarrier.try_wait.parity.acquire.cluster.shared::cta.b64 p, [%1], %2;\nselp.u32 %0, 1, 0, p;\n}\n" : "=r"(ok) : "r"(bar), "r"(parity) : "memory");
  } while (!ok && ++n < MBAR_LIMIT);
}
__device__ __forceinline__ void tma_load_2d(uint32_t dst, const CUtensorMap* tm, uint32_t bar, int c0, int c1) {
  asm volatile("cp.async.bulk.tensor.2d.shared::cluster.global.mbarrier::complete_tx::bytes [%0], [%1, {%3, %4}], [%2];"
    :: "r"(dst), "l"(tm), "r"(bar), "r"(c0), "r"(c1) : "memory");
}
__device__ __forceinline__ void tma_load_2d_hint(uint32_t dst, const CUtensorMap* tm, uint32_t bar, int c0, int c1, uint64_t pol) {
  asm volatile("cp.async.bulk.tensor.2d.shared::cluster.global.mbarrier::complete_tx::bytes.L2::cache_hint [%0], [%1, {%3, %4}], [%2], %5;"
    :: "r"(dst), "l"(tm), "r"(bar), "r"(c0), "r"(c1), "l"(pol) : "memory");
}
__device__ __forceinline__ uint64_t policy_evict_first() { uint64_t p; asm volatile("createpolicy.fractional.L2::evict_first.b64 %0, 1.0;" : "=l"(p)); return p; }
__device__ __forceinline__ void tma_store_2d(const CUtensorMap* tm, uint32_t src, int c0, int c1) {
  asm volatile("cp.async.bulk.tensor.2d.global.shared::cta.bulk_group [%0, {%2, %3}], [%1];" :: "l"(tm), "r"(src), "r"(c0), "r"(c1) : "memory");
}
__device__ __forceinline__ void tma_prefetch_2d(const CUtensorMap* tm, int c0, int c1) {
  asm volatile("cp.async.bulk.prefetch.tensor.2d.L2.global.tile [%0, {%1, %2}];" :: "l"(tm), "r"(c0), "r"(c1) : "memory");
}
__device__ __forceinline__ void bulk_load(uint32_t dst, const void* src, uint32_t bytes, uint32_t bar) {
  asm volatile("cp.async.bulk.shared::cluster.global.mbarrier::complete_tx::bytes [%0], [%1], %2, [%3];" :: "r"(dst), "l"(src), "r"(bytes), "r"(bar) : "memory");
}
__device__ __forceinline__ void bulk_commit() { asm volatile("cp.async.bulk.commit_group;" ::: "memory"); }
__device__ __forceinline__ void bulk_wait_all() { asm volatile("cp.async.bulk.wait_group 0;" ::: "memory"); }
__device__ __forceinline__ void fence_async_smem() { asm volatile("fence.proxy.async.shared::cta;" ::: "memory"); }
__device__ __forceinline__ void wgmma_fence() { asm volatile("wgmma.fence.sync.aligned;" ::: "memory"); }
__device__ __forceinline__ void wgmma_commit() { asm volatile("wgmma.commit_group.sync.aligned;" ::: "memory"); }
__device__ __forceinline__ void wgmma_wait0() { asm volatile("wgmma.wait_group.sync.aligned 0;" ::: "memory"); }
__device__ __forceinline__ void bar_sync(int id, int n) { asm volatile("bar.sync %0, %1;" :: "r"(id), "r"(n) : "memory"); }
__device__ __forceinline__ void bar_arrive(int id, int n) { asm volatile("bar.arrive %0, %1;" :: "r"(id), "r"(n) : "memory"); }
template<int R> __device__ __forceinline__ void reg_inc() { asm volatile("setmaxnreg.inc.sync.aligned.u32 %0;" :: "n"(R)); }
template<int R> __device__ __forceinline__ void reg_dec() { asm volatile("setmaxnreg.dec.sync.aligned.u32 %0;" :: "n"(R)); }
__device__ __forceinline__ bool elect_one() {
  uint32_t p;
  asm volatile("{\n.reg .pred q;\nelect.sync _|q, 0xffffffff;\nselp.u32 %0, 1, 0, q;\n}\n" : "=r"(p));
  return p != 0;
}
__device__ __forceinline__ uint32_t mapa(uint32_t addr, uint32_t cta) { uint32_t r; asm volatile("mapa.shared::cluster.u32 %0, %1, %2;" : "=r"(r) : "r"(addr), "r"(cta)); return r; }
__device__ __forceinline__ void st_async_v4(uint32_t addr, uint32_t bar, uint32_t a, uint32_t b, uint32_t c, uint32_t d) {
  asm volatile("st.async.weak.shared::cluster.mbarrier::complete_tx::bytes.v4.b32 [%0], {%2, %3, %4, %5}, [%1];" :: "r"(addr), "r"(bar), "r"(a), "r"(b), "r"(c), "r"(d) : "memory");
}
__device__ __forceinline__ void stsm_x4(uint32_t addr, uint32_t a, uint32_t b, uint32_t c, uint32_t d) {
  asm volatile("stmatrix.sync.aligned.m8n8.x4.shared.b16 [%0], {%1, %2, %3, %4};" :: "r"(addr), "r"(a), "r"(b), "r"(c), "r"(d));
}
__device__ __forceinline__ uint4 lds128_v(uint32_t addr) { uint4 v; asm volatile("ld.shared.v4.b32 {%0, %1, %2, %3}, [%4];" : "=r"(v.x), "=r"(v.y), "=r"(v.z), "=r"(v.w) : "r"(addr)); return v; }
extern __shared__ __align__(1024) uint8_t smem_raw[];
template<class T> __device__ __forceinline__ T& smem_at(uint32_t addr) { return *reinterpret_cast<T*>(__cvta_shared_to_generic(addr)); }
#define SM_(T, off) smem_at<T>(sb + (off))
__device__ __forceinline__ uint4 ldg_nc128(const void* p) { uint4 v; asm volatile("ld.global.nc.v4.b32 {%0, %1, %2, %3}, [%4];" : "=r"(v.x), "=r"(v.y), "=r"(v.z), "=r"(v.w) : "l"(p)); return v; }
__device__ __forceinline__ void pkt_st128(void* p, uint32_t a, uint32_t b, uint32_t c, uint32_t d) {
  asm volatile("{\n.reg .b128 v;\n.reg .b64 lo, hi;\nmov.b64 lo, {%1, %2};\nmov.b64 hi, {%3, %4};\nmov.b128 v, {lo, hi};\nst.relaxed.gpu.global.b128 [%0], v;\n}\n"
    :: "l"(p), "r"(a), "r"(b), "r"(c), "r"(d) : "memory");
}
__device__ __forceinline__ uint4 pkt_ld128(const void* p) {
  uint4 r;
  asm volatile("{\n.reg .b128 v;\n.reg .b64 lo, hi;\nld.relaxed.gpu.global.b128 v, [%4];\nmov.b128 {lo, hi}, v;\nmov.b64 {%0, %1}, lo;\nmov.b64 {%2, %3}, hi;\n}\n"
    : "=r"(r.x), "=r"(r.y), "=r"(r.z), "=r"(r.w) : "l"(p) : "memory");
  return r;
}
__device__ __forceinline__ void pkt_ld128_if(uint4& r, const void* p, bool cond) {
  asm volatile("{\n.reg .pred q;\n.reg .b64 lo, hi;\nsetp.ne.b32 q, %5, 0;\nmov.b64 lo, {%0, %1};\nmov.b64 hi, {%2, %3};\n"
               "@q ld.relaxed.gpu.global.v2.b64 {lo, hi}, [%4];\nmov.b64 {%0, %1}, lo;\nmov.b64 {%2, %3}, hi;\n}\n"
    : "+r"(r.x), "+r"(r.y), "+r"(r.z), "+r"(r.w) : "l"(p), "r"((uint32_t)cond) : "memory");
}
__device__ __forceinline__ void pkt_st64(void* p, uint32_t a, uint32_t b) {
  asm volatile("{\n.reg .b64 v;\nmov.b64 v, {%1, %2};\nst.relaxed.gpu.global.b64 [%0], v;\n}\n" :: "l"(p), "r"(a), "r"(b) : "memory");
}
__device__ __forceinline__ uint2 pkt_ld64(const void* p) {
  uint2 r;
  asm volatile("{\n.reg .b64 v;\nld.relaxed.gpu.global.b64 v, [%2];\nmov.b64 {%0, %1}, v;\n}\n" : "=r"(r.x), "=r"(r.y) : "l"(p) : "memory");
  return r;
}
__device__ __forceinline__ uint32_t ld_relaxed32(const void* p) { uint32_t v; asm volatile("ld.relaxed.gpu.global.b32 %0, [%1];" : "=r"(v) : "l"(p) : "memory"); return v; }
__device__ __forceinline__ void st_relaxed32(void* p, uint32_t v) { asm volatile("st.relaxed.gpu.global.b32 [%0], %1;" :: "l"(p), "r"(v) : "memory"); }
__device__ __forceinline__ uint32_t code_of(uint32_t tag) { return tag % 3u + 1u; }
__device__ __forceinline__ uint32_t with_bit(float v, uint32_t bit) { return (__float_as_uint(v) & ~1u) | (bit & 1u); }
__device__ __forceinline__ uint32_t pair_code(uint32_t a, uint32_t b) { return (a & 1u) | ((b & 1u) << 1); }
__device__ __forceinline__ uint32_t pack_bf16(float lo, float hi) { uint32_t r; asm("cvt.rn.bf16x2.f32 %0, %1, %2;" : "=r"(r) : "f"(hi), "f"(lo)); return r; }
__device__ __forceinline__ float bf_lo(uint32_t v) { return __uint_as_float(v << 16); }
__device__ __forceinline__ float bf_hi(uint32_t v) { return __uint_as_float(v & 0xFFFF0000u); }
__device__ __forceinline__ float bf16r(float x) { return __uint_as_float(pack_bf16(0.f, x)); }
__device__ __forceinline__ uint32_t badd2(uint32_t a, uint32_t b) { uint32_t r; asm("add.rn.bf16x2 %0, %1, %2;" : "=r"(r) : "r"(a), "r"(b)); return r; }
__device__ __forceinline__ uint32_t bmul2(uint32_t a, uint32_t b) { uint32_t r; asm("mul.rn.bf16x2 %0, %1, %2;" : "=r"(r) : "r"(a), "r"(b)); return r; }
__device__ __forceinline__ float warp_sum(float v) {
#pragma unroll
  for (int o = 16; o > 0; o >>= 1) v += __shfl_xor_sync(0xffffffffu, v, o);
  return v;
}
__device__ __forceinline__ uint64_t make_desc(uint32_t addr) {
  return (uint64_t)((addr & 0x3FFFF) >> 4) | ((uint64_t)1 << 16) | ((uint64_t)64 << 32) | ((uint64_t)1 << 62);
}
__device__ __forceinline__ uint64_t make_desc_noswz(uint32_t addr) {
  return (uint64_t)((addr & 0x3FFFF) >> 4) | ((uint64_t)8 << 16) | ((uint64_t)16 << 32);
}
__device__ __forceinline__ uint64_t make_desc_32b(uint32_t addr) {
  return (uint64_t)((addr & 0x3FFFF) >> 4) | ((uint64_t)1 << 16) | ((uint64_t)16 << 32) | ((uint64_t)3 << 62);
}
__device__ __forceinline__ void wgmma_n256(float (&d)[128], uint64_t da, uint64_t db, int scale_d) {
  asm volatile("{\n.reg .pred p;\nsetp.ne.b32 p, %130, 0;\n"
    "wgmma.mma_async.sync.aligned.m64n256k16.f32.bf16.bf16 "
    "{%0, %1, %2, %3, %4, %5, %6, %7, %8, %9, %10, %11, %12, %13, %14, %15, %16, %17, %18, %19, %20, %21, %22, %23, %24, %25, %26, %27, %28, %29, %30, %31, "
    "%32, %33, %34, %35, %36, %37, %38, %39, %40, %41, %42, %43, %44, %45, %46, %47, %48, %49, %50, %51, %52, %53, %54, %55, %56, %57, %58, %59, %60, %61, %62, %63, "
    "%64, %65, %66, %67, %68, %69, %70, %71, %72, %73, %74, %75, %76, %77, %78, %79, %80, %81, %82, %83, %84, %85, %86, %87, %88, %89, %90, %91, %92, %93, %94, %95, "
    "%96, %97, %98, %99, %100, %101, %102, %103, %104, %105, %106, %107, %108, %109, %110, %111, %112, %113, %114, %115, %116, %117, %118, %119, %120, %121, %122, %123, %124, %125, %126, %127}, "
    "%128, %129, p, 1, 1, 0, 0;\n}\n"
    : "+f"(d[0]), "+f"(d[1]), "+f"(d[2]), "+f"(d[3]), "+f"(d[4]), "+f"(d[5]), "+f"(d[6]), "+f"(d[7]),
      "+f"(d[8]), "+f"(d[9]), "+f"(d[10]), "+f"(d[11]), "+f"(d[12]), "+f"(d[13]), "+f"(d[14]), "+f"(d[15]),
      "+f"(d[16]), "+f"(d[17]), "+f"(d[18]), "+f"(d[19]), "+f"(d[20]), "+f"(d[21]), "+f"(d[22]), "+f"(d[23]),
      "+f"(d[24]), "+f"(d[25]), "+f"(d[26]), "+f"(d[27]), "+f"(d[28]), "+f"(d[29]), "+f"(d[30]), "+f"(d[31]),
      "+f"(d[32]), "+f"(d[33]), "+f"(d[34]), "+f"(d[35]), "+f"(d[36]), "+f"(d[37]), "+f"(d[38]), "+f"(d[39]),
      "+f"(d[40]), "+f"(d[41]), "+f"(d[42]), "+f"(d[43]), "+f"(d[44]), "+f"(d[45]), "+f"(d[46]), "+f"(d[47]),
      "+f"(d[48]), "+f"(d[49]), "+f"(d[50]), "+f"(d[51]), "+f"(d[52]), "+f"(d[53]), "+f"(d[54]), "+f"(d[55]),
      "+f"(d[56]), "+f"(d[57]), "+f"(d[58]), "+f"(d[59]), "+f"(d[60]), "+f"(d[61]), "+f"(d[62]), "+f"(d[63]),
      "+f"(d[64]), "+f"(d[65]), "+f"(d[66]), "+f"(d[67]), "+f"(d[68]), "+f"(d[69]), "+f"(d[70]), "+f"(d[71]),
      "+f"(d[72]), "+f"(d[73]), "+f"(d[74]), "+f"(d[75]), "+f"(d[76]), "+f"(d[77]), "+f"(d[78]), "+f"(d[79]),
      "+f"(d[80]), "+f"(d[81]), "+f"(d[82]), "+f"(d[83]), "+f"(d[84]), "+f"(d[85]), "+f"(d[86]), "+f"(d[87]),
      "+f"(d[88]), "+f"(d[89]), "+f"(d[90]), "+f"(d[91]), "+f"(d[92]), "+f"(d[93]), "+f"(d[94]), "+f"(d[95]),
      "+f"(d[96]), "+f"(d[97]), "+f"(d[98]), "+f"(d[99]), "+f"(d[100]), "+f"(d[101]), "+f"(d[102]), "+f"(d[103]),
      "+f"(d[104]), "+f"(d[105]), "+f"(d[106]), "+f"(d[107]), "+f"(d[108]), "+f"(d[109]), "+f"(d[110]), "+f"(d[111]),
      "+f"(d[112]), "+f"(d[113]), "+f"(d[114]), "+f"(d[115]), "+f"(d[116]), "+f"(d[117]), "+f"(d[118]), "+f"(d[119]),
      "+f"(d[120]), "+f"(d[121]), "+f"(d[122]), "+f"(d[123]), "+f"(d[124]), "+f"(d[125]), "+f"(d[126]), "+f"(d[127])
    : "l"(da), "l"(db), "r"(scale_d));
}
__device__ __forceinline__ void wgmma_g1(float (&d)[128], uint64_t da, uint64_t db, int scale_d) { wgmma_n256(d, da, db, scale_d); }
__device__ __forceinline__ void wgmma_g1(float (&d)[120], uint64_t da, uint64_t db, int scale_d) {
  asm volatile("{\n.reg .pred p;\nsetp.ne.b32 p, %122, 0;\n"
    "wgmma.mma_async.sync.aligned.m64n240k16.f32.bf16.bf16 "
    "{%0, %1, %2, %3, %4, %5, %6, %7, %8, %9, %10, %11, %12, %13, %14, %15, %16, %17, %18, %19, %20, %21, %22, %23, %24, %25, %26, %27, %28, %29, %30, %31, %32, %33, %34, %35, %36, %37, %38, %39, %40, %41, %42, %43, %44, %45, %46, %47, %48, %49, %50, %51, %52, %53, %54, %55, %56, %57, %58, %59, %60, %61, %62, %63, %64, %65, %66, %67, %68, %69, %70, %71, %72, %73, %74, %75, %76, %77, %78, %79, %80, %81, %82, %83, %84, %85, %86, %87, %88, %89, %90, %91, %92, %93, %94, %95, %96, %97, %98, %99, %100, %101, %102, %103, %104, %105, %106, %107, %108, %109, %110, %111, %112, %113, %114, %115, %116, %117, %118, %119}, "
    "%120, %121, p, 1, 1, 0, 0;\n}\n"
    : "+f"(d[0]), "+f"(d[1]), "+f"(d[2]), "+f"(d[3]), "+f"(d[4]), "+f"(d[5]), "+f"(d[6]), "+f"(d[7]), "+f"(d[8]), "+f"(d[9]), "+f"(d[10]), "+f"(d[11]), "+f"(d[12]), "+f"(d[13]), "+f"(d[14]), "+f"(d[15]), "+f"(d[16]), "+f"(d[17]), "+f"(d[18]), "+f"(d[19]), "+f"(d[20]), "+f"(d[21]), "+f"(d[22]), "+f"(d[23]), "+f"(d[24]), "+f"(d[25]), "+f"(d[26]), "+f"(d[27]), "+f"(d[28]), "+f"(d[29]), "+f"(d[30]), "+f"(d[31]), "+f"(d[32]), "+f"(d[33]), "+f"(d[34]), "+f"(d[35]), "+f"(d[36]), "+f"(d[37]), "+f"(d[38]), "+f"(d[39]), "+f"(d[40]), "+f"(d[41]), "+f"(d[42]), "+f"(d[43]), "+f"(d[44]), "+f"(d[45]), "+f"(d[46]), "+f"(d[47]), "+f"(d[48]), "+f"(d[49]), "+f"(d[50]), "+f"(d[51]), "+f"(d[52]), "+f"(d[53]), "+f"(d[54]), "+f"(d[55]), "+f"(d[56]), "+f"(d[57]), "+f"(d[58]), "+f"(d[59]), "+f"(d[60]), "+f"(d[61]), "+f"(d[62]), "+f"(d[63]), "+f"(d[64]), "+f"(d[65]), "+f"(d[66]), "+f"(d[67]), "+f"(d[68]), "+f"(d[69]), "+f"(d[70]), "+f"(d[71]), "+f"(d[72]), "+f"(d[73]), "+f"(d[74]), "+f"(d[75]), "+f"(d[76]), "+f"(d[77]), "+f"(d[78]), "+f"(d[79]), "+f"(d[80]), "+f"(d[81]), "+f"(d[82]), "+f"(d[83]), "+f"(d[84]), "+f"(d[85]), "+f"(d[86]), "+f"(d[87]), "+f"(d[88]), "+f"(d[89]), "+f"(d[90]), "+f"(d[91]), "+f"(d[92]), "+f"(d[93]), "+f"(d[94]), "+f"(d[95]), "+f"(d[96]), "+f"(d[97]), "+f"(d[98]), "+f"(d[99]), "+f"(d[100]), "+f"(d[101]), "+f"(d[102]), "+f"(d[103]), "+f"(d[104]), "+f"(d[105]), "+f"(d[106]), "+f"(d[107]), "+f"(d[108]), "+f"(d[109]), "+f"(d[110]), "+f"(d[111]), "+f"(d[112]), "+f"(d[113]), "+f"(d[114]), "+f"(d[115]), "+f"(d[116]), "+f"(d[117]), "+f"(d[118]), "+f"(d[119])
    : "l"(da), "l"(db), "r"(scale_d));
}
__device__ __forceinline__ void wgmma_n256_rs(float (&d)[128], uint32_t a0, uint32_t a1, uint32_t a2, uint32_t a3, uint64_t db, int scale_d) {
  asm volatile("{\n.reg .pred p;\nsetp.ne.b32 p, %133, 0;\n"
    "wgmma.mma_async.sync.aligned.m64n256k16.f32.bf16.bf16 "
    "{%0, %1, %2, %3, %4, %5, %6, %7, %8, %9, %10, %11, %12, %13, %14, %15, %16, %17, %18, %19, %20, %21, %22, %23, %24, %25, %26, %27, %28, %29, %30, %31, "
    "%32, %33, %34, %35, %36, %37, %38, %39, %40, %41, %42, %43, %44, %45, %46, %47, %48, %49, %50, %51, %52, %53, %54, %55, %56, %57, %58, %59, %60, %61, %62, %63, "
    "%64, %65, %66, %67, %68, %69, %70, %71, %72, %73, %74, %75, %76, %77, %78, %79, %80, %81, %82, %83, %84, %85, %86, %87, %88, %89, %90, %91, %92, %93, %94, %95, "
    "%96, %97, %98, %99, %100, %101, %102, %103, %104, %105, %106, %107, %108, %109, %110, %111, %112, %113, %114, %115, %116, %117, %118, %119, %120, %121, %122, %123, %124, %125, %126, %127}, "
    "{%128, %129, %130, %131}, %132, p, 1, 1, 0;\n}\n"
    : "+f"(d[0]), "+f"(d[1]), "+f"(d[2]), "+f"(d[3]), "+f"(d[4]), "+f"(d[5]), "+f"(d[6]), "+f"(d[7]),
      "+f"(d[8]), "+f"(d[9]), "+f"(d[10]), "+f"(d[11]), "+f"(d[12]), "+f"(d[13]), "+f"(d[14]), "+f"(d[15]),
      "+f"(d[16]), "+f"(d[17]), "+f"(d[18]), "+f"(d[19]), "+f"(d[20]), "+f"(d[21]), "+f"(d[22]), "+f"(d[23]),
      "+f"(d[24]), "+f"(d[25]), "+f"(d[26]), "+f"(d[27]), "+f"(d[28]), "+f"(d[29]), "+f"(d[30]), "+f"(d[31]),
      "+f"(d[32]), "+f"(d[33]), "+f"(d[34]), "+f"(d[35]), "+f"(d[36]), "+f"(d[37]), "+f"(d[38]), "+f"(d[39]),
      "+f"(d[40]), "+f"(d[41]), "+f"(d[42]), "+f"(d[43]), "+f"(d[44]), "+f"(d[45]), "+f"(d[46]), "+f"(d[47]),
      "+f"(d[48]), "+f"(d[49]), "+f"(d[50]), "+f"(d[51]), "+f"(d[52]), "+f"(d[53]), "+f"(d[54]), "+f"(d[55]),
      "+f"(d[56]), "+f"(d[57]), "+f"(d[58]), "+f"(d[59]), "+f"(d[60]), "+f"(d[61]), "+f"(d[62]), "+f"(d[63]),
      "+f"(d[64]), "+f"(d[65]), "+f"(d[66]), "+f"(d[67]), "+f"(d[68]), "+f"(d[69]), "+f"(d[70]), "+f"(d[71]),
      "+f"(d[72]), "+f"(d[73]), "+f"(d[74]), "+f"(d[75]), "+f"(d[76]), "+f"(d[77]), "+f"(d[78]), "+f"(d[79]),
      "+f"(d[80]), "+f"(d[81]), "+f"(d[82]), "+f"(d[83]), "+f"(d[84]), "+f"(d[85]), "+f"(d[86]), "+f"(d[87]),
      "+f"(d[88]), "+f"(d[89]), "+f"(d[90]), "+f"(d[91]), "+f"(d[92]), "+f"(d[93]), "+f"(d[94]), "+f"(d[95]),
      "+f"(d[96]), "+f"(d[97]), "+f"(d[98]), "+f"(d[99]), "+f"(d[100]), "+f"(d[101]), "+f"(d[102]), "+f"(d[103]),
      "+f"(d[104]), "+f"(d[105]), "+f"(d[106]), "+f"(d[107]), "+f"(d[108]), "+f"(d[109]), "+f"(d[110]), "+f"(d[111]),
      "+f"(d[112]), "+f"(d[113]), "+f"(d[114]), "+f"(d[115]), "+f"(d[116]), "+f"(d[117]), "+f"(d[118]), "+f"(d[119]),
      "+f"(d[120]), "+f"(d[121]), "+f"(d[122]), "+f"(d[123]), "+f"(d[124]), "+f"(d[125]), "+f"(d[126]), "+f"(d[127])
    : "r"(a0), "r"(a1), "r"(a2), "r"(a3), "l"(db), "r"(scale_d));
}
__device__ __forceinline__ void wgmma_n128(float (&d)[64], uint64_t da, uint64_t db, int scale_d = 1) {
  asm volatile("{\n.reg .pred p;\nsetp.ne.b32 p, %66, 0;\n"
    "wgmma.mma_async.sync.aligned.m64n128k16.f32.bf16.bf16 "
    "{%0, %1, %2, %3, %4, %5, %6, %7, %8, %9, %10, %11, %12, %13, %14, %15, %16, %17, %18, %19, %20, %21, %22, %23, %24, %25, %26, %27, %28, %29, %30, %31, %32, %33, %34, %35, %36, %37, %38, %39, %40, %41, %42, %43, %44, %45, %46, %47, %48, %49, %50, %51, %52, %53, %54, %55, %56, %57, %58, %59, %60, %61, %62, %63}, "
    "%64, %65, p, 1, 1, 0, 0;\n}\n"
    : "+f"(d[0]), "+f"(d[1]), "+f"(d[2]), "+f"(d[3]), "+f"(d[4]), "+f"(d[5]), "+f"(d[6]), "+f"(d[7]), "+f"(d[8]), "+f"(d[9]), "+f"(d[10]), "+f"(d[11]), "+f"(d[12]), "+f"(d[13]), "+f"(d[14]), "+f"(d[15]), "+f"(d[16]), "+f"(d[17]), "+f"(d[18]), "+f"(d[19]), "+f"(d[20]), "+f"(d[21]), "+f"(d[22]), "+f"(d[23]), "+f"(d[24]), "+f"(d[25]), "+f"(d[26]), "+f"(d[27]), "+f"(d[28]), "+f"(d[29]), "+f"(d[30]), "+f"(d[31]), "+f"(d[32]), "+f"(d[33]), "+f"(d[34]), "+f"(d[35]), "+f"(d[36]), "+f"(d[37]), "+f"(d[38]), "+f"(d[39]), "+f"(d[40]), "+f"(d[41]), "+f"(d[42]), "+f"(d[43]), "+f"(d[44]), "+f"(d[45]), "+f"(d[46]), "+f"(d[47]), "+f"(d[48]), "+f"(d[49]), "+f"(d[50]), "+f"(d[51]), "+f"(d[52]), "+f"(d[53]), "+f"(d[54]), "+f"(d[55]), "+f"(d[56]), "+f"(d[57]), "+f"(d[58]), "+f"(d[59]), "+f"(d[60]), "+f"(d[61]), "+f"(d[62]), "+f"(d[63])
    : "l"(da), "l"(db), "r"(scale_d));
}
template<int N> __device__ __forceinline__ void fence_acc(float (&d)[N]) {
#pragma unroll
  for (int i = 0; i < N; i++) asm volatile("" : "+f"(d[i]) :: "memory");
}

template<int N, int I = 0, class F> __device__ __forceinline__ void static_for(F&& f) {
  if constexpr (I < N) { f(std::integral_constant<int, I>()); static_for<N, I + 1>(f); }
}

__device__ __forceinline__ void ldsm_x4_t(uint32_t addr, uint32_t& a, uint32_t& b, uint32_t& c, uint32_t& d) {
  asm volatile("ldmatrix.sync.aligned.m8n8.x4.trans.shared.b16 {%0, %1, %2, %3}, [%4];" : "=r"(a), "=r"(b), "=r"(c), "=r"(d) : "r"(addr));
}
__device__ __forceinline__ void sts128(uint32_t addr, uint32_t a, uint32_t b, uint32_t c, uint32_t d) {
  asm volatile("st.shared.v4.b32 [%0], {%1, %2, %3, %4};" :: "r"(addr), "r"(a), "r"(b), "r"(c), "r"(d));
}
__device__ __forceinline__ void mma16816(float (&c)[4], uint32_t a0, uint32_t a1, uint32_t a2, uint32_t a3, uint32_t b0, uint32_t b1) {
  asm volatile("mma.sync.aligned.m16n8k16.row.col.f32.bf16.bf16.f32 {%0, %1, %2, %3}, {%4, %5, %6, %7}, {%8, %9}, {%0, %1, %2, %3};"
      : "+f"(c[0]), "+f"(c[1]), "+f"(c[2]), "+f"(c[3]) : "r"(a0), "r"(a1), "r"(a2), "r"(a3), "r"(b0), "r"(b1));
}
__device__ __forceinline__ void mma1688(float (&c)[4], uint32_t a0, uint32_t a1, uint32_t b0) {
  asm volatile("mma.sync.aligned.m16n8k8.row.col.f32.bf16.bf16.f32 {%0, %1, %2, %3}, {%4, %5}, {%6}, {%0, %1, %2, %3};"
      : "+f"(c[0]), "+f"(c[1]), "+f"(c[2]), "+f"(c[3]) : "r"(a0), "r"(a1), "r"(b0));
}
__device__ __forceinline__ void pin(uint32_t& v) { asm volatile("shfl.sync.bfly.b32 %0, %0, 0, 0x1f, 0xffffffff;" : "+r"(v)); }
template<class T> __device__ __forceinline__ void pin(T*& v) {
  uint32_t lo = (uint32_t)(uint64_t)v, hi = (uint32_t)((uint64_t)v >> 32);
  pin(lo); pin(hi);
  v = (T*)(((uint64_t)hi << 32) | lo);
}
__device__ __forceinline__ float sel4(int q, float a, float b, float c, float d) {
  float r;
  asm("{\n.reg .pred p, o;\n.reg .f32 x, y;\n.reg .b32 t;\nand.b32 t, %1, 1;\nsetp.ne.b32 p, t, 0;\nsetp.gt.s32 o, %1, 1;\n"
      "selp.f32 x, %3, %2, p;\nselp.f32 y, %5, %4, p;\nselp.f32 %0, y, x, o;\n}\n" : "=f"(r) : "r"(q), "f"(a), "f"(b), "f"(c), "f"(d));
  return r;
}
__device__ __forceinline__ uint32_t bfma2(uint32_t a, uint32_t b, uint32_t c) { uint32_t r; asm("fma.rn.bf16x2 %0, %1, %2, %3;" : "=r"(r) : "r"(a), "r"(b), "r"(c)); return r; }
__device__ __forceinline__ void tma_load_5d(uint32_t dst, const CUtensorMap* tm, uint32_t bar, int c0) {
  asm volatile("cp.async.bulk.tensor.5d.shared::cluster.global.mbarrier::complete_tx::bytes [%0], [%1, {%3, %4, %4, %4, %4}], [%2];"
    :: "r"(dst), "l"(tm), "r"(bar), "r"(c0), "r"(0) : "memory");
}
__device__ __forceinline__ void tma_store_5d(const CUtensorMap* tm, uint32_t src, int c0, int c3, int c4) {
  asm volatile("cp.async.bulk.tensor.5d.global.shared::cta.bulk_group [%0, {%2, %3, %3, %4, %5}], [%1];" :: "l"(tm), "r"(src), "r"(c0), "r"(0), "r"(c3), "r"(c4) : "memory");
}
__device__ __forceinline__ float rcp_fast(float x) { float r; asm("rcp.approx.ftz.f32 %0, %1;" : "=f"(r) : "f"(x)); return r; }
__device__ __forceinline__ float sigmoid_fast(float x) { float e; asm("ex2.approx.ftz.f32 %0, %1;" : "=f"(e) : "f"(x * -1.4426950408889634f)); return rcp_fast(1.f + e); }
__device__ __forceinline__ float sqrt_fast(float x) { float r; asm("sqrt.approx.ftz.f32 %0, %1;" : "=f"(r) : "f"(x)); return r; }
__device__ __forceinline__ float ln_sd(float var) { return bf16r(sqrt_fast(bf16r(bf16r(fmaxf(var, 0.f)) + 1e-5f))); }
__device__ __forceinline__ uint32_t norm2(uint32_t h, uint32_t neg_mean2, float inv_sd) {
  const uint32_t d = badd2(h, neg_mean2);
  return pack_bf16(bf_lo(d) * inv_sd, bf_hi(d) * inv_sd);
}
template<int N> __device__ __forceinline__ void delay_clk() {
  if constexpr (N > 0) { const uint32_t t0 = clock(); while ((uint32_t)clock() - t0 < N) {} }
}
__device__ __forceinline__ void put_xstat(uint32_t rs, uint32_t exb, int col, uint32_t mean_rstd, int m) {
  smem_at<uint16_t>(rs + ((col & 7) >> 1) * 144 + (col >> 3) * 4 + (col & 1) * 2) = (uint16_t)(mean_rstd ^ (m << 15));
  const uint32_t nm = (mean_rstd >> 16) ^ 0x8000u;
  smem_at<uint4>(exb + (col >> 3) * 256 + (col & 7) * 16) = make_uint4(nm | (nm << 16), nm, 0, 0);
  smem_at<uint4>(exb + (col >> 3) * 256 + 128 + (col & 7) * 16) = make_uint4(0, 0, 0, 0);
}
__device__ __forceinline__ void put_dsum(uint32_t exa, int e, float c) {
  const float hi = bf16r(c), mid = bf16r(c - hi), lo = bf16r((c - hi) - mid);
  smem_at<uint4>(exa + (e >> 3) * 256 + (e & 7) * 16) = make_uint4((__float_as_uint(hi) >> 16) | (__float_as_uint(mid) & 0xFFFF0000u), __float_as_uint(lo) >> 16, 0, 0);
  smem_at<uint4>(exa + (e >> 3) * 256 + 128 + (e & 7) * 16) = make_uint4(0, 0, 0, 0);
}
__host__ __device__ constexpr int min_c(int a, int b) { return a < b ? a : b; }
template<int V> using IC = std::integral_constant<int, V>;

#define CT(slot) do {} while (0)
#define PT(slot) do {} while (0)

template<int MAP>
__global__ void __cluster_dims__(2, 1, 1) __launch_bounds__(384, 1)
fnet_moe_kernel(const __grid_constant__ Params p) {
  constexpr int NX = MAP == 0 ? NX0 : 256;
  constexpr int G1_BYTES = A_BYTES + NX * 128;
  uint32_t sb;
  asm volatile("mov.u32 %0, %1;" : "=r"(sb) : "r"(smem_u32(smem_raw)));
  const int m = blockIdx.x & 1;
  int tau, eps;
  bool helper = false;
  if (MAP == 0) {
    uint32_t smid;
    asm volatile("mov.u32 %0, %%smid;" : "=r"(smid));
    const int c = smid >> 1, e7 = ((c - 32) * 37) >> 8;
    helper = c == 60 || c == 61;
    tau = c < 32 ? (c & 7) : (c < 60 ? c - 31 - 7 * e7 : 0);
    eps = c < 32 ? (c >> 3) : (c < 60 ? 4 + e7 : c - 58);
  } else {
    tau = (blockIdx.x >> 1) & 7; eps = blockIdx.x >> 4;
  }
  const int cid = tau * 16 + eps * 2 + m;
  const bool moe = tau > 0;
  auto BAR = [&](int i) { return sb + OFF_BAR + 8 * i; };
  const CUtensorMap* tmD = m ? &p.tmD1 : &p.tmD0;
  const uint64_t pol_ef = policy_evict_first();
#define LOAD_STREAM(d, tm, bar, c0, c1) tma_load_2d_hint(d, tm, bar, c0, c1, pol_ef)
  auto helper_load = [&](int k) {
    const uint32_t sa = sb + slot_of(k) * ST_BYTES, bar = BAR(B_FULL + slot_of(k));
    const CUtensorMap* tm = eps == 3 ? &p.tmD1 : &p.tmD0;
    tma_load_5d(sa, &p.tmXh, bar, (k & 15) * 64);
    tma_load_2d(sa + A_BYTES, tm, bar, (k & 15) * 64, m * 512 + (k >> 4) * 256);
    tma_load_2d(sa + A_BYTES + 16384, tm, bar, (k & 15) * 64, m * 512 + (k >> 4) * 256 + 128);
  };
  if (threadIdx.x < 32 && elect_one()) {
    mbar_init(BAR(B_FULL), 1);
    asm volatile("fence.mbarrier_init.release.cluster;" ::: "memory");
    if (!helper) {
      tma_load_2d(sb + A_BYTES, &p.tmX, BAR(B_FULL), 0, tau * 256);
      tma_load_2d(sb, tmD, BAR(B_FULL), 0, eps * 128);
    }
    PT(52);
#pragma unroll
    for (int k = 1; k < 4; k++) mbar_init(BAR(B_FULL + k), 1);
    asm volatile("fence.mbarrier_init.release.cluster;" ::: "memory");
#pragma unroll
    for (int k = 0; k < 4; k++) mbar_expect_tx(BAR(B_FULL + k), helper ? ST_BYTES : G1_BYTES);
    if (!helper) {
#pragma unroll
      for (int k = 1; k < 4; k++) {
        tma_load_2d(sb + k * ST_BYTES + A_BYTES, &p.tmX, BAR(B_FULL + k), k * 64, tau * 256);
        LOAD_STREAM(sb + k * ST_BYTES, tmD, BAR(B_FULL + k), k * 64, eps * 128);
      }
    } else {
#pragma unroll 1
      for (int k = 0; k < 4; k++) helper_load(k);
    }
    PT(0);
  }
  __syncwarp();
  const int warp = __shfl_sync(0xffffffffu, threadIdx.x >> 5, 0);
  if (warp == 8) {
    if (elect_one()) {
#pragma unroll
      for (int b = B_EMPTY; b < B_COUNT; b++)
        mbar_init(BAR(b), b < B_EPI ? 2 : (b == B_EPI || b == B_EPI0B) ? 4 : (b < B_STD || b == B_OUT) ? 8 : (b == B_STAT || b == B_XS) ? 3 : 1);
      asm volatile("fence.mbarrier_init.release.cluster;" ::: "memory");
      mbar_expect_tx(BAR(B_XCH), 32768);
      SM_(uint32_t, OFF_SEEN) = 0;
    }
  }
  __syncthreads();

  if (warp >= 8) {
    reg_dec<REG_P>();
    asm volatile("barrier.cluster.arrive.relaxed.aligned;" ::: "memory");
    const int abrow = m * 1024 + eps * 128;
    const int f0 = (cid - 16) * 32;
    const CUtensorMap* tmWM = m ? &p.tmWM1 : &p.tmWM0;
    auto side_first = [&](int k) {
      if (NX < 256 && k == MINI_LOAD_K) {
        static_assert(NX == 256 || (mr_k(NREG_H) == MINI_LOAD_K && (NREG_H & 1) == 1), "second half of the staging buffer must be free");
        mbar_wait(BAR(B_STD + 3), 0);
        uint32_t n = 0;
        while (!((*(volatile uint32_t*)&SM_(uint32_t, OFF_SEEN) >> (4 * tau + 1)) & 1) && ++n < SPIN_LIMIT * 16) {}
        if (elect_one()) {
          mbar_expect_tx(BAR(B_A20), 12288);
          tma_load_2d(sb + OFF_MINI, &p.tmAbM, BAR(B_A20), tau * 256 + 240, abrow);
          LOAD_STREAM(sb + OFF_MINI + 4096, tmWM, BAR(B_A20), tau * 256 + 240, tau * 256 + m * 128);
          LOAD_STREAM(sb + OFF_MINI + 8192, tmWM, BAR(B_A20), tau * 256 + 240, tau * 256 + (1 - m) * 128);
        }
      }
    };
    auto side = [&](int k) {
      if (NX < 256 && k == MINI_PF_K && elect_one()) tma_prefetch_2d(tmWM, tau * 256 + 240, tau * 256 + (eps & 1) * 128);
      if (!moe) return;
      const int i = k - MR_K0, r6 = i / MR_P, u = i - MR_P * r6, h = 2 * r6 + (u >> 1);
      if (i >= 0 && u < 4 && h < NREG_H) {
        if (h < 2) mbar_wait(BAR(B_STD + 2 + h), 0);
        if (elect_one()) {
          if (!(u & 1)) mbar_expect_tx(BAR(B_MR + (h & 1)), 16384);
          LOAD_STREAM(sb + OFF_XCH + u * 8192, (u & 1) ? &p.tmU : &p.tmG, BAR(B_MR + (h & 1)), f0, h * 128);
        }
      }
      if (k >= 46 && elect_one()) {
        static_assert(mr_k(NREG_H + 1) <= 47 && MINI_K + 4 <= 46, "staging buffer must be free");
        LOAD_STREAM(sb + round_off(NREG_H + k - 46), &p.tmG, BAR(B_GU), f0, (NREG_H + k - 46) * 128);
        LOAD_STREAM(sb + round_off(NREG_H + k - 46) + 8192, &p.tmU, BAR(B_GU), f0, (NREG_H + k - 46) * 128);
      }
      if (k >= PF_K1 && !(k & 1) && elect_one()) {
        const int j = PF_N0 + ((k - PF_K1) >> 1);
        if (j < 8) tma_prefetch_2d(m ? &p.tmU : &p.tmG, f0, j * 128);
        else if (j < 12) asm volatile("cp.async.bulk.prefetch.L2.global [%0], %1;" :: "l"(p.wdown + (size_t)f0 * 1024 + (j - 8) * 8192), "r"(16384) : "memory");
      }
    };
    if (MAP == 0 && helper) {
      if (warp == 8) {
#pragma unroll 1
        for (int k = 4; k < 32; k++) {
          mbar_wait(BAR(B_EMPTY + slot_of(k)), (use_of(k) & 1) ^ 1);
          if (elect_one()) { mbar_expect_tx(BAR(B_FULL + slot_of(k)), ST_BYTES); helper_load(k); }
        }
      } else {
        const int i0 = threadIdx.x - 288, lane = threadIdx.x & 31, col0 = (eps - 2) * 8 + m * 4;
        __nanosleep(HELPER_NS);
        const uint32_t tag = ld_relaxed32(&p.s->epoch) + 1;
        if (i0 < 8) pkt_st128(&p.s->hflag[col0 * 2 + i0], 0, 0, 0, 0);
        SM_(uint32_t, OFF_TAG) = tag;
#pragma unroll 1
        for (int j0 = i0; j0 < 768; j0 += 384) {
          uint2 v[4]; uint32_t n = 0;
          while (true) {
#pragma unroll
            for (int z = 0; z < 4; z++) {
              const int j = j0 + 96 * z;
              v[z] = pkt_ld64(p.s->xstat + (j < 128 ? 256 * (j >> 4) + 240 + 2 * (j & 6) + ((j >> 2) & 2) + (j & 1)
                                          : j < 640 ? 2048 + col0 * 128 + j - 128 : (j - 640) * 16));
            }
            if (__all_sync(0xffffffffu, v[0].y == tag && v[1].y == tag && v[2].y == tag && v[3].y == tag) || ++n > SPIN_LIMIT) break;
            __nanosleep(300);
          }
#pragma unroll
          for (int z = 0; z < 4; z++) {
            const int j = j0 + 96 * z;
            if (j < 128) put_xstat(sb + OFF_RS, sb + OFF_XCH + 16384, j, v[z].x, eps - 2);
            else if (j < 640) put_dsum(sb + OFF_XCH, j - 128, __uint_as_float(v[z].x));
          }
        }
        fence_async_smem();
        __syncwarp();
        if (lane == 0) mbar_arrive(BAR(B_STAT));
      }
    } else if (warp == 8) {
      const CUtensorMap* tmW = m ? &p.tmW1 : &p.tmW0;
      const int tA = tau * 256 + m * 128, tB = tau * 256 + (1 - m) * 128;
      auto wait_slot = [&](int k) {
        mbar_wait(BAR(B_EMPTY + slot_of(k)), (use_of(k) & 1) ^ 1);
        PT(64 + k);
      };
#pragma unroll 1
      for (int k = 4; k < 24; k++) {
        const int s = slot_of(k);
        const uint32_t sa = sb + s * ST_BYTES, sbb = sa + A_BYTES;
        const int kb = kblock(tau, k - 16);
        wait_slot(k);
        if (elect_one()) {
          mbar_expect_tx(BAR(B_FULL + s), k < 16 ? G1_BYTES : (k >> 1) == 9 ? B_BYTES : k == 20 ? ST_BYTES - 8192 : ST_BYTES);
          if (k < 16) {
            LOAD_STREAM(sa, tmD, BAR(B_FULL + s), k * 64, eps * 128);
            tma_load_2d(sbb, &p.tmX, BAR(B_FULL + s), k * 64, tau * 256);
          } else {
            LOAD_STREAM(sbb, tmW, BAR(B_FULL + s), kb * 64, tA);
            LOAD_STREAM(sbb + 16384, tmW, BAR(B_FULL + s), kb * 64, tB);
            if (k < 18) {
              tma_load_2d(sa, &p.tmXr, BAR(B_FULL + s), eps * 128, tA + s * 64);
              tma_load_2d(sa + 8192, &p.tmXr, BAR(B_FULL + s), eps * 128 + 64, tA + s * 64);
            }
          }
          if (k == PUB_K1) mbar_arrive(BAR(B_LATE));
          if (k >= WPF_K0 && k < WPF_K0 + WPF_N && (eps >> 1) == ((k - WPF_K0) & 3))
            tma_prefetch_2d(tmW, kblock(tau, k - WPF_K0) * 64, tau * 256 + (eps & 1) * 128);
          if (moe && k >= PF_K0 && k < PF_K0 + 2 * PF_N0 && !(k & 1)) tma_prefetch_2d(m ? &p.tmU : &p.tmG, f0, (k - PF_K0) * 64);
        }
      }
      uint32_t seen = 0;
#pragma unroll 1
      for (int k = 24; k < 48; k++) {
        const int s = slot_of(k);
        const uint32_t sa = sb + s * ST_BYTES, sbb = sa + A_BYTES;
        const int kb = kblock(tau, k - 16);
        const uint32_t need = (1u << kb) | ((kb & 3) == 3 ? 2u << (4 * tau) : 0u);
        wait_slot(k);
        side_first(k);
        if (elect_one()) {
          mbar_expect_tx(BAR(B_FULL + s), ST_BYTES);
          LOAD_STREAM(sbb, tmW, BAR(B_FULL + s), kb * 64, tA);
          LOAD_STREAM(sbb + 16384, tmW, BAR(B_FULL + s), kb * 64, tB);
        }
        uint32_t n = 0;
        while ((seen & need) != need && ++n < SPIN_LIMIT * 16) seen = *(volatile uint32_t*)&SM_(uint32_t, OFF_SEEN);
        if (elect_one()) tma_load_2d(sa, &p.tmAbL, BAR(B_FULL + s), kb * 64, abrow);
        side(k);
      }
      if (moe) {
        mbar_wait(BAR(B_EMPTY + 0), 1);
        if (elect_one()) { mbar_expect_tx(BAR(B_GU), (8 - NREG_H) * 16384); mbar_expect_tx(BAR(B_DN), 65536); }
#pragma unroll 1
        for (int i = 0; i < 10 - NREG_H; i++) {
          if (i == 3) mbar_wait(BAR(B_EMPTY + 1), 1);
          if (i == 4) {
            mbar_wait(BAR(B_EMPTY + 2), 1);
            mbar_wait(BAR(B_XCH), 0);
            PT(53);
          }
          const uint32_t dst = sb + late_off(i);
          if (elect_one()) {
            if (i < 6 - NREG_H) {
              LOAD_STREAM(dst, &p.tmG, BAR(B_GU), f0, (NREG_H + 2 + i) * 128);
              LOAD_STREAM(dst + 8192, &p.tmU, BAR(B_GU), f0, (NREG_H + 2 + i) * 128);
            } else {
#pragma unroll
              for (int b = 0; b < 4; b++) LOAD_STREAM(dst + b * 4096, &p.tmDn, BAR(B_DN), (4 * (i - 6 + NREG_H) + b) * 64, f0);
            }
          }
          const long long t0 = clock64();
          while (i < 9 - NREG_H && clock64() - t0 < MOE_PACE_CLK) {}
        }
      }
      const int lane = threadIdx.x & 31;
      mbar_wait(BAR(B_OUT), 0);
      const uint32_t km = SM_(uint32_t, OFF_WKEY + (lane & 7) * 8);
      const uint32_t bk = __reduce_max_sync(0xffffffffu, km);
      const int ww = __ffs(__ballot_sync(0xffffffffu, km == bk)) - 1;
#pragma unroll 1
      for (int i = 1; i <= 8; i++) {
        const int W = (ww + i) & 7;
        if (i == 8) {
          mbar_wait(BAR(B_XS), 0);
          if (SM_(uint32_t, OFF_KV) == bk) {
#pragma unroll 2
            for (int j = lane; j < 256; j += 32) {
              const int rho = j >> 4, row = (tau * 2 + m) * 128 + 32 * (W >> 1) + 8 * ((rho & 7) >> 1) + 4 * (W & 1) + 2 * (rho >> 3) + (rho & 1);
              const uint4 v = lds128_v(sb + OFF_OUT + (j & 8) * 2048 + (16 * W + rho) * 128 + (((j ^ rho) & 7) << 4));
              if (row != 0xFFFF - (int)(bk & 0xFFFFu))
                asm volatile("st.global.v4.b32 [%0], {%1, %2, %3, %4};" :: "l"(p.out + (size_t)row * 1024 + eps * 128 + (j & 15) * 8), "r"(v.x), "r"(v.y), "r"(v.z), "r"(v.w));
            }
            break;
          }
        }
        if (lane == 0) {
          tma_store_5d(&p.tmOut, sb + OFF_OUT + W * 2048, eps * 128, 2 * (W & 1), tau * 8 + m * 4 + (W >> 1));
          tma_store_5d(&p.tmOut, sb + OFF_OUT + 16384 + W * 2048, eps * 128 + 64, 2 * (W & 1), tau * 8 + m * 4 + (W >> 1));
        }
        const long long t0 = clock64();
        while (i < 7 && clock64() - t0 < OUT_PACE_CLK) {}
      }
      if (lane == 0) { bulk_commit(); bulk_wait_all(); }
      PT(22);
    } else {
      const int a = warp - 9;
      const int lane = threadIdx.x & 31;
      auto stage = [&](const bf16* src, int g) {
        if (elect_one()) {
          mbar_expect_tx(BAR(B_AUX + g), 16384);
          bulk_load(sb + OFF_XCH + g * 16384, src + g * 8192, 16384, BAR(B_AUX + g));
        }
      };
      uint32_t tag = 0;
      mbar_wait(BAR(B_FULL + AUX_AFTER), 0);
      if (a == 0) PT(1);
      if (a == 1) mbar_wait(BAR(B_AUX + 0), 0);
      if (a < 2) stage(p.x + (size_t)cid * 16 * 1024, a);
#pragma unroll 1
      for (int it = 0; it < 4; it++) {
        const int g = it & 1;
        mbar_wait(BAR(B_AUX + g), it >> 1);
        if (a == 0) PT(2 + it);
        if (it == 2) tag = ld_relaxed32(&p.s->epoch) + 1;
        if (it == 2 && a == 2 && lane < 16) asm volatile("prefetch.global.L2 [%0];" :: "l"(p.wr + lane * 64));
        const uint32_t ad = sb + OFF_XCH + g * 16384 + (lane >> 2) * 2048;
        float s0 = 0.f, s1 = 0.f, q0 = 0.f, q1 = 0.f;
        auto row = [&](auto sq) {
#pragma unroll
          for (int i = 0; i < 11; i++) {
            if (i == 10 && a == 2) break;
            const uint4 v = lds128_v(ad + (((a * 44 + 4 * i + lane) & 127) << 4));
            const uint32_t ww[4] = {v.x, v.y, v.z, v.w};
#pragma unroll
            for (int z = 0; z < 4; z++) {
              const float d0 = bf_lo(ww[z]), d1 = bf_hi(ww[z]);
              s0 += d0; s1 += d1;
              if (decltype(sq)::value) { q0 = fmaf(d0, d0, q0); q1 = fmaf(d1, d1, q1); }
            }
          }
        };
        if (it < 2) row(IC<1>()); else row(IC<0>());
        s0 += s1; q0 += q1;
#pragma unroll
        for (int o = 1; o < 4; o <<= 1) { s0 += __shfl_xor_sync(0xffffffffu, s0, o); q0 += __shfl_xor_sync(0xffffffffu, q0, o); }
        if ((lane & 3) == 0) SM_(float2, OFF_PUB + a * 256 + it * 64 + (lane >> 2) * 8) = make_float2(s0, q0);
        if (it != 2) bar_sync(NB_AUX, 96);
        if (it < 2 && a == 2) stage(cid < 64 ? p.Dre + (size_t)cid * 16 * 1024 : p.Dim + (size_t)(cid - 64) * 16 * 1024, g);
      }
      if (a == 1) {
        const float2 v0 = SM_(float2, OFF_PUB + lane * 8), v1 = SM_(float2, OFF_PUB + 256 + lane * 8), v2 = SM_(float2, OFF_PUB + 512 + lane * 8);
        const float s = v0.x + v1.x + v2.x, mean = s * (1.f / 1024.f);
        const float rs = rcp_fast(ln_sd((v0.y + v1.y + v2.y) * (1.f / 1024.f) - mean * mean));
        pkt_st64((lane < 16 ? p.s->xstat : p.s->dsum) + cid * 16 + (lane & 15), lane < 16 ? pack_bf16(rs, mean) : __float_as_uint(s), tag);
        PT(6);
      }
      if (a == 2) {
        float s = 0.f;
#pragma unroll
        for (int q = 0; q < 4; q++) {
          const uint4 v = ldg_nc128(p.wr + (q * 32 + lane) * 8);
          s += ((bf_lo(v.x) + bf_hi(v.x)) + (bf_lo(v.y) + bf_hi(v.y))) + ((bf_lo(v.z) + bf_hi(v.z)) + (bf_lo(v.w) + bf_hi(v.w)));
          const int ch = q * 32 + lane - eps * 16;
          if (ch >= 0 && ch < 16) {
            SM_(uint32_t, OFF_WR + ch * 4) = v.x; SM_(uint32_t, OFF_WR + 80 + ch * 4) = v.y;
            SM_(uint32_t, OFF_WR + 160 + ch * 4) = v.z; SM_(uint32_t, OFF_WR + 240 + ch * 4) = v.w;
          }
        }
        s = warp_sum(s);
        if (lane == 0) { SM_(float, OFF_WSUM) = s; SM_(uint32_t, OFF_TAG) = tag; }
      }
      if (a < 2) __nanosleep(GATHER_NS);
      {
        const int i0 = a * 32 + lane;
        uint2 v[3], c0, c1; uint32_t n = 0;
        const uint2* dp = &p.s->dsum[abrow];
        while (true) {
#pragma unroll
          for (int q = 0; q < 3; q++) v[q] = pkt_ld64(&p.s->xstat[tau * 256 + min(i0 + 96 * q, 255)]);
          c0 = pkt_ld64(dp + i0); c1 = pkt_ld64(dp + min(i0 + 96, 127));
          if (__all_sync(0xffffffffu, v[0].y == tag && v[1].y == tag && v[2].y == tag && c0.y == tag && c1.y == tag) || ++n > SPIN_LIMIT) break;
          __nanosleep(200);
        }
#pragma unroll
        for (int q = 0; q < 3; q++) put_xstat(sb + OFF_RS, sb + OFF_EXB, min(i0 + 96 * q, 255), v[q].x, m);
        put_dsum(sb + OFF_EXA, i0, __uint_as_float(c0.x));
        put_dsum(sb + OFF_EXA, min(i0 + 96, 127), __uint_as_float(c1.x));
        fence_async_smem();
      }
      __syncwarp();
      if (lane == 0) mbar_arrive(BAR(B_STAT));
      if (a == 0) PT(7);
      if (a == 0) {
        const int sg = (lane >> 2) == tau ? sigma_of(tau, 0) : lane >> 2;
        const uint32_t* flg = reinterpret_cast<const uint32_t*>(&p.s->abflag[((eps * 2 + m) * 8 + sg) * 2]) + ((lane >> 2) == tau ? 4 : lane & 3);
        if (NX < 256 && lane == 4 * tau + 1) flg = reinterpret_cast<const uint32_t*>(&p.s->hflag[(m * 8 + eps) * 2]);
        uint32_t seen = 0;
        auto until = [&](int tile) {
          uint32_t n = 0;
          while (!((seen >> (4 * tile)) & 1) && ++n < SPIN_LIMIT) seen = __ballot_sync(0xffffffffu, ld_relaxed32(flg) == tag);
        };
        const int s0 = sigma_of(tau, 0), s1 = sigma_of(tau, 1), s2 = sigma_of(tau, 2), s3 = sigma_of(tau, 3);
        mbar_wait(BAR(B_EPI), 0);
        mbar_wait(BAR(B_FULL + 0), 0);
        mbar_wait(BAR(B_FULL + 1), 0);
        if (elect_one()) mbar_expect_tx(BAR(B_A20), 8192);
        mbar_wait(BAR(B_STDA), 0);
        PT(49);
        until(tau);
        mbar_wait(BAR(B_EPI0B), 0);
        PT(48);
        if (elect_one()) tma_load_2d(sb + OFF_XCH, &p.tmAbS, BAR(B_FULL + 0), s0 * 256, abrow);
        mbar_wait(BAR(B_FULL + 2), 0);
        mbar_wait(BAR(B_STD + 0), 0);
        until(s0);
        PT(16);
        if (elect_one()) tma_load_2d(sb + OFF_XCH + 8192, &p.tmAbS, BAR(B_A20), s0 * 256, abrow + 64);
        until(s1);
        PT(17);
        if (elect_one()) tma_load_2d(sb + OFF_XCH + 16384, &p.tmAbL, BAR(B_FULL + 1), s1 * 256, abrow);
        until(s2);
        PT(18);
        if (elect_one()) {
          tma_load_2d(sb + 2 * ST_BYTES, &p.tmAbL, BAR(B_FULL + 2), s2 * 256, abrow);
          mbar_arrive(BAR(B_PUB1));
        }
        until(s3);
        mbar_wait(BAR(B_FULL + 3), 0);
        mbar_wait(BAR(B_STD + 1), 0);
        PT(19);
        if (elect_one()) tma_load_2d(sb + 3 * ST_BYTES, &p.tmAbL, BAR(B_FULL + 3), s3 * 256, abrow);
        uint32_t n = 0;
        while (true) {
          asm volatile("fence.proxy.async.global;" ::: "memory");
          *(volatile uint32_t*)&SM_(uint32_t, OFF_SEEN) = seen;
          if (seen == 0xFFFFFFFFu || ++n > SPIN_LIMIT) break;
          seen = __ballot_sync(0xffffffffu, ld_relaxed32(flg) == tag);
          __nanosleep(100);
        }
      } else {
        uint32_t* flag = reinterpret_cast<uint32_t*>(&p.s->abflag[((eps * 2 + m) * 8 + tau) * 2]);
        mbar_wait(BAR(a == 1 ? B_EPI : B_EPI0B), 0);
        if (a == 1) PT(8);
        if (lane == 0) {
          tma_store_2d(&p.tmAbS, sb + chunk_off(0, a - 1), tau * 256, abrow + (a - 1) * 64);
          bulk_commit();
          bulk_wait_all();
        }
        if (a == 2) mbar_wait(BAR(B_STDA), 0);
        if (lane == 0) {
          st_relaxed32(flag + (a == 1 ? 4 : 0), tag);
          mbar_arrive(BAR(a == 1 ? B_STDA : B_STD));
        }
        if (a == 2) PT(12);
        if (a == 1) {
          mbar_wait(BAR(B_EPI + 1), 0);
          mbar_wait(BAR(B_LATE), 0);
          mbar_wait(BAR(B_PUB1), 0);
          PT(9);
          if (lane == 0) {
            tma_store_2d(&p.tmAbS, sb + chunk_off(1, 0), tau * 256 + 64, abrow);
            tma_store_2d(&p.tmAbS, sb + chunk_off(1, 1), tau * 256 + 64, abrow + 64);
            bulk_commit();
            bulk_wait_all();
            st_relaxed32(flag + 1, tag);
            mbar_arrive(BAR(B_STD + 1));
          }
          PT(13);
        }
        auto copy_out = [&](int c) {
          mbar_wait(BAR(B_EPI + c), 0);
          PT(8 + c);
          bf16* dst = p.s->abT + (size_t)(abrow + (lane >> 3)) * 2048 + tau * 256 + c * 64 + (lane & 7) * 8;
          const uint32_t src = sb + chunk_off(c, 0) + (lane >> 3) * 128 + (((lane & 7) ^ (lane >> 3)) << 4);
          const uint32_t on = c * 64 + (lane & 7) * 8 < NX;
#pragma unroll 4
          for (int i = 0; i < 32; i++) {
            const uint4 v = lds128_v((src ^ ((i & 1) << 6)) + i * 512);
            asm volatile("{\n.reg .pred p;\nsetp.ne.b32 p, %5, 0;\n@p st.global.v4.b32 [%0], {%1, %2, %3, %4};\n}\n"
                         :: "l"(dst + i * 4 * 2048), "r"(v.x), "r"(v.y), "r"(v.z), "r"(v.w), "r"(on));
          }
          __syncwarp();
          if (lane == 0) mbar_arrive(BAR(B_STD + c));
        };
        if (a == 2) {
#pragma unroll 1
          for (int c = 2; c < 4; c++) copy_out(c);
          asm volatile("fence.acq_rel.gpu;" ::: "memory");
          __syncwarp();
          if (lane < 2) st_relaxed32(flag + 2 + lane, tag);
          PT(15);
        }
      }
      {
        mbar_wait(BAR(B_LATE), 1);
        const int grp = tau * 2 + m;
#pragma unroll 1
        for (int i = a; i < 14; i += 3) {
          uint4* dst = i < 8 ? &p.s->ypart[cid * 256 + i * 32 + lane] : i < 12 ? &p.s->hstat[(grp * 8 + eps) * 128 + (i - 8) * 32 + lane]
                     : i == 12 ? &p.s->cand[grp * 256 + eps * 32 + lane] : &p.s->key[(((lane >> 1) & 7) * 16 + grp) * 2 + (lane & 1)];
          if (i < 13 || eps == 0) pkt_st128(dst, 0, 0, 0, 0);
          __nanosleep(200);
        }
        __syncwarp();
        if (lane == 0) mbar_arrive(BAR(B_STAT));
      }
      {
        const uint4* kp = &p.s->key[(tau * 16 + (lane & 15)) * 2];
        const int i0 = a * 32 + lane;
        mbar_wait(BAR(B_KEY), 0);
        if (a == 0) PT(43);
        uint4 kq = pkt_ld128(kp), cv[3] = {};
        uint32_t n = 0, kv;
        int gspec = -1;
        while (true) {
          const bool ok = kq.y == tag && kq.w == tag;
          kv = __reduce_max_sync(0xffffffffu, ok ? kq.x : 0u);
          const int gs = (0xFFFF - (int)(kv & 0xFFFFu)) >> 7;
          const bool cok = gs == gspec && cv[0].y == tag && cv[0].w == tag && cv[1].y == tag && cv[1].w == tag && cv[2].y == tag && cv[2].w == tag;
          if (__all_sync(0xffffffffu, ok && cok) || ++n > SPIN_LIMIT) break;
          if (!ok) kq = pkt_ld128(kp);
          const bool spec = __popc(__ballot_sync(0xffffffffu, ok)) >= 2 * SPEC_MIN;
          if (!cok && spec) {
#pragma unroll
            for (int i = 0; i < 3; i++) cv[i] = pkt_ld128(&p.s->cand[gs * 256 + min(i0 + 96 * i, 255)]);
          }
          if (spec) gspec = gs;
        }
        if (a == 0) PT(45);
        const uint32_t ms = __shfl_sync(0xffffffffu, kq.z, gspec);
        const uint32_t nm = ((ms & 0xFFFFu) ^ 0x8000u) * 0x10001u;
        const float is = rcp_fast(bf_hi(ms));
#pragma unroll
        for (int i = 0; i < 3; i++) {
          const int j = min(i0 + 96 * i, 255);
          SM_(uint2, OFF_XSEL + j * 8) = make_uint2(norm2(cv[i].x, nm, is), norm2(cv[i].z, nm, is));
        }
#pragma unroll
        for (int i = 0; i < 3; i++) SM_(uint2, OFF_HSEL + min(i0 + 96 * i, 255) * 8) = make_uint2(cv[i].x, cv[i].z);
        SM_(uint32_t, OFF_KV) = kv;
        __syncwarp();
        if (lane == 0) mbar_arrive(BAR(B_XS));
      }
    }
    asm volatile("barrier.cluster.wait.aligned;" ::: "memory");
  } else {
    reg_inc<REG_C>();
    const int tid = __shfl_sync(0xffffffffu, threadIdx.x, threadIdx.x & 31), lane = tid & 31;
    const int w = warp >> 2, wi = warp & 3, t = tid & 127;
    const int g = lane >> 2, q = lane & 3;
    const int turn_me = NB_TURN0 + w, turn_other = NB_TURN1 - w;
    auto release = [&](int s) { if (t == 0) mbar_arrive(BAR(B_EMPTY + s)); };
    if (MAP == 0 && helper) {
      asm volatile("barrier.cluster.arrive.relaxed.aligned;" ::: "memory");
      float s0[64], s1[64];
#pragma unroll
      for (int i = 0; i < 64; i++) { s0[i] = 0.f; s1[i] = 0.f; }
      if (w == 1) bar_arrive(NB_TURN0, 256);
      uint32_t o[32][2] = {};
      const int col = (eps - 2) * 8 + m * 4 + w;
      auto put = [&](auto tc, uint32_t buf) {
        constexpr int tl = decltype(tc)::value;
#pragma unroll
        for (int i = 0; i < 4; i++)
          smem_at<uint2>(buf + ((i >> 1) * 64 + wi * 16 + (i & 1) * 8 + g) * 32 + ((q * 8) ^ ((g & 4) << 2))) = make_uint2(o[8 * i + tl][0], o[8 * i + tl][1]);
      };
      auto publish = [&](int c) { if (t == 0) { bulk_wait_all(); st_relaxed32(&p.s->hflag[c * 2], SM_(uint32_t, OFF_TAG)); } };
#pragma unroll 1
      for (int pass = 0; pass < 2; pass++) {
#pragma unroll 1
        for (int k = 16 * pass; k < 16 * pass + 16; k++) {
          const int s = slot_of(k);
          mbar_wait(BAR(B_FULL + s), use_of(k) & 1);
          bar_sync(turn_me, 256);
          const uint64_t da = make_desc(sb + s * ST_BYTES + A_BYTES + w * 16384), db = make_desc(sb + s * ST_BYTES);
          wgmma_fence();
#pragma unroll
          for (int kk = 0; kk < 4; kk++) {
            wgmma_n128(s0, da + kk * 2, db + kk * 2, kk > 0 || (k & 15));
            wgmma_n128(s1, da + 512 + kk * 2, db + kk * 2, kk > 0 || (k & 15));
          }
          wgmma_commit();
          if (k < 31 || w == 0) bar_arrive(turn_other, 256);
          if (pass && !(k & 1)) {
            const uint32_t buf = sb + OFF_XCH + 20480 + w * 4096;
            static_for<8>([&](auto ic) { if (k == 16 + 2 * decltype(ic)::value) put(ic, buf); });
            fence_async_smem();
            bar_sync(NB_WG0 + w, 128);
            if (t == 0) { tma_store_2d(&p.tmAbM, buf, (k - 16) * 128 + 240, col * 128); bulk_commit(); }
          }
          wgmma_wait0();
          release(s);
          if ((k & 1) && t == 0) asm volatile("cp.async.bulk.wait_group.read 0;" ::: "memory");
        }
        if (pass) publish(col);
        mbar_wait(BAR(B_STAT), 0);
        wgmma_fence();
        wgmma_n128(s0, make_desc_noswz(sb + OFF_XCH + pass * 8192 + w * 4096), make_desc_noswz(sb + OFF_XCH + 16384));
        wgmma_n128(s1, make_desc_noswz(sb + OFF_XCH + pass * 8192 + w * 4096 + 2048), make_desc_noswz(sb + OFF_XCH + 16384));
        wgmma_commit();
        uint4 rs[4];
#pragma unroll
        for (int i = 0; i < 4; i++) rs[i] = lds128_v(sb + OFF_RS + q * 144 + i * 16);
        wgmma_wait0();
        fence_acc(s0); fence_acc(s1);
#pragma unroll
        for (int i = 0; i < 32; i++) {
          const int tl = i & 7, hr = (i >> 3) & 1;
          const float* ac = (i >> 4) ? &s1[8 * tl + 2 * hr] : &s0[8 * tl + 2 * hr];
          o[i][0] = bmul2(pack_bf16(ac[0], ac[1]), (tl & 1) ? rs[tl >> 1].z : rs[tl >> 1].x);
          o[i][1] = bmul2(pack_bf16(ac[4], ac[5]), (tl & 1) ? rs[tl >> 1].w : rs[tl >> 1].y);
        }
      }
      static_for<8>([&](auto ic) { put(ic, sb + (w * 8 + decltype(ic)::value) * 4096); });
      fence_async_smem();
      bar_sync(NB_WG0 + w, 128);
      if (t == 0) {
#pragma unroll 1
        for (int i = 0; i < 8; i++) tma_store_2d(&p.tmAbM, sb + (w * 8 + i) * 4096, i * 256 + 240, (col + 2) * 128);
        bulk_commit();
      }
      publish(col + 2);
      asm volatile("barrier.cluster.wait.aligned;" ::: "memory");
      return;
    }
    float acc[128], a1[NX / 2];
#pragma unroll
    for (int i = 0; i < NX / 2; i++) a1[i] = 0.f;
    if (w == 1) bar_arrive(NB_TURN0, 256);
    auto kstep = [&](auto& d, int k, bool first, bool a_in_xch = false, bool mini = false) {
      const int s = slot_of(k);
      mbar_wait(BAR(B_FULL + s), use_of(k) & 1);
      CT(64 + k);
      bar_sync(turn_me, 256);
      const uint64_t da = make_desc(sb + (a_in_xch ? OFF_XCH + s * 16384 : s * ST_BYTES) + w * 8192), db = make_desc(sb + s * ST_BYTES + A_BYTES);
      wgmma_fence();
      wgmma_g1(d, da, db, !first);
#pragma unroll
      for (int kk = 1; kk < 4; kk++) wgmma_g1(d, da + kk * 2, db + kk * 2, 1);
      wgmma_commit();
      if (mini) {
        CT(29);
        mbar_wait(BAR(B_A20), 1);
        CT(30);
        wgmma_fence();
        wgmma_g1(d, make_desc_32b(sb + OFF_MINI + w * 2048), make_desc_32b(sb + OFF_MINI + 4096), 1);
        wgmma_commit();
      }
      bar_arrive(turn_other, 256);
    };
    auto kdone = [&](int k) { wgmma_wait0(); release(slot_of(k)); };
    auto wgmma_wait1 = [&]() { asm volatile("wgmma.wait_group.sync.aligned 1;" ::: "memory"); };

#pragma unroll 1
    for (int k = 0; k < 14; k++) {
      kstep(a1, k, k == 0);
      if (k == 0) CT(0);
      if (k == 8 && warp == 2 && lane < 2) pkt_st128(&p.s->abflag[((eps * 2 + m) * 8 + tau) * 2 + lane], 0, 0, 0, 0);
      kdone(k);
    }
    uint32_t R[64];
    uint32_t tag;
    {
      const uint32_t rsa = sb + OFF_RS + q * 144;
      const uint64_t da2 = make_desc(sb + 2 * ST_BYTES + w * 8192), db2 = make_desc(sb + 2 * ST_BYTES + A_BYTES);
      const uint64_t da3 = make_desc(sb + 3 * ST_BYTES + w * 8192), db3 = make_desc(sb + 3 * ST_BYTES + A_BYTES);
      mbar_wait(BAR(B_FULL + 2), 1);
      CT(64 + 14);
      bar_sync(turn_me, 256);
      wgmma_fence();
#pragma unroll
      for (int kk = 0; kk < 4; kk++) wgmma_g1(a1, da2 + kk * 2, db2 + kk * 2, 1);
      wgmma_commit();
      mbar_wait(BAR(B_FULL + 3), 1);
      CT(64 + 15);
      wgmma_fence();
      wgmma_g1(a1, da3, db3, 1);
      wgmma_g1(a1, da3 + 2, db3 + 2, 1);
      wgmma_commit();
      mbar_wait(BAR(B_STAT), 0);
      tag = SM_(uint32_t, OFF_TAG);
#pragma unroll
      for (int i = 0; i < 8; i++) { const uint4 v = lds128_v(rsa + i * 16); R[8 * i] = v.x; R[8 * i + 2] = v.y; R[8 * i + 4] = v.z; R[8 * i + 6] = v.w; }
      wgmma_wait1();
      release(2);
      wgmma_fence();
      wgmma_g1(a1, da3 + 4, db3 + 4, 1);
      wgmma_g1(a1, da3 + 6, db3 + 6, 1);
      wgmma_g1(a1, make_desc_noswz(sb + OFF_EXA + w * 2048), make_desc_noswz(sb + OFF_EXB), 1);
      wgmma_commit();
      bar_arrive(turn_other, 256);
      kdone(15);
      mbar_wait(BAR(B_STAT), 0);
    }
    fence_acc(a1);
    CT(1);
    auto pack = [&](auto cc) {
      constexpr int c = decltype(cc)::value;
#pragma unroll
      for (int j = 8 * c; j < min_c(8 * c + 8, NX / 8); j++) {
        const uint32_t rs = R[2 * j];
        const float* ac = &a1[4 * j];
        R[2 * j] = bmul2(pack_bf16(ac[0], ac[1]), rs);
        R[2 * j + 1] = bmul2(pack_bf16(ac[2], ac[3]), rs);
      }
    };
    auto put_chunk = [&](auto cc) {
      constexpr int c = decltype(cc)::value;
      const int rho = 16 * wi + (lane & 15);
#pragma unroll
      for (int j = 8 * c; j < min_c(8 * c + 8, NX / 8); j += 2) {
        const int chunk = (j & 7) + (lane >> 4);
        stsm_x4(sb + chunk_off(c, w) + rho * 128 + ((chunk ^ (lane & 7)) << 4), R[2 * j], R[2 * j + 1], R[2 * j + 2], R[2 * j + 3]);
      }
    };
    auto staged = [&](int bar) {
      fence_async_smem();
      __syncwarp();
      if (lane == 0) mbar_arrive(BAR(bar));
    };
    auto mma_rs = [&](auto cc, auto k0, auto k1) {
      constexpr int c = decltype(cc)::value;
      const uint64_t db = make_desc(sb + c * ST_BYTES + A_BYTES);
#pragma unroll
      for (int kk = decltype(k0)::value; kk < decltype(k1)::value; kk++)
        wgmma_n256_rs(acc, R[16 * c + 4 * kk], R[16 * c + 4 * kk + 1], R[16 * c + 4 * kk + 2], R[16 * c + 4 * kk + 3], db + kk * 2, c + kk > 0);
      wgmma_commit();
    };
    auto kdone_x = [&](int k, auto ic) {
      constexpr int i = decltype(ic)::value;
      uint32_t r[8];
#pragma unroll
      for (int z = 0; z < 2; z++) {
        const int tr = 32 * (i & 1) + 16 * z + 8 * (lane >> 4) + (lane & 7), chunk = 2 * wi + ((lane >> 3) & 1);
        ldsm_x4_t(sb + (i >> 1) * ST_BYTES + w * 8192 + tr * 128 + ((chunk ^ (lane & 7)) << 4), r[4 * z], r[4 * z + 1], r[4 * z + 2], r[4 * z + 3]);
      }
      float f[16];
#pragma unroll
      for (int z = 0; z < 8; z++) { f[2 * z] = bf_lo(r[z]); f[2 * z + 1] = bf_hi(r[z]); }
#pragma unroll
      for (int z = 0; z < 16; z++) asm volatile("" : "+f"(f[z]));
      kdone(k);
#pragma unroll
      for (int z = 0; z < 16; z++) asm volatile("add.f32 %0, %0, %1;" : "+f"(acc[16 * i + z]) : "f"(f[z]));
    };
    pack(IC<0>());
    put_chunk(IC<0>());
    staged(w ? B_EPI0B : B_EPI);
    mbar_wait(BAR(B_STAT), 0);
    CT(21);
    pack(IC<1>());
    pack(IC<2>());
    pack(IC<3>());
#pragma unroll
    for (int i = 16; i < NX / 4; i++) asm volatile("" : "+r"(R[i]));
#pragma unroll
    for (int i = 0; i < 128; i++) asm volatile("" : "=f"(acc[i]));
    mbar_wait(BAR(B_FULL + 0), 0);
    CT(2);
    CT(64 + 16);
    bar_sync(turn_me, 256);
    wgmma_fence();
    mma_rs(IC<0>(), IC<0>(), IC<4>());
    mbar_wait(BAR(B_FULL + 1), 0);
    CT(64 + 17);
    wgmma_fence();
    mma_rs(IC<1>(), IC<0>(), IC<2>());
    wgmma_wait1();
    release(0);
    mma_rs(IC<1>(), IC<2>(), IC<4>());
    bar_arrive(turn_other, 256);
    kdone_x(17, IC<0>());
    static_for<2>([&](auto ic) {
      constexpr int c = 2 + decltype(ic)::value;
      mbar_wait(BAR(B_FULL + c), 0);
      CT(64 + 16 + c);
      bar_sync(turn_me, 256);
      wgmma_fence();
      mma_rs(IC<c>(), IC<0>(), IC<min_c(4, NX / 16 - 4 * c)>());
      bar_arrive(turn_other, 256);
      if (c == 2) { put_chunk(IC<1>()); staged(B_EPI + 1); }
      kdone_x(16 + c, IC<c - 1>());
    });
#pragma unroll 1
    for (int k = 20; k < 23; k++) {
      if (w == 1) mbar_wait(BAR(B_A20), 0);
      kstep(acc, k, false, k < 22);
      if (k == 20) {
        kdone_x(k, IC<3>());
      } else {
        if (k == 21) put_chunk(IC<2>()); else put_chunk(IC<3>());
        __syncwarp();
        if (lane == 0) mbar_arrive(BAR(B_EPI + k - 19));
        kdone(k);
      }
    }
    uint32_t wf[32][4];
    auto load_wf = [&](auto hc) {
      constexpr int h = decltype(hc)::value;
      const int d = w * 64 + (lane >> 4) * 8 + (lane & 7);
      const uint32_t ad = sb + round_off(h) + (lane & 8) * 1024 + d * 64 + ((wi ^ ((lane >> 1) & 3)) << 4);
#pragma unroll
      for (int i = 0; i < 4; i++) ldsm_x4_t(ad + i * 1024, wf[4 * h + i][0], wf[4 * h + i][1], wf[4 * h + i][2], wf[4 * h + i][3]);
    };
    auto load_wf_rest = [&]() { static_for<8 - NREG_H>([&](auto ic) { load_wf(IC<NREG_H + decltype(ic)::value>()); }); };
#pragma unroll
    for (int i = 0; i < 4 * NREG_H; i++) { wf[i][0] = 0; wf[i][1] = 0; wf[i][2] = 0; wf[i][3] = 0; }
    const int grp = tau * 2 + m;
#pragma unroll 1
    for (int k = 23; k < 46; k++) {
      kstep(acc, k, false, false, NX < 256 && k == MINI_K);
      if (moe) {
        static_for<NREG_H>([&](auto hc) {
          constexpr int h = decltype(hc)::value;
          if (k == mr_k(h) + 1) { mbar_wait(BAR(B_MR + (h & 1)), (h >> 1) & 1); CT(32 + h); load_wf(hc); }
        });
      }
      if (k == RESET_K && tid == 0) mbar_arrive(BAR(B_LATE));
      kdone(k);
    }
    asm volatile("barrier.cluster.arrive.relaxed.aligned;" ::: "memory");
    mbar_wait(BAR(B_STAT), 1);
    uint32_t wa[16][2];
    uint32_t cd = code_of(tag);
    uint4* hp_pub = &p.s->hstat[(grp * 8 + eps) * 128 + warp * 16 + g];
    const uint4* hp_poll = &p.s->hstat[(grp * 8 + 2 * q) * 128 + warp * 16 + g];
    const uint32_t vec_off = (2 * wi) * 512 + q * 128 + ((g ^ (2 * q)) << 4);
    {
      float as[64], ak[64];
      fence_acc(acc);
#pragma unroll
      for (int i = 0; i < 64; i++) asm volatile("mov.b32 %0, %1;" : "=f"(as[i]) : "f"(acc[64 + i]));
#pragma unroll
      for (int i = 0; i < 64; i++) asm volatile("mov.b32 %0, %1;" : "=f"(ak[i]) : "f"(acc[i]));
      const uint64_t da1 = make_desc(sb + 2 * ST_BYTES + w * 8192), db1 = make_desc(sb + 2 * ST_BYTES + A_BYTES);
      const uint64_t da2 = make_desc(sb + 3 * ST_BYTES + w * 8192), db2 = make_desc(sb + 3 * ST_BYTES + A_BYTES);
      mbar_wait(BAR(B_FULL + 2), 1);
      CT(64 + 46);
      mbar_wait(BAR(B_FULL + 3), 1);
      CT(64 + 47);
      bar_sync(turn_me, 256);
      wgmma_fence();
#pragma unroll
      for (int kk = 0; kk < 4; kk++) wgmma_n128(as, da1 + kk * 2, db1 + 1024 + kk * 2);
#pragma unroll
      for (int kk = 0; kk < 4; kk++) wgmma_n128(as, da2 + kk * 2, db2 + 1024 + kk * 2);
      wgmma_commit();
      bar_arrive(turn_other, 256);
      const uint32_t rx = mapa(sb + OFF_PEER + w * 4096 + vec_off, 1 - m), rb = mapa(BAR(B_XCH), 1 - m);
      asm volatile("barrier.cluster.wait.aligned;" ::: "memory");
      CT(24);
      wgmma_wait0();
      fence_acc(as);
      CT(25);
      auto keep = [&]() {
        bar_sync(turn_me, 256);
        wgmma_fence();
#pragma unroll
        for (int kk = 0; kk < 4; kk++) wgmma_n128(ak, da1 + kk * 2, db1 + kk * 2);
        wgmma_commit();
#pragma unroll
        for (int kk = 0; kk < 4; kk++) wgmma_n128(ak, da2 + kk * 2, db2 + kk * 2);
        wgmma_commit();
        if (w == 0) bar_arrive(turn_other, 256);
      };
#pragma unroll
      for (int i = 0; i < 8; i++) {
        if (i == SEND_FIRST) keep();
        const float* ac = &as[16 * (i >> 1) + 2 * (i & 1)];
        st_async_v4(rx + (i >> 1) * 8192 + (i & 1) * 512, rb, pack_bf16(ac[0], ac[1]), pack_bf16(ac[4], ac[5]), pack_bf16(ac[8], ac[9]), pack_bf16(ac[12], ac[13]));
      }
      CT(26);
#pragma unroll
      for (int i = 0; i < 4; i++) {
        const uint4 v = lds128_v(sb + OFF_WR + q * 80 + i * 16);
        const uint32_t vv[4] = {v.x, v.y, v.z, v.w};
#pragma unroll
        for (int z = 0; z < 4; z++) {
          asm volatile("{\n.reg .pred p;\nsetp.ne.b32 p, %2, 0;\nselp.b32 %0, %1, 0x3F803F80, p;\n}" : "=r"(wa[4 * i + z][0]) : "r"(vv[z]), "r"(g & 1));
          asm volatile("{\n.reg .pred p;\nsetp.ne.b32 p, %2, 0;\nselp.b32 %0, %1, 0x3F803F80, p;\n}" : "=r"(wa[4 * i + z][1]) : "r"(vv[z]), "r"(g & 1));
        }
      }
      pin(cd); pin(hp_pub); pin(hp_poll);
      CT(27);
      wgmma_wait1();
      release(2);
      wgmma_wait0();
      fence_acc(ak);
      CT(3);
#pragma unroll
      for (int i = 0; i < 8; i++) {
        const float* ac = &ak[16 * (i >> 1) + 2 * (i & 1)];
        sts128(sb + (2 + (i >> 2)) * ST_BYTES + w * 8192 + ((i >> 1) & 1) * 4096 + (i & 1) * 512 + vec_off,
               pack_bf16(ac[0], ac[1]), pack_bf16(ac[4], ac[5]), pack_bf16(ac[8], ac[9]), pack_bf16(ac[12], ac[13]));
      }
    }
    uint32_t h[8][4];
    {
      const int qq = 2 * (warp & 1) + ((lane >> 3) & 1);
      const uint32_t lo = (lane >> 4) * 512 + qq * 128 + (((lane & 7) ^ (2 * qq)) << 4);
      bar_sync(NB_BOTH, 256);
#pragma unroll
      for (int ks = 0; ks < 8; ks++)
        ldsm_x4_t(sb + (2 + w) * ST_BYTES + (ks >> 2) * 8192 + (wi >> 1) * 4096 + (ks & 3) * 1024 + lo, h[ks][0], h[ks][1], h[ks][2], h[ks][3]);
      CT(28);
      mbar_wait_cluster(BAR(B_XCH), 0);
      CT(4);
      uint32_t r[8][4];
#pragma unroll
      for (int ks = 0; ks < 8; ks++) ldsm_x4_t(sb + OFF_PEER + (warp >> 1) * 8192 + ks * 1024 + lo, r[ks][0], r[ks][1], r[ks][2], r[ks][3]);
      float d[4][4] = {};
#pragma unroll
      for (int ks = 0; ks < 8; ks++) {
#pragma unroll
        for (int i = 0; i < 4; i++) {
          h[ks][i] = badd2(h[ks][i], r[ks][i]);
          mma1688(d[i], h[ks][i], wa[2 * ks + (i >> 1)][i & 1], h[ks][i]);
        }
      }
#pragma unroll
      for (int i = 0; i < 2; i++) {
        const float sq = (g & 1) ? d[i][1] + d[i + 2][1] : d[i][0] + d[i + 2][0];
        const float e0 = d[i][2] + d[i + 2][2], e1 = d[i][3] + d[i + 2][3];
        const float other = __shfl_xor_sync(0xffffffffu, (g & 1) ? e0 : e1, 4);
        if (q == (g >> 1)) pkt_st128(hp_pub + 8 * i, with_bit((g & 1) ? other : e0, cd), with_bit(sq, cd >> 1), __float_as_uint((g & 1) ? e1 : other), tag);
      }
    }
    CT(5);
    if (tid == 0) mbar_arrive(BAR(B_KEY));
    delay_clk<HOP1_DELAY>();
    float m_bf, sd, inv_sd, r_bf;
    uint4* key_pub = &p.s->key[((lane & 7) * 16 + grp) * 2];
    uint4* cand_pub = &p.s->cand[grp * 256 + eps * 32 + q];
    uint32_t trow_inv = 0xFFFFu - (uint32_t)(grp * 128 + 32 * (warp >> 1) + 8 * (g >> 1) + 4 * (warp & 1) + (q & 2) + (g & 1));
    {
      uint4 u[4];
#pragma unroll
      for (int i = 0; i < 4; i++) u[i] = pkt_ld128(hp_poll + (i & 1) * 128 + (i >> 1) * 8);
      const float wsum = SM_(float, OFF_WSUM);
      pin(key_pub); pin(cand_pub); pin(trow_inv);
      uint32_t n = 0;
      while (true) {
        bool ok[4];
#pragma unroll
        for (int i = 0; i < 4; i++) ok[i] = u[i].w == tag && pair_code(u[i].x, u[i].y) == cd;
        const bool all = __all_sync(0xffffffffu, ok[0] && ok[1] && ok[2] && ok[3]);
        if (all || ++n > SPIN_LIMIT) break;
#pragma unroll
        for (int i = 0; i < 4; i++) pkt_ld128_if(u[i], hp_poll + (i & 1) * 128 + (i >> 1) * 8, !ok[i]);
      }
      CT(6);
      float a[3], b[3];
      a[0] = __uint_as_float(u[0].x & ~1u) + __uint_as_float(u[1].x & ~1u); b[0] = __uint_as_float(u[2].x & ~1u) + __uint_as_float(u[3].x & ~1u);
      a[1] = __uint_as_float(u[0].y & ~1u) + __uint_as_float(u[1].y & ~1u); b[1] = __uint_as_float(u[2].y & ~1u) + __uint_as_float(u[3].y & ~1u);
      a[2] = __uint_as_float(u[0].z) + __uint_as_float(u[1].z); b[2] = __uint_as_float(u[2].z) + __uint_as_float(u[3].z);
#pragma unroll
      for (int i = 0; i < 3; i++) {
        a[i] = ((q & 2) ? b[i] : a[i]) + __shfl_xor_sync(0xffffffffu, (q & 2) ? a[i] : b[i], 2);
        a[i] += __shfl_xor_sync(0xffffffffu, a[i], 1);
      }
      const float mu = a[0] * (1.f / 1024.f);
      m_bf = bf16r(mu);
      sd = ln_sd(a[1] * (1.f / 1024.f) - mu * mu);
      inv_sd = rcp_fast(sd);
      r_bf = bf16r((a[2] - m_bf * wsum) * inv_sd);
    }
    {
      const uint32_t u = __float_as_uint(r_bf);
      const uint32_t ord = (u & 0x80000000u) ? ~u : (u | 0x80000000u);
      const uint32_t key = (ord & 0xFFFF0000u) | trow_inv;
      const uint32_t wk = __reduce_max_sync(0xffffffffu, key);
      if (key == wk) SM_(uint2, OFF_WKEY + warp * 8) = make_uint2(wk, (__float_as_uint(m_bf) >> 16) | __float_as_uint(sd));
      const uint32_t wmask = __ballot_sync(0xffffffffu, key == wk);
      const bool hi = (wmask & 0xCCCCCCCCu) != 0;
      uint32_t c[16];
#pragma unroll
      for (int ks = 0; ks < 8; ks++) { c[2 * ks] = hi ? h[ks][1] : h[ks][0]; c[2 * ks + 1] = hi ? h[ks][3] : h[ks][2]; }
      bar_sync(NB_BOTH, 256);
      const uint2 km = SM_(uint2, OFF_WKEY + (lane & 7) * 8);
      const uint32_t bk = __reduce_max_sync(0xffffffffu, km.x);
      if (wk == bk) {
        if ((wmask >> (lane & 28)) & 15) {
#pragma unroll
          for (int ks = 0; ks < 8; ks++) pkt_st128(cand_pub + ks * 4, c[2 * ks], tag, c[2 * ks + 1], tag);
        }
      } else if (eps == 0) {
        const uint32_t kx = __shfl_sync(0xffffffffu, km.x, warp ^ 1), ms = __shfl_sync(0xffffffffu, km.y, warp ^ 1);
        if (kx == bk && lane < 8) pkt_st128(key_pub, bk, tag, ms, tag);
      }
      CT(7);
    }
    {
      const float ih = bf16r(inv_sd);
      const uint32_t nm = pack_bf16(-m_bf, -m_bf), iv = pack_bf16(ih, inv_sd - ih);
      const uint32_t nm_o = __shfl_xor_sync(0xffffffffu, nm, 2), iv_o = __shfl_xor_sync(0xffffffffu, iv, 2);
      const uint32_t nm2[2] = {(q & 2) ? nm_o : nm, (q & 2) ? nm : nm_o}, iv2[2] = {(q & 2) ? iv_o : iv, (q & 2) ? iv : iv_o};
      const uint32_t hi2[2] = {__byte_perm(iv2[0], 0, 0x1010), __byte_perm(iv2[1], 0, 0x1010)}, lo2[2] = {__byte_perm(iv2[0], 0, 0x3232), __byte_perm(iv2[1], 0, 0x3232)};
      const uint32_t oa = sb + OFF_OUT + (warp * 16 + (lane & 15)) * 128;
#pragma unroll
      for (int ks = 0; ks < 8; ks++) {
        uint32_t o[4];
#pragma unroll
        for (int i = 0; i < 4; i++) {
          const uint32_t dd = badd2(h[ks][i], nm2[i & 1]);
          o[i] = badd2(h[ks][i], bfma2(dd, hi2[i & 1], bmul2(dd, lo2[i & 1])));
        }
        stsm_x4(oa + (ks >> 2) * 16384 + (((2 * (ks & 3) + (lane >> 4)) ^ (lane & 7)) << 4), o[0], o[1], o[2], o[3]);
      }
      staged(B_OUT);
    }
    CT(8);
    uint32_t df[16][4];
    auto load_df = [&]() {
      const int frow = (lane & 7) + ((lane >> 4) << 3), hi = (lane >> 3) & 1;
      const uint32_t base = sb + down_off(warp >> 1) + (warp & 1) * 8192 + frow * 128;
#pragma unroll
      for (int mt = 0; mt < 8; mt++) {
#pragma unroll
        for (int ks = 0; ks < 2; ks++)
          ldsm_x4_t(base + (mt >> 2) * 4096 + ks * 2048 + (((2 * (mt & 3) + hi) ^ (lane & 7)) << 4),
                    df[2 * mt + ks][0], df[2 * mt + ks][1], df[2 * mt + ks][2], df[2 * mt + ks][3]);
      }
    };
    if (moe) {
      mbar_wait(BAR(B_GU), 0);
      load_wf_rest();
      mbar_wait(BAR(B_DN), 0);
      load_df();
    }
    uint4* y_pub = &p.s->ypart[cid * 256 + tid];
    uint32_t xs_ad = sb + OFF_XSEL + (8 * (g >> 2) + 4 * w + (g & 3)) * 32 + q * 8, gp_ad = sb + OFF_GP + (wi * 8 + g) * 16 + w * 8 + (q >> 1) * 4;
    pin(y_pub); pin(xs_ad); pin(gp_ad);
    mbar_wait(BAR(B_XS), 0);
    CT(9);
    if (moe) {
      float gd[8][4] = {};
      uint2 bx[4];
#pragma unroll
      for (int r = 0; r < 4; r++) bx[r] = smem_at<uint2>(xs_ad + r * 512);
#pragma unroll
      for (int r = 0; r < 4; r++) {
#pragma unroll
        for (int i = 0; i < 8; i++) mma16816(gd[i], wf[8 * r + i][0], wf[8 * r + i][1], wf[8 * r + i][2], wf[8 * r + i][3], bx[r].x, bx[r].y);
      }
      const float gs = sel4(q, gd[0][0] + gd[1][1], gd[2][0] + gd[3][1], gd[4][0] + gd[5][1], gd[6][0] + gd[7][1]);
      const float us = sel4(q, gd[0][2] + gd[1][3], gd[2][2] + gd[3][3], gd[4][2] + gd[5][3], gd[6][2] + gd[7][3]);
      float v = ((q & 2) ? us : gs) + __shfl_xor_sync(0xffffffffu, (q & 2) ? gs : us, 2);
      v += __shfl_xor_sync(0xffffffffu, v, 1);
      smem_at<float>(gp_ad) = v;
      CT(10);
      bar_sync(NB_BOTH, 256);
      uint32_t bq[4];
      {
        const float4 p0 = SM_(float4, OFF_GP + lane * 16);
        const float gt = bf16r(p0.x + p0.z), up = bf16r(p0.y + p0.w);
        const float act = bf16r(gt * sigmoid_fast(gt)) * up;
        const uint32_t pr = pack_bf16(act, __shfl_down_sync(0xffffffffu, act, 1));
#pragma unroll
        for (int i = 0; i < 4; i++) bq[i] = __shfl_sync(0xffffffffu, pr, 8 * i + 2 * q);
      }
      CT(11);
      float yd[8][4] = {};
#pragma unroll
      for (int ks = 0; ks < 2; ks++) {
#pragma unroll
        for (int mt = 0; mt < 8; mt++) mma16816(yd[mt], df[2 * mt + ks][0], df[2 * mt + ks][1], df[2 * mt + ks][2], df[2 * mt + ks][3], bq[2 * ks], bq[2 * ks + 1]);
      }
      pkt_st128(y_pub, with_bit(sel4(q, yd[0][0], yd[2][0], yd[4][0], yd[6][0]), cd), with_bit(sel4(q, yd[0][2], yd[2][2], yd[4][2], yd[6][2]), cd >> 1),
                with_bit(sel4(q, yd[1][0], yd[3][0], yd[5][0], yd[7][0]), cd), with_bit(sel4(q, yd[1][2], yd[3][2], yd[5][2], yd[7][2]), cd >> 1));
    } else {
      const long long tw = clock64();
      while (clock64() - tw < IDLE_WAIT_CLK) __nanosleep(100);
    }
    CT(12);
    const uint32_t kv = SM_(uint32_t, OFF_KV);
    const int tsel = 0xFFFF - (int)(kv & 0xFFFFu);
    const float r_sel = __uint_as_float((kv & 0x80000000u) ? (kv & 0x7FFF0000u) : (~kv & 0xFFFF0000u));
    const float sig = bf16r(sigmoid_fast(r_sel));
    const int pfin = 2 * cid + (tid & 1);
    const int col_fin = (pfin >> 5) * 128 + (pfin & 3) * 32 + ((pfin & 31) >> 2) + 8 * ((tid >> 1) & 3);
    const int sel_off = (col_fin >> 4) * 32 + ((col_fin & 7) >> 1) * 8 + ((col_fin >> 3) & 1) * 4 + (col_fin & 1) * 2;
    const float hn_fin = __uint_as_float((uint32_t)SM_(uint16_t, OFF_XSEL + sel_off) << 16), h_fin = __uint_as_float((uint32_t)SM_(uint16_t, OFF_HSEL + sel_off) << 16);
    bf16* out_fin = p.out + (size_t)tsel * 1024 + col_fin;
    {
      const uint4* src = &p.s->ypart[(16 + (tid >> 1)) * 256 + pfin];
      pin(src); pin(out_fin);
      uint4 v = make_uint4(0, 0, 0, 0);
      if (warp < 7) {
        delay_clk<HOP3_DELAY>();
        uint32_t n = 0;
        bool ok = false;
        do {
          pkt_ld128_if(v, src, !ok);
          ok = pair_code(v.x, v.y) == cd && pair_code(v.z, v.w) == cd;
        } while (!__all_sync(0xffffffffu, ok) && ++n < SPIN_LIMIT);
      }
      CT(13);
      const float y0 = __uint_as_float(v.x & ~1u), y1 = __uint_as_float(v.y & ~1u), y2 = __uint_as_float(v.z & ~1u), y3 = __uint_as_float(v.w & ~1u);
      const float a0 = ((lane & 2) ? y1 : y0) + __shfl_xor_sync(0xffffffffu, (lane & 2) ? y0 : y1, 2);
      const float a1 = ((lane & 2) ? y3 : y2) + __shfl_xor_sync(0xffffffffu, (lane & 2) ? y2 : y3, 2);
      float b = ((lane & 4) ? a1 : a0) + __shfl_xor_sync(0xffffffffu, (lane & 4) ? a0 : a1, 4);
      b += __shfl_xor_sync(0xffffffffu, b, 8);
      b += __shfl_xor_sync(0xffffffffu, b, 16);
      if (lane < 8) SM_(float, OFF_FIN + lane * 32 + warp * 4) = b;
    }
    bar_sync(NB_BOTH, 256);
    if (tid < 8) {
      const float4 y0 = SM_(float4, OFF_FIN + tid * 32), y1 = SM_(float4, OFF_FIN + tid * 32 + 16);
      const float y = ((y0.x + y0.y) + (y0.z + y0.w)) + ((y1.x + y1.y) + y1.z);
      *out_fin = __float2bfloat16_rn(h_fin + bf16r(hn_fin + bf16r(bf16r(y) * sig)));
      if (cid == 0 && tid == 0) st_relaxed32(&p.s->epoch, tag);
    }
    CT(14);
  }
}

__global__ void __launch_bounds__(384, 1) occupancy_probe_kernel() {}

typedef CUresult (*EncodeFn)(CUtensorMap*, CUtensorMapDataType, cuuint32_t, void*, const cuuint64_t*, const cuuint64_t*, const cuuint32_t*, const cuuint32_t*,
                             CUtensorMapInterleave, CUtensorMapSwizzle, CUtensorMapL2promotion, CUtensorMapFloatOOBfill);

static void make_tm(EncodeFn enc, CUtensorMap* tm, const void* ptr, uint64_t rows, uint64_t cols, uint32_t brows, uint32_t bcols, CUtensorMapSwizzle sw,
                    CUtensorMapL2promotion promo = CU_TENSOR_MAP_L2_PROMOTION_L2_128B) {
  cuuint64_t dims[2] = {cols, rows};
  cuuint64_t strides[1] = {cols * 2};
  cuuint32_t box[2] = {bcols, brows};
  cuuint32_t es[2] = {1, 1};
  enc(tm, CU_TENSOR_MAP_DATA_TYPE_BFLOAT16, 2, const_cast<void*>(ptr), dims, strides, box, es, CU_TENSOR_MAP_INTERLEAVE_NONE, sw,
      promo, CU_TENSOR_MAP_FLOAT_OOB_FILL_NONE);
}

extern "C" void kernel_launch(void* const* d_in, const int* in_sizes, int n_in, void* d_out, int out_size) {
  (void)in_sizes; (void)n_in; (void)out_size;
  static EncodeFn enc = nullptr;
  static void* abT = nullptr;
  static int map = 0;
  if (!enc) {
    void* fn = nullptr; cudaDriverEntryPointQueryResult st;
    cudaGetDriverEntryPoint("cuTensorMapEncodeTiled", &fn, cudaEnableDefault, &st);
    enc = (EncodeFn)fn;
    cudaGetSymbolAddress(&abT, g_scratch);
    cudaFuncSetAttribute(fnet_moe_kernel<0>, cudaFuncAttributeMaxDynamicSharedMemorySize, SMEM_TOTAL);
    cudaFuncSetAttribute(fnet_moe_kernel<1>, cudaFuncAttributeMaxDynamicSharedMemorySize, SMEM_TOTAL);
    cudaFuncSetAttribute(occupancy_probe_kernel, cudaFuncAttributeMaxDynamicSharedMemorySize, SMEM_TOTAL);
    cudaFuncSetAttribute(occupancy_probe_kernel, cudaFuncAttributeNonPortableClusterSizeAllowed, 1);
    auto max_clusters = [&](int size) {
      cudaLaunchConfig_t cfg = {};
      cfg.gridDim = dim3(128); cfg.blockDim = dim3(384); cfg.dynamicSmemBytes = SMEM_TOTAL;
      cudaLaunchAttribute at[1];
      at[0].id = cudaLaunchAttributeClusterDimension; at[0].val.clusterDim.x = size; at[0].val.clusterDim.y = 1; at[0].val.clusterDim.z = 1;
      cfg.attrs = at; cfg.numAttrs = 1;
      int ncl = 0;
      return cudaOccupancyMaxActiveClusters(&ncl, occupancy_probe_kernel, &cfg) == cudaSuccess ? ncl : 0;
    };
    int dev = 0, sms = 0;
    cudaGetDevice(&dev);
    cudaDeviceGetAttribute(&sms, cudaDevAttrMultiProcessorCount, dev);
    map = (sms == 132 && max_clusters(2) == 66 && max_clusters(16) == 7) ? 0 : 1;
    (void)cudaGetLastError();
  }
  Params p;
  const bf16* x = (const bf16*)d_in[0];
  make_tm(enc, &p.tmD0, d_in[3], 1024, 1024, 128, 64, CU_TENSOR_MAP_SWIZZLE_128B);
  make_tm(enc, &p.tmD1, d_in[4], 1024, 1024, 128, 64, CU_TENSOR_MAP_SWIZZLE_128B);
  make_tm(enc, &p.tmX, x, 2048, 1024, map == 0 ? NX0 : 256, 64, CU_TENSOR_MAP_SWIZZLE_128B);
  make_tm(enc, &p.tmXr, x, 2048, 1024, 64, 64, CU_TENSOR_MAP_SWIZZLE_128B);
  make_tm(enc, &p.tmAbS, abT, 2048, 2048, 64, 64, CU_TENSOR_MAP_SWIZZLE_128B);
  make_tm(enc, &p.tmAbL, abT, 2048, 2048, 128, 64, CU_TENSOR_MAP_SWIZZLE_128B);
  make_tm(enc, &p.tmW0, d_in[1], 2048, 2048, 128, 64, CU_TENSOR_MAP_SWIZZLE_128B);
  make_tm(enc, &p.tmW1, d_in[2], 2048, 2048, 128, 64, CU_TENSOR_MAP_SWIZZLE_128B);
  {
    cuuint64_t dims[5] = {1024, 2, 4, 4, 64};
    cuuint64_t strides[4] = {2048, 8 * 2048, 2 * 2048, 32 * 2048};
    cuuint32_t box[5] = {64, 2, 4, 2, 1};
    cuuint32_t es[5] = {1, 1, 1, 1, 1};
    enc(&p.tmOut, CU_TENSOR_MAP_DATA_TYPE_BFLOAT16, 5, d_out, dims, strides, box, es, CU_TENSOR_MAP_INTERLEAVE_NONE, CU_TENSOR_MAP_SWIZZLE_128B,
        CU_TENSOR_MAP_L2_PROMOTION_NONE, CU_TENSOR_MAP_FLOAT_OOB_FILL_NONE);
  }
  {
    cuuint64_t dims[5] = {1024, 2, 4, 2, 8};
    cuuint64_t strides[4] = {2048, 4 * 2048, 2 * 2048, 256 * 2048};
    cuuint32_t box[5] = {64, 2, 4, 2, 8};
    cuuint32_t es[5] = {1, 1, 1, 1, 1};
    enc(&p.tmXh, CU_TENSOR_MAP_DATA_TYPE_BFLOAT16, 5, const_cast<bf16*>(x) + 240 * 1024, dims, strides, box, es, CU_TENSOR_MAP_INTERLEAVE_NONE,
        CU_TENSOR_MAP_SWIZZLE_128B, CU_TENSOR_MAP_L2_PROMOTION_L2_128B, CU_TENSOR_MAP_FLOAT_OOB_FILL_NONE);
  }
  make_tm(enc, &p.tmAbM, abT, 2048, 2048, 128, 16, CU_TENSOR_MAP_SWIZZLE_32B, CU_TENSOR_MAP_L2_PROMOTION_NONE);
  make_tm(enc, &p.tmWM0, d_in[1], 2048, 2048, 128, 16, CU_TENSOR_MAP_SWIZZLE_32B, CU_TENSOR_MAP_L2_PROMOTION_NONE);
  make_tm(enc, &p.tmWM1, d_in[2], 2048, 2048, 128, 16, CU_TENSOR_MAP_SWIZZLE_32B, CU_TENSOR_MAP_L2_PROMOTION_NONE);
  make_tm(enc, &p.tmG, d_in[7], 1024, 3584, 128, 32, CU_TENSOR_MAP_SWIZZLE_64B);
  make_tm(enc, &p.tmU, d_in[8], 1024, 3584, 128, 32, CU_TENSOR_MAP_SWIZZLE_64B);
  make_tm(enc, &p.tmDn, d_in[9], 3584, 1024, 32, 64, CU_TENSOR_MAP_SWIZZLE_128B);
  p.x = x; p.Dre = (const bf16*)d_in[3]; p.Dim = (const bf16*)d_in[4];
  p.wr = (const bf16*)d_in[6]; p.wdown = (const bf16*)d_in[9]; p.wgate = (const bf16*)d_in[7]; p.wup = (const bf16*)d_in[8];
  p.out = (bf16*)d_out; p.s = (Scratch*)abT;
  if (map == 1) fnet_moe_kernel<1><<<128, 384, SMEM_TOTAL>>>(p);
  else fnet_moe_kernel<0><<<132, 384, SMEM_TOTAL>>>(p);
}
```

```cpp
#include <cuda.h>
#include <cuda_runtime.h>
#include <cuda_bf16.h>
#include <stdint.h>
#include <type_traits>

typedef __nv_bfloat16 bf16;

constexpr int NX0 = 240;
constexpr int REG_C = 232, REG_P = 40;
constexpr int LG = 2;
constexpr int RW0 = LG > 0 ? 1024 : 1, RW1 = LG > 1 ? 512 : 2 >> LG, RW2 = LG > 2 ? 256 : 4 >> LG, RW3 = 8 >> LG;
__host__ __device__ constexpr int row_of(int p) { return (p & 1) * RW0 + ((p >> 1) & 1) * RW1 + ((p >> 2) & 1) * RW2 + (p >> 3) * RW3; }
__host__ __device__ constexpr int group_of(int row) { return (row & (256 * RW3 - 1)) / (16 * RW3); }
__device__ __forceinline__ int sigma_of(int tau, int r) { return r + (r >= tau); }
__device__ __forceinline__ int kblock(int tau, int j) {
  const int i = j - 4, c = (i * 37) >> 8;
  return j < 4 ? tau * 4 + j : sigma_of(tau, i - 7 * c) * 4 + c;
}
constexpr int AUX_AFTER = 1;
constexpr int PF_K0 = 8, PF_N0 = 2, PF_K1 = 24;
constexpr int WPF_K0 = 12, WPF_N = 10;
constexpr int PUB_K1 = 22;
constexpr int NREG_H = 5;
constexpr int MR_K0 = 29, MR_P = 6;
constexpr int MINI_PF_K = 39, MINI_LOAD_K = 43, MINI_K = 42;
constexpr int RESET_K = 37;
constexpr int SEND_FIRST = 2;
constexpr int HELPER_NS = 5000;
constexpr int GATHER_NS = 400;
constexpr int MOE_PACE_CLK = 300;
constexpr int OUT_PACE_CLK = 70;
constexpr int HOP1_DELAY = 150, HOP3_DELAY = 450;
constexpr int SPEC_MIN = 10;
constexpr int IDLE_WAIT_CLK = 1200;
__host__ __device__ constexpr int mr_k(int h) { return MR_K0 + MR_P * (h >> 1) + 2 * (h & 1); }
constexpr int A_BYTES = 128 * 64 * 2;
constexpr int B_BYTES = 256 * 64 * 2;
constexpr int ST_BYTES = A_BYTES + B_BYTES;
constexpr int OFF_XCH = 4 * ST_BYTES;
constexpr int OFF_BAR = OFF_XCH + 32768;
constexpr int OFF_WR = OFF_BAR + 384;
constexpr int OFF_RS = OFF_WR + 384;
constexpr int OFF_PUB = OFF_RS + 640;
constexpr int OFF_MISC = OFF_PUB + 768;
constexpr int SMEM_TOTAL = OFF_MISC + 256;
constexpr int OFF_WSUM = OFF_MISC, OFF_TAG = OFF_MISC + 4;
constexpr int OFF_SEEN = OFF_MISC + 8;
constexpr int OFF_KV = OFF_MISC + 12;
constexpr int OFF_WKEY = OFF_MISC + 32;
constexpr int OFF_MINI = OFF_XCH + 16384;
constexpr int OFF_EXA = OFF_XCH;
constexpr int OFF_EXB = OFF_XCH + 4096;
__host__ __device__ constexpr int chunk_off(int c, int w) { return (c < 2 ? (c + 2) * ST_BYTES : OFF_XCH + (c - 2) * 16384) + w * 8192; }
__host__ __device__ constexpr int late_off(int i) { return i < 4 ? i * 16384 : 2 * ST_BYTES + A_BYTES + (i - 4) * 16384; }
__host__ __device__ constexpr int round_off(int h) { return h < NREG_H + 2 ? OFF_XCH + (h & 1) * 16384 : late_off(h - NREG_H - 2); }
__host__ __device__ constexpr int down_off(int i) { return late_off(6 - NREG_H + i); }
constexpr int OFF_PEER = ST_BYTES + A_BYTES;
constexpr int OFF_OUT = 3 * ST_BYTES + A_BYTES;
constexpr int OFF_XSEL = OFF_PEER;
constexpr int OFF_HSEL = OFF_PEER + 4096;
constexpr int OFF_GP = OFF_PEER + 8192;
constexpr int OFF_FIN = OFF_PEER + 9216;
__device__ __forceinline__ int slot_of(int k) { return k & 3; }
__device__ __forceinline__ int use_of(int k) { return k >> 2; }
enum { B_FULL = 0, B_EMPTY = 4, B_EPI = 8, B_STD = 12, B_EPI0B = 16, B_LATE = 17, B_STAT = 18, B_XCH = 19, B_MR = 20  , B_GU = 22,
       B_DN = 23, B_AUX = 24  , B_OUT = 26, B_KEY = 27, B_XS = 28, B_A20 = 29, B_STDA = 30, B_PUB1 = 31, B_COUNT = 32 };
enum { NB_TURN0 = 1, NB_TURN1 = 2, NB_WG0 = 3, NB_BOTH = 5, NB_AUX = 6 };

struct Scratch {
  bf16 abT[2048 * 2048];
  uint2 xstat[2048];
  uint2 dsum[2048];
  uint4 abflag[16 * 8 * 2];
  uint4 hflag[16 * 2];
  uint4 hstat[16 * 8 * 128];
  uint4 cand[16 * 256];
  uint4 key[8 * 16 * 2];
  uint4 ypart[128 * 256];
  uint32_t epoch;
};
__device__ __align__(1024) Scratch g_scratch;

struct Params {
  Scratch* s; bf16* out;
  const bf16* x; const bf16* Dre; const bf16* Dim; const bf16* wr; const bf16* wdown; const bf16* wgate; const bf16* wup;
  CUtensorMap tmX, tmD0, tmD1, tmXr, tmAbS, tmAbL, tmW0, tmW1, tmOut, tmG, tmU, tmDn, tmXh, tmAbM, tmWM0, tmWM1;
};

#define SPIN_LIMIT (1u << 14)
#define MBAR_LIMIT (1u << 10)
__device__ __forceinline__ uint32_t smem_u32(const void* p) { return (uint32_t)__cvta_generic_to_shared(p); }
__device__ __forceinline__ void mbar_init(uint32_t bar, uint32_t cnt) { asm volatile("mbarrier.init.shared::cta.b64 [%0], %1;" :: "r"(bar), "r"(cnt) : "memory"); }
__device__ __forceinline__ void mbar_expect_tx(uint32_t bar, uint32_t bytes) { asm volatile("mbarrier.arrive.expect_tx.shared::cta.b64 _, [%0], %1;" :: "r"(bar), "r"(bytes) : "memory"); }
__device__ __forceinline__ void mbar_arrive(uint32_t bar) { asm volatile("mbarrier.arrive.shared::cta.b64 _, [%0];" :: "r"(bar) : "memory"); }
__device__ __forceinline__ void mbar_wait(uint32_t bar, uint32_t parity) {
  uint32_t ok, n = 0;
  do {
    asm volatile("{\n.reg .pred p;\nmbarrier.try_wait.parity.shared::cta.b64 p, [%1], %2;\nselp.u32 %0, 1, 0, p;\n}\n" : "=r"(ok) : "r"(bar), "r"(parity) : "memory");
  } while (!ok && ++n < MBAR_LIMIT);
}
__device__ __forceinline__ void mbar_wait_cluster(uint32_t bar, uint32_t parity) {
  uint32_t ok, n = 0;
  do {
    asm volatile("{\n.reg .pred p;\nmbarrier.try_wait.parity.acquire.cluster.shared::cta.b64 p, [%1], %2;\nselp.u32 %0, 1, 0, p;\n}\n" : "=r"(ok) : "r"(bar), "r"(parity) : "memory");
  } while (!ok && ++n < MBAR_LIMIT);
}
__device__ __forceinline__ void tma_load_2d(uint32_t dst, const CUtensorMap* tm, uint32_t bar, int c0, int c1) {
  asm volatile("cp.async.bulk.tensor.2d.shared::cluster.global.mbarrier::complete_tx::bytes [%0], [%1, {%3, %4}], [%2];"
    :: "r"(dst), "l"(tm), "r"(bar), "r"(c0), "r"(c1) : "memory");
}
__device__ __forceinline__ void tma_load_2d_hint(uint32_t dst, const CUtensorMap* tm, uint32_t bar, int c0, int c1, uint64_t pol) {
  asm volatile("cp.async.bulk.tensor.2d.shared::cluster.global.mbarrier::complete_tx::bytes.L2::cache_hint [%0], [%1, {%3, %4}], [%2], %5;"
    :: "r"(dst), "l"(tm), "r"(bar), "r"(c0), "r"(c1), "l"(pol) : "memory");
}
__device__ __forceinline__ uint64_t policy_evict_first() { uint64_t p; asm volatile("createpolicy.fractional.L2::evict_first.b64 %0, 1.0;" : "=l"(p)); return p; }
__device__ __forceinline__ void tma_store_2d(const CUtensorMap* tm, uint32_t src, int c0, int c1) {
  asm volatile("cp.async.bulk.tensor.2d.global.shared::cta.bulk_group [%0, {%2, %3}], [%1];" :: "l"(tm), "r"(src), "r"(c0), "r"(c1) : "memory");
}
__device__ __forceinline__ void tma_prefetch_2d(const CUtensorMap* tm, int c0, int c1) {
  asm volatile("cp.async.bulk.prefetch.tensor.2d.L2.global.tile [%0, {%1, %2}];" :: "l"(tm), "r"(c0), "r"(c1) : "memory");
}
__device__ __forceinline__ void bulk_load(uint32_t dst, const void* src, uint32_t bytes, uint32_t bar) {
  asm volatile("cp.async.bulk.shared::cluster.global.mbarrier::complete_tx::bytes [%0], [%1], %2, [%3];" :: "r"(dst), "l"(src), "r"(bytes), "r"(bar) : "memory");
}
__device__ __forceinline__ void bulk_commit() { asm volatile("cp.async.bulk.commit_group;" ::: "memory"); }
__device__ __forceinline__ void bulk_wait_all() { asm volatile("cp.async.bulk.wait_group 0;" ::: "memory"); }
__device__ __forceinline__ void fence_async_smem() { asm volatile("fence.proxy.async.shared::cta;" ::: "memory"); }
__device__ __forceinline__ void wgmma_fence() { asm volatile("wgmma.fence.sync.aligned;" ::: "memory"); }
__device__ __forceinline__ void wgmma_commit() { asm volatile("wgmma.commit_group.sync.aligned;" ::: "memory"); }
__device__ __forceinline__ void wgmma_wait0() { asm volatile("wgmma.wait_group.sync.aligned 0;" ::: "memory"); }
__device__ __forceinline__ void bar_sync(int id, int n) { asm volatile("bar.sync %0, %1;" :: "r"(id), "r"(n) : "memory"); }
__device__ __forceinline__ void bar_arrive(int id, int n) { asm volatile("bar.arrive %0, %1;" :: "r"(id), "r"(n) : "memory"); }
template<int R> __device__ __forceinline__ void reg_inc() { asm volatile("setmaxnreg.inc.sync.aligned.u32 %0;" :: "n"(R)); }
template<int R> __device__ __forceinline__ void reg_dec() { asm volatile("setmaxnreg.dec.sync.aligned.u32 %0;" :: "n"(R)); }
__device__ __forceinline__ bool elect_one() {
  uint32_t p;
  asm volatile("{\n.reg .pred q;\nelect.sync _|q, 0xffffffff;\nselp.u32 %0, 1, 0, q;\n}\n" : "=r"(p));
  return p != 0;
}
__device__ __forceinline__ uint32_t mapa(uint32_t addr, uint32_t cta) { uint32_t r; asm volatile("mapa.shared::cluster.u32 %0, %1, %2;" : "=r"(r) : "r"(addr), "r"(cta)); return r; }
__device__ __forceinline__ void st_async_v4(uint32_t addr, uint32_t bar, uint32_t a, uint32_t b, uint32_t c, uint32_t d) {
  asm volatile("st.async.weak.shared::cluster.mbarrier::complete_tx::bytes.v4.b32 [%0], {%2, %3, %4, %5}, [%1];" :: "r"(addr), "r"(bar), "r"(a), "r"(b), "r"(c), "r"(d) : "memory");
}
__device__ __forceinline__ void stsm_x4(uint32_t addr, uint32_t a, uint32_t b, uint32_t c, uint32_t d) {
  asm volatile("stmatrix.sync.aligned.m8n8.x4.shared.b16 [%0], {%1, %2, %3, %4};" :: "r"(addr), "r"(a), "r"(b), "r"(c), "r"(d));
}
__device__ __forceinline__ uint4 lds128_v(uint32_t addr) { uint4 v; asm volatile("ld.shared.v4.b32 {%0, %1, %2, %3}, [%4];" : "=r"(v.x), "=r"(v.y), "=r"(v.z), "=r"(v.w) : "r"(addr)); return v; }
extern __shared__ __align__(1024) uint8_t smem_raw[];
template<class T> __device__ __forceinline__ T& smem_at(uint32_t addr) { return *reinterpret_cast<T*>(__cvta_shared_to_generic(addr)); }
#define SM_(T, off) smem_at<T>(sb + (off))
__device__ __forceinline__ uint4 ldg_nc128(const void* p) { uint4 v; asm volatile("ld.global.nc.v4.b32 {%0, %1, %2, %3}, [%4];" : "=r"(v.x), "=r"(v.y), "=r"(v.z), "=r"(v.w) : "l"(p)); return v; }
__device__ __forceinline__ void pkt_st128(void* p, uint32_t a, uint32_t b, uint32_t c, uint32_t d) {
  asm volatile("{\n.reg .b128 v;\n.reg .b64 lo, hi;\nmov.b64 lo, {%1, %2};\nmov.b64 hi, {%3, %4};\nmov.b128 v, {lo, hi};\nst.relaxed.gpu.global.b128 [%0], v;\n}\n"
    :: "l"(p), "r"(a), "r"(b), "r"(c), "r"(d) : "memory");
}
__device__ __forceinline__ uint4 pkt_ld128(const void* p) {
  uint4 r;
  asm volatile("{\n.reg .b128 v;\n.reg .b64 lo, hi;\nld.relaxed.gpu.global.b128 v, [%4];\nmov.b128 {lo, hi}, v;\nmov.b64 {%0, %1}, lo;\nmov.b64 {%2, %3}, hi;\n}\n"
    : "=r"(r.x), "=r"(r.y), "=r"(r.z), "=r"(r.w) : "l"(p) : "memory");
  return r;
}
__device__ __forceinline__ void pkt_ld128_if(uint4& r, const void* p, bool cond) {
  asm volatile("{\n.reg .pred q;\n.reg .b64 lo, hi;\nsetp.ne.b32 q, %5, 0;\nmov.b64 lo, {%0, %1};\nmov.b64 hi, {%2, %3};\n"
               "@q ld.relaxed.gpu.global.v2.b64 {lo, hi}, [%4];\nmov.b64 {%0, %1}, lo;\nmov.b64 {%2, %3}, hi;\n}\n"
    : "+r"(r.x), "+r"(r.y), "+r"(r.z), "+r"(r.w) : "l"(p), "r"((uint32_t)cond) : "memory");
}
__device__ __forceinline__ void pkt_st64(void* p, uint32_t a, uint32_t b) {
  asm volatile("{\n.reg .b64 v;\nmov.b64 v, {%1, %2};\nst.relaxed.gpu.global.b64 [%0], v;\n}\n" :: "l"(p), "r"(a), "r"(b) : "memory");
}
__device__ __forceinline__ uint2 pkt_ld64(const void* p) {
  uint2 r;
  asm volatile("{\n.reg .b64 v;\nld.relaxed.gpu.global.b64 v, [%2];\nmov.b64 {%0, %1}, v;\n}\n" : "=r"(r.x), "=r"(r.y) : "l"(p) : "memory");
  return r;
}
__device__ __forceinline__ uint32_t ld_relaxed32(const void* p) { uint32_t v; asm volatile("ld.relaxed.gpu.global.b32 %0, [%1];" : "=r"(v) : "l"(p) : "memory"); return v; }
__device__ __forceinline__ void st_relaxed32(void* p, uint32_t v) { asm volatile("st.relaxed.gpu.global.b32 [%0], %1;" :: "l"(p), "r"(v) : "memory"); }
__device__ __forceinline__ uint32_t code_of(uint32_t tag) { return tag % 3u + 1u; }
__device__ __forceinline__ uint32_t with_bit(float v, uint32_t bit) { return (__float_as_uint(v) & ~1u) | (bit & 1u); }
__device__ __forceinline__ uint32_t pair_code(uint32_t a, uint32_t b) { return (a & 1u) | ((b & 1u) << 1); }
__device__ __forceinline__ uint32_t pack_bf16(float lo, float hi) { uint32_t r; asm("cvt.rn.bf16x2.f32 %0, %1, %2;" : "=r"(r) : "f"(hi), "f"(lo)); return r; }
__device__ __forceinline__ float bf_lo(uint32_t v) { return __uint_as_float(v << 16); }
__device__ __forceinline__ float bf_hi(uint32_t v) { return __uint_as_float(v & 0xFFFF0000u); }
__device__ __forceinline__ float bf16r(float x) { return __uint_as_float(pack_bf16(0.f, x)); }
__device__ __forceinline__ uint32_t badd2(uint32_t a, uint32_t b) { uint32_t r; asm("add.rn.bf16x2 %0, %1, %2;" : "=r"(r) : "r"(a), "r"(b)); return r; }
__device__ __forceinline__ uint32_t bmul2(uint32_t a, uint32_t b) { uint32_t r; asm("mul.rn.bf16x2 %0, %1, %2;" : "=r"(r) : "r"(a), "r"(b)); return r; }
__device__ __forceinline__ float warp_sum(float v) {
#pragma unroll
  for (int o = 16; o > 0; o >>= 1) v += __shfl_xor_sync(0xffffffffu, v, o);
  return v;
}
__device__ __forceinline__ uint64_t make_desc(uint32_t addr) {
  return (uint64_t)((addr & 0x3FFFF) >> 4) | ((uint64_t)1 << 16) | ((uint64_t)64 << 32) | ((uint64_t)1 << 62);
}
__device__ __forceinline__ uint64_t make_desc_noswz(uint32_t addr) {
  return (uint64_t)((addr & 0x3FFFF) >> 4) | ((uint64_t)8 << 16) | ((uint64_t)16 << 32);
}
__device__ __forceinline__ uint64_t make_desc_32b(uint32_t addr) {
  return (uint64_t)((addr & 0x3FFFF) >> 4) | ((uint64_t)1 << 16) | ((uint64_t)16 << 32) | ((uint64_t)3 << 62);
}
__device__ __forceinline__ void wgmma_n256(float (&d)[128], uint64_t da, uint64_t db, int scale_d) {
  asm volatile("{\n.reg .pred p;\nsetp.ne.b32 p, %130, 0;\n"
    "wgmma.mma_async.sync.aligned.m64n256k16.f32.bf16.bf16 "
    "{%0, %1, %2, %3, %4, %5, %6, %7, %8, %9, %10, %11, %12, %13, %14, %15, %16, %17, %18, %19, %20, %21, %22, %23, %24, %25, %26, %27, %28, %29, %30, %31, "
    "%32, %33, %34, %35, %36, %37, %38, %39, %40, %41, %42, %43, %44, %45, %46, %47, %48, %49, %50, %51, %52, %53, %54, %55, %56, %57, %58, %59, %60, %61, %62, %63, "
    "%64, %65, %66, %67, %68, %69, %70, %71, %72, %73, %74, %75, %76, %77, %78, %79, %80, %81, %82, %83, %84, %85, %86, %87, %88, %89, %90, %91, %92, %93, %94, %95, "
    "%96, %97, %98, %99, %100, %101, %102, %103, %104, %105, %106, %107, %108, %109, %110, %111, %112, %113, %114, %115, %116, %117, %118, %119, %120, %121, %122, %123, %124, %125, %126, %127}, "
    "%128, %129, p, 1, 1, 0, 0;\n}\n"
    : "+f"(d[0]), "+f"(d[1]), "+f"(d[2]), "+f"(d[3]), "+f"(d[4]), "+f"(d[5]), "+f"(d[6]), "+f"(d[7]),
      "+f"(d[8]), "+f"(d[9]), "+f"(d[10]), "+f"(d[11]), "+f"(d[12]), "+f"(d[13]), "+f"(d[14]), "+f"(d[15]),
      "+f"(d[16]), "+f"(d[17]), "+f"(d[18]), "+f"(d[19]), "+f"(d[20]), "+f"(d[21]), "+f"(d[22]), "+f"(d[23]),
      "+f"(d[24]), "+f"(d[25]), "+f"(d[26]), "+f"(d[27]), "+f"(d[28]), "+f"(d[29]), "+f"(d[30]), "+f"(d[31]),
      "+f"(d[32]), "+f"(d[33]), "+f"(d[34]), "+f"(d[35]), "+f"(d[36]), "+f"(d[37]), "+f"(d[38]), "+f"(d[39]),
      "+f"(d[40]), "+f"(d[41]), "+f"(d[42]), "+f"(d[43]), "+f"(d[44]), "+f"(d[45]), "+f"(d[46]), "+f"(d[47]),
      "+f"(d[48]), "+f"(d[49]), "+f"(d[50]), "+f"(d[51]), "+f"(d[52]), "+f"(d[53]), "+f"(d[54]), "+f"(d[55]),
      "+f"(d[56]), "+f"(d[57]), "+f"(d[58]), "+f"(d[59]), "+f"(d[60]), "+f"(d[61]), "+f"(d[62]), "+f"(d[63]),
      "+f"(d[64]), "+f"(d[65]), "+f"(d[66]), "+f"(d[67]), "+f"(d[68]), "+f"(d[69]), "+f"(d[70]), "+f"(d[71]),
      "+f"(d[72]), "+f"(d[73]), "+f"(d[74]), "+f"(d[75]), "+f"(d[76]), "+f"(d[77]), "+f"(d[78]), "+f"(d[79]),
      "+f"(d[80]), "+f"(d[81]), "+f"(d[82]), "+f"(d[83]), "+f"(d[84]), "+f"(d[85]), "+f"(d[86]), "+f"(d[87]),
      "+f"(d[88]), "+f"(d[89]), "+f"(d[90]), "+f"(d[91]), "+f"(d[92]), "+f"(d[93]), "+f"(d[94]), "+f"(d[95]),
      "+f"(d[96]), "+f"(d[97]), "+f"(d[98]), "+f"(d[99]), "+f"(d[100]), "+f"(d[101]), "+f"(d[102]), "+f"(d[103]),
      "+f"(d[104]), "+f"(d[105]), "+f"(d[106]), "+f"(d[107]), "+f"(d[108]), "+f"(d[109]), "+f"(d[110]), "+f"(d[111]),
      "+f"(d[112]), "+f"(d[113]), "+f"(d[114]), "+f"(d[115]), "+f"(d[116]), "+f"(d[117]), "+f"(d[118]), "+f"(d[119]),
      "+f"(d[120]), "+f"(d[121]), "+f"(d[122]), "+f"(d[123]), "+f"(d[124]), "+f"(d[125]), "+f"(d[126]), "+f"(d[127])
    : "l"(da), "l"(db), "r"(scale_d));
}
__device__ __forceinline__ void wgmma_g1(float (&d)[128], uint64_t da, uint64_t db, int scale_d) { wgmma_n256(d, da, db, scale_d); }
__device__ __forceinline__ void wgmma_g1(float (&d)[120], uint64_t da, uint64_t db, int scale_d) {
  asm volatile("{\n.reg .pred p;\nsetp.ne.b32 p, %122, 0;\n"
    "wgmma.mma_async.sync.aligned.m64n240k16.f32.bf16.bf16 "
    "{%0, %1, %2, %3, %4, %5, %6, %7, %8, %9, %10, %11, %12, %13, %14, %15, %16, %17, %18, %19, %20, %21, %22, %23, %24, %25, %26, %27, %28, %29, %30, %31, %32, %33, %34, %35, %36, %37, %38, %39, %40, %41, %42, %43, %44, %45, %46, %47, %48, %49, %50, %51, %52, %53, %54, %55, %56, %57, %58, %59, %60, %61, %62, %63, %64, %65, %66, %67, %68, %69, %70, %71, %72, %73, %74, %75, %76, %77, %78, %79, %80, %81, %82, %83, %84, %85, %86, %87, %88, %89, %90, %91, %92, %93, %94, %95, %96, %97, %98, %99, %100, %101, %102, %103, %104, %105, %106, %107, %108, %109, %110, %111, %112, %113, %114, %115, %116, %117, %118, %119}, "
    "%120, %121, p, 1, 1, 0, 0;\n}\n"
    : "+f"(d[0]), "+f"(d[1]), "+f"(d[2]), "+f"(d[3]), "+f"(d[4]), "+f"(d[5]), "+f"(d[6]), "+f"(d[7]), "+f"(d[8]), "+f"(d[9]), "+f"(d[10]), "+f"(d[11]), "+f"(d[12]), "+f"(d[13]), "+f"(d[14]), "+f"(d[15]), "+f"(d[16]), "+f"(d[17]), "+f"(d[18]), "+f"(d[19]), "+f"(d[20]), "+f"(d[21]), "+f"(d[22]), "+f"(d[23]), "+f"(d[24]), "+f"(d[25]), "+f"(d[26]), "+f"(d[27]), "+f"(d[28]), "+f"(d[29]), "+f"(d[30]), "+f"(d[31]), "+f"(d[32]), "+f"(d[33]), "+f"(d[34]), "+f"(d[35]), "+f"(d[36]), "+f"(d[37]), "+f"(d[38]), "+f"(d[39]), "+f"(d[40]), "+f"(d[41]), "+f"(d[42]), "+f"(d[43]), "+f"(d[44]), "+f"(d[45]), "+f"(d[46]), "+f"(d[47]), "+f"(d[48]), "+f"(d[49]), "+f"(d[50]), "+f"(d[51]), "+f"(d[52]), "+f"(d[53]), "+f"(d[54]), "+f"(d[55]), "+f"(d[56]), "+f"(d[57]), "+f"(d[58]), "+f"(d[59]), "+f"(d[60]), "+f"(d[61]), "+f"(d[62]), "+f"(d[63]), "+f"(d[64]), "+f"(d[65]), "+f"(d[66]), "+f"(d[67]), "+f"(d[68]), "+f"(d[69]), "+f"(d[70]), "+f"(d[71]), "+f"(d[72]), "+f"(d[73]), "+f"(d[74]), "+f"(d[75]), "+f"(d[76]), "+f"(d[77]), "+f"(d[78]), "+f"(d[79]), "+f"(d[80]), "+f"(d[81]), "+f"(d[82]), "+f"(d[83]), "+f"(d[84]), "+f"(d[85]), "+f"(d[86]), "+f"(d[87]), "+f"(d[88]), "+f"(d[89]), "+f"(d[90]), "+f"(d[91]), "+f"(d[92]), "+f"(d[93]), "+f"(d[94]), "+f"(d[95]), "+f"(d[96]), "+f"(d[97]), "+f"(d[98]), "+f"(d[99]), "+f"(d[100]), "+f"(d[101]), "+f"(d[102]), "+f"(d[103]), "+f"(d[104]), "+f"(d[105]), "+f"(d[106]), "+f"(d[107]), "+f"(d[108]), "+f"(d[109]), "+f"(d[110]), "+f"(d[111]), "+f"(d[112]), "+f"(d[113]), "+f"(d[114]), "+f"(d[115]), "+f"(d[116]), "+f"(d[117]), "+f"(d[118]), "+f"(d[119])
    : "l"(da), "l"(db), "r"(scale_d));
}
__device__ __forceinline__ void wgmma_n256_rs(float (&d)[128], uint32_t a0, uint32_t a1, uint32_t a2, uint32_t a3, uint64_t db, int scale_d) {
  asm volatile("{\n.reg .pred p;\nsetp.ne.b32 p, %133, 0;\n"
    "wgmma.mma_async.sync.aligned.m64n256k16.f32.bf16.bf16 "
    "{%0, %1, %2, %3, %4, %5, %6, %7, %8, %9, %10, %11, %12, %13, %14, %15, %16, %17, %18, %19, %20, %21, %22, %23, %24, %25, %26, %27, %28, %29, %30, %31, "
    "%32, %33, %34, %35, %36, %37, %38, %39, %40, %41, %42, %43, %44, %45, %46, %47, %48, %49, %50, %51, %52, %53, %54, %55, %56, %57, %58, %59, %60, %61, %62, %63, "
    "%64, %65, %66, %67, %68, %69, %70, %71, %72, %73, %74, %75, %76, %77, %78, %79, %80, %81, %82, %83, %84, %85, %86, %87, %88, %89, %90, %91, %92, %93, %94, %95, "
    "%96, %97, %98, %99, %100, %101, %102, %103, %104, %105, %106, %107, %108, %109, %110, %111, %112, %113, %114, %115, %116, %117, %118, %119, %120, %121, %122, %123, %124, %125, %126, %127}, "
    "{%128, %129, %130, %131}, %132, p, 1, 1, 0;\n}\n"
    : "+f"(d[0]), "+f"(d[1]), "+f"(d[2]), "+f"(d[3]), "+f"(d[4]), "+f"(d[5]), "+f"(d[6]), "+f"(d[7]),
      "+f"(d[8]), "+f"(d[9]), "+f"(d[10]), "+f"(d[11]), "+f"(d[12]), "+f"(d[13]), "+f"(d[14]), "+f"(d[15]),
      "+f"(d[16]), "+f"(d[17]), "+f"(d[18]), "+f"(d[19]), "+f"(d[20]), "+f"(d[21]), "+f"(d[22]), "+f"(d[23]),
      "+f"(d[24]), "+f"(d[25]), "+f"(d[26]), "+f"(d[27]), "+f"(d[28]), "+f"(d[29]), "+f"(d[30]), "+f"(d[31]),
      "+f"(d[32]), "+f"(d[33]), "+f"(d[34]), "+f"(d[35]), "+f"(d[36]), "+f"(d[37]), "+f"(d[38]), "+f"(d[39]),
      "+f"(d[40]), "+f"(d[41]), "+f"(d[42]), "+f"(d[43]), "+f"(d[44]), "+f"(d[45]), "+f"(d[46]), "+f"(d[47]),
      "+f"(d[48]), "+f"(d[49]), "+f"(d[50]), "+f"(d[51]), "+f"(d[52]), "+f"(d[53]), "+f"(d[54]), "+f"(d[55]),
      "+f"(d[56]), "+f"(d[57]), "+f"(d[58]), "+f"(d[59]), "+f"(d[60]), "+f"(d[61]), "+f"(d[62]), "+f"(d[63]),
      "+f"(d[64]), "+f"(d[65]), "+f"(d[66]), "+f"(d[67]), "+f"(d[68]), "+f"(d[69]), "+f"(d[70]), "+f"(d[71]),
      "+f"(d[72]), "+f"(d[73]), "+f"(d[74]), "+f"(d[75]), "+f"(d[76]), "+f"(d[77]), "+f"(d[78]), "+f"(d[79]),
      "+f"(d[80]), "+f"(d[81]), "+f"(d[82]), "+f"(d[83]), "+f"(d[84]), "+f"(d[85]), "+f"(d[86]), "+f"(d[87]),
      "+f"(d[88]), "+f"(d[89]), "+f"(d[90]), "+f"(d[91]), "+f"(d[92]), "+f"(d[93]), "+f"(d[94]), "+f"(d[95]),
      "+f"(d[96]), "+f"(d[97]), "+f"(d[98]), "+f"(d[99]), "+f"(d[100]), "+f"(d[101]), "+f"(d[102]), "+f"(d[103]),
      "+f"(d[104]), "+f"(d[105]), "+f"(d[106]), "+f"(d[107]), "+f"(d[108]), "+f"(d[109]), "+f"(d[110]), "+f"(d[111]),
      "+f"(d[112]), "+f"(d[113]), "+f"(d[114]), "+f"(d[115]), "+f"(d[116]), "+f"(d[117]), "+f"(d[118]), "+f"(d[119]),
      "+f"(d[120]), "+f"(d[121]), "+f"(d[122]), "+f"(d[123]), "+f"(d[124]), "+f"(d[125]), "+f"(d[126]), "+f"(d[127])
    : "r"(a0), "r"(a1), "r"(a2), "r"(a3), "l"(db), "r"(scale_d));
}
__device__ __forceinline__ void wgmma_n128(float (&d)[64], uint64_t da, uint64_t db, int scale_d = 1) {
  asm volatile("{\n.reg .pred p;\nsetp.ne.b32 p, %66, 0;\n"
    "wgmma.mma_async.sync.aligned.m64n128k16.f32.bf16.bf16 "
    "{%0, %1, %2, %3, %4, %5, %6, %7, %8, %9, %10, %11, %12, %13, %14, %15, %16, %17, %18, %19, %20, %21, %22, %23, %24, %25, %26, %27, %28, %29, %30, %31, %32, %33, %34, %35, %36, %37, %38, %39, %40, %41, %42, %43, %44, %45, %46, %47, %48, %49, %50, %51, %52, %53, %54, %55, %56, %57, %58, %59, %60, %61, %62, %63}, "
    "%64, %65, p, 1, 1, 0, 0;\n}\n"
    : "+f"(d[0]), "+f"(d[1]), "+f"(d[2]), "+f"(d[3]), "+f"(d[4]), "+f"(d[5]), "+f"(d[6]), "+f"(d[7]), "+f"(d[8]), "+f"(d[9]), "+f"(d[10]), "+f"(d[11]), "+f"(d[12]), "+f"(d[13]), "+f"(d[14]), "+f"(d[15]), "+f"(d[16]), "+f"(d[17]), "+f"(d[18]), "+f"(d[19]), "+f"(d[20]), "+f"(d[21]), "+f"(d[22]), "+f"(d[23]), "+f"(d[24]), "+f"(d[25]), "+f"(d[26]), "+f"(d[27]), "+f"(d[28]), "+f"(d[29]), "+f"(d[30]), "+f"(d[31]), "+f"(d[32]), "+f"(d[33]), "+f"(d[34]), "+f"(d[35]), "+f"(d[36]), "+f"(d[37]), "+f"(d[38]), "+f"(d[39]), "+f"(d[40]), "+f"(d[41]), "+f"(d[42]), "+f"(d[43]), "+f"(d[44]), "+f"(d[45]), "+f"(d[46]), "+f"(d[47]), "+f"(d[48]), "+f"(d[49]), "+f"(d[50]), "+f"(d[51]), "+f"(d[52]), "+f"(d[53]), "+f"(d[54]), "+f"(d[55]), "+f"(d[56]), "+f"(d[57]), "+f"(d[58]), "+f"(d[59]), "+f"(d[60]), "+f"(d[61]), "+f"(d[62]), "+f"(d[63])
    : "l"(da), "l"(db), "r"(scale_d));
}
template<int N> __device__ __forceinline__ void fence_acc(float (&d)[N]) {
#pragma unroll
  for (int i = 0; i < N; i++) asm volatile("" : "+f"(d[i]) :: "memory");
}

template<int N, int I = 0, class F> __device__ __forceinline__ void static_for(F&& f) {
  if constexpr (I < N) { f(std::integral_constant<int, I>()); static_for<N, I + 1>(f); }
}

__device__ __forceinline__ void ldsm_x4_t(uint32_t addr, uint32_t& a, uint32_t& b, uint32_t& c, uint32_t& d) {
  asm volatile("ldmatrix.sync.aligned.m8n8.x4.trans.shared.b16 {%0, %1, %2, %3}, [%4];" : "=r"(a), "=r"(b), "=r"(c), "=r"(d) : "r"(addr));
}
__device__ __forceinline__ void sts128(uint32_t addr, uint32_t a, uint32_t b, uint32_t c, uint32_t d) {
  asm volatile("st.shared.v4.b32 [%0], {%1, %2, %3, %4};" :: "r"(addr), "r"(a), "r"(b), "r"(c), "r"(d));
}
__device__ __forceinline__ void mma16816(float (&c)[4], uint32_t a0, uint32_t a1, uint32_t a2, uint32_t a3, uint32_t b0, uint32_t b1) {
  asm volatile("mma.sync.aligned.m16n8k16.row.col.f32.bf16.bf16.f32 {%0, %1, %2, %3}, {%4, %5, %6, %7}, {%8, %9}, {%0, %1, %2, %3};"
      : "+f"(c[0]), "+f"(c[1]), "+f"(c[2]), "+f"(c[3]) : "r"(a0), "r"(a1), "r"(a2), "r"(a3), "r"(b0), "r"(b1));
}
__device__ __forceinline__ void mma1688(float (&c)[4], uint32_t a0, uint32_t a1, uint32_t b0) {
  asm volatile("mma.sync.aligned.m16n8k8.row.col.f32.bf16.bf16.f32 {%0, %1, %2, %3}, {%4, %5}, {%6}, {%0, %1, %2, %3};"
      : "+f"(c[0]), "+f"(c[1]), "+f"(c[2]), "+f"(c[3]) : "r"(a0), "r"(a1), "r"(b0));
}
__device__ __forceinline__ void pin(uint32_t& v) { asm volatile("shfl.sync.bfly.b32 %0, %0, 0, 0x1f, 0xffffffff;" : "+r"(v)); }
template<class T> __device__ __forceinline__ void pin(T*& v) {
  uint32_t lo = (uint32_t)(uint64_t)v, hi = (uint32_t)((uint64_t)v >> 32);
  pin(lo); pin(hi);
  v = (T*)(((uint64_t)hi << 32) | lo);
}
__device__ __forceinline__ float sel4(int q, float a, float b, float c, float d) {
  float r;
  asm("{\n.reg .pred p, o;\n.reg .f32 x, y;\n.reg .b32 t;\nand.b32 t, %1, 1;\nsetp.ne.b32 p, t, 0;\nsetp.gt.s32 o, %1, 1;\n"
      "selp.f32 x, %3, %2, p;\nselp.f32 y, %5, %4, p;\nselp.f32 %0, y, x, o;\n}\n" : "=f"(r) : "r"(q), "f"(a), "f"(b), "f"(c), "f"(d));
  return r;
}
__device__ __forceinline__ uint32_t bfma2(uint32_t a, uint32_t b, uint32_t c) { uint32_t r; asm("fma.rn.bf16x2 %0, %1, %2, %3;" : "=r"(r) : "r"(a), "r"(b), "r"(c)); return r; }
__device__ __forceinline__ void tma_load_5d(uint32_t dst, const CUtensorMap* tm, uint32_t bar, int c0, int c4) {
  asm volatile("cp.async.bulk.tensor.5d.shared::cluster.global.mbarrier::complete_tx::bytes [%0], [%1, {%3, %4, %4, %4, %5}], [%2];"
    :: "r"(dst), "l"(tm), "r"(bar), "r"(c0), "r"(0), "r"(c4) : "memory");
}
__device__ __forceinline__ void tma_load_5d_hint(uint32_t dst, const CUtensorMap* tm, uint32_t bar, int c0, int c4, uint64_t pol) {
  asm volatile("cp.async.bulk.tensor.5d.shared::cluster.global.mbarrier::complete_tx::bytes.L2::cache_hint [%0], [%1, {%3, %4, %4, %4, %5}], [%2], %6;"
    :: "r"(dst), "l"(tm), "r"(bar), "r"(c0), "r"(0), "r"(c4), "l"(pol) : "memory");
}
__device__ __forceinline__ void tma_prefetch_5d(const CUtensorMap* tm, int c0, int c4) {
  asm volatile("cp.async.bulk.prefetch.tensor.5d.L2.global.tile [%0, {%1, %2, %2, %2, %3}];" :: "l"(tm), "r"(c0), "r"(0), "r"(c4) : "memory");
}
__device__ __forceinline__ void tma_store_5d(const CUtensorMap* tm, uint32_t src, int c0, int c4) {
  asm volatile("cp.async.bulk.tensor.5d.global.shared::cta.bulk_group [%0, {%2, %3, %3, %3, %4}], [%1];" :: "l"(tm), "r"(src), "r"(c0), "r"(0), "r"(c4) : "memory");
}
__device__ __forceinline__ float rcp_fast(float x) { float r; asm("rcp.approx.ftz.f32 %0, %1;" : "=f"(r) : "f"(x)); return r; }
__device__ __forceinline__ float sigmoid_fast(float x) { float e; asm("ex2.approx.ftz.f32 %0, %1;" : "=f"(e) : "f"(x * -1.4426950408889634f)); return rcp_fast(1.f + e); }
__device__ __forceinline__ float sqrt_fast(float x) { float r; asm("sqrt.approx.ftz.f32 %0, %1;" : "=f"(r) : "f"(x)); return r; }
__device__ __forceinline__ float ln_sd(float var) { return bf16r(sqrt_fast(bf16r(bf16r(fmaxf(var, 0.f)) + 1e-5f))); }
__device__ __forceinline__ uint32_t norm2(uint32_t h, uint32_t neg_mean2, float inv_sd) {
  const uint32_t d = badd2(h, neg_mean2);
  return pack_bf16(bf_lo(d) * inv_sd, bf_hi(d) * inv_sd);
}
template<int N> __device__ __forceinline__ void delay_clk() {
  if constexpr (N > 0) { const uint32_t t0 = clock(); while ((uint32_t)clock() - t0 < N) {} }
}
__device__ __forceinline__ void put_xstat(uint32_t rs, uint32_t exb, int col, uint32_t mean_rstd, int m) {
  smem_at<uint16_t>(rs + ((col & 7) >> 1) * 144 + (col >> 3) * 4 + (col & 1) * 2) = (uint16_t)(mean_rstd ^ (m << 15));
  const uint32_t nm = (mean_rstd >> 16) ^ 0x8000u;
  smem_at<uint4>(exb + (col >> 3) * 256 + (col & 7) * 16) = make_uint4(nm | (nm << 16), nm, 0, 0);
  smem_at<uint4>(exb + (col >> 3) * 256 + 128 + (col & 7) * 16) = make_uint4(0, 0, 0, 0);
}
__device__ __forceinline__ void put_dsum(uint32_t exa, int e, float c) {
  const float hi = bf16r(c), mid = bf16r(c - hi), lo = bf16r((c - hi) - mid);
  smem_at<uint4>(exa + (e >> 3) * 256 + (e & 7) * 16) = make_uint4((__float_as_uint(hi) >> 16) | (__float_as_uint(mid) & 0xFFFF0000u), __float_as_uint(lo) >> 16, 0, 0);
  smem_at<uint4>(exa + (e >> 3) * 256 + 128 + (e & 7) * 16) = make_uint4(0, 0, 0, 0);
}
__host__ __device__ constexpr int min_c(int a, int b) { return a < b ? a : b; }
template<int V> using IC = std::integral_constant<int, V>;

#define CT(slot) do {} while (0)
#define PT(slot) do {} while (0)

template<int MAP>
__global__ void __cluster_dims__(2, 1, 1) __launch_bounds__(384, 1)
fnet_moe_kernel(const __grid_constant__ Params p) {
  constexpr int NX = MAP == 0 ? NX0 : 256;
  constexpr int G1_BYTES = A_BYTES + NX * 128;
  uint32_t sb;
  asm volatile("mov.u32 %0, %1;" : "=r"(sb) : "r"(smem_u32(smem_raw)));
  const int m = blockIdx.x & 1;
  int tau, eps;
  bool helper = false;
  if (MAP == 0) {
    uint32_t smid;
    asm volatile("mov.u32 %0, %%smid;" : "=r"(smid));
    const int c = smid >> 1, e7 = ((c - 32) * 37) >> 8;
    helper = c == 60 || c == 61;
    tau = c < 32 ? (c & 7) : (c < 60 ? c - 31 - 7 * e7 : 0);
    eps = c < 32 ? (c >> 3) : (c < 60 ? 4 + e7 : c - 58);
  } else {
    tau = (blockIdx.x >> 1) & 7; eps = blockIdx.x >> 4;
  }
  const int cid = tau * 16 + eps * 2 + m;
  const bool moe = tau > 0;
  auto BAR = [&](int i) { return sb + OFF_BAR + 8 * i; };
  const CUtensorMap* tmD = m ? &p.tmD1 : &p.tmD0;
  const uint64_t pol_ef = policy_evict_first();
#define LOAD_STREAM(d, tm, bar, c0, c1) tma_load_2d_hint(d, tm, bar, c0, c1, pol_ef)
#define LOAD_W(d, tm, bar, c0, grp) tma_load_5d_hint(d, tm, bar, c0, (grp) * 16, pol_ef)
  auto helper_load = [&](int k) {
    const uint32_t sa = sb + slot_of(k) * ST_BYTES, bar = BAR(B_FULL + slot_of(k));
    const CUtensorMap* tm = eps == 3 ? &p.tmD1 : &p.tmD0;
    tma_load_5d(sa, &p.tmXh, bar, (k & 15) * 64, 0);
    tma_load_2d(sa + A_BYTES, tm, bar, (k & 15) * 64, m * 512 + (k >> 4) * 256);
    tma_load_2d(sa + A_BYTES + 16384, tm, bar, (k & 15) * 64, m * 512 + (k >> 4) * 256 + 128);
  };
  if (threadIdx.x < 32 && elect_one()) {
    mbar_init(BAR(B_FULL), 1);
    asm volatile("fence.mbarrier_init.release.cluster;" ::: "memory");
    if (!helper) {
      tma_load_2d(sb + A_BYTES, &p.tmX, BAR(B_FULL), 0, tau * 256);
      tma_load_2d(sb, tmD, BAR(B_FULL), 0, eps * 128);
    }
    PT(52);
#pragma unroll
    for (int k = 1; k < 4; k++) mbar_init(BAR(B_FULL + k), 1);
    asm volatile("fence.mbarrier_init.release.cluster;" ::: "memory");
#pragma unroll
    for (int k = 0; k < 4; k++) mbar_expect_tx(BAR(B_FULL + k), helper ? ST_BYTES : G1_BYTES);
    if (!helper) {
#pragma unroll
      for (int k = 1; k < 4; k++) {
        tma_load_2d(sb + k * ST_BYTES + A_BYTES, &p.tmX, BAR(B_FULL + k), k * 64, tau * 256);
        LOAD_STREAM(sb + k * ST_BYTES, tmD, BAR(B_FULL + k), k * 64, eps * 128);
      }
    } else {
#pragma unroll 1
      for (int k = 0; k < 4; k++) helper_load(k);
    }
    PT(0);
  }
  __syncwarp();
  const int warp = __shfl_sync(0xffffffffu, threadIdx.x >> 5, 0);
  if (warp == 8) {
    if (elect_one()) {
#pragma unroll
      for (int b = B_EMPTY; b < B_COUNT; b++)
        mbar_init(BAR(b), b < B_EPI ? 2 : (b == B_EPI || b == B_EPI0B) ? 4 : (b < B_STD || b == B_OUT) ? 8 : (b == B_STAT || b == B_XS) ? 3 : 1);
      asm volatile("fence.mbarrier_init.release.cluster;" ::: "memory");
      mbar_expect_tx(BAR(B_XCH), 32768);
      SM_(uint32_t, OFF_SEEN) = 0;
    }
  }
  __syncthreads();

  if (warp >= 8) {
    reg_dec<REG_P>();
    asm volatile("barrier.cluster.arrive.relaxed.aligned;" ::: "memory");
    const int abrow = m * 1024 + eps * 128;
    const int f0 = (cid - 16) * 32;
    const CUtensorMap* tmWM = m ? &p.tmWM1 : &p.tmWM0;
    auto side_first = [&](int k) {
      if (NX < 256 && k == MINI_LOAD_K) {
        static_assert(NX == 256 || (mr_k(NREG_H) == MINI_LOAD_K && (NREG_H & 1) == 1), "second half of the staging buffer must be free");
        mbar_wait(BAR(B_STD + 3), 0);
        uint32_t n = 0;
        while (!((*(volatile uint32_t*)&SM_(uint32_t, OFF_SEEN) >> (4 * tau + 1)) & 1) && ++n < SPIN_LIMIT * 16) {}
        if (elect_one()) {
          mbar_expect_tx(BAR(B_A20), 12288);
          tma_load_2d(sb + OFF_MINI, &p.tmAbM, BAR(B_A20), tau * 256 + 240, abrow);
          LOAD_W(sb + OFF_MINI + 4096, tmWM, BAR(B_A20), tau * 256 + 240, tau * 2 + m);
          LOAD_W(sb + OFF_MINI + 8192, tmWM, BAR(B_A20), tau * 256 + 240, tau * 2 + 1 - m);
        }
      }
    };
    auto side = [&](int k) {
      if (NX < 256 && k == MINI_PF_K && elect_one()) tma_prefetch_5d(tmWM, tau * 256 + 240, tau * 32 + (eps & 1) * 16);
      if (!moe) return;
      const int i = k - MR_K0, r6 = i / MR_P, u = i - MR_P * r6, h = 2 * r6 + (u >> 1);
      if (i >= 0 && u < 4 && h < NREG_H) {
        if (h < 2) mbar_wait(BAR(B_STD + 2 + h), 0);
        if (elect_one()) {
          if (!(u & 1)) mbar_expect_tx(BAR(B_MR + (h & 1)), 16384);
          LOAD_STREAM(sb + OFF_XCH + u * 8192, (u & 1) ? &p.tmU : &p.tmG, BAR(B_MR + (h & 1)), f0, h * 128);
        }
      }
      if (k >= 46 && elect_one()) {
        static_assert(mr_k(NREG_H + 1) <= 47 && MINI_K + 4 <= 46, "staging buffer must be free");
        LOAD_STREAM(sb + round_off(NREG_H + k - 46), &p.tmG, BAR(B_GU), f0, (NREG_H + k - 46) * 128);
        LOAD_STREAM(sb + round_off(NREG_H + k - 46) + 8192, &p.tmU, BAR(B_GU), f0, (NREG_H + k - 46) * 128);
      }
      if (k >= PF_K1 && !(k & 1) && elect_one()) {
        const int j = PF_N0 + ((k - PF_K1) >> 1);
        if (j < 8) tma_prefetch_2d(m ? &p.tmU : &p.tmG, f0, j * 128);
        else if (j < 12) asm volatile("cp.async.bulk.prefetch.L2.global [%0], %1;" :: "l"(p.wdown + (size_t)f0 * 1024 + (j - 8) * 8192), "r"(16384) : "memory");
      }
    };
    if (MAP == 0 && helper) {
      if (warp == 8) {
#pragma unroll 1
        for (int k = 4; k < 32; k++) {
          mbar_wait(BAR(B_EMPTY + slot_of(k)), (use_of(k) & 1) ^ 1);
          if (elect_one()) { mbar_expect_tx(BAR(B_FULL + slot_of(k)), ST_BYTES); helper_load(k); }
        }
      } else {
        const int i0 = threadIdx.x - 288, lane = threadIdx.x & 31, col0 = (eps - 2) * 8 + m * 4;
        __nanosleep(HELPER_NS);
        const uint32_t tag = ld_relaxed32(&p.s->epoch) + 1;
        if (i0 < 8) pkt_st128(&p.s->hflag[col0 * 2 + i0], 0, 0, 0, 0);
        SM_(uint32_t, OFF_TAG) = tag;
#pragma unroll 1
        for (int j0 = i0; j0 < 768; j0 += 384) {
          uint2 v[4]; uint32_t n = 0;
          while (true) {
#pragma unroll
            for (int z = 0; z < 4; z++) {
              const int j = j0 + 96 * z;
              v[z] = pkt_ld64(p.s->xstat + (j < 128 ? 256 * (j >> 4) + 240 + 2 * (j & 6) + ((j >> 2) & 2) + (j & 1)
                                          : j < 640 ? 2048 + col0 * 128 + j - 128 : (j - 640) * 16));
            }
            if (__all_sync(0xffffffffu, v[0].y == tag && v[1].y == tag && v[2].y == tag && v[3].y == tag) || ++n > SPIN_LIMIT) break;
            __nanosleep(300);
          }
#pragma unroll
          for (int z = 0; z < 4; z++) {
            const int j = j0 + 96 * z;
            if (j < 128) put_xstat(sb + OFF_RS, sb + OFF_XCH + 16384, j, v[z].x, eps - 2);
            else if (j < 640) put_dsum(sb + OFF_XCH, j - 128, __uint_as_float(v[z].x));
          }
        }
        fence_async_smem();
        __syncwarp();
        if (lane == 0) mbar_arrive(BAR(B_STAT));
      }
    } else if (warp == 8) {
      const CUtensorMap* tmW = m ? &p.tmW1 : &p.tmW0;
      const int gA = tau * 2 + m, gB = tau * 2 + 1 - m;
      auto wait_slot = [&](int k) {
        mbar_wait(BAR(B_EMPTY + slot_of(k)), (use_of(k) & 1) ^ 1);
        PT(64 + k);
      };
#pragma unroll 1
      for (int k = 4; k < 24; k++) {
        const int s = slot_of(k);
        const uint32_t sa = sb + s * ST_BYTES, sbb = sa + A_BYTES;
        const int kb = kblock(tau, k - 16);
        wait_slot(k);
        if (elect_one()) {
          mbar_expect_tx(BAR(B_FULL + s), k < 16 ? G1_BYTES : (k >> 1) == 9 ? B_BYTES : k == 20 ? ST_BYTES - 8192 : ST_BYTES);
          if (k < 16) {
            LOAD_STREAM(sa, tmD, BAR(B_FULL + s), k * 64, eps * 128);
            tma_load_2d(sbb, &p.tmX, BAR(B_FULL + s), k * 64, tau * 256);
          } else {
            LOAD_W(sbb, tmW, BAR(B_FULL + s), kb * 64, gA);
            LOAD_W(sbb + 16384, tmW, BAR(B_FULL + s), kb * 64, gB);
            if (k < 18) {
              tma_load_5d(sa, &p.tmXr, BAR(B_FULL + s), eps * 128, gA * 16 + s * 8);
              tma_load_5d(sa + 8192, &p.tmXr, BAR(B_FULL + s), eps * 128 + 64, gA * 16 + s * 8);
            }
          }
          if (k == PUB_K1) mbar_arrive(BAR(B_LATE));
          if (k >= WPF_K0 && k < WPF_K0 + WPF_N && (eps >> 1) == ((k - WPF_K0) & 3))
            tma_prefetch_5d(tmW, kblock(tau, k - WPF_K0) * 64, tau * 32 + (eps & 1) * 16);
          if (moe && k >= PF_K0 && k < PF_K0 + 2 * PF_N0 && !(k & 1)) tma_prefetch_2d(m ? &p.tmU : &p.tmG, f0, (k - PF_K0) * 64);
        }
      }
      uint32_t seen = 0;
#pragma unroll 1
      for (int k = 24; k < 48; k++) {
        const int s = slot_of(k);
        const uint32_t sa = sb + s * ST_BYTES, sbb = sa + A_BYTES;
        const int kb = kblock(tau, k - 16);
        const uint32_t need = (1u << kb) | ((kb & 3) == 3 ? 2u << (4 * tau) : 0u);
        wait_slot(k);
        side_first(k);
        if (elect_one()) {
          mbar_expect_tx(BAR(B_FULL + s), ST_BYTES);
          LOAD_W(sbb, tmW, BAR(B_FULL + s), kb * 64, gA);
          LOAD_W(sbb + 16384, tmW, BAR(B_FULL + s), kb * 64, gB);
        }
        uint32_t n = 0;
        while ((seen & need) != need && ++n < SPIN_LIMIT * 16) seen = *(volatile uint32_t*)&SM_(uint32_t, OFF_SEEN);
        if (elect_one()) tma_load_2d(sa, &p.tmAbL, BAR(B_FULL + s), kb * 64, abrow);
        side(k);
      }
      if (moe) {
        mbar_wait(BAR(B_EMPTY + 0), 1);
        if (elect_one()) { mbar_expect_tx(BAR(B_GU), (8 - NREG_H) * 16384); mbar_expect_tx(BAR(B_DN), 65536); }
#pragma unroll 1
        for (int i = 0; i < 10 - NREG_H; i++) {
          if (i == 3) mbar_wait(BAR(B_EMPTY + 1), 1);
          if (i == 4) {
            mbar_wait(BAR(B_EMPTY + 2), 1);
            mbar_wait(BAR(B_XCH), 0);
            PT(53);
          }
          const uint32_t dst = sb + late_off(i);
          if (elect_one()) {
            if (i < 6 - NREG_H) {
              LOAD_STREAM(dst, &p.tmG, BAR(B_GU), f0, (NREG_H + 2 + i) * 128);
              LOAD_STREAM(dst + 8192, &p.tmU, BAR(B_GU), f0, (NREG_H + 2 + i) * 128);
            } else {
#pragma unroll
              for (int b = 0; b < 4; b++) LOAD_STREAM(dst + b * 4096, &p.tmDn, BAR(B_DN), (4 * (i - 6 + NREG_H) + b) * 64, f0);
            }
          }
          const long long t0 = clock64();
          while (i < 9 - NREG_H && clock64() - t0 < MOE_PACE_CLK) {}
        }
      }
      const int lane = threadIdx.x & 31;
      mbar_wait(BAR(B_OUT), 0);
      const uint32_t km = SM_(uint32_t, OFF_WKEY + (lane & 7) * 8);
      const uint32_t bk = __reduce_max_sync(0xffffffffu, km);
      const int ww = __ffs(__ballot_sync(0xffffffffu, km == bk)) - 1;
#pragma unroll 1
      for (int i = 1; i <= 8; i++) {
        const int W = (ww + i) & 7;
        if (i == 8) {
          mbar_wait(BAR(B_XS), 0);
          if (SM_(uint32_t, OFF_KV) == bk) {
#pragma unroll 2
            for (int j = lane; j < 256; j += 32) {
              const int rho = j >> 4, row = row_of(gA * 128 + 32 * (W >> 1) + 8 * ((rho & 7) >> 1) + 4 * (W & 1) + 2 * (rho >> 3) + (rho & 1));
              const uint4 v = lds128_v(sb + OFF_OUT + (j & 8) * 2048 + (16 * W + rho) * 128 + (((j ^ rho) & 7) << 4));
              if (row != 0xFFFF - (int)(bk & 0xFFFFu))
                asm volatile("st.global.v4.b32 [%0], {%1, %2, %3, %4};" :: "l"(p.out + (size_t)row * 1024 + eps * 128 + (j & 15) * 8), "r"(v.x), "r"(v.y), "r"(v.z), "r"(v.w));
            }
            break;
          }
        }
        if (lane == 0) {
          tma_store_5d(&p.tmOut, sb + OFF_OUT + W * 2048, eps * 128, row_of(gA * 128 + 32 * (W >> 1) + 4 * (W & 1)));
          tma_store_5d(&p.tmOut, sb + OFF_OUT + 16384 + W * 2048, eps * 128 + 64, row_of(gA * 128 + 32 * (W >> 1) + 4 * (W & 1)));
        }
        const long long t0 = clock64();
        while (i < 7 && clock64() - t0 < OUT_PACE_CLK) {}
      }
      if (lane == 0) { bulk_commit(); bulk_wait_all(); }
      PT(22);
    } else {
      const int a = warp - 9;
      const int lane = threadIdx.x & 31;
      auto stage = [&](const bf16* src, int g) {
        if (elect_one()) {
          mbar_expect_tx(BAR(B_AUX + g), 16384);
          bulk_load(sb + OFF_XCH + g * 16384, src + g * 8192, 16384, BAR(B_AUX + g));
        }
      };
      uint32_t tag = 0;
      mbar_wait(BAR(B_FULL + AUX_AFTER), 0);
      if (a == 0) PT(1);
      if (a == 1) mbar_wait(BAR(B_AUX + 0), 0);
      if (a < 2) stage(p.x + (size_t)cid * 16 * 1024, a);
#pragma unroll 1
      for (int it = 0; it < 4; it++) {
        const int g = it & 1;
        mbar_wait(BAR(B_AUX + g), it >> 1);
        if (a == 0) PT(2 + it);
        if (it == 2) tag = ld_relaxed32(&p.s->epoch) + 1;
        if (it == 2 && a == 2 && lane < 16) asm volatile("prefetch.global.L2 [%0];" :: "l"(p.wr + lane * 64));
        const uint32_t ad = sb + OFF_XCH + g * 16384 + (lane >> 2) * 2048;
        float s0 = 0.f, s1 = 0.f, q0 = 0.f, q1 = 0.f;
        auto row = [&](auto sq) {
#pragma unroll
          for (int i = 0; i < 11; i++) {
            if (i == 10 && a == 2) break;
            const uint4 v = lds128_v(ad + (((a * 44 + 4 * i + lane) & 127) << 4));
            const uint32_t ww[4] = {v.x, v.y, v.z, v.w};
#pragma unroll
            for (int z = 0; z < 4; z++) {
              const float d0 = bf_lo(ww[z]), d1 = bf_hi(ww[z]);
              s0 += d0; s1 += d1;
              if (decltype(sq)::value) { q0 = fmaf(d0, d0, q0); q1 = fmaf(d1, d1, q1); }
            }
          }
        };
        if (it < 2) row(IC<1>()); else row(IC<0>());
        s0 += s1; q0 += q1;
#pragma unroll
        for (int o = 1; o < 4; o <<= 1) { s0 += __shfl_xor_sync(0xffffffffu, s0, o); q0 += __shfl_xor_sync(0xffffffffu, q0, o); }
        if ((lane & 3) == 0) SM_(float2, OFF_PUB + a * 256 + it * 64 + (lane >> 2) * 8) = make_float2(s0, q0);
        if (it != 2) bar_sync(NB_AUX, 96);
        if (it < 2 && a == 2) stage(cid < 64 ? p.Dre + (size_t)cid * 16 * 1024 : p.Dim + (size_t)(cid - 64) * 16 * 1024, g);
      }
      if (a == 1) {
        const float2 v0 = SM_(float2, OFF_PUB + lane * 8), v1 = SM_(float2, OFF_PUB + 256 + lane * 8), v2 = SM_(float2, OFF_PUB + 512 + lane * 8);
        const float s = v0.x + v1.x + v2.x, mean = s * (1.f / 1024.f);
        const float rs = rcp_fast(ln_sd((v0.y + v1.y + v2.y) * (1.f / 1024.f) - mean * mean));
        pkt_st64((lane < 16 ? p.s->xstat : p.s->dsum) + cid * 16 + (lane & 15), lane < 16 ? pack_bf16(rs, mean) : __float_as_uint(s), tag);
        PT(6);
      }
      if (a == 2) {
        float s = 0.f;
#pragma unroll
        for (int q = 0; q < 4; q++) {
          const uint4 v = ldg_nc128(p.wr + (q * 32 + lane) * 8);
          s += ((bf_lo(v.x) + bf_hi(v.x)) + (bf_lo(v.y) + bf_hi(v.y))) + ((bf_lo(v.z) + bf_hi(v.z)) + (bf_lo(v.w) + bf_hi(v.w)));
          const int ch = q * 32 + lane - eps * 16;
          if (ch >= 0 && ch < 16) {
            SM_(uint32_t, OFF_WR + ch * 4) = v.x; SM_(uint32_t, OFF_WR + 80 + ch * 4) = v.y;
            SM_(uint32_t, OFF_WR + 160 + ch * 4) = v.z; SM_(uint32_t, OFF_WR + 240 + ch * 4) = v.w;
          }
        }
        s = warp_sum(s);
        if (lane == 0) { SM_(float, OFF_WSUM) = s; SM_(uint32_t, OFF_TAG) = tag; }
      }
      if (a < 2) __nanosleep(GATHER_NS);
      {
        const int i0 = a * 32 + lane;
        uint2 v[3], c0, c1; uint32_t n = 0;
        const uint2* dp = &p.s->dsum[abrow];
        while (true) {
#pragma unroll
          for (int q = 0; q < 3; q++) v[q] = pkt_ld64(&p.s->xstat[tau * 256 + min(i0 + 96 * q, 255)]);
          c0 = pkt_ld64(dp + i0); c1 = pkt_ld64(dp + min(i0 + 96, 127));
          if (__all_sync(0xffffffffu, v[0].y == tag && v[1].y == tag && v[2].y == tag && c0.y == tag && c1.y == tag) || ++n > SPIN_LIMIT) break;
          __nanosleep(200);
        }
#pragma unroll
        for (int q = 0; q < 3; q++) put_xstat(sb + OFF_RS, sb + OFF_EXB, min(i0 + 96 * q, 255), v[q].x, m);
        put_dsum(sb + OFF_EXA, i0, __uint_as_float(c0.x));
        put_dsum(sb + OFF_EXA, min(i0 + 96, 127), __uint_as_float(c1.x));
        fence_async_smem();
      }
      __syncwarp();
      if (lane == 0) mbar_arrive(BAR(B_STAT));
      if (a == 0) PT(7);
      if (a == 0) {
        const int sg = (lane >> 2) == tau ? sigma_of(tau, 0) : lane >> 2;
        const uint32_t* flg = reinterpret_cast<const uint32_t*>(&p.s->abflag[((eps * 2 + m) * 8 + sg) * 2]) + ((lane >> 2) == tau ? 4 : lane & 3);
        if (NX < 256 && lane == 4 * tau + 1) flg = reinterpret_cast<const uint32_t*>(&p.s->hflag[(m * 8 + eps) * 2]);
        uint32_t seen = 0;
        auto until = [&](int tile) {
          uint32_t n = 0;
          while (!((seen >> (4 * tile)) & 1) && ++n < SPIN_LIMIT) seen = __ballot_sync(0xffffffffu, ld_relaxed32(flg) == tag);
        };
        const int s0 = sigma_of(tau, 0), s1 = sigma_of(tau, 1), s2 = sigma_of(tau, 2), s3 = sigma_of(tau, 3);
        mbar_wait(BAR(B_EPI), 0);
        mbar_wait(BAR(B_FULL + 0), 0);
        mbar_wait(BAR(B_FULL + 1), 0);
        if (elect_one()) mbar_expect_tx(BAR(B_A20), 8192);
        mbar_wait(BAR(B_STDA), 0);
        PT(49);
        until(tau);
        mbar_wait(BAR(B_EPI0B), 0);
        PT(48);
        if (elect_one()) tma_load_2d(sb + OFF_XCH, &p.tmAbS, BAR(B_FULL + 0), s0 * 256, abrow);
        mbar_wait(BAR(B_FULL + 2), 0);
        mbar_wait(BAR(B_STD + 0), 0);
        until(s0);
        PT(16);
        if (elect_one()) tma_load_2d(sb + OFF_XCH + 8192, &p.tmAbS, BAR(B_A20), s0 * 256, abrow + 64);
        until(s1);
        PT(17);
        if (elect_one()) tma_load_2d(sb + OFF_XCH + 16384, &p.tmAbL, BAR(B_FULL + 1), s1 * 256, abrow);
        until(s2);
        PT(18);
        if (elect_one()) {
          tma_load_2d(sb + 2 * ST_BYTES, &p.tmAbL, BAR(B_FULL + 2), s2 * 256, abrow);
          mbar_arrive(BAR(B_PUB1));
        }
        until(s3);
        mbar_wait(BAR(B_FULL + 3), 0);
        mbar_wait(BAR(B_STD + 1), 0);
        PT(19);
        if (elect_one()) tma_load_2d(sb + 3 * ST_BYTES, &p.tmAbL, BAR(B_FULL + 3), s3 * 256, abrow);
        uint32_t n = 0;
        while (true) {
          asm volatile("fence.proxy.async.global;" ::: "memory");
          *(volatile uint32_t*)&SM_(uint32_t, OFF_SEEN) = seen;
          if (seen == 0xFFFFFFFFu || ++n > SPIN_LIMIT) break;
          seen = __ballot_sync(0xffffffffu, ld_relaxed32(flg) == tag);
          __nanosleep(100);
        }
      } else {
        uint32_t* flag = reinterpret_cast<uint32_t*>(&p.s->abflag[((eps * 2 + m) * 8 + tau) * 2]);
        mbar_wait(BAR(a == 1 ? B_EPI : B_EPI0B), 0);
        if (a == 1) PT(8);
        if (lane == 0) {
          tma_store_2d(&p.tmAbS, sb + chunk_off(0, a - 1), tau * 256, abrow + (a - 1) * 64);
          bulk_commit();
          bulk_wait_all();
        }
        if (a == 2) mbar_wait(BAR(B_STDA), 0);
        if (lane == 0) {
          st_relaxed32(flag + (a == 1 ? 4 : 0), tag);
          mbar_arrive(BAR(a == 1 ? B_STDA : B_STD));
        }
        if (a == 2) PT(12);
        if (a == 1) {
          mbar_wait(BAR(B_EPI + 1), 0);
          mbar_wait(BAR(B_LATE), 0);
          mbar_wait(BAR(B_PUB1), 0);
          PT(9);
          if (lane == 0) {
            tma_store_2d(&p.tmAbS, sb + chunk_off(1, 0), tau * 256 + 64, abrow);
            tma_store_2d(&p.tmAbS, sb + chunk_off(1, 1), tau * 256 + 64, abrow + 64);
            bulk_commit();
            bulk_wait_all();
            st_relaxed32(flag + 1, tag);
            mbar_arrive(BAR(B_STD + 1));
          }
          PT(13);
        }
        auto copy_out = [&](int c) {
          mbar_wait(BAR(B_EPI + c), 0);
          PT(8 + c);
          bf16* dst = p.s->abT + (size_t)(abrow + (lane >> 3)) * 2048 + tau * 256 + c * 64 + (lane & 7) * 8;
          const uint32_t src = sb + chunk_off(c, 0) + (lane >> 3) * 128 + (((lane & 7) ^ (lane >> 3)) << 4);
          const uint32_t on = c * 64 + (lane & 7) * 8 < NX;
#pragma unroll 4
          for (int i = 0; i < 32; i++) {
            const uint4 v = lds128_v((src ^ ((i & 1) << 6)) + i * 512);
            asm volatile("{\n.reg .pred p;\nsetp.ne.b32 p, %5, 0;\n@p st.global.v4.b32 [%0], {%1, %2, %3, %4};\n}\n"
                         :: "l"(dst + i * 4 * 2048), "r"(v.x), "r"(v.y), "r"(v.z), "r"(v.w), "r"(on));
          }
          __syncwarp();
          if (lane == 0) mbar_arrive(BAR(B_STD + c));
        };
        if (a == 2) {
#pragma unroll 1
          for (int c = 2; c < 4; c++) copy_out(c);
          asm volatile("fence.acq_rel.gpu;" ::: "memory");
          __syncwarp();
          if (lane < 2) st_relaxed32(flag + 2 + lane, tag);
          PT(15);
        }
      }
      {
        mbar_wait(BAR(B_LATE), 1);
        const int grp = tau * 2 + m;
#pragma unroll 1
        for (int i = a; i < 14; i += 3) {
          uint4* dst = i < 8 ? &p.s->ypart[cid * 256 + i * 32 + lane] : i < 12 ? &p.s->hstat[(grp * 8 + eps) * 128 + (i - 8) * 32 + lane]
                     : i == 12 ? &p.s->cand[grp * 256 + eps * 32 + lane] : &p.s->key[(((lane >> 1) & 7) * 16 + grp) * 2 + (lane & 1)];
          if (i < 13 || eps == 0) pkt_st128(dst, 0, 0, 0, 0);
          __nanosleep(200);
        }
        __syncwarp();
        if (lane == 0) mbar_arrive(BAR(B_STAT));
      }
      {
        const uint4* kp = &p.s->key[(tau * 16 + (lane & 15)) * 2];
        const int i0 = a * 32 + lane;
        mbar_wait(BAR(B_KEY), 0);
        if (a == 0) PT(43);
        uint4 kq = pkt_ld128(kp), cv[3] = {};
        uint32_t n = 0, kv;
        int gspec = -1;
        while (true) {
          const bool ok = kq.y == tag && kq.w == tag;
          kv = __reduce_max_sync(0xffffffffu, ok ? kq.x : 0u);
          const int gs = group_of(0xFFFF - (int)(kv & 0xFFFFu));
          const bool cok = gs == gspec && cv[0].y == tag && cv[0].w == tag && cv[1].y == tag && cv[1].w == tag && cv[2].y == tag && cv[2].w == tag;
          if (__all_sync(0xffffffffu, ok && cok) || ++n > SPIN_LIMIT) break;
          if (!ok) kq = pkt_ld128(kp);
          const bool spec = __popc(__ballot_sync(0xffffffffu, ok)) >= 2 * SPEC_MIN;
          if (!cok && spec) {
#pragma unroll
            for (int i = 0; i < 3; i++) cv[i] = pkt_ld128(&p.s->cand[gs * 256 + min(i0 + 96 * i, 255)]);
          }
          if (spec) gspec = gs;
        }
        if (a == 0) PT(45);
        const uint32_t ms = __shfl_sync(0xffffffffu, kq.z, gspec);
        const uint32_t nm = ((ms & 0xFFFFu) ^ 0x8000u) * 0x10001u;
        const float is = rcp_fast(bf_hi(ms));
#pragma unroll
        for (int i = 0; i < 3; i++) {
          const int j = min(i0 + 96 * i, 255);
          SM_(uint2, OFF_XSEL + j * 8) = make_uint2(norm2(cv[i].x, nm, is), norm2(cv[i].z, nm, is));
        }
#pragma unroll
        for (int i = 0; i < 3; i++) SM_(uint2, OFF_HSEL + min(i0 + 96 * i, 255) * 8) = make_uint2(cv[i].x, cv[i].z);
        SM_(uint32_t, OFF_KV) = kv;
        __syncwarp();
        if (lane == 0) mbar_arrive(BAR(B_XS));
      }
    }
    asm volatile("barrier.cluster.wait.aligned;" ::: "memory");
  } else {
    reg_inc<REG_C>();
    const int tid = __shfl_sync(0xffffffffu, threadIdx.x, threadIdx.x & 31), lane = tid & 31;
    const int w = warp >> 2, wi = warp & 3, t = tid & 127;
    const int g = lane >> 2, q = lane & 3;
    const int turn_me = NB_TURN0 + w, turn_other = NB_TURN1 - w;
    auto release = [&](int s) { if (t == 0) mbar_arrive(BAR(B_EMPTY + s)); };
    if (MAP == 0 && helper) {
      asm volatile("barrier.cluster.arrive.relaxed.aligned;" ::: "memory");
      float s0[64], s1[64];
#pragma unroll
      for (int i = 0; i < 64; i++) { s0[i] = 0.f; s1[i] = 0.f; }
      if (w == 1) bar_arrive(NB_TURN0, 256);
      uint32_t o[32][2] = {};
      const int col = (eps - 2) * 8 + m * 4 + w;
      auto put = [&](auto tc, uint32_t buf) {
        constexpr int tl = decltype(tc)::value;
#pragma unroll
        for (int i = 0; i < 4; i++)
          smem_at<uint2>(buf + ((i >> 1) * 64 + wi * 16 + (i & 1) * 8 + g) * 32 + ((q * 8) ^ ((g & 4) << 2))) = make_uint2(o[8 * i + tl][0], o[8 * i + tl][1]);
      };
      auto publish = [&](int c) { if (t == 0) { bulk_wait_all(); st_relaxed32(&p.s->hflag[c * 2], SM_(uint32_t, OFF_TAG)); } };
#pragma unroll 1
      for (int pass = 0; pass < 2; pass++) {
#pragma unroll 1
        for (int k = 16 * pass; k < 16 * pass + 16; k++) {
          const int s = slot_of(k);
          mbar_wait(BAR(B_FULL + s), use_of(k) & 1);
          bar_sync(turn_me, 256);
          const uint64_t da = make_desc(sb + s * ST_BYTES + A_BYTES + w * 16384), db = make_desc(sb + s * ST_BYTES);
          wgmma_fence();
#pragma unroll
          for (int kk = 0; kk < 4; kk++) {
            wgmma_n128(s0, da + kk * 2, db + kk * 2, kk > 0 || (k & 15));
            wgmma_n128(s1, da + 512 + kk * 2, db + kk * 2, kk > 0 || (k & 15));
          }
          wgmma_commit();
          if (k < 31 || w == 0) bar_arrive(turn_other, 256);
          if (pass && !(k & 1)) {
            const uint32_t buf = sb + OFF_XCH + 20480 + w * 4096;
            static_for<8>([&](auto ic) { if (k == 16 + 2 * decltype(ic)::value) put(ic, buf); });
            fence_async_smem();
            bar_sync(NB_WG0 + w, 128);
            if (t == 0) { tma_store_2d(&p.tmAbM, buf, (k - 16) * 128 + 240, col * 128); bulk_commit(); }
          }
          wgmma_wait0();
          release(s);
          if ((k & 1) && t == 0) asm volatile("cp.async.bulk.wait_group.read 0;" ::: "memory");
        }
        if (pass) publish(col);
        mbar_wait(BAR(B_STAT), 0);
        wgmma_fence();
        wgmma_n128(s0, make_desc_noswz(sb + OFF_XCH + pass * 8192 + w * 4096), make_desc_noswz(sb + OFF_XCH + 16384));
        wgmma_n128(s1, make_desc_noswz(sb + OFF_XCH + pass * 8192 + w * 4096 + 2048), make_desc_noswz(sb + OFF_XCH + 16384));
        wgmma_commit();
        uint4 rs[4];
#pragma unroll
        for (int i = 0; i < 4; i++) rs[i] = lds128_v(sb + OFF_RS + q * 144 + i * 16);
        wgmma_wait0();
        fence_acc(s0); fence_acc(s1);
#pragma unroll
        for (int i = 0; i < 32; i++) {
          const int tl = i & 7, hr = (i >> 3) & 1;
          const float* ac = (i >> 4) ? &s1[8 * tl + 2 * hr] : &s0[8 * tl + 2 * hr];
          o[i][0] = bmul2(pack_bf16(ac[0], ac[1]), (tl & 1) ? rs[tl >> 1].z : rs[tl >> 1].x);
          o[i][1] = bmul2(pack_bf16(ac[4], ac[5]), (tl & 1) ? rs[tl >> 1].w : rs[tl >> 1].y);
        }
      }
      static_for<8>([&](auto ic) { put(ic, sb + (w * 8 + decltype(ic)::value) * 4096); });
      fence_async_smem();
      bar_sync(NB_WG0 + w, 128);
      if (t == 0) {
#pragma unroll 1
        for (int i = 0; i < 8; i++) tma_store_2d(&p.tmAbM, sb + (w * 8 + i) * 4096, i * 256 + 240, (col + 2) * 128);
        bulk_commit();
      }
      publish(col + 2);
      asm volatile("barrier.cluster.wait.aligned;" ::: "memory");
      return;
    }
    float acc[128], a1[NX / 2];
#pragma unroll
    for (int i = 0; i < NX / 2; i++) a1[i] = 0.f;
    if (w == 1) bar_arrive(NB_TURN0, 256);
    auto kstep = [&](auto& d, int k, bool first, bool a_in_xch = false, bool mini = false) {
      const int s = slot_of(k);
      mbar_wait(BAR(B_FULL + s), use_of(k) & 1);
      CT(64 + k);
      bar_sync(turn_me, 256);
      const uint64_t da = make_desc(sb + (a_in_xch ? OFF_XCH + s * 16384 : s * ST_BYTES) + w * 8192), db = make_desc(sb + s * ST_BYTES + A_BYTES);
      wgmma_fence();
      wgmma_g1(d, da, db, !first);
#pragma unroll
      for (int kk = 1; kk < 4; kk++) wgmma_g1(d, da + kk * 2, db + kk * 2, 1);
      wgmma_commit();
      if (mini) {
        CT(29);
        mbar_wait(BAR(B_A20), 1);
        CT(30);
        wgmma_fence();
        wgmma_g1(d, make_desc_32b(sb + OFF_MINI + w * 2048), make_desc_32b(sb + OFF_MINI + 4096), 1);
        wgmma_commit();
      }
      bar_arrive(turn_other, 256);
    };
    auto kdone = [&](int k) { wgmma_wait0(); release(slot_of(k)); };
    auto wgmma_wait1 = [&]() { asm volatile("wgmma.wait_group.sync.aligned 1;" ::: "memory"); };

#pragma unroll 1
    for (int k = 0; k < 14; k++) {
      kstep(a1, k, k == 0);
      if (k == 0) CT(0);
      if (k == 8 && warp == 2 && lane < 2) pkt_st128(&p.s->abflag[((eps * 2 + m) * 8 + tau) * 2 + lane], 0, 0, 0, 0);
      kdone(k);
    }
    uint32_t R[64];
    uint32_t tag;
    {
      const uint32_t rsa = sb + OFF_RS + q * 144;
      const uint64_t da2 = make_desc(sb + 2 * ST_BYTES + w * 8192), db2 = make_desc(sb + 2 * ST_BYTES + A_BYTES);
      const uint64_t da3 = make_desc(sb + 3 * ST_BYTES + w * 8192), db3 = make_desc(sb + 3 * ST_BYTES + A_BYTES);
      mbar_wait(BAR(B_FULL + 2), 1);
      CT(64 + 14);
      bar_sync(turn_me, 256);
      wgmma_fence();
#pragma unroll
      for (int kk = 0; kk < 4; kk++) wgmma_g1(a1, da2 + kk * 2, db2 + kk * 2, 1);
      wgmma_commit();
      mbar_wait(BAR(B_FULL + 3), 1);
      CT(64 + 15);
      wgmma_fence();
      wgmma_g1(a1, da3, db3, 1);
      wgmma_g1(a1, da3 + 2, db3 + 2, 1);
      wgmma_commit();
      mbar_wait(BAR(B_STAT), 0);
      tag = SM_(uint32_t, OFF_TAG);
#pragma unroll
      for (int i = 0; i < 8; i++) { const uint4 v = lds128_v(rsa + i * 16); R[8 * i] = v.x; R[8 * i + 2] = v.y; R[8 * i + 4] = v.z; R[8 * i + 6] = v.w; }
      wgmma_wait1();
      release(2);
      wgmma_fence();
      wgmma_g1(a1, da3 + 4, db3 + 4, 1);
      wgmma_g1(a1, da3 + 6, db3 + 6, 1);
      wgmma_g1(a1, make_desc_noswz(sb + OFF_EXA + w * 2048), make_desc_noswz(sb + OFF_EXB), 1);
      wgmma_commit();
      bar_arrive(turn_other, 256);
      kdone(15);
      mbar_wait(BAR(B_STAT), 0);
    }
    fence_acc(a1);
    CT(1);
    auto pack = [&](auto cc) {
      constexpr int c = decltype(cc)::value;
#pragma unroll
      for (int j = 8 * c; j < min_c(8 * c + 8, NX / 8); j++) {
        const uint32_t rs = R[2 * j];
        const float* ac = &a1[4 * j];
        R[2 * j] = bmul2(pack_bf16(ac[0], ac[1]), rs);
        R[2 * j + 1] = bmul2(pack_bf16(ac[2], ac[3]), rs);
      }
    };
    auto put_chunk = [&](auto cc) {
      constexpr int c = decltype(cc)::value;
      const int rho = 16 * wi + (lane & 15);
#pragma unroll
      for (int j = 8 * c; j < min_c(8 * c + 8, NX / 8); j += 2) {
        const int chunk = (j & 7) + (lane >> 4);
        stsm_x4(sb + chunk_off(c, w) + rho * 128 + ((chunk ^ (lane & 7)) << 4), R[2 * j], R[2 * j + 1], R[2 * j + 2], R[2 * j + 3]);
      }
    };
    auto staged = [&](int bar) {
      fence_async_smem();
      __syncwarp();
      if (lane == 0) mbar_arrive(BAR(bar));
    };
    auto mma_rs = [&](auto cc, auto k0, auto k1) {
      constexpr int c = decltype(cc)::value;
      const uint64_t db = make_desc(sb + c * ST_BYTES + A_BYTES);
#pragma unroll
      for (int kk = decltype(k0)::value; kk < decltype(k1)::value; kk++)
        wgmma_n256_rs(acc, R[16 * c + 4 * kk], R[16 * c + 4 * kk + 1], R[16 * c + 4 * kk + 2], R[16 * c + 4 * kk + 3], db + kk * 2, c + kk > 0);
      wgmma_commit();
    };
    auto kdone_x = [&](int k, auto ic) {
      constexpr int i = decltype(ic)::value;
      uint32_t r[8];
#pragma unroll
      for (int z = 0; z < 2; z++) {
        const int tr = 32 * (i & 1) + 16 * z + 8 * (lane >> 4) + (lane & 7), chunk = 2 * wi + ((lane >> 3) & 1);
        ldsm_x4_t(sb + (i >> 1) * ST_BYTES + w * 8192 + tr * 128 + ((chunk ^ (lane & 7)) << 4), r[4 * z], r[4 * z + 1], r[4 * z + 2], r[4 * z + 3]);
      }
      float f[16];
#pragma unroll
      for (int z = 0; z < 8; z++) { f[2 * z] = bf_lo(r[z]); f[2 * z + 1] = bf_hi(r[z]); }
#pragma unroll
      for (int z = 0; z < 16; z++) asm volatile("" : "+f"(f[z]));
      kdone(k);
#pragma unroll
      for (int z = 0; z < 16; z++) asm volatile("add.f32 %0, %0, %1;" : "+f"(acc[16 * i + z]) : "f"(f[z]));
    };
    pack(IC<0>());
    put_chunk(IC<0>());
    staged(w ? B_EPI0B : B_EPI);
    mbar_wait(BAR(B_STAT), 0);
    CT(21);
    pack(IC<1>());
    pack(IC<2>());
    pack(IC<3>());
#pragma unroll
    for (int i = 16; i < NX / 4; i++) asm volatile("" : "+r"(R[i]));
#pragma unroll
    for (int i = 0; i < 128; i++) asm volatile("" : "=f"(acc[i]));
    mbar_wait(BAR(B_FULL + 0), 0);
    CT(2);
    CT(64 + 16);
    bar_sync(turn_me, 256);
    wgmma_fence();
    mma_rs(IC<0>(), IC<0>(), IC<4>());
    mbar_wait(BAR(B_FULL + 1), 0);
    CT(64 + 17);
    wgmma_fence();
    mma_rs(IC<1>(), IC<0>(), IC<2>());
    wgmma_wait1();
    release(0);
    mma_rs(IC<1>(), IC<2>(), IC<4>());
    bar_arrive(turn_other, 256);
    kdone_x(17, IC<0>());
    static_for<2>([&](auto ic) {
      constexpr int c = 2 + decltype(ic)::value;
      mbar_wait(BAR(B_FULL + c), 0);
      CT(64 + 16 + c);
      bar_sync(turn_me, 256);
      wgmma_fence();
      mma_rs(IC<c>(), IC<0>(), IC<min_c(4, NX / 16 - 4 * c)>());
      bar_arrive(turn_other, 256);
      if (c == 2) { put_chunk(IC<1>()); staged(B_EPI + 1); }
      kdone_x(16 + c, IC<c - 1>());
    });
#pragma unroll 1
    for (int k = 20; k < 23; k++) {
      if (w == 1) mbar_wait(BAR(B_A20), 0);
      kstep(acc, k, false, k < 22);
      if (k == 20) {
        kdone_x(k, IC<3>());
      } else {
        if (k == 21) put_chunk(IC<2>()); else put_chunk(IC<3>());
        __syncwarp();
        if (lane == 0) mbar_arrive(BAR(B_EPI + k - 19));
        kdone(k);
      }
    }
    uint32_t wf[32][4];
    auto load_wf = [&](auto hc) {
      constexpr int h = decltype(hc)::value;
      const int d = w * 64 + (lane >> 4) * 8 + (lane & 7);
      const uint32_t ad = sb + round_off(h) + (lane & 8) * 1024 + d * 64 + ((wi ^ ((lane >> 1) & 3)) << 4);
#pragma unroll
      for (int i = 0; i < 4; i++) ldsm_x4_t(ad + i * 1024, wf[4 * h + i][0], wf[4 * h + i][1], wf[4 * h + i][2], wf[4 * h + i][3]);
    };
    auto load_wf_rest = [&]() { static_for<8 - NREG_H>([&](auto ic) { load_wf(IC<NREG_H + decltype(ic)::value>()); }); };
#pragma unroll
    for (int i = 0; i < 4 * NREG_H; i++) { wf[i][0] = 0; wf[i][1] = 0; wf[i][2] = 0; wf[i][3] = 0; }
    const int grp = tau * 2 + m;
#pragma unroll 1
    for (int k = 23; k < 46; k++) {
      kstep(acc, k, false, false, NX < 256 && k == MINI_K);
      if (moe) {
        static_for<NREG_H>([&](auto hc) {
          constexpr int h = decltype(hc)::value;
          if (k == mr_k(h) + 1) { mbar_wait(BAR(B_MR + (h & 1)), (h >> 1) & 1); CT(32 + h); load_wf(hc); }
        });
      }
      if (k == RESET_K && tid == 0) mbar_arrive(BAR(B_LATE));
      kdone(k);
    }
    asm volatile("barrier.cluster.arrive.relaxed.aligned;" ::: "memory");
    mbar_wait(BAR(B_STAT), 1);
    uint32_t wa[16][2];
    uint32_t cd = code_of(tag);
    uint4* hp_pub = &p.s->hstat[(grp * 8 + eps) * 128 + warp * 16 + g];
    const uint4* hp_poll = &p.s->hstat[(grp * 8 + 2 * q) * 128 + warp * 16 + g];
    const uint32_t vec_off = (2 * wi) * 512 + q * 128 + ((g ^ (2 * q)) << 4);
    {
      float as[64], ak[64];
      fence_acc(acc);
#pragma unroll
      for (int i = 0; i < 64; i++) asm volatile("mov.b32 %0, %1;" : "=f"(as[i]) : "f"(acc[64 + i]));
#pragma unroll
      for (int i = 0; i < 64; i++) asm volatile("mov.b32 %0, %1;" : "=f"(ak[i]) : "f"(acc[i]));
      const uint64_t da1 = make_desc(sb + 2 * ST_BYTES + w * 8192), db1 = make_desc(sb + 2 * ST_BYTES + A_BYTES);
      const uint64_t da2 = make_desc(sb + 3 * ST_BYTES + w * 8192), db2 = make_desc(sb + 3 * ST_BYTES + A_BYTES);
      mbar_wait(BAR(B_FULL + 2), 1);
      CT(64 + 46);
      mbar_wait(BAR(B_FULL + 3), 1);
      CT(64 + 47);
      bar_sync(turn_me, 256);
      wgmma_fence();
#pragma unroll
      for (int kk = 0; kk < 4; kk++) wgmma_n128(as, da1 + kk * 2, db1 + 1024 + kk * 2);
#pragma unroll
      for (int kk = 0; kk < 4; kk++) wgmma_n128(as, da2 + kk * 2, db2 + 1024 + kk * 2);
      wgmma_commit();
      bar_arrive(turn_other, 256);
      const uint32_t rx = mapa(sb + OFF_PEER + w * 4096 + vec_off, 1 - m), rb = mapa(BAR(B_XCH), 1 - m);
      asm volatile("barrier.cluster.wait.aligned;" ::: "memory");
      CT(24);
      wgmma_wait0();
      fence_acc(as);
      CT(25);
      auto keep = [&]() {
        bar_sync(turn_me, 256);
        wgmma_fence();
#pragma unroll
        for (int kk = 0; kk < 4; kk++) wgmma_n128(ak, da1 + kk * 2, db1 + kk * 2);
        wgmma_commit();
#pragma unroll
        for (int kk = 0; kk < 4; kk++) wgmma_n128(ak, da2 + kk * 2, db2 + kk * 2);
        wgmma_commit();
        if (w == 0) bar_arrive(turn_other, 256);
      };
#pragma unroll
      for (int i = 0; i < 8; i++) {
        if (i == SEND_FIRST) keep();
        const float* ac = &as[16 * (i >> 1) + 2 * (i & 1)];
        st_async_v4(rx + (i >> 1) * 8192 + (i & 1) * 512, rb, pack_bf16(ac[0], ac[1]), pack_bf16(ac[4], ac[5]), pack_bf16(ac[8], ac[9]), pack_bf16(ac[12], ac[13]));
      }
      CT(26);
#pragma unroll
      for (int i = 0; i < 4; i++) {
        const uint4 v = lds128_v(sb + OFF_WR + q * 80 + i * 16);
        const uint32_t vv[4] = {v.x, v.y, v.z, v.w};
#pragma unroll
        for (int z = 0; z < 4; z++) {
          asm volatile("{\n.reg .pred p;\nsetp.ne.b32 p, %2, 0;\nselp.b32 %0, %1, 0x3F803F80, p;\n}" : "=r"(wa[4 * i + z][0]) : "r"(vv[z]), "r"(g & 1));
          asm volatile("{\n.reg .pred p;\nsetp.ne.b32 p, %2, 0;\nselp.b32 %0, %1, 0x3F803F80, p;\n}" : "=r"(wa[4 * i + z][1]) : "r"(vv[z]), "r"(g & 1));
        }
      }
      pin(cd); pin(hp_pub); pin(hp_poll);
      CT(27);
      wgmma_wait1();
      release(2);
      wgmma_wait0();
      fence_acc(ak);
      CT(3);
#pragma unroll
      for (int i = 0; i < 8; i++) {
        const float* ac = &ak[16 * (i >> 1) + 2 * (i & 1)];
        sts128(sb + (2 + (i >> 2)) * ST_BYTES + w * 8192 + ((i >> 1) & 1) * 4096 + (i & 1) * 512 + vec_off,
               pack_bf16(ac[0], ac[1]), pack_bf16(ac[4], ac[5]), pack_bf16(ac[8], ac[9]), pack_bf16(ac[12], ac[13]));
      }
    }
    uint32_t h[8][4];
    {
      const int qq = 2 * (warp & 1) + ((lane >> 3) & 1);
      const uint32_t lo = (lane >> 4) * 512 + qq * 128 + (((lane & 7) ^ (2 * qq)) << 4);
      bar_sync(NB_BOTH, 256);
#pragma unroll
      for (int ks = 0; ks < 8; ks++)
        ldsm_x4_t(sb + (2 + w) * ST_BYTES + (ks >> 2) * 8192 + (wi >> 1) * 4096 + (ks & 3) * 1024 + lo, h[ks][0], h[ks][1], h[ks][2], h[ks][3]);
      CT(28);
      mbar_wait_cluster(BAR(B_XCH), 0);
      CT(4);
      uint32_t r[8][4];
#pragma unroll
      for (int ks = 0; ks < 8; ks++) ldsm_x4_t(sb + OFF_PEER + (warp >> 1) * 8192 + ks * 1024 + lo, r[ks][0], r[ks][1], r[ks][2], r[ks][3]);
      float d[4][4] = {};
#pragma unroll
      for (int ks = 0; ks < 8; ks++) {
#pragma unroll
        for (int i = 0; i < 4; i++) {
          h[ks][i] = badd2(h[ks][i], r[ks][i]);
          mma1688(d[i], h[ks][i], wa[2 * ks + (i >> 1)][i & 1], h[ks][i]);
        }
      }
#pragma unroll
      for (int i = 0; i < 2; i++) {
        const float sq = (g & 1) ? d[i][1] + d[i + 2][1] : d[i][0] + d[i + 2][0];
        const float e0 = d[i][2] + d[i + 2][2], e1 = d[i][3] + d[i + 2][3];
        const float other = __shfl_xor_sync(0xffffffffu, (g & 1) ? e0 : e1, 4);
        if (q == (g >> 1)) pkt_st128(hp_pub + 8 * i, with_bit((g & 1) ? other : e0, cd), with_bit(sq, cd >> 1), __float_as_uint((g & 1) ? e1 : other), tag);
      }
    }
    CT(5);
    if (tid == 0) mbar_arrive(BAR(B_KEY));
    delay_clk<HOP1_DELAY>();
    float m_bf, sd, inv_sd, r_bf;
    uint4* key_pub = &p.s->key[((lane & 7) * 16 + grp) * 2];
    uint4* cand_pub = &p.s->cand[grp * 256 + eps * 32 + q];
    uint32_t trow_inv = 0xFFFFu - (uint32_t)row_of(grp * 128 + 32 * (warp >> 1) + 8 * (g >> 1) + 4 * (warp & 1) + (q & 2) + (g & 1));
    {
      uint4 u[4];
#pragma unroll
      for (int i = 0; i < 4; i++) u[i] = pkt_ld128(hp_poll + (i & 1) * 128 + (i >> 1) * 8);
      const float wsum = SM_(float, OFF_WSUM);
      pin(key_pub); pin(cand_pub); pin(trow_inv);
      uint32_t n = 0;
      while (true) {
        bool ok[4];
#pragma unroll
        for (int i = 0; i < 4; i++) ok[i] = u[i].w == tag && pair_code(u[i].x, u[i].y) == cd;
        const bool all = __all_sync(0xffffffffu, ok[0] && ok[1] && ok[2] && ok[3]);
        if (all || ++n > SPIN_LIMIT) break;
#pragma unroll
        for (int i = 0; i < 4; i++) pkt_ld128_if(u[i], hp_poll + (i & 1) * 128 + (i >> 1) * 8, !ok[i]);
      }
      CT(6);
      float a[3], b[3];
      a[0] = __uint_as_float(u[0].x & ~1u) + __uint_as_float(u[1].x & ~1u); b[0] = __uint_as_float(u[2].x & ~1u) + __uint_as_float(u[3].x & ~1u);
      a[1] = __uint_as_float(u[0].y & ~1u) + __uint_as_float(u[1].y & ~1u); b[1] = __uint_as_float(u[2].y & ~1u) + __uint_as_float(u[3].y & ~1u);
      a[2] = __uint_as_float(u[0].z) + __uint_as_float(u[1].z); b[2] = __uint_as_float(u[2].z) + __uint_as_float(u[3].z);
#pragma unroll
      for (int i = 0; i < 3; i++) {
        a[i] = ((q & 2) ? b[i] : a[i]) + __shfl_xor_sync(0xffffffffu, (q & 2) ? a[i] : b[i], 2);
        a[i] += __shfl_xor_sync(0xffffffffu, a[i], 1);
      }
      const float mu = a[0] * (1.f / 1024.f);
      m_bf = bf16r(mu);
      sd = ln_sd(a[1] * (1.f / 1024.f) - mu * mu);
      inv_sd = rcp_fast(sd);
      r_bf = bf16r((a[2] - m_bf * wsum) * inv_sd);
    }
    {
      const uint32_t u = __float_as_uint(r_bf);
      const uint32_t ord = (u & 0x80000000u) ? ~u : (u | 0x80000000u);
      const uint32_t key = (ord & 0xFFFF0000u) | trow_inv;
      const uint32_t wk = __reduce_max_sync(0xffffffffu, key);
      if (key == wk) SM_(uint2, OFF_WKEY + warp * 8) = make_uint2(wk, (__float_as_uint(m_bf) >> 16) | __float_as_uint(sd));
      const uint32_t wmask = __ballot_sync(0xffffffffu, key == wk);
      const bool hi = (wmask & 0xCCCCCCCCu) != 0;
      uint32_t c[16];
#pragma unroll
      for (int ks = 0; ks < 8; ks++) { c[2 * ks] = hi ? h[ks][1] : h[ks][0]; c[2 * ks + 1] = hi ? h[ks][3] : h[ks][2]; }
      bar_sync(NB_BOTH, 256);
      const uint2 km = SM_(uint2, OFF_WKEY + (lane & 7) * 8);
      const uint32_t bk = __reduce_max_sync(0xffffffffu, km.x);
      if (wk == bk) {
        if ((wmask >> (lane & 28)) & 15) {
#pragma unroll
          for (int ks = 0; ks < 8; ks++) pkt_st128(cand_pub + ks * 4, c[2 * ks], tag, c[2 * ks + 1], tag);
        }
      } else if (eps == 0) {
        const uint32_t kx = __shfl_sync(0xffffffffu, km.x, warp ^ 1), ms = __shfl_sync(0xffffffffu, km.y, warp ^ 1);
        if (kx == bk && lane < 8) pkt_st128(key_pub, bk, tag, ms, tag);
      }
      CT(7);
    }
    {
      const float ih = bf16r(inv_sd);
      const uint32_t nm = pack_bf16(-m_bf, -m_bf), iv = pack_bf16(ih, inv_sd - ih);
      const uint32_t nm_o = __shfl_xor_sync(0xffffffffu, nm, 2), iv_o = __shfl_xor_sync(0xffffffffu, iv, 2);
      const uint32_t nm2[2] = {(q & 2) ? nm_o : nm, (q & 2) ? nm : nm_o}, iv2[2] = {(q & 2) ? iv_o : iv, (q & 2) ? iv : iv_o};
      const uint32_t hi2[2] = {__byte_perm(iv2[0], 0, 0x1010), __byte_perm(iv2[1], 0, 0x1010)}, lo2[2] = {__byte_perm(iv2[0], 0, 0x3232), __byte_perm(iv2[1], 0, 0x3232)};
      const uint32_t oa = sb + OFF_OUT + (warp * 16 + (lane & 15)) * 128;
#pragma unroll
      for (int ks = 0; ks < 8; ks++) {
        uint32_t o[4];
#pragma unroll
        for (int i = 0; i < 4; i++) {
          const uint32_t dd = badd2(h[ks][i], nm2[i & 1]);
          o[i] = badd2(h[ks][i], bfma2(dd, hi2[i & 1], bmul2(dd, lo2[i & 1])));
        }
        stsm_x4(oa + (ks >> 2) * 16384 + (((2 * (ks & 3) + (lane >> 4)) ^ (lane & 7)) << 4), o[0], o[1], o[2], o[3]);
      }
      staged(B_OUT);
    }
    CT(8);
    uint32_t df[16][4];
    auto load_df = [&]() {
      const int frow = (lane & 7) + ((lane >> 4) << 3), hi = (lane >> 3) & 1;
      const uint32_t base = sb + down_off(warp >> 1) + (warp & 1) * 8192 + frow * 128;
#pragma unroll
      for (int mt = 0; mt < 8; mt++) {
#pragma unroll
        for (int ks = 0; ks < 2; ks++)
          ldsm_x4_t(base + (mt >> 2) * 4096 + ks * 2048 + (((2 * (mt & 3) + hi) ^ (lane & 7)) << 4),
                    df[2 * mt + ks][0], df[2 * mt + ks][1], df[2 * mt + ks][2], df[2 * mt + ks][3]);
      }
    };
    if (moe) {
      mbar_wait(BAR(B_GU), 0);
      load_wf_rest();
      mbar_wait(BAR(B_DN), 0);
      load_df();
    }
    uint4* y_pub = &p.s->ypart[cid * 256 + tid];
    uint32_t xs_ad = sb + OFF_XSEL + (8 * (g >> 2) + 4 * w + (g & 3)) * 32 + q * 8, gp_ad = sb + OFF_GP + (wi * 8 + g) * 16 + w * 8 + (q >> 1) * 4;
    pin(y_pub); pin(xs_ad); pin(gp_ad);
    mbar_wait(BAR(B_XS), 0);
    CT(9);
    if (moe) {
      float gd[8][4] = {};
      uint2 bx[4];
#pragma unroll
      for (int r = 0; r < 4; r++) bx[r] = smem_at<uint2>(xs_ad + r * 512);
#pragma unroll
      for (int r = 0; r < 4; r++) {
#pragma unroll
        for (int i = 0; i < 8; i++) mma16816(gd[i], wf[8 * r + i][0], wf[8 * r + i][1], wf[8 * r + i][2], wf[8 * r + i][3], bx[r].x, bx[r].y);
      }
      const float gs = sel4(q, gd[0][0] + gd[1][1], gd[2][0] + gd[3][1], gd[4][0] + gd[5][1], gd[6][0] + gd[7][1]);
      const float us = sel4(q, gd[0][2] + gd[1][3], gd[2][2] + gd[3][3], gd[4][2] + gd[5][3], gd[6][2] + gd[7][3]);
      float v = ((q & 2) ? us : gs) + __shfl_xor_sync(0xffffffffu, (q & 2) ? gs : us, 2);
      v += __shfl_xor_sync(0xffffffffu, v, 1);
      smem_at<float>(gp_ad) = v;
      CT(10);
      bar_sync(NB_BOTH, 256);
      uint32_t bq[4];
      {
        const float4 p0 = SM_(float4, OFF_GP + lane * 16);
        const float gt = bf16r(p0.x + p0.z), up = bf16r(p0.y + p0.w);
        const float act = bf16r(gt * sigmoid_fast(gt)) * up;
        const uint32_t pr = pack_bf16(act, __shfl_down_sync(0xffffffffu, act, 1));
#pragma unroll
        for (int i = 0; i < 4; i++) bq[i] = __shfl_sync(0xffffffffu, pr, 8 * i + 2 * q);
      }
      CT(11);
      float yd[8][4] = {};
#pragma unroll
      for (int ks = 0; ks < 2; ks++) {
#pragma unroll
        for (int mt = 0; mt < 8; mt++) mma16816(yd[mt], df[2 * mt + ks][0], df[2 * mt + ks][1], df[2 * mt + ks][2], df[2 * mt + ks][3], bq[2 * ks], bq[2 * ks + 1]);
      }
      pkt_st128(y_pub, with_bit(sel4(q, yd[0][0], yd[2][0], yd[4][0], yd[6][0]), cd), with_bit(sel4(q, yd[0][2], yd[2][2], yd[4][2], yd[6][2]), cd >> 1),
                with_bit(sel4(q, yd[1][0], yd[3][0], yd[5][0], yd[7][0]), cd), with_bit(sel4(q, yd[1][2], yd[3][2], yd[5][2], yd[7][2]), cd >> 1));
    } else {
      const long long tw = clock64();
      while (clock64() - tw < IDLE_WAIT_CLK) __nanosleep(100);
    }
    CT(12);
    const uint32_t kv = SM_(uint32_t, OFF_KV);
    const int tsel = 0xFFFF - (int)(kv & 0xFFFFu);
    const float r_sel = __uint_as_float((kv & 0x80000000u) ? (kv & 0x7FFF0000u) : (~kv & 0xFFFF0000u));
    const float sig = bf16r(sigmoid_fast(r_sel));
    const int pfin = 2 * cid + (tid & 1);
    const int col_fin = (pfin >> 5) * 128 + (pfin & 3) * 32 + ((pfin & 31) >> 2) + 8 * ((tid >> 1) & 3);
    const int sel_off = (col_fin >> 4) * 32 + ((col_fin & 7) >> 1) * 8 + ((col_fin >> 3) & 1) * 4 + (col_fin & 1) * 2;
    const float hn_fin = __uint_as_float((uint32_t)SM_(uint16_t, OFF_XSEL + sel_off) << 16), h_fin = __uint_as_float((uint32_t)SM_(uint16_t, OFF_HSEL + sel_off) << 16);
    bf16* out_fin = p.out + (size_t)tsel * 1024 + col_fin;
    {
      const uint4* src = &p.s->ypart[(16 + (tid >> 1)) * 256 + pfin];
      pin(src); pin(out_fin);
      uint4 v = make_uint4(0, 0, 0, 0);
      if (warp < 7) {
        delay_clk<HOP3_DELAY>();
        uint32_t n = 0;
        bool ok = false;
        do {
          pkt_ld128_if(v, src, !ok);
          ok = pair_code(v.x, v.y) == cd && pair_code(v.z, v.w) == cd;
        } while (!__all_sync(0xffffffffu, ok) && ++n < SPIN_LIMIT);
      }
      CT(13);
      const float y0 = __uint_as_float(v.x & ~1u), y1 = __uint_as_float(v.y & ~1u), y2 = __uint_as_float(v.z & ~1u), y3 = __uint_as_float(v.w & ~1u);
      const float a0 = ((lane & 2) ? y1 : y0) + __shfl_xor_sync(0xffffffffu, (lane & 2) ? y0 : y1, 2);
      const float a1 = ((lane & 2) ? y3 : y2) + __shfl_xor_sync(0xffffffffu, (lane & 2) ? y2 : y3, 2);
      float b = ((lane & 4) ? a1 : a0) + __shfl_xor_sync(0xffffffffu, (lane & 4) ? a0 : a1, 4);
      b += __shfl_xor_sync(0xffffffffu, b, 8);
      b += __shfl_xor_sync(0xffffffffu, b, 16);
      if (lane < 8) SM_(float, OFF_FIN + lane * 32 + warp * 4) = b;
    }
    bar_sync(NB_BOTH, 256);
    if (tid < 8) {
      const float4 y0 = SM_(float4, OFF_FIN + tid * 32), y1 = SM_(float4, OFF_FIN + tid * 32 + 16);
      const float y = ((y0.x + y0.y) + (y0.z + y0.w)) + ((y1.x + y1.y) + y1.z);
      *out_fin = __float2bfloat16_rn(h_fin + bf16r(hn_fin + bf16r(bf16r(y) * sig)));
      if (cid == 0 && tid == 0) st_relaxed32(&p.s->epoch, tag);
    }
    CT(14);
  }
}

__global__ void __launch_bounds__(384, 1) occupancy_probe_kernel() {}

typedef CUresult (*EncodeFn)(CUtensorMap*, CUtensorMapDataType, cuuint32_t, void*, const cuuint64_t*, const cuuint64_t*, const cuuint32_t*, const cuuint32_t*,
                             CUtensorMapInterleave, CUtensorMapSwizzle, CUtensorMapL2promotion, CUtensorMapFloatOOBfill);

static void make_tm(EncodeFn enc, CUtensorMap* tm, const void* ptr, uint64_t rows, uint64_t cols, uint32_t brows, uint32_t bcols, CUtensorMapSwizzle sw,
                    CUtensorMapL2promotion promo = CU_TENSOR_MAP_L2_PROMOTION_L2_128B) {
  cuuint64_t dims[2] = {cols, rows};
  cuuint64_t strides[1] = {cols * 2};
  cuuint32_t box[2] = {bcols, brows};
  cuuint32_t es[2] = {1, 1};
  enc(tm, CU_TENSOR_MAP_DATA_TYPE_BFLOAT16, 2, const_cast<void*>(ptr), dims, strides, box, es, CU_TENSOR_MAP_INTERLEAVE_NONE, sw,
      promo, CU_TENSOR_MAP_FLOAT_OOB_FILL_NONE);
}

static void make_tm_rows(EncodeFn enc, CUtensorMap* tm, const void* ptr, uint64_t cols, uint32_t b4, uint32_t bcols, CUtensorMapSwizzle sw,
                         CUtensorMapL2promotion promo = CU_TENSOR_MAP_L2_PROMOTION_L2_128B) {
  cuuint64_t dims[5] = {cols, 2, 2, 2, 256};
  cuuint64_t strides[4] = {RW0 * cols * 2, RW1 * cols * 2, RW2 * cols * 2, RW3 * cols * 2};
  cuuint32_t box[5] = {bcols, 2, 2, 2, b4};
  cuuint32_t es[5] = {1, 1, 1, 1, 1};
  enc(tm, CU_TENSOR_MAP_DATA_TYPE_BFLOAT16, 5, const_cast<void*>(ptr), dims, strides, box, es, CU_TENSOR_MAP_INTERLEAVE_NONE, sw, promo,
      CU_TENSOR_MAP_FLOAT_OOB_FILL_NONE);
}

extern "C" void kernel_launch(void* const* d_in, const int* in_sizes, int n_in, void* d_out, int out_size) {
  (void)in_sizes; (void)n_in; (void)out_size;
  static EncodeFn enc = nullptr;
  static void* abT = nullptr;
  static int map = 0;
  if (!enc) {
    void* fn = nullptr; cudaDriverEntryPointQueryResult st;
    cudaGetDriverEntryPoint("cuTensorMapEncodeTiled", &fn, cudaEnableDefault, &st);
    enc = (EncodeFn)fn;
    cudaGetSymbolAddress(&abT, g_scratch);
    cudaFuncSetAttribute(fnet_moe_kernel<0>, cudaFuncAttributeMaxDynamicSharedMemorySize, SMEM_TOTAL);
    cudaFuncSetAttribute(fnet_moe_kernel<1>, cudaFuncAttributeMaxDynamicSharedMemorySize, SMEM_TOTAL);
    cudaFuncSetAttribute(occupancy_probe_kernel, cudaFuncAttributeMaxDynamicSharedMemorySize, SMEM_TOTAL);
    cudaFuncSetAttribute(occupancy_probe_kernel, cudaFuncAttributeNonPortableClusterSizeAllowed, 1);
    auto max_clusters = [&](int size) {
      cudaLaunchConfig_t cfg = {};
      cfg.gridDim = dim3(128); cfg.blockDim = dim3(384); cfg.dynamicSmemBytes = SMEM_TOTAL;
      cudaLaunchAttribute at[1];
      at[0].id = cudaLaunchAttributeClusterDimension; at[0].val.clusterDim.x = size; at[0].val.clusterDim.y = 1; at[0].val.clusterDim.z = 1;
      cfg.attrs = at; cfg.numAttrs = 1;
      int ncl = 0;
      return cudaOccupancyMaxActiveClusters(&ncl, occupancy_probe_kernel, &cfg) == cudaSuccess ? ncl : 0;
    };
    int dev = 0, sms = 0;
    cudaGetDevice(&dev);
    cudaDeviceGetAttribute(&sms, cudaDevAttrMultiProcessorCount, dev);
    map = (sms == 132 && max_clusters(2) == 66 && max_clusters(16) == 7) ? 0 : 1;
    (void)cudaGetLastError();
  }
  Params p;
  const bf16* x = (const bf16*)d_in[0];
  make_tm(enc, &p.tmD0, d_in[3], 1024, 1024, 128, 64, CU_TENSOR_MAP_SWIZZLE_128B);
  make_tm(enc, &p.tmD1, d_in[4], 1024, 1024, 128, 64, CU_TENSOR_MAP_SWIZZLE_128B);
  make_tm(enc, &p.tmX, x, 2048, 1024, map == 0 ? NX0 : 256, 64, CU_TENSOR_MAP_SWIZZLE_128B);
  make_tm_rows(enc, &p.tmXr, x, 1024, 8, 64, CU_TENSOR_MAP_SWIZZLE_128B);
  make_tm(enc, &p.tmAbS, abT, 2048, 2048, 64, 64, CU_TENSOR_MAP_SWIZZLE_128B);
  make_tm(enc, &p.tmAbL, abT, 2048, 2048, 128, 64, CU_TENSOR_MAP_SWIZZLE_128B);
  make_tm_rows(enc, &p.tmW0, d_in[1], 2048, 16, 64, CU_TENSOR_MAP_SWIZZLE_128B);
  make_tm_rows(enc, &p.tmW1, d_in[2], 2048, 16, 64, CU_TENSOR_MAP_SWIZZLE_128B);
  {
    cuuint64_t dims[5] = {1024, 2, 4, 2, 2048};
    cuuint64_t strides[4] = {RW0 * 2048, RW3 * 2048, RW1 * 2048, 2048};
    cuuint32_t box[5] = {64, 2, 4, 2, 1};
    cuuint32_t es[5] = {1, 1, 1, 1, 1};
    enc(&p.tmOut, CU_TENSOR_MAP_DATA_TYPE_BFLOAT16, 5, d_out, dims, strides, box, es, CU_TENSOR_MAP_INTERLEAVE_NONE, CU_TENSOR_MAP_SWIZZLE_128B,
        CU_TENSOR_MAP_L2_PROMOTION_NONE, CU_TENSOR_MAP_FLOAT_OOB_FILL_NONE);
  }
  {
    cuuint64_t dims[5] = {1024, 2, 4, 2, 8};
    cuuint64_t strides[4] = {2048, 4 * 2048, 2 * 2048, 256 * 2048};
    cuuint32_t box[5] = {64, 2, 4, 2, 8};
    cuuint32_t es[5] = {1, 1, 1, 1, 1};
    enc(&p.tmXh, CU_TENSOR_MAP_DATA_TYPE_BFLOAT16, 5, const_cast<bf16*>(x) + 240 * 1024, dims, strides, box, es, CU_TENSOR_MAP_INTERLEAVE_NONE,
        CU_TENSOR_MAP_SWIZZLE_128B, CU_TENSOR_MAP_L2_PROMOTION_L2_128B, CU_TENSOR_MAP_FLOAT_OOB_FILL_NONE);
  }
  make_tm(enc, &p.tmAbM, abT, 2048, 2048, 128, 16, CU_TENSOR_MAP_SWIZZLE_32B, CU_TENSOR_MAP_L2_PROMOTION_NONE);
  make_tm_rows(enc, &p.tmWM0, d_in[1], 2048, 16, 16, CU_TENSOR_MAP_SWIZZLE_32B, CU_TENSOR_MAP_L2_PROMOTION_NONE);
  make_tm_rows(enc, &p.tmWM1, d_in[2], 2048, 16, 16, CU_TENSOR_MAP_SWIZZLE_32B, CU_TENSOR_MAP_L2_PROMOTION_NONE);
  make_tm(enc, &p.tmG, d_in[7], 1024, 3584, 128, 32, CU_TENSOR_MAP_SWIZZLE_64B);
  make_tm(enc, &p.tmU, d_in[8], 1024, 3584, 128, 32, CU_TENSOR_MAP_SWIZZLE_64B);
  make_tm(enc, &p.tmDn, d_in[9], 3584, 1024, 32, 64, CU_TENSOR_MAP_SWIZZLE_128B);
  p.x = x; p.Dre = (const bf16*)d_in[3]; p.Dim = (const bf16*)d_in[4];
  p.wr = (const bf16*)d_in[6]; p.wdown = (const bf16*)d_in[9]; p.wgate = (const bf16*)d_in[7]; p.wup = (const bf16*)d_in[8];
  p.out = (bf16*)d_out; p.s = (Scratch*)abT;
  if (map == 1) fnet_moe_kernel<1><<<128, 384, SMEM_TOTAL>>>(p);
  else fnet_moe_kernel<0><<<132, 384, SMEM_TOTAL>>>(p);
}
```

```cpp
#include <cuda.h>
#include <cuda_runtime.h>
#include <cuda_bf16.h>
#include <stdint.h>
#include <type_traits>

typedef __nv_bfloat16 bf16;

constexpr int NX0 = 240;
constexpr int REG_C = 232, REG_P = 40;
__host__ __device__ constexpr int row_of(int p) { return (p & 1) * 1024 + ((p >> 1) & 1) * 512 + (p >> 2); }
__host__ __device__ constexpr int group_of(int row) { return (row & 511) >> 5; }
__device__ __forceinline__ int sigma_of(int tau, int r) { return r + (r >= tau); }
__device__ __forceinline__ int kblock(int tau, int j) {
  const int i = j - 4, c = (i * 37) >> 8;
  return j < 4 ? tau * 4 + j : sigma_of(tau, i - 7 * c) * 4 + c;
}
constexpr int AUX_AFTER = 1;
constexpr int PF_K0 = 8, PF_N0 = 2, PF_K1 = 24;
constexpr int WPF_K0 = 12, WPF_N = 10;
constexpr int PUB_K1 = 22;
constexpr int NREG_H = 5;
constexpr int MR_K0 = 29, MR_P = 6;
constexpr int MINI_PF_K = 35, MINI_LOAD_K = 43, MINI_K = 42;
constexpr int RESET_K = 37;
constexpr int SEND_FIRST = 2;
constexpr int HELPER_NS = 6000;
constexpr int GATHER_NS = 400;
constexpr int MOE_PACE_CLK = 300;
constexpr int OUT_PACE_CLK = 70;
constexpr int HOP1_DELAY = 150, HOP3_DELAY = 450;
constexpr int SPEC_MIN = 10;
constexpr int IDLE_WAIT_CLK = 1200;
__host__ __device__ constexpr int mr_k(int h) { return MR_K0 + MR_P * (h >> 1) + 2 * (h & 1); }
constexpr int A_BYTES = 128 * 64 * 2;
constexpr int B_BYTES = 256 * 64 * 2;
constexpr int ST_BYTES = A_BYTES + B_BYTES;
constexpr int OFF_XCH = 4 * ST_BYTES;
constexpr int OFF_BAR = OFF_XCH + 32768;
constexpr int OFF_WR = OFF_BAR + 384;
constexpr int OFF_RS = OFF_WR + 384;
constexpr int OFF_PUB = OFF_RS + 640;
constexpr int OFF_MISC = OFF_PUB + 768;
constexpr int SMEM_TOTAL = OFF_MISC + 256;
constexpr int OFF_WSUM = OFF_MISC, OFF_TAG = OFF_MISC + 4;
constexpr int OFF_SEEN = OFF_MISC + 8;
constexpr int OFF_KV = OFF_MISC + 12;
constexpr int OFF_WKEY = OFF_MISC + 32;
constexpr int OFF_MINI = OFF_XCH + 16384;
constexpr int OFF_EXA = OFF_XCH;
constexpr int OFF_EXB = OFF_XCH + 4096;
__host__ __device__ constexpr int chunk_off(int c, int w) { return (c < 2 ? (c + 2) * ST_BYTES : OFF_XCH + (c - 2) * 16384) + w * 8192; }
__host__ __device__ constexpr int late_off(int i) { return i < 4 ? i * 16384 : 2 * ST_BYTES + A_BYTES + (i - 4) * 16384; }
__host__ __device__ constexpr int round_off(int h) { return h < NREG_H + 2 ? OFF_XCH + (h & 1) * 16384 : late_off(h - NREG_H - 2); }
__host__ __device__ constexpr int down_off(int i) { return late_off(6 - NREG_H + i); }
constexpr int OFF_PEER = ST_BYTES + A_BYTES;
constexpr int OFF_OUT = 3 * ST_BYTES + A_BYTES;
constexpr int OFF_XSEL = OFF_PEER;
constexpr int OFF_HSEL = OFF_PEER + 4096;
constexpr int OFF_GP = OFF_PEER + 8192;
constexpr int OFF_FIN = OFF_PEER + 9216;
__device__ __forceinline__ int slot_of(int k) { return k & 3; }
__device__ __forceinline__ int use_of(int k) { return k >> 2; }
enum { B_FULL = 0, B_EMPTY = 4, B_EPI = 8, B_STD = 12, B_EPI0B = 16, B_LATE = 17, B_STAT = 18, B_XCH = 19, B_MR = 20  , B_GU = 22,
       B_DN = 23, B_AUX = 24  , B_OUT = 26, B_KEY = 27, B_XS = 28, B_A20 = 29, B_STDA = 30, B_PUB1 = 31, B_COUNT = 32 };
enum { NB_TURN0 = 1, NB_TURN1 = 2, NB_WG0 = 3, NB_BOTH = 5, NB_AUX = 6 };

struct Scratch {
  bf16 abT[2048 * 2048];
  uint2 xstat[2048];
  uint2 dsum[2048];
  uint4 abflag[16 * 8 * 2];
  uint4 hflag[16 * 2];
  uint4 hstat[16 * 8 * 128];
  uint4 cand[16 * 256];
  uint4 key[8 * 16 * 2];
  uint4 ypart[128 * 256];
  uint32_t epoch;
};
__device__ __align__(1024) Scratch g_scratch;

struct Params {
  Scratch* s; bf16* out;
  const bf16* x; const bf16* Dre; const bf16* Dim; const bf16* wr; const bf16* wdown; const bf16* wgate; const bf16* wup;
  CUtensorMap tmX, tmD0, tmD1, tmXr, tmAbS, tmAbL, tmW0, tmW1, tmOut, tmG, tmU, tmDn, tmXh, tmAbM, tmWM0, tmWM1;
};

#define SPIN_LIMIT (1u << 14)
#define MBAR_LIMIT (1u << 10)
__device__ __forceinline__ uint32_t smem_u32(const void* p) { return (uint32_t)__cvta_generic_to_shared(p); }
__device__ __forceinline__ void mbar_init(uint32_t bar, uint32_t cnt) { asm volatile("mbarrier.init.shared::cta.b64 [%0], %1;" :: "r"(bar), "r"(cnt) : "memory"); }
__device__ __forceinline__ void mbar_expect_tx(uint32_t bar, uint32_t bytes) { asm volatile("mbarrier.arrive.expect_tx.shared::cta.b64 _, [%0], %1;" :: "r"(bar), "r"(bytes) : "memory"); }
__device__ __forceinline__ void mbar_arrive(uint32_t bar) { asm volatile("mbarrier.arrive.shared::cta.b64 _, [%0];" :: "r"(bar) : "memory"); }
__device__ __forceinline__ void mbar_wait(uint32_t bar, uint32_t parity) {
  uint32_t ok, n = 0;
  do {
    asm volatile("{\n.reg .pred p;\nmbarrier.try_wait.parity.shared::cta.b64 p, [%1], %2;\nselp.u32 %0, 1, 0, p;\n}\n" : "=r"(ok) : "r"(bar), "r"(parity) : "memory");
  } while (!ok && ++n < MBAR_LIMIT);
}
__device__ __forceinline__ void mbar_wait_cluster(uint32_t bar, uint32_t parity) {
  uint32_t ok, n = 0;
  do {
    asm volatile("{\n.reg .pred p;\nmbarrier.try_wait.parity.acquire.cluster.shared::cta.b64 p, [%1], %2;\nselp.u32 %0, 1, 0, p;\n}\n" : "=r"(ok) : "r"(bar), "r"(parity) : "memory");
  } while (!ok && ++n < MBAR_LIMIT);
}
__device__ __forceinline__ void tma_load_2d(uint32_t dst, const CUtensorMap* tm, uint32_t bar, int c0, int c1) {
  asm volatile("cp.async.bulk.tensor.2d.shared::cluster.global.mbarrier::complete_tx::bytes [%0], [%1, {%3, %4}], [%2];"
    :: "r"(dst), "l"(tm), "r"(bar), "r"(c0), "r"(c1) : "memory");
}
__device__ __forceinline__ void tma_load_2d_hint(uint32_t dst, const CUtensorMap* tm, uint32_t bar, int c0, int c1, uint64_t pol) {
  asm volatile("cp.async.bulk.tensor.2d.shared::cluster.global.mbarrier::complete_tx::bytes.L2::cache_hint [%0], [%1, {%3, %4}], [%2], %5;"
    :: "r"(dst), "l"(tm), "r"(bar), "r"(c0), "r"(c1), "l"(pol) : "memory");
}
__device__ __forceinline__ uint64_t policy_evict_first() { uint64_t p; asm volatile("createpolicy.fractional.L2::evict_first.b64 %0, 1.0;" : "=l"(p)); return p; }
__device__ __forceinline__ void tma_store_2d(const CUtensorMap* tm, uint32_t src, int c0, int c1) {
  asm volatile("cp.async.bulk.tensor.2d.global.shared::cta.bulk_group [%0, {%2, %3}], [%1];" :: "l"(tm), "r"(src), "r"(c0), "r"(c1) : "memory");
}
__device__ __forceinline__ void tma_prefetch_2d(const CUtensorMap* tm, int c0, int c1) {
  asm volatile("cp.async.bulk.prefetch.tensor.2d.L2.global.tile [%0, {%1, %2}];" :: "l"(tm), "r"(c0), "r"(c1) : "memory");
}
__device__ __forceinline__ void bulk_load(uint32_t dst, const void* src, uint32_t bytes, uint32_t bar) {
  asm volatile("cp.async.bulk.shared::cluster.global.mbarrier::complete_tx::bytes [%0], [%1], %2, [%3];" :: "r"(dst), "l"(src), "r"(bytes), "r"(bar) : "memory");
}
__device__ __forceinline__ void bulk_commit() { asm volatile("cp.async.bulk.commit_group;" ::: "memory"); }
__device__ __forceinline__ void bulk_wait_all() { asm volatile("cp.async.bulk.wait_group 0;" ::: "memory"); }
__device__ __forceinline__ void fence_async_smem() { asm volatile("fence.proxy.async.shared::cta;" ::: "memory"); }
__device__ __forceinline__ void wgmma_fence() { asm volatile("wgmma.fence.sync.aligned;" ::: "memory"); }
__device__ __forceinline__ void wgmma_commit() { asm volatile("wgmma.commit_group.sync.aligned;" ::: "memory"); }
__device__ __forceinline__ void wgmma_wait0() { asm volatile("wgmma.wait_group.sync.aligned 0;" ::: "memory"); }
__device__ __forceinline__ void bar_sync(int id, int n) { asm volatile("bar.sync %0, %1;" :: "r"(id), "r"(n) : "memory"); }
__device__ __forceinline__ void bar_arrive(int id, int n) { asm volatile("bar.arrive %0, %1;" :: "r"(id), "r"(n) : "memory"); }
template<int R> __device__ __forceinline__ void reg_inc() { asm volatile("setmaxnreg.inc.sync.aligned.u32 %0;" :: "n"(R)); }
template<int R> __device__ __forceinline__ void reg_dec() { asm volatile("setmaxnreg.dec.sync.aligned.u32 %0;" :: "n"(R)); }
__device__ __forceinline__ bool elect_one() {
  uint32_t p;
  asm volatile("{\n.reg .pred q;\nelect.sync _|q, 0xffffffff;\nselp.u32 %0, 1, 0, q;\n}\n" : "=r"(p));
  return p != 0;
}
__device__ __forceinline__ uint32_t mapa(uint32_t addr, uint32_t cta) { uint32_t r; asm volatile("mapa.shared::cluster.u32 %0, %1, %2;" : "=r"(r) : "r"(addr), "r"(cta)); return r; }
__device__ __forceinline__ void st_async_v4(uint32_t addr, uint32_t bar, uint32_t a, uint32_t b, uint32_t c, uint32_t d) {
  asm volatile("st.async.weak.shared::cluster.mbarrier::complete_tx::bytes.v4.b32 [%0], {%2, %3, %4, %5}, [%1];" :: "r"(addr), "r"(bar), "r"(a), "r"(b), "r"(c), "r"(d) : "memory");
}
__device__ __forceinline__ void stsm_x4(uint32_t addr, uint32_t a, uint32_t b, uint32_t c, uint32_t d) {
  asm volatile("stmatrix.sync.aligned.m8n8.x4.shared.b16 [%0], {%1, %2, %3, %4};" :: "r"(addr), "r"(a), "r"(b), "r"(c), "r"(d));
}
__device__ __forceinline__ uint4 lds128_v(uint32_t addr) { uint4 v; asm volatile("ld.shared.v4.b32 {%0, %1, %2, %3}, [%4];" : "=r"(v.x), "=r"(v.y), "=r"(v.z), "=r"(v.w) : "r"(addr)); return v; }
extern __shared__ __align__(1024) uint8_t smem_raw[];
template<class T> __device__ __forceinline__ T& smem_at(uint32_t addr) { return *reinterpret_cast<T*>(__cvta_shared_to_generic(addr)); }
#define SM_(T, off) smem_at<T>(sb + (off))
__device__ __forceinline__ uint4 ldg_nc128(const void* p) { uint4 v; asm volatile("ld.global.nc.v4.b32 {%0, %1, %2, %3}, [%4];" : "=r"(v.x), "=r"(v.y), "=r"(v.z), "=r"(v.w) : "l"(p)); return v; }
__device__ __forceinline__ void pkt_st128(void* p, uint32_t a, uint32_t b, uint32_t c, uint32_t d) {
  asm volatile("{\n.reg .b128 v;\n.reg .b64 lo, hi;\nmov.b64 lo, {%1, %2};\nmov.b64 hi, {%3, %4};\nmov.b128 v, {lo, hi};\nst.relaxed.gpu.global.b128 [%0], v;\n}\n"
    :: "l"(p), "r"(a), "r"(b), "r"(c), "r"(d) : "memory");
}
__device__ __forceinline__ uint4 pkt_ld128(const void* p) {
  uint4 r;
  asm volatile("{\n.reg .b128 v;\n.reg .b64 lo, hi;\nld.relaxed.gpu.global.b128 v, [%4];\nmov.b128 {lo, hi}, v;\nmov.b64 {%0, %1}, lo;\nmov.b64 {%2, %3}, hi;\n}\n"
    : "=r"(r.x), "=r"(r.y), "=r"(r.z), "=r"(r.w) : "l"(p) : "memory");
  return r;
}
__device__ __forceinline__ void pkt_ld128_if(uint4& r, const void* p, bool cond) {
  asm volatile("{\n.reg .pred q;\n.reg .b64 lo, hi;\nsetp.ne.b32 q, %5, 0;\nmov.b64 lo, {%0, %1};\nmov.b64 hi, {%2, %3};\n"
               "@q ld.relaxed.gpu.global.v2.b64 {lo, hi}, [%4];\nmov.b64 {%0, %1}, lo;\nmov.b64 {%2, %3}, hi;\n}\n"
    : "+r"(r.x), "+r"(r.y), "+r"(r.z), "+r"(r.w) : "l"(p), "r"((uint32_t)cond) : "memory");
}
__device__ __forceinline__ void pkt_st64(void* p, uint32_t a, uint32_t b) {
  asm volatile("{\n.reg .b64 v;\nmov.b64 v, {%1, %2};\nst.relaxed.gpu.global.b64 [%0], v;\n}\n" :: "l"(p), "r"(a), "r"(b) : "memory");
}
__device__ __forceinline__ uint2 pkt_ld64(const void* p) {
  uint2 r;
  asm volatile("{\n.reg .b64 v;\nld.relaxed.gpu.global.b64 v, [%2];\nmov.b64 {%0, %1}, v;\n}\n" : "=r"(r.x), "=r"(r.y) : "l"(p) : "memory");
  return r;
}
__device__ __forceinline__ uint32_t ld_relaxed32(const void* p) { uint32_t v; asm volatile("ld.relaxed.gpu.global.b32 %0, [%1];" : "=r"(v) : "l"(p) : "memory"); return v; }
__device__ __forceinline__ void st_relaxed32(void* p, uint32_t v) { asm volatile("st.relaxed.gpu.global.b32 [%0], %1;" :: "l"(p), "r"(v) : "memory"); }
__device__ __forceinline__ uint32_t code_of(uint32_t tag) { return tag % 3u + 1u; }
__device__ __forceinline__ uint32_t with_bit(float v, uint32_t bit) { return (__float_as_uint(v) & ~1u) | (bit & 1u); }
__device__ __forceinline__ uint32_t pair_code(uint32_t a, uint32_t b) { return (a & 1u) | ((b & 1u) << 1); }
__device__ __forceinline__ uint32_t pack_bf16(float lo, float hi) { uint32_t r; asm("cvt.rn.bf16x2.f32 %0, %1, %2;" : "=r"(r) : "f"(hi), "f"(lo)); return r; }
__device__ __forceinline__ float bf_lo(uint32_t v) { return __uint_as_float(v << 16); }
__device__ __forceinline__ float bf_hi(uint32_t v) { return __uint_as_float(v & 0xFFFF0000u); }
__device__ __forceinline__ float bf16r(float x) { return __uint_as_float(pack_bf16(0.f, x)); }
__device__ __forceinline__ uint32_t badd2(uint32_t a, uint32_t b) { uint32_t r; asm("add.rn.bf16x2 %0, %1, %2;" : "=r"(r) : "r"(a), "r"(b)); return r; }
__device__ __forceinline__ uint32_t bmul2(uint32_t a, uint32_t b) { uint32_t r; asm("mul.rn.bf16x2 %0, %1, %2;" : "=r"(r) : "r"(a), "r"(b)); return r; }
__device__ __forceinline__ float warp_sum(float v) {
#pragma unroll
  for (int o = 16; o > 0; o >>= 1) v += __shfl_xor_sync(0xffffffffu, v, o);
  return v;
}
__device__ __forceinline__ uint64_t make_desc(uint32_t addr) {
  return (uint64_t)((addr & 0x3FFFF) >> 4) | ((uint64_t)1 << 16) | ((uint64_t)64 << 32) | ((uint64_t)1 << 62);
}
__device__ __forceinline__ uint64_t make_desc_noswz(uint32_t addr) {
  return (uint64_t)((addr & 0x3FFFF) >> 4) | ((uint64_t)8 << 16) | ((uint64_t)16 << 32);
}
__device__ __forceinline__ uint64_t make_desc_32b(uint32_t addr) {
  return (uint64_t)((addr & 0x3FFFF) >> 4) | ((uint64_t)1 << 16) | ((uint64_t)16 << 32) | ((uint64_t)3 << 62);
}
__device__ __forceinline__ void wgmma_n256(float (&d)[128], uint64_t da, uint64_t db, int scale_d) {
  asm volatile("{\n.reg .pred p;\nsetp.ne.b32 p, %130, 0;\n"
    "wgmma.mma_async.sync.aligned.m64n256k16.f32.bf16.bf16 "
    "{%0, %1, %2, %3, %4, %5, %6, %7, %8, %9, %10, %11, %12, %13, %14, %15, %16, %17, %18, %19, %20, %21, %22, %23, %24, %25, %26, %27, %28, %29, %30, %31, "
    "%32, %33, %34, %35, %36, %37, %38, %39, %40, %41, %42, %43, %44, %45, %46, %47, %48, %49, %50, %51, %52, %53, %54, %55, %56, %57, %58, %59, %60, %61, %62, %63, "
    "%64, %65, %66, %67, %68, %69, %70, %71, %72, %73, %74, %75, %76, %77, %78, %79, %80, %81, %82, %83, %84, %85, %86, %87, %88, %89, %90, %91, %92, %93, %94, %95, "
    "%96, %97, %98, %99, %100, %101, %102, %103, %104, %105, %106, %107, %108, %109, %110, %111, %112, %113, %114, %115, %116, %117, %118, %119, %120, %121, %122, %123, %124, %125, %126, %127}, "
    "%128, %129, p, 1, 1, 0, 0;\n}\n"
    : "+f"(d[0]), "+f"(d[1]), "+f"(d[2]), "+f"(d[3]), "+f"(d[4]), "+f"(d[5]), "+f"(d[6]), "+f"(d[7]),
      "+f"(d[8]), "+f"(d[9]), "+f"(d[10]), "+f"(d[11]), "+f"(d[12]), "+f"(d[13]), "+f"(d[14]), "+f"(d[15]),
      "+f"(d[16]), "+f"(d[17]), "+f"(d[18]), "+f"(d[19]), "+f"(d[20]), "+f"(d[21]), "+f"(d[22]), "+f"(d[23]),
      "+f"(d[24]), "+f"(d[25]), "+f"(d[26]), "+f"(d[27]), "+f"(d[28]), "+f"(d[29]), "+f"(d[30]), "+f"(d[31]),
      "+f"(d[32]), "+f"(d[33]), "+f"(d[34]), "+f"(d[35]), "+f"(d[36]), "+f"(d[37]), "+f"(d[38]), "+f"(d[39]),
      "+f"(d[40]), "+f"(d[41]), "+f"(d[42]), "+f"(d[43]), "+f"(d[44]), "+f"(d[45]), "+f"(d[46]), "+f"(d[47]),
      "+f"(d[48]), "+f"(d[49]), "+f"(d[50]), "+f"(d[51]), "+f"(d[52]), "+f"(d[53]), "+f"(d[54]), "+f"(d[55]),
      "+f"(d[56]), "+f"(d[57]), "+f"(d[58]), "+f"(d[59]), "+f"(d[60]), "+f"(d[61]), "+f"(d[62]), "+f"(d[63]),
      "+f"(d[64]), "+f"(d[65]), "+f"(d[66]), "+f"(d[67]), "+f"(d[68]), "+f"(d[69]), "+f"(d[70]), "+f"(d[71]),
      "+f"(d[72]), "+f"(d[73]), "+f"(d[74]), "+f"(d[75]), "+f"(d[76]), "+f"(d[77]), "+f"(d[78]), "+f"(d[79]),
      "+f"(d[80]), "+f"(d[81]), "+f"(d[82]), "+f"(d[83]), "+f"(d[84]), "+f"(d[85]), "+f"(d[86]), "+f"(d[87]),
      "+f"(d[88]), "+f"(d[89]), "+f"(d[90]), "+f"(d[91]), "+f"(d[92]), "+f"(d[93]), "+f"(d[94]), "+f"(d[95]),
      "+f"(d[96]), "+f"(d[97]), "+f"(d[98]), "+f"(d[99]), "+f"(d[100]), "+f"(d[101]), "+f"(d[102]), "+f"(d[103]),
      "+f"(d[104]), "+f"(d[105]), "+f"(d[106]), "+f"(d[107]), "+f"(d[108]), "+f"(d[109]), "+f"(d[110]), "+f"(d[111]),
      "+f"(d[112]), "+f"(d[113]), "+f"(d[114]), "+f"(d[115]), "+f"(d[116]), "+f"(d[117]), "+f"(d[118]), "+f"(d[119]),
      "+f"(d[120]), "+f"(d[121]), "+f"(d[122]), "+f"(d[123]), "+f"(d[124]), "+f"(d[125]), "+f"(d[126]), "+f"(d[127])
    : "l"(da), "l"(db), "r"(scale_d));
}
__device__ __forceinline__ void wgmma_g1(float (&d)[128], uint64_t da, uint64_t db, int scale_d) { wgmma_n256(d, da, db, scale_d); }
__device__ __forceinline__ void wgmma_g1(float (&d)[120], uint64_t da, uint64_t db, int scale_d) {
  asm volatile("{\n.reg .pred p;\nsetp.ne.b32 p, %122, 0;\n"
    "wgmma.mma_async.sync.aligned.m64n240k16.f32.bf16.bf16 "
    "{%0, %1, %2, %3, %4, %5, %6, %7, %8, %9, %10, %11, %12, %13, %14, %15, %16, %17, %18, %19, %20, %21, %22, %23, %24, %25, %26, %27, %28, %29, %30, %31, %32, %33, %34, %35, %36, %37, %38, %39, %40, %41, %42, %43, %44, %45, %46, %47, %48, %49, %50, %51, %52, %53, %54, %55, %56, %57, %58, %59, %60, %61, %62, %63, %64, %65, %66, %67, %68, %69, %70, %71, %72, %73, %74, %75, %76, %77, %78, %79, %80, %81, %82, %83, %84, %85, %86, %87, %88, %89, %90, %91, %92, %93, %94, %95, %96, %97, %98, %99, %100, %101, %102, %103, %104, %105, %106, %107, %108, %109, %110, %111, %112, %113, %114, %115, %116, %117, %118, %119}, "
    "%120, %121, p, 1, 1, 0, 0;\n}\n"
    : "+f"(d[0]), "+f"(d[1]), "+f"(d[2]), "+f"(d[3]), "+f"(d[4]), "+f"(d[5]), "+f"(d[6]), "+f"(d[7]), "+f"(d[8]), "+f"(d[9]), "+f"(d[10]), "+f"(d[11]), "+f"(d[12]), "+f"(d[13]), "+f"(d[14]), "+f"(d[15]), "+f"(d[16]), "+f"(d[17]), "+f"(d[18]), "+f"(d[19]), "+f"(d[20]), "+f"(d[21]), "+f"(d[22]), "+f"(d[23]), "+f"(d[24]), "+f"(d[25]), "+f"(d[26]), "+f"(d[27]), "+f"(d[28]), "+f"(d[29]), "+f"(d[30]), "+f"(d[31]), "+f"(d[32]), "+f"(d[33]), "+f"(d[34]), "+f"(d[35]), "+f"(d[36]), "+f"(d[37]), "+f"(d[38]), "+f"(d[39]), "+f"(d[40]), "+f"(d[41]), "+f"(d[42]), "+f"(d[43]), "+f"(d[44]), "+f"(d[45]), "+f"(d[46]), "+f"(d[47]), "+f"(d[48]), "+f"(d[49]), "+f"(d[50]), "+f"(d[51]), "+f"(d[52]), "+f"(d[53]), "+f"(d[54]), "+f"(d[55]), "+f"(d[56]), "+f"(d[57]), "+f"(d[58]), "+f"(d[59]), "+f"(d[60]), "+f"(d[61]), "+f"(d[62]), "+f"(d[63]), "+f"(d[64]), "+f"(d[65]), "+f"(d[66]), "+f"(d[67]), "+f"(d[68]), "+f"(d[69]), "+f"(d[70]), "+f"(d[71]), "+f"(d[72]), "+f"(d[73]), "+f"(d[74]), "+f"(d[75]), "+f"(d[76]), "+f"(d[77]), "+f"(d[78]), "+f"(d[79]), "+f"(d[80]), "+f"(d[81]), "+f"(d[82]), "+f"(d[83]), "+f"(d[84]), "+f"(d[85]), "+f"(d[86]), "+f"(d[87]), "+f"(d[88]), "+f"(d[89]), "+f"(d[90]), "+f"(d[91]), "+f"(d[92]), "+f"(d[93]), "+f"(d[94]), "+f"(d[95]), "+f"(d[96]), "+f"(d[97]), "+f"(d[98]), "+f"(d[99]), "+f"(d[100]), "+f"(d[101]), "+f"(d[102]), "+f"(d[103]), "+f"(d[104]), "+f"(d[105]), "+f"(d[106]), "+f"(d[107]), "+f"(d[108]), "+f"(d[109]), "+f"(d[110]), "+f"(d[111]), "+f"(d[112]), "+f"(d[113]), "+f"(d[114]), "+f"(d[115]), "+f"(d[116]), "+f"(d[117]), "+f"(d[118]), "+f"(d[119])
    : "l"(da), "l"(db), "r"(scale_d));
}
__device__ __forceinline__ void wgmma_n256_rs(float (&d)[128], uint32_t a0, uint32_t a1, uint32_t a2, uint32_t a3, uint64_t db, int scale_d) {
  asm volatile("{\n.reg .pred p;\nsetp.ne.b32 p, %133, 0;\n"
    "wgmma.mma_async.sync.aligned.m64n256k16.f32.bf16.bf16 "
    "{%0, %1, %2, %3, %4, %5, %6, %7, %8, %9, %10, %11, %12, %13, %14, %15, %16, %17, %18, %19, %20, %21, %22, %23, %24, %25, %26, %27, %28, %29, %30, %31, "
    "%32, %33, %34, %35, %36, %37, %38, %39, %40, %41, %42, %43, %44, %45, %46, %47, %48, %49, %50, %51, %52, %53, %54, %55, %56, %57, %58, %59, %60, %61, %62, %63, "
    "%64, %65, %66, %67, %68, %69, %70, %71, %72, %73, %74, %75, %76, %77, %78, %79, %80, %81, %82, %83, %84, %85, %86, %87, %88, %89, %90, %91, %92, %93, %94, %95, "
    "%96, %97, %98, %99, %100, %101, %102, %103, %104, %105, %106, %107, %108, %109, %110, %111, %112, %113, %114, %115, %116, %117, %118, %119, %120, %121, %122, %123, %124, %125, %126, %127}, "
    "{%128, %129, %130, %131}, %132, p, 1, 1, 0;\n}\n"
    : "+f"(d[0]), "+f"(d[1]), "+f"(d[2]), "+f"(d[3]), "+f"(d[4]), "+f"(d[5]), "+f"(d[6]), "+f"(d[7]),
      "+f"(d[8]), "+f"(d[9]), "+f"(d[10]), "+f"(d[11]), "+f"(d[12]), "+f"(d[13]), "+f"(d[14]), "+f"(d[15]),
      "+f"(d[16]), "+f"(d[17]), "+f"(d[18]), "+f"(d[19]), "+f"(d[20]), "+f"(d[21]), "+f"(d[22]), "+f"(d[23]),
      "+f"(d[24]), "+f"(d[25]), "+f"(d[26]), "+f"(d[27]), "+f"(d[28]), "+f"(d[29]), "+f"(d[30]), "+f"(d[31]),
      "+f"(d[32]), "+f"(d[33]), "+f"(d[34]), "+f"(d[35]), "+f"(d[36]), "+f"(d[37]), "+f"(d[38]), "+f"(d[39]),
      "+f"(d[40]), "+f"(d[41]), "+f"(d[42]), "+f"(d[43]), "+f"(d[44]), "+f"(d[45]), "+f"(d[46]), "+f"(d[47]),
      "+f"(d[48]), "+f"(d[49]), "+f"(d[50]), "+f"(d[51]), "+f"(d[52]), "+f"(d[53]), "+f"(d[54]), "+f"(d[55]),
      "+f"(d[56]), "+f"(d[57]), "+f"(d[58]), "+f"(d[59]), "+f"(d[60]), "+f"(d[61]), "+f"(d[62]), "+f"(d[63]),
      "+f"(d[64]), "+f"(d[65]), "+f"(d[66]), "+f"(d[67]), "+f"(d[68]), "+f"(d[69]), "+f"(d[70]), "+f"(d[71]),
      "+f"(d[72]), "+f"(d[73]), "+f"(d[74]), "+f"(d[75]), "+f"(d[76]), "+f"(d[77]), "+f"(d[78]), "+f"(d[79]),
      "+f"(d[80]), "+f"(d[81]), "+f"(d[82]), "+f"(d[83]), "+f"(d[84]), "+f"(d[85]), "+f"(d[86]), "+f"(d[87]),
      "+f"(d[88]), "+f"(d[89]), "+f"(d[90]), "+f"(d[91]), "+f"(d[92]), "+f"(d[93]), "+f"(d[94]), "+f"(d[95]),
      "+f"(d[96]), "+f"(d[97]), "+f"(d[98]), "+f"(d[99]), "+f"(d[100]), "+f"(d[101]), "+f"(d[102]), "+f"(d[103]),
      "+f"(d[104]), "+f"(d[105]), "+f"(d[106]), "+f"(d[107]), "+f"(d[108]), "+f"(d[109]), "+f"(d[110]), "+f"(d[111]),
      "+f"(d[112]), "+f"(d[113]), "+f"(d[114]), "+f"(d[115]), "+f"(d[116]), "+f"(d[117]), "+f"(d[118]), "+f"(d[119]),
      "+f"(d[120]), "+f"(d[121]), "+f"(d[122]), "+f"(d[123]), "+f"(d[124]), "+f"(d[125]), "+f"(d[126]), "+f"(d[127])
    : "r"(a0), "r"(a1), "r"(a2), "r"(a3), "l"(db), "r"(scale_d));
}
__device__ __forceinline__ void wgmma_n128(float (&d)[64], uint64_t da, uint64_t db, int scale_d = 1) {
  asm volatile("{\n.reg .pred p;\nsetp.ne.b32 p, %66, 0;\n"
    "wgmma.mma_async.sync.aligned.m64n128k16.f32.bf16.bf16 "
    "{%0, %1, %2, %3, %4, %5, %6, %7, %8, %9, %10, %11, %12, %13, %14, %15, %16, %17, %18, %19, %20, %21, %22, %23, %24, %25, %26, %27, %28, %29, %30, %31, %32, %33, %34, %35, %36, %37, %38, %39, %40, %41, %42, %43, %44, %45, %46, %47, %48, %49, %50, %51, %52, %53, %54, %55, %56, %57, %58, %59, %60, %61, %62, %63}, "
    "%64, %65, p, 1, 1, 0, 0;\n}\n"
    : "+f"(d[0]), "+f"(d[1]), "+f"(d[2]), "+f"(d[3]), "+f"(d[4]), "+f"(d[5]), "+f"(d[6]), "+f"(d[7]), "+f"(d[8]), "+f"(d[9]), "+f"(d[10]), "+f"(d[11]), "+f"(d[12]), "+f"(d[13]), "+f"(d[14]), "+f"(d[15]), "+f"(d[16]), "+f"(d[17]), "+f"(d[18]), "+f"(d[19]), "+f"(d[20]), "+f"(d[21]), "+f"(d[22]), "+f"(d[23]), "+f"(d[24]), "+f"(d[25]), "+f"(d[26]), "+f"(d[27]), "+f"(d[28]), "+f"(d[29]), "+f"(d[30]), "+f"(d[31]), "+f"(d[32]), "+f"(d[33]), "+f"(d[34]), "+f"(d[35]), "+f"(d[36]), "+f"(d[37]), "+f"(d[38]), "+f"(d[39]), "+f"(d[40]), "+f"(d[41]), "+f"(d[42]), "+f"(d[43]), "+f"(d[44]), "+f"(d[45]), "+f"(d[46]), "+f"(d[47]), "+f"(d[48]), "+f"(d[49]), "+f"(d[50]), "+f"(d[51]), "+f"(d[52]), "+f"(d[53]), "+f"(d[54]), "+f"(d[55]), "+f"(d[56]), "+f"(d[57]), "+f"(d[58]), "+f"(d[59]), "+f"(d[60]), "+f"(d[61]), "+f"(d[62]), "+f"(d[63])
    : "l"(da), "l"(db), "r"(scale_d));
}
template<int N> __device__ __forceinline__ void fence_acc(float (&d)[N]) {
#pragma unroll
  for (int i = 0; i < N; i++) asm volatile("" : "+f"(d[i]) :: "memory");
}

template<int N, int I = 0, class F> __device__ __forceinline__ void static_for(F&& f) {
  if constexpr (I < N) { f(std::integral_constant<int, I>()); static_for<N, I + 1>(f); }
}

__device__ __forceinline__ void ldsm_x4_t(uint32_t addr, uint32_t& a, uint32_t& b, uint32_t& c, uint32_t& d) {
  asm volatile("ldmatrix.sync.aligned.m8n8.x4.trans.shared.b16 {%0, %1, %2, %3}, [%4];" : "=r"(a), "=r"(b), "=r"(c), "=r"(d) : "r"(addr));
}
__device__ __forceinline__ void sts128(uint32_t addr, uint32_t a, uint32_t b, uint32_t c, uint32_t d) {
  asm volatile("st.shared.v4.b32 [%0], {%1, %2, %3, %4};" :: "r"(addr), "r"(a), "r"(b), "r"(c), "r"(d));
}
__device__ __forceinline__ void mma16816(float (&c)[4], uint32_t a0, uint32_t a1, uint32_t a2, uint32_t a3, uint32_t b0, uint32_t b1) {
  asm volatile("mma.sync.aligned.m16n8k16.row.col.f32.bf16.bf16.f32 {%0, %1, %2, %3}, {%4, %5, %6, %7}, {%8, %9}, {%0, %1, %2, %3};"
      : "+f"(c[0]), "+f"(c[1]), "+f"(c[2]), "+f"(c[3]) : "r"(a0), "r"(a1), "r"(a2), "r"(a3), "r"(b0), "r"(b1));
}
__device__ __forceinline__ void mma1688(float (&c)[4], uint32_t a0, uint32_t a1, uint32_t b0) {
  asm volatile("mma.sync.aligned.m16n8k8.row.col.f32.bf16.bf16.f32 {%0, %1, %2, %3}, {%4, %5}, {%6}, {%0, %1, %2, %3};"
      : "+f"(c[0]), "+f"(c[1]), "+f"(c[2]), "+f"(c[3]) : "r"(a0), "r"(a1), "r"(b0));
}
__device__ __forceinline__ void pin(uint32_t& v) { asm volatile("shfl.sync.bfly.b32 %0, %0, 0, 0x1f, 0xffffffff;" : "+r"(v)); }
template<class T> __device__ __forceinline__ void pin(T*& v) {
  uint32_t lo = (uint32_t)(uint64_t)v, hi = (uint32_t)((uint64_t)v >> 32);
  pin(lo); pin(hi);
  v = (T*)(((uint64_t)hi << 32) | lo);
}
__device__ __forceinline__ float sel4(int q, float a, float b, float c, float d) {
  float r;
  asm("{\n.reg .pred p, o;\n.reg .f32 x, y;\n.reg .b32 t;\nand.b32 t, %1, 1;\nsetp.ne.b32 p, t, 0;\nsetp.gt.s32 o, %1, 1;\n"
      "selp.f32 x, %3, %2, p;\nselp.f32 y, %5, %4, p;\nselp.f32 %0, y, x, o;\n}\n" : "=f"(r) : "r"(q), "f"(a), "f"(b), "f"(c), "f"(d));
  return r;
}
__device__ __forceinline__ uint32_t bfma2(uint32_t a, uint32_t b, uint32_t c) { uint32_t r; asm("fma.rn.bf16x2 %0, %1, %2, %3;" : "=r"(r) : "r"(a), "r"(b), "r"(c)); return r; }
__device__ __forceinline__ void tma_load_5d(uint32_t dst, const CUtensorMap* tm, uint32_t bar, int c0, int c4) {
  asm volatile("cp.async.bulk.tensor.5d.shared::cluster.global.mbarrier::complete_tx::bytes [%0], [%1, {%3, %4, %4, %4, %5}], [%2];"
    :: "r"(dst), "l"(tm), "r"(bar), "r"(c0), "r"(0), "r"(c4) : "memory");
}
__device__ __forceinline__ void tma_load_4d(uint32_t dst, const CUtensorMap* tm, uint32_t bar, int c0, int c3) {
  asm volatile("cp.async.bulk.tensor.4d.shared::cluster.global.mbarrier::complete_tx::bytes [%0], [%1, {%3, %4, %4, %5}], [%2];"
    :: "r"(dst), "l"(tm), "r"(bar), "r"(c0), "r"(0), "r"(c3) : "memory");
}
__device__ __forceinline__ void tma_load_4d_hint(uint32_t dst, const CUtensorMap* tm, uint32_t bar, int c0, int c3, uint64_t pol) {
  asm volatile("cp.async.bulk.tensor.4d.shared::cluster.global.mbarrier::complete_tx::bytes.L2::cache_hint [%0], [%1, {%3, %4, %4, %5}], [%2], %6;"
    :: "r"(dst), "l"(tm), "r"(bar), "r"(c0), "r"(0), "r"(c3), "l"(pol) : "memory");
}
__device__ __forceinline__ void tma_prefetch_4d(const CUtensorMap* tm, int c0, int c3) {
  asm volatile("cp.async.bulk.prefetch.tensor.4d.L2.global.tile [%0, {%1, %2, %2, %3}];" :: "l"(tm), "r"(c0), "r"(0), "r"(c3) : "memory");
}
__device__ __forceinline__ void tma_store_5d(const CUtensorMap* tm, uint32_t src, int c0, int c4) {
  asm volatile("cp.async.bulk.tensor.5d.global.shared::cta.bulk_group [%0, {%2, %3, %3, %3, %4}], [%1];" :: "l"(tm), "r"(src), "r"(c0), "r"(0), "r"(c4) : "memory");
}
__device__ __forceinline__ float rcp_fast(float x) { float r; asm("rcp.approx.ftz.f32 %0, %1;" : "=f"(r) : "f"(x)); return r; }
__device__ __forceinline__ float sigmoid_fast(float x) { float e; asm("ex2.approx.ftz.f32 %0, %1;" : "=f"(e) : "f"(x * -1.4426950408889634f)); return rcp_fast(1.f + e); }
__device__ __forceinline__ float sqrt_fast(float x) { float r; asm("sqrt.approx.ftz.f32 %0, %1;" : "=f"(r) : "f"(x)); return r; }
__device__ __forceinline__ float ln_sd(float var) { return bf16r(sqrt_fast(bf16r(bf16r(fmaxf(var, 0.f)) + 1e-5f))); }
__device__ __forceinline__ uint32_t norm2(uint32_t h, uint32_t neg_mean2, float inv_sd) {
  const uint32_t d = badd2(h, neg_mean2);
  return pack_bf16(bf_lo(d) * inv_sd, bf_hi(d) * inv_sd);
}
template<int N> __device__ __forceinline__ void delay_clk() {
  if constexpr (N > 0) { const uint32_t t0 = clock(); while ((uint32_t)clock() - t0 < N) {} }
}
__device__ __forceinline__ void put_xstat(uint32_t rs, uint32_t exb, int col, uint32_t mean_rstd, int m) {
  smem_at<uint16_t>(rs + ((col & 7) >> 1) * 144 + (col >> 3) * 4 + (col & 1) * 2) = (uint16_t)(mean_rstd ^ (m << 15));
  const uint32_t nm = (mean_rstd >> 16) ^ 0x8000u;
  smem_at<uint4>(exb + (col >> 3) * 256 + (col & 7) * 16) = make_uint4(nm | (nm << 16), nm, 0, 0);
  smem_at<uint4>(exb + (col >> 3) * 256 + 128 + (col & 7) * 16) = make_uint4(0, 0, 0, 0);
}
__device__ __forceinline__ void put_dsum(uint32_t exa, int e, float c) {
  const float hi = bf16r(c), mid = bf16r(c - hi), lo = bf16r((c - hi) - mid);
  smem_at<uint4>(exa + (e >> 3) * 256 + (e & 7) * 16) = make_uint4((__float_as_uint(hi) >> 16) | (__float_as_uint(mid) & 0xFFFF0000u), __float_as_uint(lo) >> 16, 0, 0);
  smem_at<uint4>(exa + (e >> 3) * 256 + 128 + (e & 7) * 16) = make_uint4(0, 0, 0, 0);
}
__host__ __device__ constexpr int min_c(int a, int b) { return a < b ? a : b; }
template<int V> using IC = std::integral_constant<int, V>;

#define CT(slot) do {} while (0)
#define PT(slot) do {} while (0)

template<int MAP>
__global__ void __cluster_dims__(2, 1, 1) __launch_bounds__(384, 1)
fnet_moe_kernel(const __grid_constant__ Params p) {
  constexpr int NX = MAP == 0 ? NX0 : 256;
  constexpr int G1_BYTES = A_BYTES + NX * 128;
  uint32_t sb;
  asm volatile("mov.u32 %0, %1;" : "=r"(sb) : "r"(smem_u32(smem_raw)));
  const int m = blockIdx.x & 1;
  int tau, eps;
  bool helper = false;
  if (MAP == 0) {
    uint32_t smid;
    asm volatile("mov.u32 %0, %%smid;" : "=r"(smid));
    const int c = smid >> 1, e7 = ((c - 32) * 37) >> 8;
    helper = c == 60 || c == 61;
    tau = c < 32 ? (c & 7) : (c < 60 ? c - 31 - 7 * e7 : 0);
    eps = c < 32 ? (c >> 3) : (c < 60 ? 4 + e7 : c - 58);
  } else {
    tau = (blockIdx.x >> 1) & 7; eps = blockIdx.x >> 4;
  }
  const int cid = tau * 16 + eps * 2 + m;
  const bool moe = tau > 0;
  auto BAR = [&](int i) { return sb + OFF_BAR + 8 * i; };
  const CUtensorMap* tmD = m ? &p.tmD1 : &p.tmD0;
  const uint64_t pol_ef = policy_evict_first();
#define LOAD_STREAM(d, tm, bar, c0, c1) tma_load_2d_hint(d, tm, bar, c0, c1, pol_ef)
#define LOAD_W(d, tm, bar, c0, grp) tma_load_4d_hint(d, tm, bar, c0, (grp) * 32, pol_ef)
  auto helper_load = [&](int k) {
    const uint32_t sa = sb + slot_of(k) * ST_BYTES, bar = BAR(B_FULL + slot_of(k));
    const CUtensorMap* tm = eps == 3 ? &p.tmD1 : &p.tmD0;
    tma_load_5d(sa, &p.tmXh, bar, (k & 15) * 64, 0);
    tma_load_2d(sa + A_BYTES, tm, bar, (k & 15) * 64, m * 512 + (k >> 4) * 256);
    tma_load_2d(sa + A_BYTES + 16384, tm, bar, (k & 15) * 64, m * 512 + (k >> 4) * 256 + 128);
  };
  if (threadIdx.x < 32 && elect_one()) {
    mbar_init(BAR(B_FULL), 1);
    asm volatile("fence.mbarrier_init.release.cluster;" ::: "memory");
    if (!helper) {
      tma_load_2d(sb + A_BYTES, &p.tmX, BAR(B_FULL), 0, tau * 256);
      tma_load_2d(sb, tmD, BAR(B_FULL), 0, eps * 128);
    }
    PT(52);
#pragma unroll
    for (int k = 1; k < 4; k++) mbar_init(BAR(B_FULL + k), 1);
    asm volatile("fence.mbarrier_init.release.cluster;" ::: "memory");
#pragma unroll
    for (int k = 0; k < 4; k++) mbar_expect_tx(BAR(B_FULL + k), helper ? ST_BYTES : G1_BYTES);
    if (!helper) {
#pragma unroll
      for (int k = 1; k < 4; k++) {
        tma_load_2d(sb + k * ST_BYTES + A_BYTES, &p.tmX, BAR(B_FULL + k), k * 64, tau * 256);
        LOAD_STREAM(sb + k * ST_BYTES, tmD, BAR(B_FULL + k), k * 64, eps * 128);
      }
    } else {
#pragma unroll 1
      for (int k = 0; k < 4; k++) helper_load(k);
    }
    PT(0);
  }
  __syncwarp();
  const int warp = __shfl_sync(0xffffffffu, threadIdx.x >> 5, 0);
  if (warp == 8) {
    if (elect_one()) {
#pragma unroll
      for (int b = B_EMPTY; b < B_COUNT; b++)
        mbar_init(BAR(b), b < B_EPI ? 2 : (b == B_EPI || b == B_EPI0B) ? 4 : (b < B_STD || b == B_OUT) ? 8 : (b == B_STAT || b == B_XS) ? 3 : 1);
      asm volatile("fence.mbarrier_init.release.cluster;" ::: "memory");
      mbar_expect_tx(BAR(B_XCH), 32768);
      SM_(uint32_t, OFF_SEEN) = 0;
    }
  }
  __syncthreads();

  if (warp >= 8) {
    reg_dec<REG_P>();
    asm volatile("barrier.cluster.arrive.relaxed.aligned;" ::: "memory");
    const int abrow = m * 1024 + eps * 128;
    const int f0 = (cid - 16) * 32;
    const CUtensorMap* tmWM = m ? &p.tmWM1 : &p.tmWM0;
    auto side_first = [&](int k) {
      if (NX < 256 && k == MINI_LOAD_K) {
        static_assert(NX == 256 || (mr_k(NREG_H) == MINI_LOAD_K && (NREG_H & 1) == 1), "second half of the staging buffer must be free");
        mbar_wait(BAR(B_STD + 3), 0);
        uint32_t n = 0;
        while (!((*(volatile uint32_t*)&SM_(uint32_t, OFF_SEEN) >> (4 * tau + 1)) & 1) && ++n < SPIN_LIMIT * 16) {}
        if (elect_one()) {
          mbar_expect_tx(BAR(B_A20), 12288);
          tma_load_2d(sb + OFF_MINI, &p.tmAbM, BAR(B_A20), tau * 256 + 240, abrow);
          LOAD_W(sb + OFF_MINI + 4096, tmWM, BAR(B_A20), tau * 256 + 240, tau * 2 + m);
          LOAD_W(sb + OFF_MINI + 8192, tmWM, BAR(B_A20), tau * 256 + 240, tau * 2 + 1 - m);
        }
      }
    };
    auto side = [&](int k) {
      if (NX < 256 && k == MINI_PF_K && elect_one()) tma_prefetch_4d(tmWM, tau * 256 + 240, tau * 64 + (eps & 1) * 32);
      if (!moe) return;
      const int i = k - MR_K0, r6 = i / MR_P, u = i - MR_P * r6, h = 2 * r6 + (u >> 1);
      if (i >= 0 && u < 4 && h < NREG_H) {
        if (h < 2) mbar_wait(BAR(B_STD + 2 + h), 0);
        if (elect_one()) {
          if (!(u & 1)) mbar_expect_tx(BAR(B_MR + (h & 1)), 16384);
          LOAD_STREAM(sb + OFF_XCH + u * 8192, (u & 1) ? &p.tmU : &p.tmG, BAR(B_MR + (h & 1)), f0, h * 128);
        }
      }
      if (k >= 46 && elect_one()) {
        static_assert(mr_k(NREG_H + 1) <= 47 && MINI_K + 4 <= 46, "staging buffer must be free");
        LOAD_STREAM(sb + round_off(NREG_H + k - 46), &p.tmG, BAR(B_GU), f0, (NREG_H + k - 46) * 128);
        LOAD_STREAM(sb + round_off(NREG_H + k - 46) + 8192, &p.tmU, BAR(B_GU), f0, (NREG_H + k - 46) * 128);
      }
      if (k >= PF_K1 && !(k & 1) && elect_one()) {
        const int j = PF_N0 + ((k - PF_K1) >> 1);
        if (j < 8) tma_prefetch_2d(m ? &p.tmU : &p.tmG, f0, j * 128);
        else if (j < 12) asm volatile("cp.async.bulk.prefetch.L2.global [%0], %1;" :: "l"(p.wdown + (size_t)f0 * 1024 + (j - 8) * 8192), "r"(16384) : "memory");
      }
    };
    if (MAP == 0 && helper) {
      if (warp == 8) {
#pragma unroll 1
        for (int k = 4; k < 32; k++) {
          mbar_wait(BAR(B_EMPTY + slot_of(k)), (use_of(k) & 1) ^ 1);
          if (elect_one()) { mbar_expect_tx(BAR(B_FULL + slot_of(k)), ST_BYTES); helper_load(k); }
        }
      } else {
        const int i0 = threadIdx.x - 288, lane = threadIdx.x & 31, col0 = (eps - 2) * 8 + m * 4;
        __nanosleep(HELPER_NS);
        const uint32_t tag = ld_relaxed32(&p.s->epoch) + 1;
        if (i0 < 8) pkt_st128(&p.s->hflag[col0 * 2 + i0], 0, 0, 0, 0);
        SM_(uint32_t, OFF_TAG) = tag;
#pragma unroll 1
        for (int j0 = i0; j0 < 768; j0 += 384) {
          uint2 v[4]; uint32_t n = 0;
          while (true) {
#pragma unroll
            for (int z = 0; z < 4; z++) {
              const int j = j0 + 96 * z;
              v[z] = pkt_ld64(p.s->xstat + (j < 128 ? 256 * (j >> 4) + 240 + 2 * (j & 6) + ((j >> 2) & 2) + (j & 1)
                                          : j < 640 ? 2048 + col0 * 128 + j - 128 : (j - 640) * 16));
            }
            if (__all_sync(0xffffffffu, v[0].y == tag && v[1].y == tag && v[2].y == tag && v[3].y == tag) || ++n > SPIN_LIMIT) break;
            __nanosleep(300);
          }
#pragma unroll
          for (int z = 0; z < 4; z++) {
            const int j = j0 + 96 * z;
            if (j < 128) put_xstat(sb + OFF_RS, sb + OFF_XCH + 16384, j, v[z].x, eps - 2);
            else if (j < 640) put_dsum(sb + OFF_XCH, j - 128, __uint_as_float(v[z].x));
          }
        }
        fence_async_smem();
        __syncwarp();
        if (lane == 0) mbar_arrive(BAR(B_STAT));
      }
    } else if (warp == 8) {
      const CUtensorMap* tmW = m ? &p.tmW1 : &p.tmW0;
      const int gA = tau * 2 + m, gB = tau * 2 + 1 - m;
      auto wait_slot = [&](int k) {
        mbar_wait(BAR(B_EMPTY + slot_of(k)), (use_of(k) & 1) ^ 1);
        PT(64 + k);
      };
#pragma unroll 1
      for (int k = 4; k < 24; k++) {
        const int s = slot_of(k);
        const uint32_t sa = sb + s * ST_BYTES, sbb = sa + A_BYTES;
        const int kb = kblock(tau, k - 16);
        wait_slot(k);
        if (elect_one()) {
          mbar_expect_tx(BAR(B_FULL + s), k < 16 ? G1_BYTES : (k >> 1) == 9 ? B_BYTES : k == 20 ? ST_BYTES - 8192 : ST_BYTES);
          if (k < 16) {
            LOAD_STREAM(sa, tmD, BAR(B_FULL + s), k * 64, eps * 128);
            tma_load_2d(sbb, &p.tmX, BAR(B_FULL + s), k * 64, tau * 256);
          } else {
            LOAD_W(sbb, tmW, BAR(B_FULL + s), kb * 64, gA);
            LOAD_W(sbb + 16384, tmW, BAR(B_FULL + s), kb * 64, gB);
            if (k < 18) {
              tma_load_4d(sa, &p.tmXr, BAR(B_FULL + s), eps * 128, gA * 32 + s * 16);
              tma_load_4d(sa + 8192, &p.tmXr, BAR(B_FULL + s), eps * 128 + 64, gA * 32 + s * 16);
            }
          }
          if (k == PUB_K1) mbar_arrive(BAR(B_LATE));
          if (k >= WPF_K0 && k < WPF_K0 + WPF_N && (eps >> 1) == ((k - WPF_K0) & 3))
            tma_prefetch_4d(tmW, kblock(tau, k - WPF_K0) * 64, tau * 64 + (eps & 1) * 32);
          if (moe && k >= PF_K0 && k < PF_K0 + 2 * PF_N0 && !(k & 1)) tma_prefetch_2d(m ? &p.tmU : &p.tmG, f0, (k - PF_K0) * 64);
        }
      }
      uint32_t seen = 0;
#pragma unroll 1
      for (int k = 24; k < 48; k++) {
        const int s = slot_of(k);
        const uint32_t sa = sb + s * ST_BYTES, sbb = sa + A_BYTES;
        const int kb = kblock(tau, k - 16);
        const uint32_t need = (1u << kb) | ((kb & 3) == 3 ? 2u << (4 * tau) : 0u);
        wait_slot(k);
        side_first(k);
        if (elect_one()) {
          mbar_expect_tx(BAR(B_FULL + s), ST_BYTES);
          LOAD_W(sbb, tmW, BAR(B_FULL + s), kb * 64, gA);
          LOAD_W(sbb + 16384, tmW, BAR(B_FULL + s), kb * 64, gB);
        }
        uint32_t n = 0;
        while ((seen & need) != need && ++n < SPIN_LIMIT * 16) seen = *(volatile uint32_t*)&SM_(uint32_t, OFF_SEEN);
        if (elect_one()) tma_load_2d(sa, &p.tmAbL, BAR(B_FULL + s), kb * 64, abrow);
        side(k);
      }
      if (moe) {
        mbar_wait(BAR(B_EMPTY + 0), 1);
        if (elect_one()) { mbar_expect_tx(BAR(B_GU), (8 - NREG_H) * 16384); mbar_expect_tx(BAR(B_DN), 65536); }
#pragma unroll 1
        for (int i = 0; i < 10 - NREG_H; i++) {
          if (i == 3) mbar_wait(BAR(B_EMPTY + 1), 1);
          if (i == 4) {
            mbar_wait(BAR(B_EMPTY + 2), 1);
            mbar_wait(BAR(B_XCH), 0);
            PT(53);
          }
          const uint32_t dst = sb + late_off(i);
          if (elect_one()) {
            if (i < 6 - NREG_H) {
              LOAD_STREAM(dst, &p.tmG, BAR(B_GU), f0, (NREG_H + 2 + i) * 128);
              LOAD_STREAM(dst + 8192, &p.tmU, BAR(B_GU), f0, (NREG_H + 2 + i) * 128);
            } else {
#pragma unroll
              for (int b = 0; b < 4; b++) LOAD_STREAM(dst + b * 4096, &p.tmDn, BAR(B_DN), (4 * (i - 6 + NREG_H) + b) * 64, f0);
            }
          }
          const long long t0 = clock64();
          while (i < 9 - NREG_H && clock64() - t0 < MOE_PACE_CLK) {}
        }
      }
      const int lane = threadIdx.x & 31;
      mbar_wait(BAR(B_OUT), 0);
      const uint32_t km = SM_(uint32_t, OFF_WKEY + (lane & 7) * 8);
      const uint32_t bk = __reduce_max_sync(0xffffffffu, km);
      const int ww = __ffs(__ballot_sync(0xffffffffu, km == bk)) - 1;
#pragma unroll 1
      for (int i = 1; i <= 8; i++) {
        const int W = (ww + i) & 7;
        if (i == 8) {
          mbar_wait(BAR(B_XS), 0);
          if (SM_(uint32_t, OFF_KV) == bk) {
#pragma unroll 2
            for (int j = lane; j < 256; j += 32) {
              const int rho = j >> 4, row = row_of(gA * 128 + 32 * (W >> 1) + 8 * ((rho & 7) >> 1) + 4 * (W & 1) + 2 * (rho >> 3) + (rho & 1));
              const uint4 v = lds128_v(sb + OFF_OUT + (j & 8) * 2048 + (16 * W + rho) * 128 + (((j ^ rho) & 7) << 4));
              if (row != 0xFFFF - (int)(bk & 0xFFFFu))
                asm volatile("st.global.v4.b32 [%0], {%1, %2, %3, %4};" :: "l"(p.out + (size_t)row * 1024 + eps * 128 + (j & 15) * 8), "r"(v.x), "r"(v.y), "r"(v.z), "r"(v.w));
            }
            break;
          }
        }
        if (lane == 0) {
          tma_store_5d(&p.tmOut, sb + OFF_OUT + W * 2048, eps * 128, row_of(gA * 128 + 32 * (W >> 1) + 4 * (W & 1)));
          tma_store_5d(&p.tmOut, sb + OFF_OUT + 16384 + W * 2048, eps * 128 + 64, row_of(gA * 128 + 32 * (W >> 1) + 4 * (W & 1)));
        }
        const long long t0 = clock64();
        while (i < 7 && clock64() - t0 < OUT_PACE_CLK) {}
      }
      if (lane == 0) { bulk_commit(); bulk_wait_all(); }
      PT(22);
    } else {
      const int a = warp - 9;
      const int lane = threadIdx.x & 31;
      auto stage = [&](const bf16* src, int g) {
        if (elect_one()) {
          mbar_expect_tx(BAR(B_AUX + g), 16384);
          bulk_load(sb + OFF_XCH + g * 16384, src + g * 8192, 16384, BAR(B_AUX + g));
        }
      };
      uint32_t tag = 0;
      mbar_wait(BAR(B_FULL + AUX_AFTER), 0);
      if (a == 0) PT(1);
      if (a == 1) mbar_wait(BAR(B_AUX + 0), 0);
      if (a < 2) stage(p.x + (size_t)cid * 16 * 1024, a);
#pragma unroll 1
      for (int it = 0; it < 4; it++) {
        const int g = it & 1;
        mbar_wait(BAR(B_AUX + g), it >> 1);
        if (a == 0) PT(2 + it);
        if (it == 2) tag = ld_relaxed32(&p.s->epoch) + 1;
        if (it == 2 && a == 2 && lane < 16) asm volatile("prefetch.global.L2 [%0];" :: "l"(p.wr + lane * 64));
        const uint32_t ad = sb + OFF_XCH + g * 16384 + (lane >> 2) * 2048;
        float s0 = 0.f, s1 = 0.f, q0 = 0.f, q1 = 0.f;
        auto row = [&](auto sq) {
#pragma unroll
          for (int i = 0; i < 11; i++) {
            if (i == 10 && a == 2) break;
            const uint4 v = lds128_v(ad + (((a * 44 + 4 * i + lane) & 127) << 4));
            const uint32_t ww[4] = {v.x, v.y, v.z, v.w};
#pragma unroll
            for (int z = 0; z < 4; z++) {
              const float d0 = bf_lo(ww[z]), d1 = bf_hi(ww[z]);
              s0 += d0; s1 += d1;
              if (decltype(sq)::value) { q0 = fmaf(d0, d0, q0); q1 = fmaf(d1, d1, q1); }
            }
          }
        };
        if (it < 2) row(IC<1>()); else row(IC<0>());
        s0 += s1; q0 += q1;
#pragma unroll
        for (int o = 1; o < 4; o <<= 1) { s0 += __shfl_xor_sync(0xffffffffu, s0, o); q0 += __shfl_xor_sync(0xffffffffu, q0, o); }
        if ((lane & 3) == 0) SM_(float2, OFF_PUB + a * 256 + it * 64 + (lane >> 2) * 8) = make_float2(s0, q0);
        if (it != 2) bar_sync(NB_AUX, 96);
        if (it < 2 && a == 2) stage(cid < 64 ? p.Dre + (size_t)cid * 16 * 1024 : p.Dim + (size_t)(cid - 64) * 16 * 1024, g);
      }
      if (a == 1) {
        const float2 v0 = SM_(float2, OFF_PUB + lane * 8), v1 = SM_(float2, OFF_PUB + 256 + lane * 8), v2 = SM_(float2, OFF_PUB + 512 + lane * 8);
        const float s = v0.x + v1.x + v2.x, mean = s * (1.f / 1024.f);
        const float rs = rcp_fast(ln_sd((v0.y + v1.y + v2.y) * (1.f / 1024.f) - mean * mean));
        pkt_st64((lane < 16 ? p.s->xstat : p.s->dsum) + cid * 16 + (lane & 15), lane < 16 ? pack_bf16(rs, mean) : __float_as_uint(s), tag);
        PT(6);
      }
      if (a == 2) {
        float s = 0.f;
#pragma unroll
        for (int q = 0; q < 4; q++) {
          const uint4 v = ldg_nc128(p.wr + (q * 32 + lane) * 8);
          s += ((bf_lo(v.x) + bf_hi(v.x)) + (bf_lo(v.y) + bf_hi(v.y))) + ((bf_lo(v.z) + bf_hi(v.z)) + (bf_lo(v.w) + bf_hi(v.w)));
          const int ch = q * 32 + lane - eps * 16;
          if (ch >= 0 && ch < 16) {
            SM_(uint32_t, OFF_WR + ch * 4) = v.x; SM_(uint32_t, OFF_WR + 80 + ch * 4) = v.y;
            SM_(uint32_t, OFF_WR + 160 + ch * 4) = v.z; SM_(uint32_t, OFF_WR + 240 + ch * 4) = v.w;
          }
        }
        s = warp_sum(s);
        if (lane == 0) { SM_(float, OFF_WSUM) = s; SM_(uint32_t, OFF_TAG) = tag; }
      }
      if (a < 2) __nanosleep(GATHER_NS);
      {
        const int i0 = a * 32 + lane;
        uint2 v[3], c0, c1; uint32_t n = 0;
        const uint2* dp = &p.s->dsum[abrow];
        while (true) {
#pragma unroll
          for (int q = 0; q < 3; q++) v[q] = pkt_ld64(&p.s->xstat[tau * 256 + min(i0 + 96 * q, 255)]);
          c0 = pkt_ld64(dp + i0); c1 = pkt_ld64(dp + min(i0 + 96, 127));
          if (__all_sync(0xffffffffu, v[0].y == tag && v[1].y == tag && v[2].y == tag && c0.y == tag && c1.y == tag) || ++n > SPIN_LIMIT) break;
          __nanosleep(200);
        }
#pragma unroll
        for (int q = 0; q < 3; q++) put_xstat(sb + OFF_RS, sb + OFF_EXB, min(i0 + 96 * q, 255), v[q].x, m);
        put_dsum(sb + OFF_EXA, i0, __uint_as_float(c0.x));
        put_dsum(sb + OFF_EXA, min(i0 + 96, 127), __uint_as_float(c1.x));
        fence_async_smem();
      }
      __syncwarp();
      if (lane == 0) mbar_arrive(BAR(B_STAT));
      if (a == 0) PT(7);
      if (a == 0) {
        const int sg = (lane >> 2) == tau ? sigma_of(tau, 0) : lane >> 2;
        const uint32_t* flg = reinterpret_cast<const uint32_t*>(&p.s->abflag[((eps * 2 + m) * 8 + sg) * 2]) + ((lane >> 2) == tau ? 4 : lane & 3);
        if (NX < 256 && lane == 4 * tau + 1) flg = reinterpret_cast<const uint32_t*>(&p.s->hflag[(m * 8 + eps) * 2]);
        uint32_t seen = 0;
        auto until = [&](int tile) {
          uint32_t n = 0;
          while (!((seen >> (4 * tile)) & 1) && ++n < SPIN_LIMIT) seen = __ballot_sync(0xffffffffu, ld_relaxed32(flg) == tag);
        };
        const int s0 = sigma_of(tau, 0), s1 = sigma_of(tau, 1), s2 = sigma_of(tau, 2), s3 = sigma_of(tau, 3);
        mbar_wait(BAR(B_EPI), 0);
        mbar_wait(BAR(B_FULL + 0), 0);
        mbar_wait(BAR(B_FULL + 1), 0);
        if (elect_one()) mbar_expect_tx(BAR(B_A20), 8192);
        mbar_wait(BAR(B_STDA), 0);
        PT(49);
        until(tau);
        mbar_wait(BAR(B_EPI0B), 0);
        PT(48);
        if (elect_one()) tma_load_2d(sb + OFF_XCH, &p.tmAbS, BAR(B_FULL + 0), s0 * 256, abrow);
        mbar_wait(BAR(B_FULL + 2), 0);
        mbar_wait(BAR(B_STD + 0), 0);
        until(s0);
        PT(16);
        if (elect_one()) tma_load_2d(sb + OFF_XCH + 8192, &p.tmAbS, BAR(B_A20), s0 * 256, abrow + 64);
        until(s1);
        PT(17);
        if (elect_one()) tma_load_2d(sb + OFF_XCH + 16384, &p.tmAbL, BAR(B_FULL + 1), s1 * 256, abrow);
        until(s2);
        PT(18);
        if (elect_one()) {
          tma_load_2d(sb + 2 * ST_BYTES, &p.tmAbL, BAR(B_FULL + 2), s2 * 256, abrow);
          mbar_arrive(BAR(B_PUB1));
        }
        until(s3);
        mbar_wait(BAR(B_FULL + 3), 0);
        mbar_wait(BAR(B_STD + 1), 0);
        PT(19);
        if (elect_one()) tma_load_2d(sb + 3 * ST_BYTES, &p.tmAbL, BAR(B_FULL + 3), s3 * 256, abrow);
        uint32_t n = 0;
        while (true) {
          asm volatile("fence.proxy.async.global;" ::: "memory");
          *(volatile uint32_t*)&SM_(uint32_t, OFF_SEEN) = seen;
          if (seen == 0xFFFFFFFFu || ++n > SPIN_LIMIT) break;
          seen = __ballot_sync(0xffffffffu, ld_relaxed32(flg) == tag);
          __nanosleep(100);
        }
      } else {
        uint32_t* flag = reinterpret_cast<uint32_t*>(&p.s->abflag[((eps * 2 + m) * 8 + tau) * 2]);
        mbar_wait(BAR(a == 1 ? B_EPI : B_EPI0B), 0);
        if (a == 1) PT(8);
        if (lane == 0) {
          tma_store_2d(&p.tmAbS, sb + chunk_off(0, a - 1), tau * 256, abrow + (a - 1) * 64);
          bulk_commit();
          bulk_wait_all();
        }
        if (a == 2) mbar_wait(BAR(B_STDA), 0);
        if (lane == 0) {
          st_relaxed32(flag + (a == 1 ? 4 : 0), tag);
          mbar_arrive(BAR(a == 1 ? B_STDA : B_STD));
        }
        if (a == 2) PT(12);
        if (a == 1) {
          mbar_wait(BAR(B_EPI + 1), 0);
          mbar_wait(BAR(B_LATE), 0);
          mbar_wait(BAR(B_PUB1), 0);
          PT(9);
          if (lane == 0) {
            tma_store_2d(&p.tmAbS, sb + chunk_off(1, 0), tau * 256 + 64, abrow);
            tma_store_2d(&p.tmAbS, sb + chunk_off(1, 1), tau * 256 + 64, abrow + 64);
            bulk_commit();
            bulk_wait_all();
            st_relaxed32(flag + 1, tag);
            mbar_arrive(BAR(B_STD + 1));
          }
          PT(13);
        }
        auto copy_out = [&](int c) {
          mbar_wait(BAR(B_EPI + c), 0);
          PT(8 + c);
          bf16* dst = p.s->abT + (size_t)(abrow + (lane >> 3)) * 2048 + tau * 256 + c * 64 + (lane & 7) * 8;
          const uint32_t src = sb + chunk_off(c, 0) + (lane >> 3) * 128 + (((lane & 7) ^ (lane >> 3)) << 4);
          const uint32_t on = c * 64 + (lane & 7) * 8 < NX;
#pragma unroll 4
          for (int i = 0; i < 32; i++) {
            const uint4 v = lds128_v((src ^ ((i & 1) << 6)) + i * 512);
            asm volatile("{\n.reg .pred p;\nsetp.ne.b32 p, %5, 0;\n@p st.global.v4.b32 [%0], {%1, %2, %3, %4};\n}\n"
                         :: "l"(dst + i * 4 * 2048), "r"(v.x), "r"(v.y), "r"(v.z), "r"(v.w), "r"(on));
          }
          __syncwarp();
          if (lane == 0) mbar_arrive(BAR(B_STD + c));
        };
        if (a == 2) {
#pragma unroll 1
          for (int c = 2; c < 4; c++) copy_out(c);
          asm volatile("fence.acq_rel.gpu;" ::: "memory");
          __syncwarp();
          if (lane < 2) st_relaxed32(flag + 2 + lane, tag);
          PT(15);
        }
      }
      {
        mbar_wait(BAR(B_LATE), 1);
        const int grp = tau * 2 + m;
#pragma unroll 1
        for (int i = a; i < 14; i += 3) {
          uint4* dst = i < 8 ? &p.s->ypart[cid * 256 + i * 32 + lane] : i < 12 ? &p.s->hstat[(grp * 8 + eps) * 128 + (i - 8) * 32 + lane]
                     : i == 12 ? &p.s->cand[grp * 256 + eps * 32 + lane] : &p.s->key[(((lane >> 1) & 7) * 16 + grp) * 2 + (lane & 1)];
          if (i < 13 || eps == 0) pkt_st128(dst, 0, 0, 0, 0);
          __nanosleep(200);
        }
        __syncwarp();
        if (lane == 0) mbar_arrive(BAR(B_STAT));
      }
      {
        const uint4* kp = &p.s->key[(tau * 16 + (lane & 15)) * 2];
        const int i0 = a * 32 + lane;
        mbar_wait(BAR(B_KEY), 0);
        if (a == 0) PT(43);
        uint4 kq = pkt_ld128(kp), cv[3] = {};
        uint32_t n = 0, kv;
        int gspec = -1;
        while (true) {
          const bool ok = kq.y == tag && kq.w == tag;
          kv = __reduce_max_sync(0xffffffffu, ok ? kq.x : 0u);
          const int gs = group_of(0xFFFF - (int)(kv & 0xFFFFu));
          const bool cok = gs == gspec && cv[0].y == tag && cv[0].w == tag && cv[1].y == tag && cv[1].w == tag && cv[2].y == tag && cv[2].w == tag;
          if (__all_sync(0xffffffffu, ok && cok) || ++n > SPIN_LIMIT) break;
          if (!ok) kq = pkt_ld128(kp);
          const bool spec = __popc(__ballot_sync(0xffffffffu, ok)) >= 2 * SPEC_MIN;
          if (!cok && spec) {
#pragma unroll
            for (int i = 0; i < 3; i++) cv[i] = pkt_ld128(&p.s->cand[gs * 256 + min(i0 + 96 * i, 255)]);
          }
          if (spec) gspec = gs;
        }
        if (a == 0) PT(45);
        const uint32_t ms = __shfl_sync(0xffffffffu, kq.z, gspec);
        const uint32_t nm = ((ms & 0xFFFFu) ^ 0x8000u) * 0x10001u;
        const float is = rcp_fast(bf_hi(ms));
#pragma unroll
        for (int i = 0; i < 3; i++) {
          const int j = min(i0 + 96 * i, 255);
          SM_(uint2, OFF_XSEL + j * 8) = make_uint2(norm2(cv[i].x, nm, is), norm2(cv[i].z, nm, is));
        }
#pragma unroll
        for (int i = 0; i < 3; i++) SM_(uint2, OFF_HSEL + min(i0 + 96 * i, 255) * 8) = make_uint2(cv[i].x, cv[i].z);
        SM_(uint32_t, OFF_KV) = kv;
        __syncwarp();
        if (lane == 0) mbar_arrive(BAR(B_XS));
      }
    }
    asm volatile("barrier.cluster.wait.aligned;" ::: "memory");
  } else {
    reg_inc<REG_C>();
    const int tid = __shfl_sync(0xffffffffu, threadIdx.x, threadIdx.x & 31), lane = tid & 31;
    const int w = warp >> 2, wi = warp & 3, t = tid & 127;
    const int g = lane >> 2, q = lane & 3;
    const int turn_me = NB_TURN0 + w, turn_other = NB_TURN1 - w;
    auto release = [&](int s) { if (t == 0) mbar_arrive(BAR(B_EMPTY + s)); };
    if (MAP == 0 && helper) {
      asm volatile("barrier.cluster.arrive.relaxed.aligned;" ::: "memory");
      float s0[64], s1[64];
#pragma unroll
      for (int i = 0; i < 64; i++) { s0[i] = 0.f; s1[i] = 0.f; }
      if (w == 1) bar_arrive(NB_TURN0, 256);
      uint32_t o[32][2] = {};
      const int col = (eps - 2) * 8 + m * 4 + w;
      auto put = [&](auto tc, uint32_t buf) {
        constexpr int tl = decltype(tc)::value;
#pragma unroll
        for (int i = 0; i < 4; i++)
          smem_at<uint2>(buf + ((i >> 1) * 64 + wi * 16 + (i & 1) * 8 + g) * 32 + ((q * 8) ^ ((g & 4) << 2))) = make_uint2(o[8 * i + tl][0], o[8 * i + tl][1]);
      };
      auto publish = [&](int c) { if (t == 0) { bulk_wait_all(); st_relaxed32(&p.s->hflag[c * 2], SM_(uint32_t, OFF_TAG)); } };
#pragma unroll 1
      for (int pass = 0; pass < 2; pass++) {
#pragma unroll 1
        for (int k = 16 * pass; k < 16 * pass + 16; k++) {
          const int s = slot_of(k);
          mbar_wait(BAR(B_FULL + s), use_of(k) & 1);
          bar_sync(turn_me, 256);
          const uint64_t da = make_desc(sb + s * ST_BYTES + A_BYTES + w * 16384), db = make_desc(sb + s * ST_BYTES);
          wgmma_fence();
#pragma unroll
          for (int kk = 0; kk < 4; kk++) {
            wgmma_n128(s0, da + kk * 2, db + kk * 2, kk > 0 || (k & 15));
            wgmma_n128(s1, da + 512 + kk * 2, db + kk * 2, kk > 0 || (k & 15));
          }
          wgmma_commit();
          if (k < 31 || w == 0) bar_arrive(turn_other, 256);
          if (pass && !(k & 1)) {
            const uint32_t buf = sb + OFF_XCH + 20480 + w * 4096;
            static_for<8>([&](auto ic) { if (k == 16 + 2 * decltype(ic)::value) put(ic, buf); });
            fence_async_smem();
            bar_sync(NB_WG0 + w, 128);
            if (t == 0) { tma_store_2d(&p.tmAbM, buf, (k - 16) * 128 + 240, col * 128); bulk_commit(); }
          }
          wgmma_wait0();
          release(s);
          if ((k & 1) && t == 0) asm volatile("cp.async.bulk.wait_group.read 0;" ::: "memory");
        }
        if (pass) publish(col);
        mbar_wait(BAR(B_STAT), 0);
        wgmma_fence();
        wgmma_n128(s0, make_desc_noswz(sb + OFF_XCH + pass * 8192 + w * 4096), make_desc_noswz(sb + OFF_XCH + 16384));
        wgmma_n128(s1, make_desc_noswz(sb + OFF_XCH + pass * 8192 + w * 4096 + 2048), make_desc_noswz(sb + OFF_XCH + 16384));
        wgmma_commit();
        uint4 rs[4];
#pragma unroll
        for (int i = 0; i < 4; i++) rs[i] = lds128_v(sb + OFF_RS + q * 144 + i * 16);
        wgmma_wait0();
        fence_acc(s0); fence_acc(s1);
#pragma unroll
        for (int i = 0; i < 32; i++) {
          const int tl = i & 7, hr = (i >> 3) & 1;
          const float* ac = (i >> 4) ? &s1[8 * tl + 2 * hr] : &s0[8 * tl + 2 * hr];
          o[i][0] = bmul2(pack_bf16(ac[0], ac[1]), (tl & 1) ? rs[tl >> 1].z : rs[tl >> 1].x);
          o[i][1] = bmul2(pack_bf16(ac[4], ac[5]), (tl & 1) ? rs[tl >> 1].w : rs[tl >> 1].y);
        }
      }
      static_for<8>([&](auto ic) { put(ic, sb + (w * 8 + decltype(ic)::value) * 4096); });
      fence_async_smem();
      bar_sync(NB_WG0 + w, 128);
      if (t == 0) {
#pragma unroll 1
        for (int i = 0; i < 8; i++) tma_store_2d(&p.tmAbM, sb + (w * 8 + i) * 4096, i * 256 + 240, (col + 2) * 128);
        bulk_commit();
      }
      publish(col + 2);
      asm volatile("barrier.cluster.wait.aligned;" ::: "memory");
      return;
    }
    float acc[128], a1[NX / 2];
#pragma unroll
    for (int i = 0; i < NX / 2; i++) a1[i] = 0.f;
    if (w == 1) bar_arrive(NB_TURN0, 256);
    auto kstep = [&](auto& d, int k, bool first, bool a_in_xch = false, bool mini = false) {
      const int s = slot_of(k);
      mbar_wait(BAR(B_FULL + s), use_of(k) & 1);
      CT(64 + k);
      bar_sync(turn_me, 256);
      const uint64_t da = make_desc(sb + (a_in_xch ? OFF_XCH + s * 16384 : s * ST_BYTES) + w * 8192), db = make_desc(sb + s * ST_BYTES + A_BYTES);
      wgmma_fence();
      wgmma_g1(d, da, db, !first);
#pragma unroll
      for (int kk = 1; kk < 4; kk++) wgmma_g1(d, da + kk * 2, db + kk * 2, 1);
      wgmma_commit();
      if (mini) {
        CT(29);
        mbar_wait(BAR(B_A20), 1);
        CT(30);
        wgmma_fence();
        wgmma_g1(d, make_desc_32b(sb + OFF_MINI + w * 2048), make_desc_32b(sb + OFF_MINI + 4096), 1);
        wgmma_commit();
      }
      bar_arrive(turn_other, 256);
    };
    auto kdone = [&](int k) { wgmma_wait0(); release(slot_of(k)); };
    auto wgmma_wait1 = [&]() { asm volatile("wgmma.wait_group.sync.aligned 1;" ::: "memory"); };

#pragma unroll 1
    for (int k = 0; k < 14; k++) {
      kstep(a1, k, k == 0);
      if (k == 0) CT(0);
      if (k == 8 && warp == 2 && lane < 2) pkt_st128(&p.s->abflag[((eps * 2 + m) * 8 + tau) * 2 + lane], 0, 0, 0, 0);
      kdone(k);
    }
    uint32_t R[64];
    uint32_t tag;
    {
      const uint32_t rsa = sb + OFF_RS + q * 144;
      const uint64_t da2 = make_desc(sb + 2 * ST_BYTES + w * 8192), db2 = make_desc(sb + 2 * ST_BYTES + A_BYTES);
      const uint64_t da3 = make_desc(sb + 3 * ST_BYTES + w * 8192), db3 = make_desc(sb + 3 * ST_BYTES + A_BYTES);
      mbar_wait(BAR(B_FULL + 2), 1);
      CT(64 + 14);
      bar_sync(turn_me, 256);
      wgmma_fence();
#pragma unroll
      for (int kk = 0; kk < 4; kk++) wgmma_g1(a1, da2 + kk * 2, db2 + kk * 2, 1);
      wgmma_commit();
      mbar_wait(BAR(B_FULL + 3), 1);
      CT(64 + 15);
      wgmma_fence();
      wgmma_g1(a1, da3, db3, 1);
      wgmma_g1(a1, da3 + 2, db3 + 2, 1);
      wgmma_commit();
      mbar_wait(BAR(B_STAT), 0);
      tag = SM_(uint32_t, OFF_TAG);
#pragma unroll
      for (int i = 0; i < 8; i++) { const uint4 v = lds128_v(rsa + i * 16); R[8 * i] = v.x; R[8 * i + 2] = v.y; R[8 * i + 4] = v.z; R[8 * i + 6] = v.w; }
      wgmma_wait1();
      release(2);
      wgmma_fence();
      wgmma_g1(a1, da3 + 4, db3 + 4, 1);
      wgmma_g1(a1, da3 + 6, db3 + 6, 1);
      wgmma_g1(a1, make_desc_noswz(sb + OFF_EXA + w * 2048), make_desc_noswz(sb + OFF_EXB), 1);
      wgmma_commit();
      bar_arrive(turn_other, 256);
      kdone(15);
      mbar_wait(BAR(B_STAT), 0);
    }
    fence_acc(a1);
    CT(1);
    auto pack = [&](auto cc) {
      constexpr int c = decltype(cc)::value;
#pragma unroll
      for (int j = 8 * c; j < min_c(8 * c + 8, NX / 8); j++) {
        const uint32_t rs = R[2 * j];
        const float* ac = &a1[4 * j];
        R[2 * j] = bmul2(pack_bf16(ac[0], ac[1]), rs);
        R[2 * j + 1] = bmul2(pack_bf16(ac[2], ac[3]), rs);
      }
    };
    auto put_chunk = [&](auto cc) {
      constexpr int c = decltype(cc)::value;
      const int rho = 16 * wi + (lane & 15);
#pragma unroll
      for (int j = 8 * c; j < min_c(8 * c + 8, NX / 8); j += 2) {
        const int chunk = (j & 7) + (lane >> 4);
        stsm_x4(sb + chunk_off(c, w) + rho * 128 + ((chunk ^ (lane & 7)) << 4), R[2 * j], R[2 * j + 1], R[2 * j + 2], R[2 * j + 3]);
      }
    };
    auto staged = [&](int bar) {
      fence_async_smem();
      __syncwarp();
      if (lane == 0) mbar_arrive(BAR(bar));
    };
    auto mma_rs = [&](auto cc, auto k0, auto k1) {
      constexpr int c = decltype(cc)::value;
      const uint64_t db = make_desc(sb + c * ST_BYTES + A_BYTES);
#pragma unroll
      for (int kk = decltype(k0)::value; kk < decltype(k1)::value; kk++)
        wgmma_n256_rs(acc, R[16 * c + 4 * kk], R[16 * c + 4 * kk + 1], R[16 * c + 4 * kk + 2], R[16 * c + 4 * kk + 3], db + kk * 2, c + kk > 0);
      wgmma_commit();
    };
    auto kdone_x = [&](int k, auto ic) {
      constexpr int i = decltype(ic)::value;
      uint32_t r[8];
#pragma unroll
      for (int z = 0; z < 2; z++) {
        const int tr = 32 * (i & 1) + 16 * z + 8 * (lane >> 4) + (lane & 7), chunk = 2 * wi + ((lane >> 3) & 1);
        ldsm_x4_t(sb + (i >> 1) * ST_BYTES + w * 8192 + tr * 128 + ((chunk ^ (lane & 7)) << 4), r[4 * z], r[4 * z + 1], r[4 * z + 2], r[4 * z + 3]);
      }
      float f[16];
#pragma unroll
      for (int z = 0; z < 8; z++) { f[2 * z] = bf_lo(r[z]); f[2 * z + 1] = bf_hi(r[z]); }
#pragma unroll
      for (int z = 0; z < 16; z++) asm volatile("" : "+f"(f[z]));
      kdone(k);
#pragma unroll
      for (int z = 0; z < 16; z++) asm volatile("add.f32 %0, %0, %1;" : "+f"(acc[16 * i + z]) : "f"(f[z]));
    };
    pack(IC<0>());
    put_chunk(IC<0>());
    staged(w ? B_EPI0B : B_EPI);
    mbar_wait(BAR(B_STAT), 0);
    CT(21);
    pack(IC<1>());
    pack(IC<2>());
    pack(IC<3>());
#pragma unroll
    for (int i = 16; i < NX / 4; i++) asm volatile("" : "+r"(R[i]));
#pragma unroll
    for (int i = 0; i < 128; i++) asm volatile("" : "=f"(acc[i]));
    mbar_wait(BAR(B_FULL + 0), 0);
    CT(2);
    CT(64 + 16);
    bar_sync(turn_me, 256);
    wgmma_fence();
    mma_rs(IC<0>(), IC<0>(), IC<4>());
    mbar_wait(BAR(B_FULL + 1), 0);
    CT(64 + 17);
    wgmma_fence();
    mma_rs(IC<1>(), IC<0>(), IC<2>());
    wgmma_wait1();
    release(0);
    mma_rs(IC<1>(), IC<2>(), IC<4>());
    bar_arrive(turn_other, 256);
    kdone_x(17, IC<0>());
    static_for<2>([&](auto ic) {
      constexpr int c = 2 + decltype(ic)::value;
      mbar_wait(BAR(B_FULL + c), 0);
      CT(64 + 16 + c);
      bar_sync(turn_me, 256);
      wgmma_fence();
      mma_rs(IC<c>(), IC<0>(), IC<min_c(4, NX / 16 - 4 * c)>());
      bar_arrive(turn_other, 256);
      if (c == 2) { put_chunk(IC<1>()); staged(B_EPI + 1); }
      kdone_x(16 + c, IC<c - 1>());
    });
#pragma unroll 1
    for (int k = 20; k < 23; k++) {
      if (w == 1) mbar_wait(BAR(B_A20), 0);
      kstep(acc, k, false, k < 22);
      if (k == 20) {
        kdone_x(k, IC<3>());
      } else {
        if (k == 21) put_chunk(IC<2>()); else put_chunk(IC<3>());
        __syncwarp();
        if (lane == 0) mbar_arrive(BAR(B_EPI + k - 19));
        kdone(k);
      }
    }
    uint32_t wf[32][4];
    auto load_wf = [&](auto hc) {
      constexpr int h = decltype(hc)::value;
      const int d = w * 64 + (lane >> 4) * 8 + (lane & 7);
      const uint32_t ad = sb + round_off(h) + (lane & 8) * 1024 + d * 64 + ((wi ^ ((lane >> 1) & 3)) << 4);
#pragma unroll
      for (int i = 0; i < 4; i++) ldsm_x4_t(ad + i * 1024, wf[4 * h + i][0], wf[4 * h + i][1], wf[4 * h + i][2], wf[4 * h + i][3]);
    };
    auto load_wf_rest = [&]() { static_for<8 - NREG_H>([&](auto ic) { load_wf(IC<NREG_H + decltype(ic)::value>()); }); };
#pragma unroll
    for (int i = 0; i < 4 * NREG_H; i++) { wf[i][0] = 0; wf[i][1] = 0; wf[i][2] = 0; wf[i][3] = 0; }
    const int grp = tau * 2 + m;
#pragma unroll 1
    for (int k = 23; k < 46; k++) {
      kstep(acc, k, false, false, NX < 256 && k == MINI_K);
      if (moe) {
        static_for<NREG_H>([&](auto hc) {
          constexpr int h = decltype(hc)::value;
          if (k == mr_k(h) + 1) { mbar_wait(BAR(B_MR + (h & 1)), (h >> 1) & 1); CT(32 + h); load_wf(hc); }
        });
      }
      if (k == RESET_K && tid == 0) mbar_arrive(BAR(B_LATE));
      kdone(k);
    }
    asm volatile("barrier.cluster.arrive.relaxed.aligned;" ::: "memory");
    mbar_wait(BAR(B_STAT), 1);
    uint32_t wa[16][2];
    uint32_t cd = code_of(tag);
    uint4* hp_pub = &p.s->hstat[(grp * 8 + eps) * 128 + warp * 16 + g];
    const uint4* hp_poll = &p.s->hstat[(grp * 8 + 2 * q) * 128 + warp * 16 + g];
    const uint32_t vec_off = (2 * wi) * 512 + q * 128 + ((g ^ (2 * q)) << 4);
    {
      float as[64], ak[64];
      fence_acc(acc);
#pragma unroll
      for (int i = 0; i < 64; i++) asm volatile("mov.b32 %0, %1;" : "=f"(as[i]) : "f"(acc[64 + i]));
#pragma unroll
      for (int i = 0; i < 64; i++) asm volatile("mov.b32 %0, %1;" : "=f"(ak[i]) : "f"(acc[i]));
      const uint64_t da1 = make_desc(sb + 2 * ST_BYTES + w * 8192), db1 = make_desc(sb + 2 * ST_BYTES + A_BYTES);
      const uint64_t da2 = make_desc(sb + 3 * ST_BYTES + w * 8192), db2 = make_desc(sb + 3 * ST_BYTES + A_BYTES);
      mbar_wait(BAR(B_FULL + 2), 1);
      CT(64 + 46);
      mbar_wait(BAR(B_FULL + 3), 1);
      CT(64 + 47);
      bar_sync(turn_me, 256);
      wgmma_fence();
#pragma unroll
      for (int kk = 0; kk < 4; kk++) wgmma_n128(as, da1 + kk * 2, db1 + 1024 + kk * 2);
#pragma unroll
      for (int kk = 0; kk < 4; kk++) wgmma_n128(as, da2 + kk * 2, db2 + 1024 + kk * 2);
      wgmma_commit();
      bar_arrive(turn_other, 256);
      const uint32_t rx = mapa(sb + OFF_PEER + w * 4096 + vec_off, 1 - m), rb = mapa(BAR(B_XCH), 1 - m);
      asm volatile("barrier.cluster.wait.aligned;" ::: "memory");
      CT(24);
      wgmma_wait0();
      fence_acc(as);
      CT(25);
      auto keep = [&]() {
        bar_sync(turn_me, 256);
        wgmma_fence();
#pragma unroll
        for (int kk = 0; kk < 4; kk++) wgmma_n128(ak, da1 + kk * 2, db1 + kk * 2);
        wgmma_commit();
#pragma unroll
        for (int kk = 0; kk < 4; kk++) wgmma_n128(ak, da2 + kk * 2, db2 + kk * 2);
        wgmma_commit();
        if (w == 0) bar_arrive(turn_other, 256);
      };
#pragma unroll
      for (int i = 0; i < 8; i++) {
        if (i == SEND_FIRST) keep();
        const float* ac = &as[16 * (i >> 1) + 2 * (i & 1)];
        st_async_v4(rx + (i >> 1) * 8192 + (i & 1) * 512, rb, pack_bf16(ac[0], ac[1]), pack_bf16(ac[4], ac[5]), pack_bf16(ac[8], ac[9]), pack_bf16(ac[12], ac[13]));
      }
      CT(26);
#pragma unroll
      for (int i = 0; i < 4; i++) {
        const uint4 v = lds128_v(sb + OFF_WR + q * 80 + i * 16);
        const uint32_t vv[4] = {v.x, v.y, v.z, v.w};
#pragma unroll
        for (int z = 0; z < 4; z++) {
          asm volatile("{\n.reg .pred p;\nsetp.ne.b32 p, %2, 0;\nselp.b32 %0, %1, 0x3F803F80, p;\n}" : "=r"(wa[4 * i + z][0]) : "r"(vv[z]), "r"(g & 1));
          asm volatile("{\n.reg .pred p;\nsetp.ne.b32 p, %2, 0;\nselp.b32 %0, %1, 0x3F803F80, p;\n}" : "=r"(wa[4 * i + z][1]) : "r"(vv[z]), "r"(g & 1));
        }
      }
      pin(cd); pin(hp_pub); pin(hp_poll);
      CT(27);
      wgmma_wait1();
      release(2);
      wgmma_wait0();
      fence_acc(ak);
      CT(3);
#pragma unroll
      for (int i = 0; i < 8; i++) {
        const float* ac = &ak[16 * (i >> 1) + 2 * (i & 1)];
        sts128(sb + (2 + (i >> 2)) * ST_BYTES + w * 8192 + ((i >> 1) & 1) * 4096 + (i & 1) * 512 + vec_off,
               pack_bf16(ac[0], ac[1]), pack_bf16(ac[4], ac[5]), pack_bf16(ac[8], ac[9]), pack_bf16(ac[12], ac[13]));
      }
    }
    uint32_t h[8][4];
    {
      const int qq = 2 * (warp & 1) + ((lane >> 3) & 1);
      const uint32_t lo = (lane >> 4) * 512 + qq * 128 + (((lane & 7) ^ (2 * qq)) << 4);
      bar_sync(NB_BOTH, 256);
#pragma unroll
      for (int ks = 0; ks < 8; ks++)
        ldsm_x4_t(sb + (2 + w) * ST_BYTES + (ks >> 2) * 8192 + (wi >> 1) * 4096 + (ks & 3) * 1024 + lo, h[ks][0], h[ks][1], h[ks][2], h[ks][3]);
      CT(28);
      mbar_wait_cluster(BAR(B_XCH), 0);
      CT(4);
      uint32_t r[8][4];
#pragma unroll
      for (int ks = 0; ks < 8; ks++) ldsm_x4_t(sb + OFF_PEER + (warp >> 1) * 8192 + ks * 1024 + lo, r[ks][0], r[ks][1], r[ks][2], r[ks][3]);
      float d[4][4] = {};
#pragma unroll
      for (int ks = 0; ks < 8; ks++) {
#pragma unroll
        for (int i = 0; i < 4; i++) {
          h[ks][i] = badd2(h[ks][i], r[ks][i]);
          mma1688(d[i], h[ks][i], wa[2 * ks + (i >> 1)][i & 1], h[ks][i]);
        }
      }
#pragma unroll
      for (int i = 0; i < 2; i++) {
        const float sq = (g & 1) ? d[i][1] + d[i + 2][1] : d[i][0] + d[i + 2][0];
        const float e0 = d[i][2] + d[i + 2][2], e1 = d[i][3] + d[i + 2][3];
        const float other = __shfl_xor_sync(0xffffffffu, (g & 1) ? e0 : e1, 4);
        if (q == (g >> 1)) pkt_st128(hp_pub + 8 * i, with_bit((g & 1) ? other : e0, cd), with_bit(sq, cd >> 1), __float_as_uint((g & 1) ? e1 : other), tag);
      }
    }
    CT(5);
    if (tid == 0) mbar_arrive(BAR(B_KEY));
    delay_clk<HOP1_DELAY>();
    float m_bf, sd, inv_sd, r_bf;
    uint4* key_pub = &p.s->key[((lane & 7) * 16 + grp) * 2];
    uint4* cand_pub = &p.s->cand[grp * 256 + eps * 32 + q];
    uint32_t trow_inv = 0xFFFFu - (uint32_t)row_of(grp * 128 + 32 * (warp >> 1) + 8 * (g >> 1) + 4 * (warp & 1) + (q & 2) + (g & 1));
    {
      uint4 u[4];
#pragma unroll
      for (int i = 0; i < 4; i++) u[i] = pkt_ld128(hp_poll + (i & 1) * 128 + (i >> 1) * 8);
      const float wsum = SM_(float, OFF_WSUM);
      pin(key_pub); pin(cand_pub); pin(trow_inv);
      uint32_t n = 0;
      while (true) {
        bool ok[4];
#pragma unroll
        for (int i = 0; i < 4; i++) ok[i] = u[i].w == tag && pair_code(u[i].x, u[i].y) == cd;
        const bool all = __all_sync(0xffffffffu, ok[0] && ok[1] && ok[2] && ok[3]);
        if (all || ++n > SPIN_LIMIT) break;
#pragma unroll
        for (int i = 0; i < 4; i++) pkt_ld128_if(u[i], hp_poll + (i & 1) * 128 + (i >> 1) * 8, !ok[i]);
      }
      CT(6);
      float a[3], b[3];
      a[0] = __uint_as_float(u[0].x & ~1u) + __uint_as_float(u[1].x & ~1u); b[0] = __uint_as_float(u[2].x & ~1u) + __uint_as_float(u[3].x & ~1u);
      a[1] = __uint_as_float(u[0].y & ~1u) + __uint_as_float(u[1].y & ~1u); b[1] = __uint_as_float(u[2].y & ~1u) + __uint_as_float(u[3].y & ~1u);
      a[2] = __uint_as_float(u[0].z) + __uint_as_float(u[1].z); b[2] = __uint_as_float(u[2].z) + __uint_as_float(u[3].z);
#pragma unroll
      for (int i = 0; i < 3; i++) {
        a[i] = ((q & 2) ? b[i] : a[i]) + __shfl_xor_sync(0xffffffffu, (q & 2) ? a[i] : b[i], 2);
        a[i] += __shfl_xor_sync(0xffffffffu, a[i], 1);
      }
      const float mu = a[0] * (1.f / 1024.f);
      m_bf = bf16r(mu);
      sd = ln_sd(a[1] * (1.f / 1024.f) - mu * mu);
      inv_sd = rcp_fast(sd);
      r_bf = bf16r((a[2] - m_bf * wsum) * inv_sd);
    }
    {
      const uint32_t u = __float_as_uint(r_bf);
      const uint32_t ord = (u & 0x80000000u) ? ~u : (u | 0x80000000u);
      const uint32_t key = (ord & 0xFFFF0000u) | trow_inv;
      const uint32_t wk = __reduce_max_sync(0xffffffffu, key);
      if (key == wk) SM_(uint2, OFF_WKEY + warp * 8) = make_uint2(wk, (__float_as_uint(m_bf) >> 16) | __float_as_uint(sd));
      const uint32_t wmask = __ballot_sync(0xffffffffu, key == wk);
      const bool hi = (wmask & 0xCCCCCCCCu) != 0;
      uint32_t c[16];
#pragma unroll
      for (int ks = 0; ks < 8; ks++) { c[2 * ks] = hi ? h[ks][1] : h[ks][0]; c[2 * ks + 1] = hi ? h[ks][3] : h[ks][2]; }
      bar_sync(NB_BOTH, 256);
      const uint2 km = SM_(uint2, OFF_WKEY + (lane & 7) * 8);
      const uint32_t bk = __reduce_max_sync(0xffffffffu, km.x);
      if (wk == bk) {
        if ((wmask >> (lane & 28)) & 15) {
#pragma unroll
          for (int ks = 0; ks < 8; ks++) pkt_st128(cand_pub + ks * 4, c[2 * ks], tag, c[2 * ks + 1], tag);
        }
      } else if (eps == 0) {
        const uint32_t kx = __shfl_sync(0xffffffffu, km.x, warp ^ 1), ms = __shfl_sync(0xffffffffu, km.y, warp ^ 1);
        if (kx == bk && lane < 8) pkt_st128(key_pub, bk, tag, ms, tag);
      }
      CT(7);
    }
    {
      const float ih = bf16r(inv_sd);
      const uint32_t nm = pack_bf16(-m_bf, -m_bf), iv = pack_bf16(ih, inv_sd - ih);
      const uint32_t nm_o = __shfl_xor_sync(0xffffffffu, nm, 2), iv_o = __shfl_xor_sync(0xffffffffu, iv, 2);
      const uint32_t nm2[2] = {(q & 2) ? nm_o : nm, (q & 2) ? nm : nm_o}, iv2[2] = {(q & 2) ? iv_o : iv, (q & 2) ? iv : iv_o};
      const uint32_t hi2[2] = {__byte_perm(iv2[0], 0, 0x1010), __byte_perm(iv2[1], 0, 0x1010)}, lo2[2] = {__byte_perm(iv2[0], 0, 0x3232), __byte_perm(iv2[1], 0, 0x3232)};
      const uint32_t oa = sb + OFF_OUT + (warp * 16 + (lane & 15)) * 128;
#pragma unroll
      for (int ks = 0; ks < 8; ks++) {
        uint32_t o[4];
#pragma unroll
        for (int i = 0; i < 4; i++) {
          const uint32_t dd = badd2(h[ks][i], nm2[i & 1]);
          o[i] = badd2(h[ks][i], bfma2(dd, hi2[i & 1], bmul2(dd, lo2[i & 1])));
        }
        stsm_x4(oa + (ks >> 2) * 16384 + (((2 * (ks & 3) + (lane >> 4)) ^ (lane & 7)) << 4), o[0], o[1], o[2], o[3]);
      }
      staged(B_OUT);
    }
    CT(8);
    uint32_t df[16][4];
    auto load_df = [&]() {
      const int frow = (lane & 7) + ((lane >> 4) << 3), hi = (lane >> 3) & 1;
      const uint32_t base = sb + down_off(warp >> 1) + (warp & 1) * 8192 + frow * 128;
#pragma unroll
      for (int mt = 0; mt < 8; mt++) {
#pragma unroll
        for (int ks = 0; ks < 2; ks++)
          ldsm_x4_t(base + (mt >> 2) * 4096 + ks * 2048 + (((2 * (mt & 3) + hi) ^ (lane & 7)) << 4),
                    df[2 * mt + ks][0], df[2 * mt + ks][1], df[2 * mt + ks][2], df[2 * mt + ks][3]);
      }
    };
    if (moe) {
      mbar_wait(BAR(B_GU), 0);
      load_wf_rest();
      mbar_wait(BAR(B_DN), 0);
      load_df();
    }
    uint4* y_pub = &p.s->ypart[cid * 256 + tid];
    uint32_t xs_ad = sb + OFF_XSEL + (8 * (g >> 2) + 4 * w + (g & 3)) * 32 + q * 8, gp_ad = sb + OFF_GP + (wi * 8 + g) * 16 + w * 8 + (q >> 1) * 4;
    pin(y_pub); pin(xs_ad); pin(gp_ad);
    mbar_wait(BAR(B_XS), 0);
    CT(9);
    if (moe) {
      float gd[8][4] = {};
      uint2 bx[4];
#pragma unroll
      for (int r = 0; r < 4; r++) bx[r] = smem_at<uint2>(xs_ad + r * 512);
#pragma unroll
      for (int r = 0; r < 4; r++) {
#pragma unroll
        for (int i = 0; i < 8; i++) mma16816(gd[i], wf[8 * r + i][0], wf[8 * r + i][1], wf[8 * r + i][2], wf[8 * r + i][3], bx[r].x, bx[r].y);
      }
      const float gs = sel4(q, gd[0][0] + gd[1][1], gd[2][0] + gd[3][1], gd[4][0] + gd[5][1], gd[6][0] + gd[7][1]);
      const float us = sel4(q, gd[0][2] + gd[1][3], gd[2][2] + gd[3][3], gd[4][2] + gd[5][3], gd[6][2] + gd[7][3]);
      float v = ((q & 2) ? us : gs) + __shfl_xor_sync(0xffffffffu, (q & 2) ? gs : us, 2);
      v += __shfl_xor_sync(0xffffffffu, v, 1);
      smem_at<float>(gp_ad) = v;
      CT(10);
      bar_sync(NB_BOTH, 256);
      uint32_t bq[4];
      {
        const float4 p0 = SM_(float4, OFF_GP + lane * 16);
        const float gt = bf16r(p0.x + p0.z), up = bf16r(p0.y + p0.w);
        const float act = bf16r(gt * sigmoid_fast(gt)) * up;
        const uint32_t pr = pack_bf16(act, __shfl_down_sync(0xffffffffu, act, 1));
#pragma unroll
        for (int i = 0; i < 4; i++) bq[i] = __shfl_sync(0xffffffffu, pr, 8 * i + 2 * q);
      }
      CT(11);
      float yd[8][4] = {};
#pragma unroll
      for (int ks = 0; ks < 2; ks++) {
#pragma unroll
        for (int mt = 0; mt < 8; mt++) mma16816(yd[mt], df[2 * mt + ks][0], df[2 * mt + ks][1], df[2 * mt + ks][2], df[2 * mt + ks][3], bq[2 * ks], bq[2 * ks + 1]);
      }
      pkt_st128(y_pub, with_bit(sel4(q, yd[0][0], yd[2][0], yd[4][0], yd[6][0]), cd), with_bit(sel4(q, yd[0][2], yd[2][2], yd[4][2], yd[6][2]), cd >> 1),
                with_bit(sel4(q, yd[1][0], yd[3][0], yd[5][0], yd[7][0]), cd), with_bit(sel4(q, yd[1][2], yd[3][2], yd[5][2], yd[7][2]), cd >> 1));
    } else {
      const long long tw = clock64();
      while (clock64() - tw < IDLE_WAIT_CLK) __nanosleep(100);
    }
    CT(12);
    const uint32_t kv = SM_(uint32_t, OFF_KV);
    const int tsel = 0xFFFF - (int)(kv & 0xFFFFu);
    const float r_sel = __uint_as_float((kv & 0x80000000u) ? (kv & 0x7FFF0000u) : (~kv & 0xFFFF0000u));
    const float sig = bf16r(sigmoid_fast(r_sel));
    const int pfin = 2 * cid + (tid & 1);
    const int col_fin = (pfin >> 5) * 128 + (pfin & 3) * 32 + ((pfin & 31) >> 2) + 8 * ((tid >> 1) & 3);
    const int sel_off = (col_fin >> 4) * 32 + ((col_fin & 7) >> 1) * 8 + ((col_fin >> 3) & 1) * 4 + (col_fin & 1) * 2;
    const float hn_fin = __uint_as_float((uint32_t)SM_(uint16_t, OFF_XSEL + sel_off) << 16), h_fin = __uint_as_float((uint32_t)SM_(uint16_t, OFF_HSEL + sel_off) << 16);
    bf16* out_fin = p.out + (size_t)tsel * 1024 + col_fin;
    {
      const uint4* src = &p.s->ypart[(16 + (tid >> 1)) * 256 + pfin];
      pin(src); pin(out_fin);
      uint4 v = make_uint4(0, 0, 0, 0);
      if (warp < 7) {
        delay_clk<HOP3_DELAY>();
        uint32_t n = 0;
        bool ok = false;
        do {
          pkt_ld128_if(v, src, !ok);
          ok = pair_code(v.x, v.y) == cd && pair_code(v.z, v.w) == cd;
        } while (!__all_sync(0xffffffffu, ok) && ++n < SPIN_LIMIT);
      }
      CT(13);
      const float y0 = __uint_as_float(v.x & ~1u), y1 = __uint_as_float(v.y & ~1u), y2 = __uint_as_float(v.z & ~1u), y3 = __uint_as_float(v.w & ~1u);
      const float a0 = ((lane & 2) ? y1 : y0) + __shfl_xor_sync(0xffffffffu, (lane & 2) ? y0 : y1, 2);
      const float a1 = ((lane & 2) ? y3 : y2) + __shfl_xor_sync(0xffffffffu, (lane & 2) ? y2 : y3, 2);
      float b = ((lane & 4) ? a1 : a0) + __shfl_xor_sync(0xffffffffu, (lane & 4) ? a0 : a1, 4);
      b += __shfl_xor_sync(0xffffffffu, b, 8);
      b += __shfl_xor_sync(0xffffffffu, b, 16);
      if (lane < 8) SM_(float, OFF_FIN + lane * 32 + warp * 4) = b;
    }
    bar_sync(NB_BOTH, 256);
    if (tid < 8) {
      const float4 y0 = SM_(float4, OFF_FIN + tid * 32), y1 = SM_(float4, OFF_FIN + tid * 32 + 16);
      const float y = ((y0.x + y0.y) + (y0.z + y0.w)) + ((y1.x + y1.y) + y1.z);
      *out_fin = __float2bfloat16_rn(h_fin + bf16r(hn_fin + bf16r(bf16r(y) * sig)));
      if (cid == 0 && tid == 0) st_relaxed32(&p.s->epoch, tag);
    }
    CT(14);
  }
}

__global__ void __launch_bounds__(384, 1) occupancy_probe_kernel() {}

typedef CUresult (*EncodeFn)(CUtensorMap*, CUtensorMapDataType, cuuint32_t, void*, const cuuint64_t*, const cuuint64_t*, const cuuint32_t*, const cuuint32_t*,
                             CUtensorMapInterleave, CUtensorMapSwizzle, CUtensorMapL2promotion, CUtensorMapFloatOOBfill);

static void make_tm(EncodeFn enc, CUtensorMap* tm, const void* ptr, uint64_t rows, uint64_t cols, uint32_t brows, uint32_t bcols, CUtensorMapSwizzle sw,
                    CUtensorMapL2promotion promo = CU_TENSOR_MAP_L2_PROMOTION_L2_128B) {
  cuuint64_t dims[2] = {cols, rows};
  cuuint64_t strides[1] = {cols * 2};
  cuuint32_t box[2] = {bcols, brows};
  cuuint32_t es[2] = {1, 1};
  enc(tm, CU_TENSOR_MAP_DATA_TYPE_BFLOAT16, 2, const_cast<void*>(ptr), dims, strides, box, es, CU_TENSOR_MAP_INTERLEAVE_NONE, sw,
      promo, CU_TENSOR_MAP_FLOAT_OOB_FILL_NONE);
}

static void make_tm_rows(EncodeFn enc, CUtensorMap* tm, const void* ptr, uint64_t cols, uint32_t brows, uint32_t bcols, CUtensorMapSwizzle sw,
                         CUtensorMapL2promotion promo = CU_TENSOR_MAP_L2_PROMOTION_L2_128B) {
  cuuint64_t dims[4] = {cols, 2, 2, 512};
  cuuint64_t strides[3] = {row_of(1) * cols * 2, row_of(2) * cols * 2, row_of(4) * cols * 2};
  cuuint32_t box[4] = {bcols, 2, 2, brows / 4};
  cuuint32_t es[4] = {1, 1, 1, 1};
  enc(tm, CU_TENSOR_MAP_DATA_TYPE_BFLOAT16, 4, const_cast<void*>(ptr), dims, strides, box, es, CU_TENSOR_MAP_INTERLEAVE_NONE, sw, promo,
      CU_TENSOR_MAP_FLOAT_OOB_FILL_NONE);
}

extern "C" void kernel_launch(void* const* d_in, const int* in_sizes, int n_in, void* d_out, int out_size) {
  (void)in_sizes; (void)n_in; (void)out_size;
  static EncodeFn enc = nullptr;
  static void* abT = nullptr;
  static int map = 0;
  if (!enc) {
    void* fn = nullptr; cudaDriverEntryPointQueryResult st;
    cudaGetDriverEntryPoint("cuTensorMapEncodeTiled", &fn, cudaEnableDefault, &st);
    enc = (EncodeFn)fn;
    cudaGetSymbolAddress(&abT, g_scratch);
    cudaFuncSetAttribute(fnet_moe_kernel<0>, cudaFuncAttributeMaxDynamicSharedMemorySize, SMEM_TOTAL);
    cudaFuncSetAttribute(fnet_moe_kernel<1>, cudaFuncAttributeMaxDynamicSharedMemorySize, SMEM_TOTAL);
    cudaFuncSetAttribute(occupancy_probe_kernel, cudaFuncAttributeMaxDynamicSharedMemorySize, SMEM_TOTAL);
    cudaFuncSetAttribute(occupancy_probe_kernel, cudaFuncAttributeNonPortableClusterSizeAllowed, 1);
    auto max_clusters = [&](int size) {
      cudaLaunchConfig_t cfg = {};
      cfg.gridDim = dim3(128); cfg.blockDim = dim3(384); cfg.dynamicSmemBytes = SMEM_TOTAL;
      cudaLaunchAttribute at[1];
      at[0].id = cudaLaunchAttributeClusterDimension; at[0].val.clusterDim.x = size; at[0].val.clusterDim.y = 1; at[0].val.clusterDim.z = 1;
      cfg.attrs = at; cfg.numAttrs = 1;
      int ncl = 0;
      return cudaOccupancyMaxActiveClusters(&ncl, occupancy_probe_kernel, &cfg) == cudaSuccess ? ncl : 0;
    };
    int dev = 0, sms = 0;
    cudaGetDevice(&dev);
    cudaDeviceGetAttribute(&sms, cudaDevAttrMultiProcessorCount, dev);
    map = (sms == 132 && max_clusters(2) == 66 && max_clusters(16) == 7) ? 0 : 1;
    (void)cudaGetLastError();
  }
  Params p;
  const bf16* x = (const bf16*)d_in[0];
  make_tm(enc, &p.tmD0, d_in[3], 1024, 1024, 128, 64, CU_TENSOR_MAP_SWIZZLE_128B);
  make_tm(enc, &p.tmD1, d_in[4], 1024, 1024, 128, 64, CU_TENSOR_MAP_SWIZZLE_128B);
  make_tm(enc, &p.tmX, x, 2048, 1024, map == 0 ? NX0 : 256, 64, CU_TENSOR_MAP_SWIZZLE_128B);
  make_tm_rows(enc, &p.tmXr, x, 1024, 64, 64, CU_TENSOR_MAP_SWIZZLE_128B);
  make_tm(enc, &p.tmAbS, abT, 2048, 2048, 64, 64, CU_TENSOR_MAP_SWIZZLE_128B);
  make_tm(enc, &p.tmAbL, abT, 2048, 2048, 128, 64, CU_TENSOR_MAP_SWIZZLE_128B);
  make_tm_rows(enc, &p.tmW0, d_in[1], 2048, 128, 64, CU_TENSOR_MAP_SWIZZLE_128B);
  make_tm_rows(enc, &p.tmW1, d_in[2], 2048, 128, 64, CU_TENSOR_MAP_SWIZZLE_128B);
  {
    cuuint64_t dims[5] = {1024, 2, 4, 2, 2048};
    cuuint64_t strides[4] = {row_of(1) * 2048, row_of(8) * 2048, row_of(2) * 2048, 2048};
    cuuint32_t box[5] = {64, 2, 4, 2, 1};
    cuuint32_t es[5] = {1, 1, 1, 1, 1};
    enc(&p.tmOut, CU_TENSOR_MAP_DATA_TYPE_BFLOAT16, 5, d_out, dims, strides, box, es, CU_TENSOR_MAP_INTERLEAVE_NONE, CU_TENSOR_MAP_SWIZZLE_128B,
        CU_TENSOR_MAP_L2_PROMOTION_NONE, CU_TENSOR_MAP_FLOAT_OOB_FILL_NONE);
  }
  {
    cuuint64_t dims[5] = {1024, 2, 4, 2, 8};
    cuuint64_t strides[4] = {2048, 4 * 2048, 2 * 2048, 256 * 2048};
    cuuint32_t box[5] = {64, 2, 4, 2, 8};
    cuuint32_t es[5] = {1, 1, 1, 1, 1};
    enc(&p.tmXh, CU_TENSOR_MAP_DATA_TYPE_BFLOAT16, 5, const_cast<bf16*>(x) + 240 * 1024, dims, strides, box, es, CU_TENSOR_MAP_INTERLEAVE_NONE,
        CU_TENSOR_MAP_SWIZZLE_128B, CU_TENSOR_MAP_L2_PROMOTION_L2_128B, CU_TENSOR_MAP_FLOAT_OOB_FILL_NONE);
  }
  make_tm(enc, &p.tmAbM, abT, 2048, 2048, 128, 16, CU_TENSOR_MAP_SWIZZLE_32B, CU_TENSOR_MAP_L2_PROMOTION_NONE);
  make_tm_rows(enc, &p.tmWM0, d_in[1], 2048, 128, 16, CU_TENSOR_MAP_SWIZZLE_32B, CU_TENSOR_MAP_L2_PROMOTION_NONE);
  make_tm_rows(enc, &p.tmWM1, d_in[2], 2048, 128, 16, CU_TENSOR_MAP_SWIZZLE_32B, CU_TENSOR_MAP_L2_PROMOTION_NONE);
  make_tm(enc, &p.tmG, d_in[7], 1024, 3584, 128, 32, CU_TENSOR_MAP_SWIZZLE_64B);
  make_tm(enc, &p.tmU, d_in[8], 1024, 3584, 128, 32, CU_TENSOR_MAP_SWIZZLE_64B);
  make_tm(enc, &p.tmDn, d_in[9], 3584, 1024, 32, 64, CU_TENSOR_MAP_SWIZZLE_128B);
  p.x = x; p.Dre = (const bf16*)d_in[3]; p.Dim = (const bf16*)d_in[4];
  p.wr = (const bf16*)d_in[6]; p.wdown = (const bf16*)d_in[9]; p.wgate = (const bf16*)d_in[7]; p.wup = (const bf16*)d_in[8];
  p.out = (bf16*)d_out; p.s = (Scratch*)abT;
  if (map == 1) fnet_moe_kernel<1><<<128, 384, SMEM_TOTAL>>>(p);
  else fnet_moe_kernel<0><<<132, 384, SMEM_TOTAL>>>(p);
}
```

```cpp
#include <cuda.h>
#include <cuda_runtime.h>
#include <cuda_bf16.h>
#include <stdint.h>
#include <type_traits>

typedef __nv_bfloat16 bf16;

constexpr int NX0 = 240;
constexpr int REG_C = 232, REG_P = 40;
__host__ __device__ constexpr int row_of(int p) { return (p & 1) * 1024 + ((p >> 1) & 1) * 512 + (p >> 2); }
__host__ __device__ constexpr int group_of(int row) { return (row & 511) >> 5; }
__device__ __forceinline__ int sigma_of(int tau, int r) { return r + (r >= tau); }
__device__ __forceinline__ int kblock(int tau, int j) {
  const int i = j - 4, c = (i * 37) >> 8;
  return j < 4 ? tau * 4 + j : sigma_of(tau, i - 7 * c) * 4 + c;
}
constexpr int AUX_AFTER = 1;
constexpr int PF_K0 = 8, PF_N0 = 2, PF_K1 = 24;
constexpr int WPF_K0 = 12, WPF_N = 10;
constexpr int WPF2_K = 44, WPF2_N = 4;
constexpr int GU_K = 46;
constexpr int PUB_K1 = 22;
constexpr int NREG_H = 5;
constexpr int MR_K0 = 29, MR_P = 6;
constexpr int MINI_PF_K = 35, MINI_LOAD_K = 43, MINI_K = 42;
constexpr int RESET_K = 37;
constexpr int SEND_FIRST = 2;
constexpr int GATHER_NS = 400;
constexpr int MOE_PACE_CLK = 300;
constexpr int OUT_PACE_CLK = 70;
constexpr int HOP1_DELAY = 150, HOP3_DELAY = 450;
constexpr int SPEC_MIN = 10;
constexpr int IDLE_WAIT_CLK = 1200;
__host__ __device__ constexpr int mr_k(int h) { return MR_K0 + MR_P * (h >> 1) + 2 * (h & 1); }
constexpr int A_BYTES = 128 * 64 * 2;
constexpr int B_BYTES = 256 * 64 * 2;
constexpr int ST_BYTES = A_BYTES + B_BYTES;
constexpr int OFF_XCH = 4 * ST_BYTES;
constexpr int OFF_BAR = OFF_XCH + 32768;
constexpr int OFF_WR = OFF_BAR + 384;
constexpr int OFF_RS = OFF_WR + 384;
constexpr int OFF_PUB = OFF_RS + 640;
constexpr int OFF_MISC = OFF_PUB + 768;
constexpr int SMEM_TOTAL = OFF_MISC + 256;
constexpr int OFF_WSUM = OFF_MISC, OFF_TAG = OFF_MISC + 4;
constexpr int OFF_SEEN = OFF_MISC + 8;
constexpr int OFF_KV = OFF_MISC + 12;
constexpr int OFF_WKEY = OFF_MISC + 32;
constexpr int OFF_MINI = OFF_XCH + 16384;
constexpr int OFF_EXA = OFF_XCH;
constexpr int OFF_EXB = OFF_XCH + 4096;
__host__ __device__ constexpr int chunk_off(int c, int w) { return (c < 2 ? (c + 2) * ST_BYTES : OFF_XCH + (c - 2) * 16384) + w * 8192; }
__host__ __device__ constexpr int late_off(int i) { return i < 4 ? i * 16384 : 2 * ST_BYTES + A_BYTES + (i - 4) * 16384; }
__host__ __device__ constexpr int round_off(int h) { return h < NREG_H + 2 ? OFF_XCH + (h & 1) * 16384 : late_off(h - NREG_H - 2); }
__host__ __device__ constexpr int down_off(int i) { return late_off(6 - NREG_H + i); }
constexpr int OFF_PEER = ST_BYTES + A_BYTES;
constexpr int OFF_OUT = 3 * ST_BYTES + A_BYTES;
constexpr int OFF_XSEL = OFF_PEER;
constexpr int OFF_HSEL = OFF_PEER + 4096;
constexpr int OFF_GP = OFF_PEER + 8192;
constexpr int OFF_FIN = OFF_PEER + 9216;
__device__ __forceinline__ int slot_of(int k) { return k & 3; }
__device__ __forceinline__ int use_of(int k) { return k >> 2; }
enum { B_FULL = 0, B_EMPTY = 4, B_EPI = 8, B_STD = 12, B_EPI0B = 16, B_LATE = 17, B_STAT = 18, B_XCH = 19, B_MR = 20  , B_GU = 22,
       B_DN = 23, B_AUX = 24  , B_OUT = 26, B_KEY = 27, B_XS = 28, B_A20 = 29, B_STDA = 30, B_PUB1 = 31, B_COUNT = 32 };
enum { NB_TURN0 = 1, NB_TURN1 = 2, NB_WG0 = 3, NB_BOTH = 5, NB_AUX = 6 };

struct Scratch {
  bf16 abT[2048 * 2048];
  uint2 xstat[2048];
  uint2 dsum[2048];
  uint4 abflag[16 * 8 * 2];
  uint4 hflag[16 * 2];
  uint4 hstat[16 * 8 * 128];
  uint4 cand[16 * 256];
  uint4 key[8 * 16 * 2];
  uint4 ypart[128 * 256];
  uint32_t epoch;
};
__device__ __align__(1024) Scratch g_scratch;

struct Params {
  Scratch* s; bf16* out;
  const bf16* x; const bf16* Dre; const bf16* Dim; const bf16* wr; const bf16* wdown; const bf16* wgate; const bf16* wup;
  CUtensorMap tmX, tmD0, tmD1, tmXr, tmAbS, tmAbL, tmW0, tmW1, tmOut, tmG, tmU, tmDn, tmXh, tmAbM, tmWM0, tmWM1;
};

#define SPIN_LIMIT (1u << 14)
#define MBAR_LIMIT (1u << 10)
__device__ __forceinline__ uint32_t smem_u32(const void* p) { return (uint32_t)__cvta_generic_to_shared(p); }
__device__ __forceinline__ void mbar_init(uint32_t bar, uint32_t cnt) { asm volatile("mbarrier.init.shared::cta.b64 [%0], %1;" :: "r"(bar), "r"(cnt) : "memory"); }
__device__ __forceinline__ void mbar_expect_tx(uint32_t bar, uint32_t bytes) { asm volatile("mbarrier.arrive.expect_tx.shared::cta.b64 _, [%0], %1;" :: "r"(bar), "r"(bytes) : "memory"); }
__device__ __forceinline__ void mbar_arrive(uint32_t bar) { asm volatile("mbarrier.arrive.shared::cta.b64 _, [%0];" :: "r"(bar) : "memory"); }
__device__ __forceinline__ void mbar_wait(uint32_t bar, uint32_t parity) {
  uint32_t ok, n = 0;
  do {
    asm volatile("{\n.reg .pred p;\nmbarrier.try_wait.parity.shared::cta.b64 p, [%1], %2;\nselp.u32 %0, 1, 0, p;\n}\n" : "=r"(ok) : "r"(bar), "r"(parity) : "memory");
  } while (!ok && ++n < MBAR_LIMIT);
}
__device__ __forceinline__ void mbar_wait_cluster(uint32_t bar, uint32_t parity) {
  uint32_t ok, n = 0;
  do {
    asm volatile("{\n.reg .pred p;\nmbarrier.try_wait.parity.acquire.cluster.shared::cta.b64 p, [%1], %2;\nselp.u32 %0, 1, 0, p;\n}\n" : "=r"(ok) : "r"(bar), "r"(parity) : "memory");
  } while (!ok && ++n < MBAR_LIMIT);
}
__device__ __forceinline__ void tma_load_2d(uint32_t dst, const CUtensorMap* tm, uint32_t bar, int c0, int c1) {
  asm volatile("cp.async.bulk.tensor.2d.shared::cluster.global.mbarrier::complete_tx::bytes [%0], [%1, {%3, %4}], [%2];"
    :: "r"(dst), "l"(tm), "r"(bar), "r"(c0), "r"(c1) : "memory");
}
__device__ __forceinline__ void tma_load_2d_hint(uint32_t dst, const CUtensorMap* tm, uint32_t bar, int c0, int c1, uint64_t pol) {
  asm volatile("cp.async.bulk.tensor.2d.shared::cluster.global.mbarrier::complete_tx::bytes.L2::cache_hint [%0], [%1, {%3, %4}], [%2], %5;"
    :: "r"(dst), "l"(tm), "r"(bar), "r"(c0), "r"(c1), "l"(pol) : "memory");
}
__device__ __forceinline__ uint64_t policy_evict_first() { uint64_t p; asm volatile("createpolicy.fractional.L2::evict_first.b64 %0, 1.0;" : "=l"(p)); return p; }
__device__ __forceinline__ void tma_store_2d(const CUtensorMap* tm, uint32_t src, int c0, int c1) {
  asm volatile("cp.async.bulk.tensor.2d.global.shared::cta.bulk_group [%0, {%2, %3}], [%1];" :: "l"(tm), "r"(src), "r"(c0), "r"(c1) : "memory");
}
__device__ __forceinline__ void tma_prefetch_2d(const CUtensorMap* tm, int c0, int c1) {
  asm volatile("cp.async.bulk.prefetch.tensor.2d.L2.global.tile [%0, {%1, %2}];" :: "l"(tm), "r"(c0), "r"(c1) : "memory");
}
__device__ __forceinline__ void bulk_load(uint32_t dst, const void* src, uint32_t bytes, uint32_t bar) {
  asm volatile("cp.async.bulk.shared::cluster.global.mbarrier::complete_tx::bytes [%0], [%1], %2, [%3];" :: "r"(dst), "l"(src), "r"(bytes), "r"(bar) : "memory");
}
__device__ __forceinline__ void bulk_commit() { asm volatile("cp.async.bulk.commit_group;" ::: "memory"); }
__device__ __forceinline__ void bulk_wait_all() { asm volatile("cp.async.bulk.wait_group 0;" ::: "memory"); }
__device__ __forceinline__ void fence_async_smem() { asm volatile("fence.proxy.async.shared::cta;" ::: "memory"); }
__device__ __forceinline__ void wgmma_fence() { asm volatile("wgmma.fence.sync.aligned;" ::: "memory"); }
__device__ __forceinline__ void wgmma_commit() { asm volatile("wgmma.commit_group.sync.aligned;" ::: "memory"); }
__device__ __forceinline__ void wgmma_wait0() { asm volatile("wgmma.wait_group.sync.aligned 0;" ::: "memory"); }
__device__ __forceinline__ void bar_sync(int id, int n) { asm volatile("bar.sync %0, %1;" :: "r"(id), "r"(n) : "memory"); }
__device__ __forceinline__ void bar_arrive(int id, int n) { asm volatile("bar.arrive %0, %1;" :: "r"(id), "r"(n) : "memory"); }
template<int R> __device__ __forceinline__ void reg_inc() { asm volatile("setmaxnreg.inc.sync.aligned.u32 %0;" :: "n"(R)); }
template<int R> __device__ __forceinline__ void reg_dec() { asm volatile("setmaxnreg.dec.sync.aligned.u32 %0;" :: "n"(R)); }
__device__ __forceinline__ bool elect_one() {
  uint32_t p;
  asm volatile("{\n.reg .pred q;\nelect.sync _|q, 0xffffffff;\nselp.u32 %0, 1, 0, q;\n}\n" : "=r"(p));
  return p != 0;
}
__device__ __forceinline__ uint32_t mapa(uint32_t addr, uint32_t cta) { uint32_t r; asm volatile("mapa.shared::cluster.u32 %0, %1, %2;" : "=r"(r) : "r"(addr), "r"(cta)); return r; }
__device__ __forceinline__ void st_async_v4(uint32_t addr, uint32_t bar, uint32_t a, uint32_t b, uint32_t c, uint32_t d) {
  asm volatile("st.async.weak.shared::cluster.mbarrier::complete_tx::bytes.v4.b32 [%0], {%2, %3, %4, %5}, [%1];" :: "r"(addr), "r"(bar), "r"(a), "r"(b), "r"(c), "r"(d) : "memory");
}
__device__ __forceinline__ void stsm_x4(uint32_t addr, uint32_t a, uint32_t b, uint32_t c, uint32_t d) {
  asm volatile("stmatrix.sync.aligned.m8n8.x4.shared.b16 [%0], {%1, %2, %3, %4};" :: "r"(addr), "r"(a), "r"(b), "r"(c), "r"(d));
}
__device__ __forceinline__ uint4 lds128_v(uint32_t addr) { uint4 v; asm volatile("ld.shared.v4.b32 {%0, %1, %2, %3}, [%4];" : "=r"(v.x), "=r"(v.y), "=r"(v.z), "=r"(v.w) : "r"(addr)); return v; }
extern __shared__ __align__(1024) uint8_t smem_raw[];
template<class T> __device__ __forceinline__ T& smem_at(uint32_t addr) { return *reinterpret_cast<T*>(__cvta_shared_to_generic(addr)); }
#define SM_(T, off) smem_at<T>(sb + (off))
__device__ __forceinline__ uint4 ldg_nc128(const void* p) { uint4 v; asm volatile("ld.global.nc.v4.b32 {%0, %1, %2, %3}, [%4];" : "=r"(v.x), "=r"(v.y), "=r"(v.z), "=r"(v.w) : "l"(p)); return v; }
__device__ __forceinline__ void pkt_st128(void* p, uint32_t a, uint32_t b, uint32_t c, uint32_t d) {
  asm volatile("{\n.reg .b128 v;\n.reg .b64 lo, hi;\nmov.b64 lo, {%1, %2};\nmov.b64 hi, {%3, %4};\nmov.b128 v, {lo, hi};\nst.relaxed.gpu.global.b128 [%0], v;\n}\n"
    :: "l"(p), "r"(a), "r"(b), "r"(c), "r"(d) : "memory");
}
__device__ __forceinline__ uint4 pkt_ld128(const void* p) {
  uint4 r;
  asm volatile("{\n.reg .b128 v;\n.reg .b64 lo, hi;\nld.relaxed.gpu.global.b128 v, [%4];\nmov.b128 {lo, hi}, v;\nmov.b64 {%0, %1}, lo;\nmov.b64 {%2, %3}, hi;\n}\n"
    : "=r"(r.x), "=r"(r.y), "=r"(r.z), "=r"(r.w) : "l"(p) : "memory");
  return r;
}
__device__ __forceinline__ void pkt_ld128_if(uint4& r, const void* p, bool cond) {
  asm volatile("{\n.reg .pred q;\n.reg .b64 lo, hi;\nsetp.ne.b32 q, %5, 0;\nmov.b64 lo, {%0, %1};\nmov.b64 hi, {%2, %3};\n"
               "@q ld.relaxed.gpu.global.v2.b64 {lo, hi}, [%4];\nmov.b64 {%0, %1}, lo;\nmov.b64 {%2, %3}, hi;\n}\n"
    : "+r"(r.x), "+r"(r.y), "+r"(r.z), "+r"(r.w) : "l"(p), "r"((uint32_t)cond) : "memory");
}
__device__ __forceinline__ void pkt_st64(void* p, uint32_t a, uint32_t b) {
  asm volatile("{\n.reg .b64 v;\nmov.b64 v, {%1, %2};\nst.relaxed.gpu.global.b64 [%0], v;\n}\n" :: "l"(p), "r"(a), "r"(b) : "memory");
}
__device__ __forceinline__ uint2 pkt_ld64(const void* p) {
  uint2 r;
  asm volatile("{\n.reg .b64 v;\nld.relaxed.gpu.global.b64 v, [%2];\nmov.b64 {%0, %1}, v;\n}\n" : "=r"(r.x), "=r"(r.y) : "l"(p) : "memory");
  return r;
}
__device__ __forceinline__ uint32_t ld_relaxed32(const void* p) { uint32_t v; asm volatile("ld.relaxed.gpu.global.b32 %0, [%1];" : "=r"(v) : "l"(p) : "memory"); return v; }
__device__ __forceinline__ void st_relaxed32(void* p, uint32_t v) { asm volatile("st.relaxed.gpu.global.b32 [%0], %1;" :: "l"(p), "r"(v) : "memory"); }
__device__ __forceinline__ uint32_t code_of(uint32_t tag) { return tag % 3u + 1u; }
__device__ __forceinline__ uint32_t with_bit(float v, uint32_t bit) { return (__float_as_uint(v) & ~1u) | (bit & 1u); }
__device__ __forceinline__ uint32_t pair_code(uint32_t a, uint32_t b) { return (a & 1u) | ((b & 1u) << 1); }
__device__ __forceinline__ uint32_t pack_bf16(float lo, float hi) { uint32_t r; asm("cvt.rn.bf16x2.f32 %0, %1, %2;" : "=r"(r) : "f"(hi), "f"(lo)); return r; }
__device__ __forceinline__ float bf_lo(uint32_t v) { return __uint_as_float(v << 16); }
__device__ __forceinline__ float bf_hi(uint32_t v) { return __uint_as_float(v & 0xFFFF0000u); }
__device__ __forceinline__ float bf16r(float x) { return __uint_as_float(pack_bf16(0.f, x)); }
__device__ __forceinline__ uint32_t badd2(uint32_t a, uint32_t b) { uint32_t r; asm("add.rn.bf16x2 %0, %1, %2;" : "=r"(r) : "r"(a), "r"(b)); return r; }
__device__ __forceinline__ uint32_t bmul2(uint32_t a, uint32_t b) { uint32_t r; asm("mul.rn.bf16x2 %0, %1, %2;" : "=r"(r) : "r"(a), "r"(b)); return r; }
__device__ __forceinline__ float warp_sum(float v) {
#pragma unroll
  for (int o = 16; o > 0; o >>= 1) v += __shfl_xor_sync(0xffffffffu, v, o);
  return v;
}
__device__ __forceinline__ uint64_t make_desc(uint32_t addr) {
  return (uint64_t)((addr & 0x3FFFF) >> 4) | ((uint64_t)1 << 16) | ((uint64_t)64 << 32) | ((uint64_t)1 << 62);
}
__device__ __forceinline__ uint64_t make_desc_noswz(uint32_t addr) {
  return (uint64_t)((addr & 0x3FFFF) >> 4) | ((uint64_t)8 << 16) | ((uint64_t)16 << 32);
}
__device__ __forceinline__ uint64_t make_desc_32b(uint32_t addr) {
  return (uint64_t)((addr & 0x3FFFF) >> 4) | ((uint64_t)1 << 16) | ((uint64_t)16 << 32) | ((uint64_t)3 << 62);
}
__device__ __forceinline__ void wgmma_n256(float (&d)[128], uint64_t da, uint64_t db, int scale_d) {
  asm volatile("{\n.reg .pred p;\nsetp.ne.b32 p, %130, 0;\n"
    "wgmma.mma_async.sync.aligned.m64n256k16.f32.bf16.bf16 "
    "{%0, %1, %2, %3, %4, %5, %6, %7, %8, %9, %10, %11, %12, %13, %14, %15, %16, %17, %18, %19, %20, %21, %22, %23, %24, %25, %26, %27, %28, %29, %30, %31, "
    "%32, %33, %34, %35, %36, %37, %38, %39, %40, %41, %42, %43, %44, %45, %46, %47, %48, %49, %50, %51, %52, %53, %54, %55, %56, %57, %58, %59, %60, %61, %62, %63, "
    "%64, %65, %66, %67, %68, %69, %70, %71, %72, %73, %74, %75, %76, %77, %78, %79, %80, %81, %82, %83, %84, %85, %86, %87, %88, %89, %90, %91, %92, %93, %94, %95, "
    "%96, %97, %98, %99, %100, %101, %102, %103, %104, %105, %106, %107, %108, %109, %110, %111, %112, %113, %114, %115, %116, %117, %118, %119, %120, %121, %122, %123, %124, %125, %126, %127}, "
    "%128, %129, p, 1, 1, 0, 0;\n}\n"
    : "+f"(d[0]), "+f"(d[1]), "+f"(d[2]), "+f"(d[3]), "+f"(d[4]), "+f"(d[5]), "+f"(d[6]), "+f"(d[7]),
      "+f"(d[8]), "+f"(d[9]), "+f"(d[10]), "+f"(d[11]), "+f"(d[12]), "+f"(d[13]), "+f"(d[14]), "+f"(d[15]),
      "+f"(d[16]), "+f"(d[17]), "+f"(d[18]), "+f"(d[19]), "+f"(d[20]), "+f"(d[21]), "+f"(d[22]), "+f"(d[23]),
      "+f"(d[24]), "+f"(d[25]), "+f"(d[26]), "+f"(d[27]), "+f"(d[28]), "+f"(d[29]), "+f"(d[30]), "+f"(d[31]),
      "+f"(d[32]), "+f"(d[33]), "+f"(d[34]), "+f"(d[35]), "+f"(d[36]), "+f"(d[37]), "+f"(d[38]), "+f"(d[39]),
      "+f"(d[40]), "+f"(d[41]), "+f"(d[42]), "+f"(d[43]), "+f"(d[44]), "+f"(d[45]), "+f"(d[46]), "+f"(d[47]),
      "+f"(d[48]), "+f"(d[49]), "+f"(d[50]), "+f"(d[51]), "+f"(d[52]), "+f"(d[53]), "+f"(d[54]), "+f"(d[55]),
      "+f"(d[56]), "+f"(d[57]), "+f"(d[58]), "+f"(d[59]), "+f"(d[60]), "+f"(d[61]), "+f"(d[62]), "+f"(d[63]),
      "+f"(d[64]), "+f"(d[65]), "+f"(d[66]), "+f"(d[67]), "+f"(d[68]), "+f"(d[69]), "+f"(d[70]), "+f"(d[71]),
      "+f"(d[72]), "+f"(d[73]), "+f"(d[74]), "+f"(d[75]), "+f"(d[76]), "+f"(d[77]), "+f"(d[78]), "+f"(d[79]),
      "+f"(d[80]), "+f"(d[81]), "+f"(d[82]), "+f"(d[83]), "+f"(d[84]), "+f"(d[85]), "+f"(d[86]), "+f"(d[87]),
      "+f"(d[88]), "+f"(d[89]), "+f"(d[90]), "+f"(d[91]), "+f"(d[92]), "+f"(d[93]), "+f"(d[94]), "+f"(d[95]),
      "+f"(d[96]), "+f"(d[97]), "+f"(d[98]), "+f"(d[99]), "+f"(d[100]), "+f"(d[101]), "+f"(d[102]), "+f"(d[103]),
      "+f"(d[104]), "+f"(d[105]), "+f"(d[106]), "+f"(d[107]), "+f"(d[108]), "+f"(d[109]), "+f"(d[110]), "+f"(d[111]),
      "+f"(d[112]), "+f"(d[113]), "+f"(d[114]), "+f"(d[115]), "+f"(d[116]), "+f"(d[117]), "+f"(d[118]), "+f"(d[119]),
      "+f"(d[120]), "+f"(d[121]), "+f"(d[122]), "+f"(d[123]), "+f"(d[124]), "+f"(d[125]), "+f"(d[126]), "+f"(d[127])
    : "l"(da), "l"(db), "r"(scale_d));
}
__device__ __forceinline__ void wgmma_g1(float (&d)[128], uint64_t da, uint64_t db, int scale_d) { wgmma_n256(d, da, db, scale_d); }
__device__ __forceinline__ void wgmma_g1(float (&d)[120], uint64_t da, uint64_t db, int scale_d) {
  asm volatile("{\n.reg .pred p;\nsetp.ne.b32 p, %122, 0;\n"
    "wgmma.mma_async.sync.aligned.m64n240k16.f32.bf16.bf16 "
    "{%0, %1, %2, %3, %4, %5, %6, %7, %8, %9, %10, %11, %12, %13, %14, %15, %16, %17, %18, %19, %20, %21, %22, %23, %24, %25, %26, %27, %28, %29, %30, %31, %32, %33, %34, %35, %36, %37, %38, %39, %40, %41, %42, %43, %44, %45, %46, %47, %48, %49, %50, %51, %52, %53, %54, %55, %56, %57, %58, %59, %60, %61, %62, %63, %64, %65, %66, %67, %68, %69, %70, %71, %72, %73, %74, %75, %76, %77, %78, %79, %80, %81, %82, %83, %84, %85, %86, %87, %88, %89, %90, %91, %92, %93, %94, %95, %96, %97, %98, %99, %100, %101, %102, %103, %104, %105, %106, %107, %108, %109, %110, %111, %112, %113, %114, %115, %116, %117, %118, %119}, "
    "%120, %121, p, 1, 1, 0, 0;\n}\n"
    : "+f"(d[0]), "+f"(d[1]), "+f"(d[2]), "+f"(d[3]), "+f"(d[4]), "+f"(d[5]), "+f"(d[6]), "+f"(d[7]), "+f"(d[8]), "+f"(d[9]), "+f"(d[10]), "+f"(d[11]), "+f"(d[12]), "+f"(d[13]), "+f"(d[14]), "+f"(d[15]), "+f"(d[16]), "+f"(d[17]), "+f"(d[18]), "+f"(d[19]), "+f"(d[20]), "+f"(d[21]), "+f"(d[22]), "+f"(d[23]), "+f"(d[24]), "+f"(d[25]), "+f"(d[26]), "+f"(d[27]), "+f"(d[28]), "+f"(d[29]), "+f"(d[30]), "+f"(d[31]), "+f"(d[32]), "+f"(d[33]), "+f"(d[34]), "+f"(d[35]), "+f"(d[36]), "+f"(d[37]), "+f"(d[38]), "+f"(d[39]), "+f"(d[40]), "+f"(d[41]), "+f"(d[42]), "+f"(d[43]), "+f"(d[44]), "+f"(d[45]), "+f"(d[46]), "+f"(d[47]), "+f"(d[48]), "+f"(d[49]), "+f"(d[50]), "+f"(d[51]), "+f"(d[52]), "+f"(d[53]), "+f"(d[54]), "+f"(d[55]), "+f"(d[56]), "+f"(d[57]), "+f"(d[58]), "+f"(d[59]), "+f"(d[60]), "+f"(d[61]), "+f"(d[62]), "+f"(d[63]), "+f"(d[64]), "+f"(d[65]), "+f"(d[66]), "+f"(d[67]), "+f"(d[68]), "+f"(d[69]), "+f"(d[70]), "+f"(d[71]), "+f"(d[72]), "+f"(d[73]), "+f"(d[74]), "+f"(d[75]), "+f"(d[76]), "+f"(d[77]), "+f"(d[78]), "+f"(d[79]), "+f"(d[80]), "+f"(d[81]), "+f"(d[82]), "+f"(d[83]), "+f"(d[84]), "+f"(d[85]), "+f"(d[86]), "+f"(d[87]), "+f"(d[88]), "+f"(d[89]), "+f"(d[90]), "+f"(d[91]), "+f"(d[92]), "+f"(d[93]), "+f"(d[94]), "+f"(d[95]), "+f"(d[96]), "+f"(d[97]), "+f"(d[98]), "+f"(d[99]), "+f"(d[100]), "+f"(d[101]), "+f"(d[102]), "+f"(d[103]), "+f"(d[104]), "+f"(d[105]), "+f"(d[106]), "+f"(d[107]), "+f"(d[108]), "+f"(d[109]), "+f"(d[110]), "+f"(d[111]), "+f"(d[112]), "+f"(d[113]), "+f"(d[114]), "+f"(d[115]), "+f"(d[116]), "+f"(d[117]), "+f"(d[118]), "+f"(d[119])
    : "l"(da), "l"(db), "r"(scale_d));
}
__device__ __forceinline__ void wgmma_n256_rs(float (&d)[128], uint32_t a0, uint32_t a1, uint32_t a2, uint32_t a3, uint64_t db, int scale_d) {
  asm volatile("{\n.reg .pred p;\nsetp.ne.b32 p, %133, 0;\n"
    "wgmma.mma_async.sync.aligned.m64n256k16.f32.bf16.bf16 "
    "{%0, %1, %2, %3, %4, %5, %6, %7, %8, %9, %10, %11, %12, %13, %14, %15, %16, %17, %18, %19, %20, %21, %22, %23, %24, %25, %26, %27, %28, %29, %30, %31, "
    "%32, %33, %34, %35, %36, %37, %38, %39, %40, %41, %42, %43, %44, %45, %46, %47, %48, %49, %50, %51, %52, %53, %54, %55, %56, %57, %58, %59, %60, %61, %62, %63, "
    "%64, %65, %66, %67, %68, %69, %70, %71, %72, %73, %74, %75, %76, %77, %78, %79, %80, %81, %82, %83, %84, %85, %86, %87, %88, %89, %90, %91, %92, %93, %94, %95, "
    "%96, %97, %98, %99, %100, %101, %102, %103, %104, %105, %106, %107, %108, %109, %110, %111, %112, %113, %114, %115, %116, %117, %118, %119, %120, %121, %122, %123, %124, %125, %126, %127}, "
    "{%128, %129, %130, %131}, %132, p, 1, 1, 0;\n}\n"
    : "+f"(d[0]), "+f"(d[1]), "+f"(d[2]), "+f"(d[3]), "+f"(d[4]), "+f"(d[5]), "+f"(d[6]), "+f"(d[7]),
      "+f"(d[8]), "+f"(d[9]), "+f"(d[10]), "+f"(d[11]), "+f"(d[12]), "+f"(d[13]), "+f"(d[14]), "+f"(d[15]),
      "+f"(d[16]), "+f"(d[17]), "+f"(d[18]), "+f"(d[19]), "+f"(d[20]), "+f"(d[21]), "+f"(d[22]), "+f"(d[23]),
      "+f"(d[24]), "+f"(d[25]), "+f"(d[26]), "+f"(d[27]), "+f"(d[28]), "+f"(d[29]), "+f"(d[30]), "+f"(d[31]),
      "+f"(d[32]), "+f"(d[33]), "+f"(d[34]), "+f"(d[35]), "+f"(d[36]), "+f"(d[37]), "+f"(d[38]), "+f"(d[39]),
      "+f"(d[40]), "+f"(d[41]), "+f"(d[42]), "+f"(d[43]), "+f"(d[44]), "+f"(d[45]), "+f"(d[46]), "+f"(d[47]),
      "+f"(d[48]), "+f"(d[49]), "+f"(d[50]), "+f"(d[51]), "+f"(d[52]), "+f"(d[53]), "+f"(d[54]), "+f"(d[55]),
      "+f"(d[56]), "+f"(d[57]), "+f"(d[58]), "+f"(d[59]), "+f"(d[60]), "+f"(d[61]), "+f"(d[62]), "+f"(d[63]),
      "+f"(d[64]), "+f"(d[65]), "+f"(d[66]), "+f"(d[67]), "+f"(d[68]), "+f"(d[69]), "+f"(d[70]), "+f"(d[71]),
      "+f"(d[72]), "+f"(d[73]), "+f"(d[74]), "+f"(d[75]), "+f"(d[76]), "+f"(d[77]), "+f"(d[78]), "+f"(d[79]),
      "+f"(d[80]), "+f"(d[81]), "+f"(d[82]), "+f"(d[83]), "+f"(d[84]), "+f"(d[85]), "+f"(d[86]), "+f"(d[87]),
      "+f"(d[88]), "+f"(d[89]), "+f"(d[90]), "+f"(d[91]), "+f"(d[92]), "+f"(d[93]), "+f"(d[94]), "+f"(d[95]),
      "+f"(d[96]), "+f"(d[97]), "+f"(d[98]), "+f"(d[99]), "+f"(d[100]), "+f"(d[101]), "+f"(d[102]), "+f"(d[103]),
      "+f"(d[104]), "+f"(d[105]), "+f"(d[106]), "+f"(d[107]), "+f"(d[108]), "+f"(d[109]), "+f"(d[110]), "+f"(d[111]),
      "+f"(d[112]), "+f"(d[113]), "+f"(d[114]), "+f"(d[115]), "+f"(d[116]), "+f"(d[117]), "+f"(d[118]), "+f"(d[119]),
      "+f"(d[120]), "+f"(d[121]), "+f"(d[122]), "+f"(d[123]), "+f"(d[124]), "+f"(d[125]), "+f"(d[126]), "+f"(d[127])
    : "r"(a0), "r"(a1), "r"(a2), "r"(a3), "l"(db), "r"(scale_d));
}
__device__ __forceinline__ void wgmma_n128(float (&d)[64], uint64_t da, uint64_t db, int scale_d = 1) {
  asm volatile("{\n.reg .pred p;\nsetp.ne.b32 p, %66, 0;\n"
    "wgmma.mma_async.sync.aligned.m64n128k16.f32.bf16.bf16 "
    "{%0, %1, %2, %3, %4, %5, %6, %7, %8, %9, %10, %11, %12, %13, %14, %15, %16, %17, %18, %19, %20, %21, %22, %23, %24, %25, %26, %27, %28, %29, %30, %31, %32, %33, %34, %35, %36, %37, %38, %39, %40, %41, %42, %43, %44, %45, %46, %47, %48, %49, %50, %51, %52, %53, %54, %55, %56, %57, %58, %59, %60, %61, %62, %63}, "
    "%64, %65, p, 1, 1, 0, 0;\n}\n"
    : "+f"(d[0]), "+f"(d[1]), "+f"(d[2]), "+f"(d[3]), "+f"(d[4]), "+f"(d[5]), "+f"(d[6]), "+f"(d[7]), "+f"(d[8]), "+f"(d[9]), "+f"(d[10]), "+f"(d[11]), "+f"(d[12]), "+f"(d[13]), "+f"(d[14]), "+f"(d[15]), "+f"(d[16]), "+f"(d[17]), "+f"(d[18]), "+f"(d[19]), "+f"(d[20]), "+f"(d[21]), "+f"(d[22]), "+f"(d[23]), "+f"(d[24]), "+f"(d[25]), "+f"(d[26]), "+f"(d[27]), "+f"(d[28]), "+f"(d[29]), "+f"(d[30]), "+f"(d[31]), "+f"(d[32]), "+f"(d[33]), "+f"(d[34]), "+f"(d[35]), "+f"(d[36]), "+f"(d[37]), "+f"(d[38]), "+f"(d[39]), "+f"(d[40]), "+f"(d[41]), "+f"(d[42]), "+f"(d[43]), "+f"(d[44]), "+f"(d[45]), "+f"(d[46]), "+f"(d[47]), "+f"(d[48]), "+f"(d[49]), "+f"(d[50]), "+f"(d[51]), "+f"(d[52]), "+f"(d[53]), "+f"(d[54]), "+f"(d[55]), "+f"(d[56]), "+f"(d[57]), "+f"(d[58]), "+f"(d[59]), "+f"(d[60]), "+f"(d[61]), "+f"(d[62]), "+f"(d[63])
    : "l"(da), "l"(db), "r"(scale_d));
}
template<int N> __device__ __forceinline__ void fence_acc(float (&d)[N]) {
#pragma unroll
  for (int i = 0; i < N; i++) asm volatile("" : "+f"(d[i]) :: "memory");
}

template<int N, int I = 0, class F> __device__ __forceinline__ void static_for(F&& f) {
  if constexpr (I < N) { f(std::integral_constant<int, I>()); static_for<N, I + 1>(f); }
}

__device__ __forceinline__ void ldsm_x4_t(uint32_t addr, uint32_t& a, uint32_t& b, uint32_t& c, uint32_t& d) {
  asm volatile("ldmatrix.sync.aligned.m8n8.x4.trans.shared.b16 {%0, %1, %2, %3}, [%4];" : "=r"(a), "=r"(b), "=r"(c), "=r"(d) : "r"(addr));
}
__device__ __forceinline__ void sts128(uint32_t addr, uint32_t a, uint32_t b, uint32_t c, uint32_t d) {
  asm volatile("st.shared.v4.b32 [%0], {%1, %2, %3, %4};" :: "r"(addr), "r"(a), "r"(b), "r"(c), "r"(d));
}
__device__ __forceinline__ void mma16816(float (&c)[4], uint32_t a0, uint32_t a1, uint32_t a2, uint32_t a3, uint32_t b0, uint32_t b1) {
  asm volatile("mma.sync.aligned.m16n8k16.row.col.f32.bf16.bf16.f32 {%0, %1, %2, %3}, {%4, %5, %6, %7}, {%8, %9}, {%0, %1, %2, %3};"
      : "+f"(c[0]), "+f"(c[1]), "+f"(c[2]), "+f"(c[3]) : "r"(a0), "r"(a1), "r"(a2), "r"(a3), "r"(b0), "r"(b1));
}
__device__ __forceinline__ void mma1688(float (&c)[4], uint32_t a0, uint32_t a1, uint32_t b0) {
  asm volatile("mma.sync.aligned.m16n8k8.row.col.f32.bf16.bf16.f32 {%0, %1, %2, %3}, {%4, %5}, {%6}, {%0, %1, %2, %3};"
      : "+f"(c[0]), "+f"(c[1]), "+f"(c[2]), "+f"(c[3]) : "r"(a0), "r"(a1), "r"(b0));
}
__device__ __forceinline__ void pin(uint32_t& v) { asm volatile("shfl.sync.bfly.b32 %0, %0, 0, 0x1f, 0xffffffff;" : "+r"(v)); }
template<class T> __device__ __forceinline__ void pin(T*& v) {
  uint32_t lo = (uint32_t)(uint64_t)v, hi = (uint32_t)((uint64_t)v >> 32);
  pin(lo); pin(hi);
  v = (T*)(((uint64_t)hi << 32) | lo);
}
__device__ __forceinline__ float sel4(int q, float a, float b, float c, float d) {
  float r;
  asm("{\n.reg .pred p, o;\n.reg .f32 x, y;\n.reg .b32 t;\nand.b32 t, %1, 1;\nsetp.ne.b32 p, t, 0;\nsetp.gt.s32 o, %1, 1;\n"
      "selp.f32 x, %3, %2, p;\nselp.f32 y, %5, %4, p;\nselp.f32 %0, y, x, o;\n}\n" : "=f"(r) : "r"(q), "f"(a), "f"(b), "f"(c), "f"(d));
  return r;
}
__device__ __forceinline__ uint32_t bfma2(uint32_t a, uint32_t b, uint32_t c) { uint32_t r; asm("fma.rn.bf16x2 %0, %1, %2, %3;" : "=r"(r) : "r"(a), "r"(b), "r"(c)); return r; }
__device__ __forceinline__ void tma_load_5d(uint32_t dst, const CUtensorMap* tm, uint32_t bar, int c0, int c4) {
  asm volatile("cp.async.bulk.tensor.5d.shared::cluster.global.mbarrier::complete_tx::bytes [%0], [%1, {%3, %4, %4, %4, %5}], [%2];"
    :: "r"(dst), "l"(tm), "r"(bar), "r"(c0), "r"(0), "r"(c4) : "memory");
}
__device__ __forceinline__ void tma_load_4d(uint32_t dst, const CUtensorMap* tm, uint32_t bar, int c0, int c3) {
  asm volatile("cp.async.bulk.tensor.4d.shared::cluster.global.mbarrier::complete_tx::bytes [%0], [%1, {%3, %4, %4, %5}], [%2];"
    :: "r"(dst), "l"(tm), "r"(bar), "r"(c0), "r"(0), "r"(c3) : "memory");
}
__device__ __forceinline__ void tma_load_4d_hint(uint32_t dst, const CUtensorMap* tm, uint32_t bar, int c0, int c3, uint64_t pol) {
  asm volatile("cp.async.bulk.tensor.4d.shared::cluster.global.mbarrier::complete_tx::bytes.L2::cache_hint [%0], [%1, {%3, %4, %4, %5}], [%2], %6;"
    :: "r"(dst), "l"(tm), "r"(bar), "r"(c0), "r"(0), "r"(c3), "l"(pol) : "memory");
}
__device__ __forceinline__ void tma_prefetch_4d(const CUtensorMap* tm, int c0, int c3) {
  asm volatile("cp.async.bulk.prefetch.tensor.4d.L2.global.tile [%0, {%1, %2, %2, %3}];" :: "l"(tm), "r"(c0), "r"(0), "r"(c3) : "memory");
}
__device__ __forceinline__ void tma_store_5d(const CUtensorMap* tm, uint32_t src, int c0, int c4) {
  asm volatile("cp.async.bulk.tensor.5d.global.shared::cta.bulk_group [%0, {%2, %3, %3, %3, %4}], [%1];" :: "l"(tm), "r"(src), "r"(c0), "r"(0), "r"(c4) : "memory");
}
__device__ __forceinline__ float rcp_fast(float x) { float r; asm("rcp.approx.ftz.f32 %0, %1;" : "=f"(r) : "f"(x)); return r; }
__device__ __forceinline__ float sigmoid_fast(float x) { float e; asm("ex2.approx.ftz.f32 %0, %1;" : "=f"(e) : "f"(x * -1.4426950408889634f)); return rcp_fast(1.f + e); }
__device__ __forceinline__ float sqrt_fast(float x) { float r; asm("sqrt.approx.ftz.f32 %0, %1;" : "=f"(r) : "f"(x)); return r; }
__device__ __forceinline__ float ln_sd(float var) { return bf16r(sqrt_fast(bf16r(bf16r(fmaxf(var, 0.f)) + 1e-5f))); }
__device__ __forceinline__ uint32_t norm2(uint32_t h, uint32_t neg_mean2, float inv_sd) {
  const uint32_t d = badd2(h, neg_mean2);
  return pack_bf16(bf_lo(d) * inv_sd, bf_hi(d) * inv_sd);
}
template<int N> __device__ __forceinline__ void delay_clk() {
  if constexpr (N > 0) { const uint32_t t0 = clock(); while ((uint32_t)clock() - t0 < N) {} }
}
__device__ __forceinline__ void put_xstat(uint32_t rs, uint32_t exb, int col, uint32_t mean_rstd, int m) {
  smem_at<uint16_t>(rs + ((col & 7) >> 1) * 144 + (col >> 3) * 4 + (col & 1) * 2) = (uint16_t)(mean_rstd ^ (m << 15));
  const uint32_t nm = (mean_rstd >> 16) ^ 0x8000u;
  smem_at<uint4>(exb + (col >> 3) * 256 + (col & 7) * 16) = make_uint4(nm | (nm << 16), nm, 0, 0);
  smem_at<uint4>(exb + (col >> 3) * 256 + 128 + (col & 7) * 16) = make_uint4(0, 0, 0, 0);
}
__device__ __forceinline__ void put_dsum(uint32_t exa, int e, float c) {
  const float hi = bf16r(c), mid = bf16r(c - hi), lo = bf16r((c - hi) - mid);
  smem_at<uint4>(exa + (e >> 3) * 256 + (e & 7) * 16) = make_uint4((__float_as_uint(hi) >> 16) | (__float_as_uint(mid) & 0xFFFF0000u), __float_as_uint(lo) >> 16, 0, 0);
  smem_at<uint4>(exa + (e >> 3) * 256 + 128 + (e & 7) * 16) = make_uint4(0, 0, 0, 0);
}
__host__ __device__ constexpr int min_c(int a, int b) { return a < b ? a : b; }
template<int V> using IC = std::integral_constant<int, V>;

#define CT(slot) do {} while (0)
#define PT(slot) do {} while (0)

template<int MAP>
__global__ void __cluster_dims__(2, 1, 1) __launch_bounds__(384, 1)
fnet_moe_kernel(const __grid_constant__ Params p) {
  constexpr int NX = MAP == 0 ? NX0 : 256;
  constexpr int G1_BYTES = A_BYTES + NX * 128;
  uint32_t sb;
  asm volatile("mov.u32 %0, %1;" : "=r"(sb) : "r"(smem_u32(smem_raw)));
  const int m = blockIdx.x & 1;
  int tau, eps;
  bool helper = false;
  if (MAP == 0) {
    uint32_t smid;
    asm volatile("mov.u32 %0, %%smid;" : "=r"(smid));
    const int c = smid >> 1, e7 = ((c - 32) * 37) >> 8;
    helper = c == 60 || c == 61;
    tau = c < 32 ? (c & 7) : (c < 60 ? c - 31 - 7 * e7 : 0);
    eps = c < 32 ? (c >> 3) : (c < 60 ? 4 + e7 : c - 58);
  } else {
    tau = (blockIdx.x >> 1) & 7; eps = blockIdx.x >> 4;
  }
  const int cid = tau * 16 + eps * 2 + m;
  const bool moe = tau > 0;
  auto BAR = [&](int i) { return sb + OFF_BAR + 8 * i; };
  const CUtensorMap* tmD = m ? &p.tmD1 : &p.tmD0;
  const uint64_t pol_ef = policy_evict_first();
#define LOAD_STREAM(d, tm, bar, c0, c1) tma_load_2d_hint(d, tm, bar, c0, c1, pol_ef)
#define LOAD_W(d, tm, bar, c0, grp) tma_load_4d_hint(d, tm, bar, c0, (grp) * 32, pol_ef)
  auto helper_load = [&](int k) {
    const uint32_t sa = sb + slot_of(k) * ST_BYTES, bar = BAR(B_FULL + slot_of(k));
    const CUtensorMap* tm = eps == 3 ? &p.tmD1 : &p.tmD0;
    tma_load_5d(sa, &p.tmXh, bar, (k & 15) * 64, 0);
    tma_load_2d(sa + A_BYTES, tm, bar, (k & 15) * 64, m * 512 + (k >> 4) * 256);
    tma_load_2d(sa + A_BYTES + 16384, tm, bar, (k & 15) * 64, m * 512 + (k >> 4) * 256 + 128);
  };
  if (threadIdx.x < 32 && elect_one()) {
    mbar_init(BAR(B_FULL), 1);
    asm volatile("fence.mbarrier_init.release.cluster;" ::: "memory");
    if (!helper) {
      tma_load_2d(sb + A_BYTES, &p.tmX, BAR(B_FULL), 0, tau * 256);
      tma_load_2d(sb, tmD, BAR(B_FULL), 0, eps * 128);
    }
    PT(52);
#pragma unroll
    for (int k = 1; k < 4; k++) mbar_init(BAR(B_FULL + k), 1);
    asm volatile("fence.mbarrier_init.release.cluster;" ::: "memory");
#pragma unroll
    for (int k = 0; k < 4; k++) mbar_expect_tx(BAR(B_FULL + k), helper ? ST_BYTES : G1_BYTES);
    if (!helper) {
#pragma unroll
      for (int k = 1; k < 4; k++) {
        tma_load_2d(sb + k * ST_BYTES + A_BYTES, &p.tmX, BAR(B_FULL + k), k * 64, tau * 256);
        LOAD_STREAM(sb + k * ST_BYTES, tmD, BAR(B_FULL + k), k * 64, eps * 128);
      }
    } else {
#pragma unroll 1
      for (int k = 0; k < 4; k++) helper_load(k);
    }
    PT(0);
  }
  __syncwarp();
  const int warp = __shfl_sync(0xffffffffu, threadIdx.x >> 5, 0);
  if (warp == 8) {
    if (elect_one()) {
#pragma unroll
      for (int b = B_EMPTY; b < B_COUNT; b++)
        mbar_init(BAR(b), b < B_EPI ? 2 : (b == B_EPI || b == B_EPI0B) ? 4 : (b < B_STD || b == B_OUT) ? 8 : (b == B_STAT || b == B_XS) ? 3 : 1);
      asm volatile("fence.mbarrier_init.release.cluster;" ::: "memory");
      mbar_expect_tx(BAR(B_XCH), 32768);
      SM_(uint32_t, OFF_SEEN) = 0;
    }
  }
  __syncthreads();

  if (warp >= 8) {
    reg_dec<REG_P>();
    asm volatile("barrier.cluster.arrive.relaxed.aligned;" ::: "memory");
    const int abrow = m * 1024 + eps * 128;
    const int f0 = (cid - 16) * 32;
    const CUtensorMap* tmWM = m ? &p.tmWM1 : &p.tmWM0;
    auto side_first = [&](int k) {
      if (NX < 256 && k == MINI_LOAD_K) {
        static_assert(NX == 256 || (mr_k(NREG_H) == MINI_LOAD_K && (NREG_H & 1) == 1), "second half of the staging buffer must be free");
        mbar_wait(BAR(B_STD + 3), 0);
        uint32_t n = 0;
        while (!((*(volatile uint32_t*)&SM_(uint32_t, OFF_SEEN) >> (4 * tau + 1)) & 1) && ++n < SPIN_LIMIT * 16) {}
        if (elect_one()) {
          mbar_expect_tx(BAR(B_A20), 12288);
          tma_load_2d(sb + OFF_MINI, &p.tmAbM, BAR(B_A20), tau * 256 + 240, abrow);
          LOAD_W(sb + OFF_MINI + 4096, tmWM, BAR(B_A20), tau * 256 + 240, tau * 2 + m);
          LOAD_W(sb + OFF_MINI + 8192, tmWM, BAR(B_A20), tau * 256 + 240, tau * 2 + 1 - m);
        }
      }
    };
    auto side = [&](int k) {
      if (NX < 256 && k == MINI_PF_K && elect_one()) tma_prefetch_4d(tmWM, tau * 256 + 240, tau * 64 + (eps & 1) * 32);
      if (k == WPF2_K && eps < WPF2_N && elect_one()) tma_prefetch_4d(m ? &p.tmW1 : &p.tmW0, kblock(tau, 31 - (eps >> 1)) * 64, tau * 64 + (eps & 1) * 32);
      if (!moe) return;
      const int i = k - MR_K0, r6 = i / MR_P, u = i - MR_P * r6, h = 2 * r6 + (u >> 1);
      if (i >= 0 && u < 4 && h < NREG_H) {
        if (h < 2) mbar_wait(BAR(B_STD + 2 + h), 0);
        if (elect_one()) {
          if (!(u & 1)) mbar_expect_tx(BAR(B_MR + (h & 1)), 16384);
          LOAD_STREAM(sb + OFF_XCH + u * 8192, (u & 1) ? &p.tmU : &p.tmG, BAR(B_MR + (h & 1)), f0, h * 128);
        }
      }
      if (k >= GU_K && k < GU_K + 2 && elect_one()) {
        static_assert(mr_k(NREG_H + 1) <= GU_K + 1 && MINI_K + 4 <= GU_K && GU_K < 47, "staging buffer must be free");
        LOAD_STREAM(sb + round_off(NREG_H + k - GU_K), &p.tmG, BAR(B_GU), f0, (NREG_H + k - GU_K) * 128);
        LOAD_STREAM(sb + round_off(NREG_H + k - GU_K) + 8192, &p.tmU, BAR(B_GU), f0, (NREG_H + k - GU_K) * 128);
      }
      if (k >= PF_K1 && !(k & 1) && elect_one()) {
        const int j = PF_N0 + ((k - PF_K1) >> 1);
        if (j < 8) tma_prefetch_2d(m ? &p.tmU : &p.tmG, f0, j * 128);
        else if (j < 12) asm volatile("cp.async.bulk.prefetch.L2.global [%0], %1;" :: "l"(p.wdown + (size_t)f0 * 1024 + (j - 8) * 8192), "r"(16384) : "memory");
      }
    };
    if (MAP == 0 && helper) {
      if (warp == 8) {
#pragma unroll 1
        for (int k = 4; k < 32; k++) {
          mbar_wait(BAR(B_EMPTY + slot_of(k)), (use_of(k) & 1) ^ 1);
          if (elect_one()) { mbar_expect_tx(BAR(B_FULL + slot_of(k)), ST_BYTES); helper_load(k); }
        }
      } else {
        const int i0 = threadIdx.x - 288, lane = threadIdx.x & 31, col0 = (eps - 2) * 8 + m * 4;
#pragma unroll 1
        for (int u = 0; u < 3; u++) mbar_wait(BAR(B_EMPTY + 0), u & 1);
        const uint32_t tag = ld_relaxed32(&p.s->epoch) + 1;
        if (i0 < 8) pkt_st128(&p.s->hflag[col0 * 2 + i0], 0, 0, 0, 0);
        SM_(uint32_t, OFF_TAG) = tag;
#pragma unroll 1
        for (int j0 = i0; j0 < 768; j0 += 384) {
          uint2 v[4]; uint32_t n = 0;
          while (true) {
#pragma unroll
            for (int z = 0; z < 4; z++) {
              const int j = j0 + 96 * z;
              v[z] = pkt_ld64(p.s->xstat + (j < 128 ? 256 * (j >> 4) + 240 + 2 * (j & 6) + ((j >> 2) & 2) + (j & 1)
                                          : j < 640 ? 2048 + col0 * 128 + j - 128 : (j - 640) * 16));
            }
            if (__all_sync(0xffffffffu, v[0].y == tag && v[1].y == tag && v[2].y == tag && v[3].y == tag) || ++n > SPIN_LIMIT) break;
            __nanosleep(300);
          }
#pragma unroll
          for (int z = 0; z < 4; z++) {
            const int j = j0 + 96 * z;
            if (j < 128) put_xstat(sb + OFF_RS, sb + OFF_XCH + 16384, j, v[z].x, eps - 2);
            else if (j < 640) put_dsum(sb + OFF_XCH, j - 128, __uint_as_float(v[z].x));
          }
        }
        fence_async_smem();
        __syncwarp();
        if (lane == 0) mbar_arrive(BAR(B_STAT));
      }
    } else if (warp == 8) {
      const CUtensorMap* tmW = m ? &p.tmW1 : &p.tmW0;
      const int gA = tau * 2 + m, gB = tau * 2 + 1 - m;
      auto wait_slot = [&](int k) {
        mbar_wait(BAR(B_EMPTY + slot_of(k)), (use_of(k) & 1) ^ 1);
        PT(64 + k);
      };
#pragma unroll 1
      for (int k = 4; k < 24; k++) {
        const int s = slot_of(k);
        const uint32_t sa = sb + s * ST_BYTES, sbb = sa + A_BYTES;
        const int kb = kblock(tau, k - 16);
        wait_slot(k);
        if (elect_one()) {
          mbar_expect_tx(BAR(B_FULL + s), k < 16 ? G1_BYTES : (k >> 1) == 9 ? B_BYTES : k == 20 ? ST_BYTES - 8192 : ST_BYTES);
          if (k < 16) {
            LOAD_STREAM(sa, tmD, BAR(B_FULL + s), k * 64, eps * 128);
            tma_load_2d(sbb, &p.tmX, BAR(B_FULL + s), k * 64, tau * 256);
          } else {
            LOAD_W(sbb, tmW, BAR(B_FULL + s), kb * 64, gA);
            LOAD_W(sbb + 16384, tmW, BAR(B_FULL + s), kb * 64, gB);
            if (k < 18) {
              tma_load_4d(sa, &p.tmXr, BAR(B_FULL + s), eps * 128, gA * 32 + s * 16);
              tma_load_4d(sa + 8192, &p.tmXr, BAR(B_FULL + s), eps * 128 + 64, gA * 32 + s * 16);
            }
          }
          if (k == PUB_K1) mbar_arrive(BAR(B_LATE));
          if (k >= WPF_K0 && k < WPF_K0 + WPF_N && (eps >> 1) == ((k - WPF_K0) & 3))
            tma_prefetch_4d(tmW, kblock(tau, k - WPF_K0) * 64, tau * 64 + (eps & 1) * 32);
          if (moe && k >= PF_K0 && k < PF_K0 + 2 * PF_N0 && !(k & 1)) tma_prefetch_2d(m ? &p.tmU : &p.tmG, f0, (k - PF_K0) * 64);
        }
      }
      uint32_t seen = 0;
#pragma unroll 1
      for (int k = 24; k < 48; k++) {
        const int s = slot_of(k);
        const uint32_t sa = sb + s * ST_BYTES, sbb = sa + A_BYTES;
        const int kb = kblock(tau, k - 16);
        const uint32_t need = (1u << kb) | ((kb & 3) == 3 ? 2u << (4 * tau) : 0u);
        wait_slot(k);
        side_first(k);
        if (elect_one()) {
          mbar_expect_tx(BAR(B_FULL + s), ST_BYTES);
          LOAD_W(sbb, tmW, BAR(B_FULL + s), kb * 64, gA);
          LOAD_W(sbb + 16384, tmW, BAR(B_FULL + s), kb * 64, gB);
        }
        uint32_t n = 0;
        while ((seen & need) != need && ++n < SPIN_LIMIT * 16) seen = *(volatile uint32_t*)&SM_(uint32_t, OFF_SEEN);
        if (elect_one()) tma_load_2d(sa, &p.tmAbL, BAR(B_FULL + s), kb * 64, abrow);
        side(k);
      }
      if (moe) {
        mbar_wait(BAR(B_EMPTY + 0), 1);
        if (elect_one()) { mbar_expect_tx(BAR(B_GU), (8 - NREG_H) * 16384); mbar_expect_tx(BAR(B_DN), 65536); }
#pragma unroll 1
        for (int i = 0; i < 10 - NREG_H; i++) {
          if (i == 3) mbar_wait(BAR(B_EMPTY + 1), 1);
          if (i == 4) {
            mbar_wait(BAR(B_EMPTY + 2), 1);
            mbar_wait(BAR(B_XCH), 0);
            PT(53);
          }
          const uint32_t dst = sb + late_off(i);
          if (elect_one()) {
            if (i < 6 - NREG_H) {
              LOAD_STREAM(dst, &p.tmG, BAR(B_GU), f0, (NREG_H + 2 + i) * 128);
              LOAD_STREAM(dst + 8192, &p.tmU, BAR(B_GU), f0, (NREG_H + 2 + i) * 128);
            } else {
#pragma unroll
              for (int b = 0; b < 4; b++) LOAD_STREAM(dst + b * 4096, &p.tmDn, BAR(B_DN), (4 * (i - 6 + NREG_H) + b) * 64, f0);
            }
          }
          const long long t0 = clock64();
          while (i < 9 - NREG_H && clock64() - t0 < MOE_PACE_CLK) {}
        }
      }
      const int lane = threadIdx.x & 31;
      mbar_wait(BAR(B_OUT), 0);
      const uint32_t km = SM_(uint32_t, OFF_WKEY + (lane & 7) * 8);
      const uint32_t bk = __reduce_max_sync(0xffffffffu, km);
      const int ww = __ffs(__ballot_sync(0xffffffffu, km == bk)) - 1;
#pragma unroll 1
      for (int i = 1; i <= 8; i++) {
        const int W = (ww + i) & 7;
        if (i == 8) {
          mbar_wait(BAR(B_XS), 0);
          if (SM_(uint32_t, OFF_KV) == bk) {
#pragma unroll 2
            for (int j = lane; j < 256; j += 32) {
              const int rho = j >> 4, row = row_of(gA * 128 + 32 * (W >> 1) + 8 * ((rho & 7) >> 1) + 4 * (W & 1) + 2 * (rho >> 3) + (rho & 1));
              const uint4 v = lds128_v(sb + OFF_OUT + (j & 8) * 2048 + (16 * W + rho) * 128 + (((j ^ rho) & 7) << 4));
              if (row != 0xFFFF - (int)(bk & 0xFFFFu))
                asm volatile("st.global.v4.b32 [%0], {%1, %2, %3, %4};" :: "l"(p.out + (size_t)row * 1024 + eps * 128 + (j & 15) * 8), "r"(v.x), "r"(v.y), "r"(v.z), "r"(v.w));
            }
            break;
          }
        }
        if (lane == 0) {
          tma_store_5d(&p.tmOut, sb + OFF_OUT + W * 2048, eps * 128, row_of(gA * 128 + 32 * (W >> 1) + 4 * (W & 1)));
          tma_store_5d(&p.tmOut, sb + OFF_OUT + 16384 + W * 2048, eps * 128 + 64, row_of(gA * 128 + 32 * (W >> 1) + 4 * (W & 1)));
        }
        const long long t0 = clock64();
        while (i < 7 && clock64() - t0 < OUT_PACE_CLK) {}
      }
      if (lane == 0) { bulk_commit(); bulk_wait_all(); }
      PT(22);
    } else {
      const int a = warp - 9;
      const int lane = threadIdx.x & 31;
      auto stage = [&](const bf16* src, int g) {
        if (elect_one()) {
          mbar_expect_tx(BAR(B_AUX + g), 16384);
          bulk_load(sb + OFF_XCH + g * 16384, src + g * 8192, 16384, BAR(B_AUX + g));
        }
      };
      uint32_t tag = 0;
      mbar_wait(BAR(B_FULL + AUX_AFTER), 0);
      if (a == 0) PT(1);
      if (a == 1) mbar_wait(BAR(B_AUX + 0), 0);
      if (a < 2) stage(p.x + (size_t)cid * 16 * 1024, a);
#pragma unroll 1
      for (int it = 0; it < 4; it++) {
        const int g = it & 1;
        mbar_wait(BAR(B_AUX + g), it >> 1);
        if (a == 0) PT(2 + it);
        if (it == 2) tag = ld_relaxed32(&p.s->epoch) + 1;
        if (it == 2 && a == 2 && lane < 16) asm volatile("prefetch.global.L2 [%0];" :: "l"(p.wr + lane * 64));
        const uint32_t ad = sb + OFF_XCH + g * 16384 + (lane >> 2) * 2048;
        float s0 = 0.f, s1 = 0.f, q0 = 0.f, q1 = 0.f;
        auto row = [&](auto sq) {
#pragma unroll
          for (int i = 0; i < 11; i++) {
            if (i == 10 && a == 2) break;
            const uint4 v = lds128_v(ad + (((a * 44 + 4 * i + lane) & 127) << 4));
            const uint32_t ww[4] = {v.x, v.y, v.z, v.w};
#pragma unroll
            for (int z = 0; z < 4; z++) {
              const float d0 = bf_lo(ww[z]), d1 = bf_hi(ww[z]);
              s0 += d0; s1 += d1;
              if (decltype(sq)::value) { q0 = fmaf(d0, d0, q0); q1 = fmaf(d1, d1, q1); }
            }
          }
        };
        if (it < 2) row(IC<1>()); else row(IC<0>());
        s0 += s1; q0 += q1;
#pragma unroll
        for (int o = 1; o < 4; o <<= 1) { s0 += __shfl_xor_sync(0xffffffffu, s0, o); q0 += __shfl_xor_sync(0xffffffffu, q0, o); }
        if ((lane & 3) == 0) SM_(float2, OFF_PUB + a * 256 + it * 64 + (lane >> 2) * 8) = make_float2(s0, q0);
        if (it != 2) bar_sync(NB_AUX, 96);
        if (it < 2 && a == 2) stage(cid < 64 ? p.Dre + (size_t)cid * 16 * 1024 : p.Dim + (size_t)(cid - 64) * 16 * 1024, g);
      }
      if (a == 1) {
        const float2 v0 = SM_(float2, OFF_PUB + lane * 8), v1 = SM_(float2, OFF_PUB + 256 + lane * 8), v2 = SM_(float2, OFF_PUB + 512 + lane * 8);
        const float s = v0.x + v1.x + v2.x, mean = s * (1.f / 1024.f);
        const float rs = rcp_fast(ln_sd((v0.y + v1.y + v2.y) * (1.f / 1024.f) - mean * mean));
        pkt_st64((lane < 16 ? p.s->xstat : p.s->dsum) + cid * 16 + (lane & 15), lane < 16 ? pack_bf16(rs, mean) : __float_as_uint(s), tag);
        PT(6);
      }
      if (a == 2) {
        float s = 0.f;
#pragma unroll
        for (int q = 0; q < 4; q++) {
          const uint4 v = ldg_nc128(p.wr + (q * 32 + lane) * 8);
          s += ((bf_lo(v.x) + bf_hi(v.x)) + (bf_lo(v.y) + bf_hi(v.y))) + ((bf_lo(v.z) + bf_hi(v.z)) + (bf_lo(v.w) + bf_hi(v.w)));
          const int ch = q * 32 + lane - eps * 16;
          if (ch >= 0 && ch < 16) {
            SM_(uint32_t, OFF_WR + ch * 4) = v.x; SM_(uint32_t, OFF_WR + 80 + ch * 4) = v.y;
            SM_(uint32_t, OFF_WR + 160 + ch * 4) = v.z; SM_(uint32_t, OFF_WR + 240 + ch * 4) = v.w;
          }
        }
        s = warp_sum(s);
        if (lane == 0) { SM_(float, OFF_WSUM) = s; SM_(uint32_t, OFF_TAG) = tag; }
      }
      if (a < 2) __nanosleep(GATHER_NS);
      {
        const int i0 = a * 32 + lane;
        uint2 v[3], c0, c1; uint32_t n = 0;
        const uint2* dp = &p.s->dsum[abrow];
        while (true) {
#pragma unroll
          for (int q = 0; q < 3; q++) v[q] = pkt_ld64(&p.s->xstat[tau * 256 + min(i0 + 96 * q, 255)]);
          c0 = pkt_ld64(dp + i0); c1 = pkt_ld64(dp + min(i0 + 96, 127));
          if (__all_sync(0xffffffffu, v[0].y == tag && v[1].y == tag && v[2].y == tag && c0.y == tag && c1.y == tag) || ++n > SPIN_LIMIT) break;
          __nanosleep(200);
        }
#pragma unroll
        for (int q = 0; q < 3; q++) put_xstat(sb + OFF_RS, sb + OFF_EXB, min(i0 + 96 * q, 255), v[q].x, m);
        put_dsum(sb + OFF_EXA, i0, __uint_as_float(c0.x));
        put_dsum(sb + OFF_EXA, min(i0 + 96, 127), __uint_as_float(c1.x));
        fence_async_smem();
      }
      __syncwarp();
      if (lane == 0) mbar_arrive(BAR(B_STAT));
      if (a == 0) PT(7);
      if (a == 0) {
        const int sg = (lane >> 2) == tau ? sigma_of(tau, 0) : lane >> 2;
        const uint32_t* flg = reinterpret_cast<const uint32_t*>(&p.s->abflag[((eps * 2 + m) * 8 + sg) * 2]) + ((lane >> 2) == tau ? 4 : lane & 3);
        if (NX < 256 && lane == 4 * tau + 1) flg = reinterpret_cast<const uint32_t*>(&p.s->hflag[(m * 8 + eps) * 2]);
        uint32_t seen = 0;
        auto until = [&](int tile) {
          uint32_t n = 0;
          while (!((seen >> (4 * tile)) & 1) && ++n < SPIN_LIMIT) seen = __ballot_sync(0xffffffffu, ld_relaxed32(flg) == tag);
        };
        const int s0 = sigma_of(tau, 0), s1 = sigma_of(tau, 1), s2 = sigma_of(tau, 2), s3 = sigma_of(tau, 3);
        mbar_wait(BAR(B_EPI), 0);
        mbar_wait(BAR(B_FULL + 0), 0);
        mbar_wait(BAR(B_FULL + 1), 0);
        if (elect_one()) mbar_expect_tx(BAR(B_A20), 8192);
        mbar_wait(BAR(B_STDA), 0);
        PT(49);
        until(tau);
        mbar_wait(BAR(B_EPI0B), 0);
        PT(48);
        if (elect_one()) tma_load_2d(sb + OFF_XCH, &p.tmAbS, BAR(B_FULL + 0), s0 * 256, abrow);
        mbar_wait(BAR(B_FULL + 2), 0);
        mbar_wait(BAR(B_STD + 0), 0);
        until(s0);
        PT(16);
        if (elect_one()) tma_load_2d(sb + OFF_XCH + 8192, &p.tmAbS, BAR(B_A20), s0 * 256, abrow + 64);
        until(s1);
        PT(17);
        if (elect_one()) tma_load_2d(sb + OFF_XCH + 16384, &p.tmAbL, BAR(B_FULL + 1), s1 * 256, abrow);
        until(s2);
        PT(18);
        if (elect_one()) {
          tma_load_2d(sb + 2 * ST_BYTES, &p.tmAbL, BAR(B_FULL + 2), s2 * 256, abrow);
          mbar_arrive(BAR(B_PUB1));
        }
        until(s3);
        mbar_wait(BAR(B_FULL + 3), 0);
        mbar_wait(BAR(B_STD + 1), 0);
        PT(19);
        if (elect_one()) tma_load_2d(sb + 3 * ST_BYTES, &p.tmAbL, BAR(B_FULL + 3), s3 * 256, abrow);
        uint32_t n = 0;
        while (true) {
          asm volatile("fence.proxy.async.global;" ::: "memory");
          *(volatile uint32_t*)&SM_(uint32_t, OFF_SEEN) = seen;
          if (seen == 0xFFFFFFFFu || ++n > SPIN_LIMIT) break;
          seen = __ballot_sync(0xffffffffu, ld_relaxed32(flg) == tag);
          __nanosleep(100);
        }
      } else {
        uint32_t* flag = reinterpret_cast<uint32_t*>(&p.s->abflag[((eps * 2 + m) * 8 + tau) * 2]);
        mbar_wait(BAR(a == 1 ? B_EPI : B_EPI0B), 0);
        if (a == 1) PT(8);
        if (lane == 0) {
          tma_store_2d(&p.tmAbS, sb + chunk_off(0, a - 1), tau * 256, abrow + (a - 1) * 64);
          bulk_commit();
          bulk_wait_all();
        }
        if (a == 2) mbar_wait(BAR(B_STDA), 0);
        if (lane == 0) {
          st_relaxed32(flag + (a == 1 ? 4 : 0), tag);
          mbar_arrive(BAR(a == 1 ? B_STDA : B_STD));
        }
        if (a == 2) PT(12);
        if (a == 1) {
          mbar_wait(BAR(B_EPI + 1), 0);
          mbar_wait(BAR(B_LATE), 0);
          mbar_wait(BAR(B_PUB1), 0);
          PT(9);
          if (lane == 0) {
            tma_store_2d(&p.tmAbS, sb + chunk_off(1, 0), tau * 256 + 64, abrow);
            tma_store_2d(&p.tmAbS, sb + chunk_off(1, 1), tau * 256 + 64, abrow + 64);
            bulk_commit();
            bulk_wait_all();
            st_relaxed32(flag + 1, tag);
            mbar_arrive(BAR(B_STD + 1));
          }
          PT(13);
        }
        auto copy_out = [&](int c) {
          mbar_wait(BAR(B_EPI + c), 0);
          PT(8 + c);
          bf16* dst = p.s->abT + (size_t)(abrow + (lane >> 3)) * 2048 + tau * 256 + c * 64 + (lane & 7) * 8;
          const uint32_t src = sb + chunk_off(c, 0) + (lane >> 3) * 128 + (((lane & 7) ^ (lane >> 3)) << 4);
          const uint32_t on = c * 64 + (lane & 7) * 8 < NX;
#pragma unroll 4
          for (int i = 0; i < 32; i++) {
            const uint4 v = lds128_v((src ^ ((i & 1) << 6)) + i * 512);
            asm volatile("{\n.reg .pred p;\nsetp.ne.b32 p, %5, 0;\n@p st.global.v4.b32 [%0], {%1, %2, %3, %4};\n}\n"
                         :: "l"(dst + i * 4 * 2048), "r"(v.x), "r"(v.y), "r"(v.z), "r"(v.w), "r"(on));
          }
          __syncwarp();
          if (lane == 0) mbar_arrive(BAR(B_STD + c));
        };
        if (a == 2) {
#pragma unroll 1
          for (int c = 2; c < 4; c++) copy_out(c);
          asm volatile("fence.acq_rel.gpu;" ::: "memory");
          __syncwarp();
          if (lane < 2) st_relaxed32(flag + 2 + lane, tag);
          PT(15);
        }
      }
      {
        mbar_wait(BAR(B_LATE), 1);
        const int grp = tau * 2 + m;
#pragma unroll 1
        for (int i = a; i < 14; i += 3) {
          uint4* dst = i < 8 ? &p.s->ypart[cid * 256 + i * 32 + lane] : i < 12 ? &p.s->hstat[(grp * 8 + eps) * 128 + (i - 8) * 32 + lane]
                     : i == 12 ? &p.s->cand[grp * 256 + eps * 32 + lane] : &p.s->key[(((lane >> 1) & 7) * 16 + grp) * 2 + (lane & 1)];
          if (i < 13 || eps == 0) pkt_st128(dst, 0, 0, 0, 0);
          __nanosleep(200);
        }
        __syncwarp();
        if (lane == 0) mbar_arrive(BAR(B_STAT));
      }
      {
        const uint4* kp = &p.s->key[(tau * 16 + (lane & 15)) * 2];
        const int i0 = a * 32 + lane;
        mbar_wait(BAR(B_KEY), 0);
        if (a == 0) PT(43);
        uint4 kq = pkt_ld128(kp), cv[3] = {};
        uint32_t n = 0, kv;
        int gspec = -1;
        while (true) {
          const bool ok = kq.y == tag && kq.w == tag;
          kv = __reduce_max_sync(0xffffffffu, ok ? kq.x : 0u);
          const int gs = group_of(0xFFFF - (int)(kv & 0xFFFFu));
          const bool cok = gs == gspec && cv[0].y == tag && cv[0].w == tag && cv[1].y == tag && cv[1].w == tag && cv[2].y == tag && cv[2].w == tag;
          if (__all_sync(0xffffffffu, ok && cok) || ++n > SPIN_LIMIT) break;
          if (!ok) kq = pkt_ld128(kp);
          const bool spec = __popc(__ballot_sync(0xffffffffu, ok)) >= 2 * SPEC_MIN;
          if (!cok && spec) {
#pragma unroll
            for (int i = 0; i < 3; i++) cv[i] = pkt_ld128(&p.s->cand[gs * 256 + min(i0 + 96 * i, 255)]);
          }
          if (spec) gspec = gs;
        }
        if (a == 0) PT(45);
        const uint32_t ms = __shfl_sync(0xffffffffu, kq.z, gspec);
        const uint32_t nm = ((ms & 0xFFFFu) ^ 0x8000u) * 0x10001u;
        const float is = rcp_fast(bf_hi(ms));
#pragma unroll
        for (int i = 0; i < 3; i++) {
          const int j = min(i0 + 96 * i, 255);
          SM_(uint2, OFF_XSEL + j * 8) = make_uint2(norm2(cv[i].x, nm, is), norm2(cv[i].z, nm, is));
        }
#pragma unroll
        for (int i = 0; i < 3; i++) SM_(uint2, OFF_HSEL + min(i0 + 96 * i, 255) * 8) = make_uint2(cv[i].x, cv[i].z);
        SM_(uint32_t, OFF_KV) = kv;
        __syncwarp();
        if (lane == 0) mbar_arrive(BAR(B_XS));
      }
    }
    asm volatile("barrier.cluster.wait.aligned;" ::: "memory");
  } else {
    reg_inc<REG_C>();
    const int tid = __shfl_sync(0xffffffffu, threadIdx.x, threadIdx.x & 31), lane = tid & 31;
    const int w = warp >> 2, wi = warp & 3, t = tid & 127;
    const int g = lane >> 2, q = lane & 3;
    const int turn_me = NB_TURN0 + w, turn_other = NB_TURN1 - w;
    auto release = [&](int s) { if (t == 0) mbar_arrive(BAR(B_EMPTY + s)); };
    if (MAP == 0 && helper) {
      asm volatile("barrier.cluster.arrive.relaxed.aligned;" ::: "memory");
      float s0[64], s1[64];
#pragma unroll
      for (int i = 0; i < 64; i++) { s0[i] = 0.f; s1[i] = 0.f; }
      if (w == 1) bar_arrive(NB_TURN0, 256);
      uint32_t o[32][2] = {};
      const int col = (eps - 2) * 8 + m * 4 + w;
      auto put = [&](auto tc, uint32_t buf) {
        constexpr int tl = decltype(tc)::value;
#pragma unroll
        for (int i = 0; i < 4; i++)
          smem_at<uint2>(buf + ((i >> 1) * 64 + wi * 16 + (i & 1) * 8 + g) * 32 + ((q * 8) ^ ((g & 4) << 2))) = make_uint2(o[8 * i + tl][0], o[8 * i + tl][1]);
      };
      auto publish = [&](int c) { if (t == 0) { bulk_wait_all(); st_relaxed32(&p.s->hflag[c * 2], SM_(uint32_t, OFF_TAG)); } };
#pragma unroll 1
      for (int pass = 0; pass < 2; pass++) {
#pragma unroll 1
        for (int k = 16 * pass; k < 16 * pass + 16; k++) {
          const int s = slot_of(k);
          mbar_wait(BAR(B_FULL + s), use_of(k) & 1);
          bar_sync(turn_me, 256);
          const uint64_t da = make_desc(sb + s * ST_BYTES + A_BYTES + w * 16384), db = make_desc(sb + s * ST_BYTES);
          wgmma_fence();
#pragma unroll
          for (int kk = 0; kk < 4; kk++) {
            wgmma_n128(s0, da + kk * 2, db + kk * 2, kk > 0 || (k & 15));
            wgmma_n128(s1, da + 512 + kk * 2, db + kk * 2, kk > 0 || (k & 15));
          }
          wgmma_commit();
          if (k < 31 || w == 0) bar_arrive(turn_other, 256);
          if (pass && !(k & 1)) {
            const uint32_t buf = sb + OFF_XCH + 20480 + w * 4096;
            static_for<8>([&](auto ic) { if (k == 16 + 2 * decltype(ic)::value) put(ic, buf); });
            fence_async_smem();
            bar_sync(NB_WG0 + w, 128);
            if (t == 0) { tma_store_2d(&p.tmAbM, buf, (k - 16) * 128 + 240, col * 128); bulk_commit(); }
          }
          wgmma_wait0();
          release(s);
          if ((k & 1) && t == 0) asm volatile("cp.async.bulk.wait_group.read 0;" ::: "memory");
        }
        if (pass) publish(col);
        mbar_wait(BAR(B_STAT), 0);
        wgmma_fence();
        wgmma_n128(s0, make_desc_noswz(sb + OFF_XCH + pass * 8192 + w * 4096), make_desc_noswz(sb + OFF_XCH + 16384));
        wgmma_n128(s1, make_desc_noswz(sb + OFF_XCH + pass * 8192 + w * 4096 + 2048), make_desc_noswz(sb + OFF_XCH + 16384));
        wgmma_commit();
        uint4 rs[4];
#pragma unroll
        for (int i = 0; i < 4; i++) rs[i] = lds128_v(sb + OFF_RS + q * 144 + i * 16);
        wgmma_wait0();
        fence_acc(s0); fence_acc(s1);
#pragma unroll
        for (int i = 0; i < 32; i++) {
          const int tl = i & 7, hr = (i >> 3) & 1;
          const float* ac = (i >> 4) ? &s1[8 * tl + 2 * hr] : &s0[8 * tl + 2 * hr];
          o[i][0] = bmul2(pack_bf16(ac[0], ac[1]), (tl & 1) ? rs[tl >> 1].z : rs[tl >> 1].x);
          o[i][1] = bmul2(pack_bf16(ac[4], ac[5]), (tl & 1) ? rs[tl >> 1].w : rs[tl >> 1].y);
        }
      }
      static_for<8>([&](auto ic) { put(ic, sb + (w * 8 + decltype(ic)::value) * 4096); });
      fence_async_smem();
      bar_sync(NB_WG0 + w, 128);
      if (t == 0) {
#pragma unroll 1
        for (int i = 0; i < 8; i++) tma_store_2d(&p.tmAbM, sb + (w * 8 + i) * 4096, i * 256 + 240, (col + 2) * 128);
        bulk_commit();
      }
      publish(col + 2);
      asm volatile("barrier.cluster.wait.aligned;" ::: "memory");
      return;
    }
    float acc[128], a1[NX / 2];
#pragma unroll
    for (int i = 0; i < NX / 2; i++) a1[i] = 0.f;
    if (w == 1) bar_arrive(NB_TURN0, 256);
    auto kstep = [&](auto& d, int k, bool first, bool a_in_xch = false, bool mini = false) {
      const int s = slot_of(k);
      mbar_wait(BAR(B_FULL + s), use_of(k) & 1);
      CT(64 + k);
      bar_sync(turn_me, 256);
      const uint64_t da = make_desc(sb + (a_in_xch ? OFF_XCH + s * 16384 : s * ST_BYTES) + w * 8192), db = make_desc(sb + s * ST_BYTES + A_BYTES);
      wgmma_fence();
      wgmma_g1(d, da, db, !first);
#pragma unroll
      for (int kk = 1; kk < 4; kk++) wgmma_g1(d, da + kk * 2, db + kk * 2, 1);
      wgmma_commit();
      if (mini) {
        CT(29);
        mbar_wait(BAR(B_A20), 1);
        CT(30);
        wgmma_fence();
        wgmma_g1(d, make_desc_32b(sb + OFF_MINI + w * 2048), make_desc_32b(sb + OFF_MINI + 4096), 1);
        wgmma_commit();
      }
      bar_arrive(turn_other, 256);
    };
    auto kdone = [&](int k) { wgmma_wait0(); release(slot_of(k)); };
    auto wgmma_wait1 = [&]() { asm volatile("wgmma.wait_group.sync.aligned 1;" ::: "memory"); };

#pragma unroll 1
    for (int k = 0; k < 14; k++) {
      kstep(a1, k, k == 0);
      if (k == 0) CT(0);
      if (k == 8 && warp == 2 && lane < 2) pkt_st128(&p.s->abflag[((eps * 2 + m) * 8 + tau) * 2 + lane], 0, 0, 0, 0);
      kdone(k);
    }
    uint32_t R[64];
    uint32_t tag;
    {
      const uint32_t rsa = sb + OFF_RS + q * 144;
      const uint64_t da2 = make_desc(sb + 2 * ST_BYTES + w * 8192), db2 = make_desc(sb + 2 * ST_BYTES + A_BYTES);
      const uint64_t da3 = make_desc(sb + 3 * ST_BYTES + w * 8192), db3 = make_desc(sb + 3 * ST_BYTES + A_BYTES);
      mbar_wait(BAR(B_FULL + 2), 1);
      CT(64 + 14);
      bar_sync(turn_me, 256);
      wgmma_fence();
#pragma unroll
      for (int kk = 0; kk < 4; kk++) wgmma_g1(a1, da2 + kk * 2, db2 + kk * 2, 1);
      wgmma_commit();
      mbar_wait(BAR(B_FULL + 3), 1);
      CT(64 + 15);
      wgmma_fence();
      wgmma_g1(a1, da3, db3, 1);
      wgmma_g1(a1, da3 + 2, db3 + 2, 1);
      wgmma_commit();
      mbar_wait(BAR(B_STAT), 0);
      tag = SM_(uint32_t, OFF_TAG);
#pragma unroll
      for (int i = 0; i < 8; i++) { const uint4 v = lds128_v(rsa + i * 16); R[8 * i] = v.x; R[8 * i + 2] = v.y; R[8 * i + 4] = v.z; R[8 * i + 6] = v.w; }
      wgmma_wait1();
      release(2);
      wgmma_fence();
      wgmma_g1(a1, da3 + 4, db3 + 4, 1);
      wgmma_g1(a1, da3 + 6, db3 + 6, 1);
      wgmma_g1(a1, make_desc_noswz(sb + OFF_EXA + w * 2048), make_desc_noswz(sb + OFF_EXB), 1);
      wgmma_commit();
      bar_arrive(turn_other, 256);
      kdone(15);
      mbar_wait(BAR(B_STAT), 0);
    }
    fence_acc(a1);
    CT(1);
    auto pack = [&](auto cc) {
      constexpr int c = decltype(cc)::value;
#pragma unroll
      for (int j = 8 * c; j < min_c(8 * c + 8, NX / 8); j++) {
        const uint32_t rs = R[2 * j];
        const float* ac = &a1[4 * j];
        R[2 * j] = bmul2(pack_bf16(ac[0], ac[1]), rs);
        R[2 * j + 1] = bmul2(pack_bf16(ac[2], ac[3]), rs);
      }
    };
    auto put_chunk = [&](auto cc) {
      constexpr int c = decltype(cc)::value;
      const int rho = 16 * wi + (lane & 15);
#pragma unroll
      for (int j = 8 * c; j < min_c(8 * c + 8, NX / 8); j += 2) {
        const int chunk = (j & 7) + (lane >> 4);
        stsm_x4(sb + chunk_off(c, w) + rho * 128 + ((chunk ^ (lane & 7)) << 4), R[2 * j], R[2 * j + 1], R[2 * j + 2], R[2 * j + 3]);
      }
    };
    auto staged = [&](int bar) {
      fence_async_smem();
      __syncwarp();
      if (lane == 0) mbar_arrive(BAR(bar));
    };
    auto mma_rs = [&](auto cc, auto k0, auto k1) {
      constexpr int c = decltype(cc)::value;
      const uint64_t db = make_desc(sb + c * ST_BYTES + A_BYTES);
#pragma unroll
      for (int kk = decltype(k0)::value; kk < decltype(k1)::value; kk++)
        wgmma_n256_rs(acc, R[16 * c + 4 * kk], R[16 * c + 4 * kk + 1], R[16 * c + 4 * kk + 2], R[16 * c + 4 * kk + 3], db + kk * 2, c + kk > 0);
      wgmma_commit();
    };
    auto kdone_x = [&](int k, auto ic) {
      constexpr int i = decltype(ic)::value;
      uint32_t r[8];
#pragma unroll
      for (int z = 0; z < 2; z++) {
        const int tr = 32 * (i & 1) + 16 * z + 8 * (lane >> 4) + (lane & 7), chunk = 2 * wi + ((lane >> 3) & 1);
        ldsm_x4_t(sb + (i >> 1) * ST_BYTES + w * 8192 + tr * 128 + ((chunk ^ (lane & 7)) << 4), r[4 * z], r[4 * z + 1], r[4 * z + 2], r[4 * z + 3]);
      }
      float f[16];
#pragma unroll
      for (int z = 0; z < 8; z++) { f[2 * z] = bf_lo(r[z]); f[2 * z + 1] = bf_hi(r[z]); }
#pragma unroll
      for (int z = 0; z < 16; z++) asm volatile("" : "+f"(f[z]));
      kdone(k);
#pragma unroll
      for (int z = 0; z < 16; z++) asm volatile("add.f32 %0, %0, %1;" : "+f"(acc[16 * i + z]) : "f"(f[z]));
    };
    pack(IC<0>());
    put_chunk(IC<0>());
    staged(w ? B_EPI0B : B_EPI);
    mbar_wait(BAR(B_STAT), 0);
    CT(21);
    pack(IC<1>());
    pack(IC<2>());
    pack(IC<3>());
#pragma unroll
    for (int i = 16; i < NX / 4; i++) asm volatile("" : "+r"(R[i]));
#pragma unroll
    for (int i = 0; i < 128; i++) asm volatile("" : "=f"(acc[i]));
    mbar_wait(BAR(B_FULL + 0), 0);
    CT(2);
    CT(64 + 16);
    bar_sync(turn_me, 256);
    wgmma_fence();
    mma_rs(IC<0>(), IC<0>(), IC<4>());
    mbar_wait(BAR(B_FULL + 1), 0);
    CT(64 + 17);
    wgmma_fence();
    mma_rs(IC<1>(), IC<0>(), IC<2>());
    wgmma_wait1();
    release(0);
    mma_rs(IC<1>(), IC<2>(), IC<4>());
    bar_arrive(turn_other, 256);
    kdone_x(17, IC<0>());
    static_for<2>([&](auto ic) {
      constexpr int c = 2 + decltype(ic)::value;
      mbar_wait(BAR(B_FULL + c), 0);
      CT(64 + 16 + c);
      bar_sync(turn_me, 256);
      wgmma_fence();
      mma_rs(IC<c>(), IC<0>(), IC<min_c(4, NX / 16 - 4 * c)>());
      bar_arrive(turn_other, 256);
      if (c == 2) { put_chunk(IC<1>()); staged(B_EPI + 1); }
      kdone_x(16 + c, IC<c - 1>());
    });
#pragma unroll 1
    for (int k = 20; k < 23; k++) {
      if (w == 1) mbar_wait(BAR(B_A20), 0);
      kstep(acc, k, false, k < 22);
      if (k == 20) {
        kdone_x(k, IC<3>());
      } else {
        if (k == 21) put_chunk(IC<2>()); else put_chunk(IC<3>());
        __syncwarp();
        if (lane == 0) mbar_arrive(BAR(B_EPI + k - 19));
        kdone(k);
      }
    }
    uint32_t wf[32][4];
    auto load_wf = [&](auto hc) {
      constexpr int h = decltype(hc)::value;
      const int d = w * 64 + (lane >> 4) * 8 + (lane & 7);
      const uint32_t ad = sb + round_off(h) + (lane & 8) * 1024 + d * 64 + ((wi ^ ((lane >> 1) & 3)) << 4);
#pragma unroll
      for (int i = 0; i < 4; i++) ldsm_x4_t(ad + i * 1024, wf[4 * h + i][0], wf[4 * h + i][1], wf[4 * h + i][2], wf[4 * h + i][3]);
    };
    auto load_wf_rest = [&]() { static_for<8 - NREG_H>([&](auto ic) { load_wf(IC<NREG_H + decltype(ic)::value>()); }); };
#pragma unroll
    for (int i = 0; i < 4 * NREG_H; i++) { wf[i][0] = 0; wf[i][1] = 0; wf[i][2] = 0; wf[i][3] = 0; }
    const int grp = tau * 2 + m;
#pragma unroll 1
    for (int k = 23; k < 46; k++) {
      kstep(acc, k, false, false, NX < 256 && k == MINI_K);
      if (moe) {
        static_for<NREG_H>([&](auto hc) {
          constexpr int h = decltype(hc)::value;
          if (k == mr_k(h) + 1) { mbar_wait(BAR(B_MR + (h & 1)), (h >> 1) & 1); CT(32 + h); load_wf(hc); }
        });
      }
      if (k == RESET_K && tid == 0) mbar_arrive(BAR(B_LATE));
      kdone(k);
    }
    asm volatile("barrier.cluster.arrive.relaxed.aligned;" ::: "memory");
    mbar_wait(BAR(B_STAT), 1);
    uint32_t wa[16][2];
    uint32_t cd = code_of(tag);
    uint4* hp_pub = &p.s->hstat[(grp * 8 + eps) * 128 + warp * 16 + g];
    const uint4* hp_poll = &p.s->hstat[(grp * 8 + 2 * q) * 128 + warp * 16 + g];
    const uint32_t vec_off = (2 * wi) * 512 + q * 128 + ((g ^ (2 * q)) << 4);
    {
      float as[64], ak[64];
      fence_acc(acc);
#pragma unroll
      for (int i = 0; i < 64; i++) asm volatile("mov.b32 %0, %1;" : "=f"(as[i]) : "f"(acc[64 + i]));
#pragma unroll
      for (int i = 0; i < 64; i++) asm volatile("mov.b32 %0, %1;" : "=f"(ak[i]) : "f"(acc[i]));
      const uint64_t da1 = make_desc(sb + 2 * ST_BYTES + w * 8192), db1 = make_desc(sb + 2 * ST_BYTES + A_BYTES);
      const uint64_t da2 = make_desc(sb + 3 * ST_BYTES + w * 8192), db2 = make_desc(sb + 3 * ST_BYTES + A_BYTES);
      mbar_wait(BAR(B_FULL + 2), 1);
      CT(64 + 46);
      bar_sync(turn_me, 256);
      wgmma_fence();
#pragma unroll
      for (int kk = 0; kk < 4; kk++) wgmma_n128(as, da1 + kk * 2, db1 + 1024 + kk * 2);
      wgmma_commit();
      mbar_wait(BAR(B_FULL + 3), 1);
      CT(64 + 47);
      wgmma_fence();
#pragma unroll
      for (int kk = 0; kk < 4; kk++) wgmma_n128(as, da2 + kk * 2, db2 + 1024 + kk * 2);
      wgmma_commit();
      bar_arrive(turn_other, 256);
      const uint32_t rx = mapa(sb + OFF_PEER + w * 4096 + vec_off, 1 - m), rb = mapa(BAR(B_XCH), 1 - m);
      asm volatile("barrier.cluster.wait.aligned;" ::: "memory");
      CT(24);
      wgmma_wait0();
      fence_acc(as);
      CT(25);
      auto keep = [&]() {
        bar_sync(turn_me, 256);
        wgmma_fence();
#pragma unroll
        for (int kk = 0; kk < 4; kk++) wgmma_n128(ak, da1 + kk * 2, db1 + kk * 2);
        wgmma_commit();
#pragma unroll
        for (int kk = 0; kk < 4; kk++) wgmma_n128(ak, da2 + kk * 2, db2 + kk * 2);
        wgmma_commit();
        if (w == 0) bar_arrive(turn_other, 256);
      };
#pragma unroll
      for (int i = 0; i < 8; i++) {
        if (i == SEND_FIRST) keep();
        const float* ac = &as[16 * (i >> 1) + 2 * (i & 1)];
        st_async_v4(rx + (i >> 1) * 8192 + (i & 1) * 512, rb, pack_bf16(ac[0], ac[1]), pack_bf16(ac[4], ac[5]), pack_bf16(ac[8], ac[9]), pack_bf16(ac[12], ac[13]));
      }
      CT(26);
#pragma unroll
      for (int i = 0; i < 4; i++) {
        const uint4 v = lds128_v(sb + OFF_WR + q * 80 + i * 16);
        const uint32_t vv[4] = {v.x, v.y, v.z, v.w};
#pragma unroll
        for (int z = 0; z < 4; z++) {
          asm volatile("{\n.reg .pred p;\nsetp.ne.b32 p, %2, 0;\nselp.b32 %0, %1, 0x3F803F80, p;\n}" : "=r"(wa[4 * i + z][0]) : "r"(vv[z]), "r"(g & 1));
          asm volatile("{\n.reg .pred p;\nsetp.ne.b32 p, %2, 0;\nselp.b32 %0, %1, 0x3F803F80, p;\n}" : "=r"(wa[4 * i + z][1]) : "r"(vv[z]), "r"(g & 1));
        }
      }
      pin(cd); pin(hp_pub); pin(hp_poll);
      CT(27);
      wgmma_wait1();
      release(2);
      wgmma_wait0();
      fence_acc(ak);
      CT(3);
#pragma unroll
      for (int i = 0; i < 8; i++) {
        const float* ac = &ak[16 * (i >> 1) + 2 * (i & 1)];
        sts128(sb + (2 + (i >> 2)) * ST_BYTES + w * 8192 + ((i >> 1) & 1) * 4096 + (i & 1) * 512 + vec_off,
               pack_bf16(ac[0], ac[1]), pack_bf16(ac[4], ac[5]), pack_bf16(ac[8], ac[9]), pack_bf16(ac[12], ac[13]));
      }
    }
    uint32_t h[8][4];
    {
      const int qq = 2 * (warp & 1) + ((lane >> 3) & 1);
      const uint32_t lo = (lane >> 4) * 512 + qq * 128 + (((lane & 7) ^ (2 * qq)) << 4);
      bar_sync(NB_BOTH, 256);
#pragma unroll
      for (int ks = 0; ks < 8; ks++)
        ldsm_x4_t(sb + (2 + w) * ST_BYTES + (ks >> 2) * 8192 + (wi >> 1) * 4096 + (ks & 3) * 1024 + lo, h[ks][0], h[ks][1], h[ks][2], h[ks][3]);
      CT(28);
      mbar_wait_cluster(BAR(B_XCH), 0);
      CT(4);
      uint32_t r[8][4];
#pragma unroll
      for (int ks = 0; ks < 8; ks++) ldsm_x4_t(sb + OFF_PEER + (warp >> 1) * 8192 + ks * 1024 + lo, r[ks][0], r[ks][1], r[ks][2], r[ks][3]);
      float d[4][4] = {};
#pragma unroll
      for (int ks = 0; ks < 8; ks++) {
#pragma unroll
        for (int i = 0; i < 4; i++) {
          h[ks][i] = badd2(h[ks][i], r[ks][i]);
          mma1688(d[i], h[ks][i], wa[2 * ks + (i >> 1)][i & 1], h[ks][i]);
        }
      }
#pragma unroll
      for (int i = 0; i < 2; i++) {
        const float sq = (g & 1) ? d[i][1] + d[i + 2][1] : d[i][0] + d[i + 2][0];
        const float e0 = d[i][2] + d[i + 2][2], e1 = d[i][3] + d[i + 2][3];
        const float other = __shfl_xor_sync(0xffffffffu, (g & 1) ? e0 : e1, 4);
        if (q == (g >> 1)) pkt_st128(hp_pub + 8 * i, with_bit((g & 1) ? other : e0, cd), with_bit(sq, cd >> 1), __float_as_uint((g & 1) ? e1 : other), tag);
      }
    }
    CT(5);
    if (tid == 0) mbar_arrive(BAR(B_KEY));
    delay_clk<HOP1_DELAY>();
    float m_bf, sd, inv_sd, r_bf;
    uint4* key_pub = &p.s->key[((lane & 7) * 16 + grp) * 2];
    uint4* cand_pub = &p.s->cand[grp * 256 + eps * 32 + q];
    uint32_t trow_inv = 0xFFFFu - (uint32_t)row_of(grp * 128 + 32 * (warp >> 1) + 8 * (g >> 1) + 4 * (warp & 1) + (q & 2) + (g & 1));
    {
      uint4 u[4];
#pragma unroll
      for (int i = 0; i < 4; i++) u[i] = pkt_ld128(hp_poll + (i & 1) * 128 + (i >> 1) * 8);
      const float wsum = SM_(float, OFF_WSUM);
      pin(key_pub); pin(cand_pub); pin(trow_inv);
      uint32_t n = 0;
      while (true) {
        bool ok[4];
#pragma unroll
        for (int i = 0; i < 4; i++) ok[i] = u[i].w == tag && pair_code(u[i].x, u[i].y) == cd;
        const bool all = __all_sync(0xffffffffu, ok[0] && ok[1] && ok[2] && ok[3]);
        if (all || ++n > SPIN_LIMIT) break;
#pragma unroll
        for (int i = 0; i < 4; i++) pkt_ld128_if(u[i], hp_poll + (i & 1) * 128 + (i >> 1) * 8, !ok[i]);
      }
      CT(6);
      float a[3], b[3];
      a[0] = __uint_as_float(u[0].x & ~1u) + __uint_as_float(u[1].x & ~1u); b[0] = __uint_as_float(u[2].x & ~1u) + __uint_as_float(u[3].x & ~1u);
      a[1] = __uint_as_float(u[0].y & ~1u) + __uint_as_float(u[1].y & ~1u); b[1] = __uint_as_float(u[2].y & ~1u) + __uint_as_float(u[3].y & ~1u);
      a[2] = __uint_as_float(u[0].z) + __uint_as_float(u[1].z); b[2] = __uint_as_float(u[2].z) + __uint_as_float(u[3].z);
#pragma unroll
      for (int i = 0; i < 3; i++) {
        a[i] = ((q & 2) ? b[i] : a[i]) + __shfl_xor_sync(0xffffffffu, (q & 2) ? a[i] : b[i], 2);
        a[i] += __shfl_xor_sync(0xffffffffu, a[i], 1);
      }
      const float mu = a[0] * (1.f / 1024.f);
      m_bf = bf16r(mu);
      sd = ln_sd(a[1] * (1.f / 1024.f) - mu * mu);
      inv_sd = rcp_fast(sd);
      r_bf = bf16r((a[2] - m_bf * wsum) * inv_sd);
    }
    {
      const uint32_t u = __float_as_uint(r_bf);
      const uint32_t ord = (u & 0x80000000u) ? ~u : (u | 0x80000000u);
      const uint32_t key = (ord & 0xFFFF0000u) | trow_inv;
      const uint32_t wk = __reduce_max_sync(0xffffffffu, key);
      if (key == wk) SM_(uint2, OFF_WKEY + warp * 8) = make_uint2(wk, (__float_as_uint(m_bf) >> 16) | __float_as_uint(sd));
      const uint32_t wmask = __ballot_sync(0xffffffffu, key == wk);
      const bool hi = (wmask & 0xCCCCCCCCu) != 0;
      uint32_t c[16];
#pragma unroll
      for (int ks = 0; ks < 8; ks++) { c[2 * ks] = hi ? h[ks][1] : h[ks][0]; c[2 * ks + 1] = hi ? h[ks][3] : h[ks][2]; }
      bar_sync(NB_BOTH, 256);
      const uint2 km = SM_(uint2, OFF_WKEY + (lane & 7) * 8);
      const uint32_t bk = __reduce_max_sync(0xffffffffu, km.x);
      if (wk == bk) {
        if ((wmask >> (lane & 28)) & 15) {
#pragma unroll
          for (int ks = 0; ks < 8; ks++) pkt_st128(cand_pub + ks * 4, c[2 * ks], tag, c[2 * ks + 1], tag);
        }
      } else if (eps == 0) {
        const uint32_t kx = __shfl_sync(0xffffffffu, km.x, warp ^ 1), ms = __shfl_sync(0xffffffffu, km.y, warp ^ 1);
        if (kx == bk && lane < 8) pkt_st128(key_pub, bk, tag, ms, tag);
      }
      CT(7);
    }
    {
      const float ih = bf16r(inv_sd);
      const uint32_t nm = pack_bf16(-m_bf, -m_bf), iv = pack_bf16(ih, inv_sd - ih);
      const uint32_t nm_o = __shfl_xor_sync(0xffffffffu, nm, 2), iv_o = __shfl_xor_sync(0xffffffffu, iv, 2);
      const uint32_t nm2[2] = {(q & 2) ? nm_o : nm, (q & 2) ? nm : nm_o}, iv2[2] = {(q & 2) ? iv_o : iv, (q & 2) ? iv : iv_o};
      const uint32_t hi2[2] = {__byte_perm(iv2[0], 0, 0x1010), __byte_perm(iv2[1], 0, 0x1010)}, lo2[2] = {__byte_perm(iv2[0], 0, 0x3232), __byte_perm(iv2[1], 0, 0x3232)};
      const uint32_t oa = sb + OFF_OUT + (warp * 16 + (lane & 15)) * 128;
#pragma unroll
      for (int ks = 0; ks < 8; ks++) {
        uint32_t o[4];
#pragma unroll
        for (int i = 0; i < 4; i++) {
          const uint32_t dd = badd2(h[ks][i], nm2[i & 1]);
          o[i] = badd2(h[ks][i], bfma2(dd, hi2[i & 1], bmul2(dd, lo2[i & 1])));
        }
        stsm_x4(oa + (ks >> 2) * 16384 + (((2 * (ks & 3) + (lane >> 4)) ^ (lane & 7)) << 4), o[0], o[1], o[2], o[3]);
      }
      staged(B_OUT);
    }
    CT(8);
    uint32_t df[16][4];
    auto load_df = [&]() {
      const int frow = (lane & 7) + ((lane >> 4) << 3), hi = (lane >> 3) & 1;
      const uint32_t base = sb + down_off(warp >> 1) + (warp & 1) * 8192 + frow * 128;
#pragma unroll
      for (int mt = 0; mt < 8; mt++) {
#pragma unroll
        for (int ks = 0; ks < 2; ks++)
          ldsm_x4_t(base + (mt >> 2) * 4096 + ks * 2048 + (((2 * (mt & 3) + hi) ^ (lane & 7)) << 4),
                    df[2 * mt + ks][0], df[2 * mt + ks][1], df[2 * mt + ks][2], df[2 * mt + ks][3]);
      }
    };
    if (moe) {
      mbar_wait(BAR(B_GU), 0);
      load_wf_rest();
      mbar_wait(BAR(B_DN), 0);
      load_df();
    }
    uint4* y_pub = &p.s->ypart[cid * 256 + tid];
    uint32_t xs_ad = sb + OFF_XSEL + (8 * (g >> 2) + 4 * w + (g & 3)) * 32 + q * 8, gp_ad = sb + OFF_GP + (wi * 8 + g) * 16 + w * 8 + (q >> 1) * 4;
    pin(y_pub); pin(xs_ad); pin(gp_ad);
    mbar_wait(BAR(B_XS), 0);
    CT(9);
    if (moe) {
      float gd[8][4] = {};
      uint2 bx[4];
#pragma unroll
      for (int r = 0; r < 4; r++) bx[r] = smem_at<uint2>(xs_ad + r * 512);
#pragma unroll
      for (int r = 0; r < 4; r++) {
#pragma unroll
        for (int i = 0; i < 8; i++) mma16816(gd[i], wf[8 * r + i][0], wf[8 * r + i][1], wf[8 * r + i][2], wf[8 * r + i][3], bx[r].x, bx[r].y);
      }
      const float gs = sel4(q, gd[0][0] + gd[1][1], gd[2][0] + gd[3][1], gd[4][0] + gd[5][1], gd[6][0] + gd[7][1]);
      const float us = sel4(q, gd[0][2] + gd[1][3], gd[2][2] + gd[3][3], gd[4][2] + gd[5][3], gd[6][2] + gd[7][3]);
      float v = ((q & 2) ? us : gs) + __shfl_xor_sync(0xffffffffu, (q & 2) ? gs : us, 2);
      v += __shfl_xor_sync(0xffffffffu, v, 1);
      smem_at<float>(gp_ad) = v;
      CT(10);
      bar_sync(NB_BOTH, 256);
      uint32_t bq[4];
      {
        const float4 p0 = SM_(float4, OFF_GP + lane * 16);
        const float gt = bf16r(p0.x + p0.z), up = bf16r(p0.y + p0.w);
        const float act = bf16r(gt * sigmoid_fast(gt)) * up;
        const uint32_t pr = pack_bf16(act, __shfl_down_sync(0xffffffffu, act, 1));
#pragma unroll
        for (int i = 0; i < 4; i++) bq[i] = __shfl_sync(0xffffffffu, pr, 8 * i + 2 * q);
      }
      CT(11);
      float yd[8][4] = {};
#pragma unroll
      for (int ks = 0; ks < 2; ks++) {
#pragma unroll
        for (int mt = 0; mt < 8; mt++) mma16816(yd[mt], df[2 * mt + ks][0], df[2 * mt + ks][1], df[2 * mt + ks][2], df[2 * mt + ks][3], bq[2 * ks], bq[2 * ks + 1]);
      }
      pkt_st128(y_pub, with_bit(sel4(q, yd[0][0], yd[2][0], yd[4][0], yd[6][0]), cd), with_bit(sel4(q, yd[0][2], yd[2][2], yd[4][2], yd[6][2]), cd >> 1),
                with_bit(sel4(q, yd[1][0], yd[3][0], yd[5][0], yd[7][0]), cd), with_bit(sel4(q, yd[1][2], yd[3][2], yd[5][2], yd[7][2]), cd >> 1));
    } else {
      const long long tw = clock64();
      while (clock64() - tw < IDLE_WAIT_CLK) __nanosleep(100);
    }
    CT(12);
    const uint32_t kv = SM_(uint32_t, OFF_KV);
    const int tsel = 0xFFFF - (int)(kv & 0xFFFFu);
    const float r_sel = __uint_as_float((kv & 0x80000000u) ? (kv & 0x7FFF0000u) : (~kv & 0xFFFF0000u));
    const float sig = bf16r(sigmoid_fast(r_sel));
    const int pfin = 2 * cid + (tid & 1);
    const int col_fin = (pfin >> 5) * 128 + (pfin & 3) * 32 + ((pfin & 31) >> 2) + 8 * ((tid >> 1) & 3);
    const int sel_off = (col_fin >> 4) * 32 + ((col_fin & 7) >> 1) * 8 + ((col_fin >> 3) & 1) * 4 + (col_fin & 1) * 2;
    const float hn_fin = __uint_as_float((uint32_t)SM_(uint16_t, OFF_XSEL + sel_off) << 16), h_fin = __uint_as_float((uint32_t)SM_(uint16_t, OFF_HSEL + sel_off) << 16);
    bf16* out_fin = p.out + (size_t)tsel * 1024 + col_fin;
    {
      const uint4* src = &p.s->ypart[(16 + (tid >> 1)) * 256 + pfin];
      pin(src); pin(out_fin);
      uint4 v = make_uint4(0, 0, 0, 0);
      if (warp < 7) {
        delay_clk<HOP3_DELAY>();
        uint32_t n = 0;
        bool ok = false;
        do {
          pkt_ld128_if(v, src, !ok);
          ok = pair_code(v.x, v.y) == cd && pair_code(v.z, v.w) == cd;
        } while (!__all_sync(0xffffffffu, ok) && ++n < SPIN_LIMIT);
      }
      CT(13);
      const float y0 = __uint_as_float(v.x & ~1u), y1 = __uint_as_float(v.y & ~1u), y2 = __uint_as_float(v.z & ~1u), y3 = __uint_as_float(v.w & ~1u);
      const float a0 = ((lane & 2) ? y1 : y0) + __shfl_xor_sync(0xffffffffu, (lane & 2) ? y0 : y1, 2);
      const float a1 = ((lane & 2) ? y3 : y2) + __shfl_xor_sync(0xffffffffu, (lane & 2) ? y2 : y3, 2);
      float b = ((lane & 4) ? a1 : a0) + __shfl_xor_sync(0xffffffffu, (lane & 4) ? a0 : a1, 4);
      b += __shfl_xor_sync(0xffffffffu, b, 8);
      b += __shfl_xor_sync(0xffffffffu, b, 16);
      if (lane < 8) SM_(float, OFF_FIN + lane * 32 + warp * 4) = b;
    }
    bar_sync(NB_BOTH, 256);
    if (tid < 8) {
      const float4 y0 = SM_(float4, OFF_FIN + tid * 32), y1 = SM_(float4, OFF_FIN + tid * 32 + 16);
      const float y = ((y0.x + y0.y) + (y0.z + y0.w)) + ((y1.x + y1.y) + y1.z);
      *out_fin = __float2bfloat16_rn(h_fin + bf16r(hn_fin + bf16r(bf16r(y) * sig)));
      if (cid == 0 && tid == 0) st_relaxed32(&p.s->epoch, tag);
    }
    CT(14);
  }
}

__global__ void __launch_bounds__(384, 1) occupancy_probe_kernel() {}

typedef CUresult (*EncodeFn)(CUtensorMap*, CUtensorMapDataType, cuuint32_t, void*, const cuuint64_t*, const cuuint64_t*, const cuuint32_t*, const cuuint32_t*,
                             CUtensorMapInterleave, CUtensorMapSwizzle, CUtensorMapL2promotion, CUtensorMapFloatOOBfill);

static void make_tm(EncodeFn enc, CUtensorMap* tm, const void* ptr, uint64_t rows, uint64_t cols, uint32_t brows, uint32_t bcols, CUtensorMapSwizzle sw,
                    CUtensorMapL2promotion promo = CU_TENSOR_MAP_L2_PROMOTION_L2_128B) {
  cuuint64_t dims[2] = {cols, rows};
  cuuint64_t strides[1] = {cols * 2};
  cuuint32_t box[2] = {bcols, brows};
  cuuint32_t es[2] = {1, 1};
  enc(tm, CU_TENSOR_MAP_DATA_TYPE_BFLOAT16, 2, const_cast<void*>(ptr), dims, strides, box, es, CU_TENSOR_MAP_INTERLEAVE_NONE, sw,
      promo, CU_TENSOR_MAP_FLOAT_OOB_FILL_NONE);
}

static void make_tm_rows(EncodeFn enc, CUtensorMap* tm, const void* ptr, uint64_t cols, uint32_t brows, uint32_t bcols, CUtensorMapSwizzle sw,
                         CUtensorMapL2promotion promo = CU_TENSOR_MAP_L2_PROMOTION_L2_128B) {
  cuuint64_t dims[4] = {cols, 2, 2, 512};
  cuuint64_t strides[3] = {row_of(1) * cols * 2, row_of(2) * cols * 2, row_of(4) * cols * 2};
  cuuint32_t box[4] = {bcols, 2, 2, brows / 4};
  cuuint32_t es[4] = {1, 1, 1, 1};
  enc(tm, CU_TENSOR_MAP_DATA_TYPE_BFLOAT16, 4, const_cast<void*>(ptr), dims, strides, box, es, CU_TENSOR_MAP_INTERLEAVE_NONE, sw, promo,
      CU_TENSOR_MAP_FLOAT_OOB_FILL_NONE);
}

extern "C" void kernel_launch(void* const* d_in, const int* in_sizes, int n_in, void* d_out, int out_size) {
  (void)in_sizes; (void)n_in; (void)out_size;
  static EncodeFn enc = nullptr;
  static void* abT = nullptr;
  static int map = 0;
  if (!enc) {
    void* fn = nullptr; cudaDriverEntryPointQueryResult st;
    cudaGetDriverEntryPoint("cuTensorMapEncodeTiled", &fn, cudaEnableDefault, &st);
    enc = (EncodeFn)fn;
    cudaGetSymbolAddress(&abT, g_scratch);
    cudaFuncSetAttribute(fnet_moe_kernel<0>, cudaFuncAttributeMaxDynamicSharedMemorySize, SMEM_TOTAL);
    cudaFuncSetAttribute(fnet_moe_kernel<1>, cudaFuncAttributeMaxDynamicSharedMemorySize, SMEM_TOTAL);
    cudaFuncSetAttribute(occupancy_probe_kernel, cudaFuncAttributeMaxDynamicSharedMemorySize, SMEM_TOTAL);
    cudaFuncSetAttribute(occupancy_probe_kernel, cudaFuncAttributeNonPortableClusterSizeAllowed, 1);
    auto max_clusters = [&](int size) {
      cudaLaunchConfig_t cfg = {};
      cfg.gridDim = dim3(128); cfg.blockDim = dim3(384); cfg.dynamicSmemBytes = SMEM_TOTAL;
      cudaLaunchAttribute at[1];
      at[0].id = cudaLaunchAttributeClusterDimension; at[0].val.clusterDim.x = size; at[0].val.clusterDim.y = 1; at[0].val.clusterDim.z = 1;
      cfg.attrs = at; cfg.numAttrs = 1;
      int ncl = 0;
      return cudaOccupancyMaxActiveClusters(&ncl, occupancy_probe_kernel, &cfg) == cudaSuccess ? ncl : 0;
    };
    int dev = 0, sms = 0;
    cudaGetDevice(&dev);
    cudaDeviceGetAttribute(&sms, cudaDevAttrMultiProcessorCount, dev);
    map = (sms == 132 && max_clusters(2) == 66 && max_clusters(16) == 7) ? 0 : 1;
    (void)cudaGetLastError();
  }
  Params p;
  const bf16* x = (const bf16*)d_in[0];
  make_tm(enc, &p.tmD0, d_in[3], 1024, 1024, 128, 64, CU_TENSOR_MAP_SWIZZLE_128B);
  make_tm(enc, &p.tmD1, d_in[4], 1024, 1024, 128, 64, CU_TENSOR_MAP_SWIZZLE_128B);
  make_tm(enc, &p.tmX, x, 2048, 1024, map == 0 ? NX0 : 256, 64, CU_TENSOR_MAP_SWIZZLE_128B);
  make_tm_rows(enc, &p.tmXr, x, 1024, 64, 64, CU_TENSOR_MAP_SWIZZLE_128B);
  make_tm(enc, &p.tmAbS, abT, 2048, 2048, 64, 64, CU_TENSOR_MAP_SWIZZLE_128B);
  make_tm(enc, &p.tmAbL, abT, 2048, 2048, 128, 64, CU_TENSOR_MAP_SWIZZLE_128B);
  make_tm_rows(enc, &p.tmW0, d_in[1], 2048, 128, 64, CU_TENSOR_MAP_SWIZZLE_128B);
  make_tm_rows(enc, &p.tmW1, d_in[2], 2048, 128, 64, CU_TENSOR_MAP_SWIZZLE_128B);
  {
    cuuint64_t dims[5] = {1024, 2, 4, 2, 2048};
    cuuint64_t strides[4] = {row_of(1) * 2048, row_of(8) * 2048, row_of(2) * 2048, 2048};
    cuuint32_t box[5] = {64, 2, 4, 2, 1};
    cuuint32_t es[5] = {1, 1, 1, 1, 1};
    enc(&p.tmOut, CU_TENSOR_MAP_DATA_TYPE_BFLOAT16, 5, d_out, dims, strides, box, es, CU_TENSOR_MAP_INTERLEAVE_NONE, CU_TENSOR_MAP_SWIZZLE_128B,
        CU_TENSOR_MAP_L2_PROMOTION_NONE, CU_TENSOR_MAP_FLOAT_OOB_FILL_NONE);
  }
  {
    cuuint64_t dims[5] = {1024, 2, 4, 2, 8};
    cuuint64_t strides[4] = {2048, 4 * 2048, 2 * 2048, 256 * 2048};
    cuuint32_t box[5] = {64, 2, 4, 2, 8};
    cuuint32_t es[5] = {1, 1, 1, 1, 1};
    enc(&p.tmXh, CU_TENSOR_MAP_DATA_TYPE_BFLOAT16, 5, const_cast<bf16*>(x) + 240 * 1024, dims, strides, box, es, CU_TENSOR_MAP_INTERLEAVE_NONE,
        CU_TENSOR_MAP_SWIZZLE_128B, CU_TENSOR_MAP_L2_PROMOTION_L2_128B, CU_TENSOR_MAP_FLOAT_OOB_FILL_NONE);
  }
  make_tm(enc, &p.tmAbM, abT, 2048, 2048, 128, 16, CU_TENSOR_MAP_SWIZZLE_32B, CU_TENSOR_MAP_L2_PROMOTION_NONE);
  make_tm_rows(enc, &p.tmWM0, d_in[1], 2048, 128, 16, CU_TENSOR_MAP_SWIZZLE_32B);
  make_tm_rows(enc, &p.tmWM1, d_in[2], 2048, 128, 16, CU_TENSOR_MAP_SWIZZLE_32B);
  make_tm(enc, &p.tmG, d_in[7], 1024, 3584, 128, 32, CU_TENSOR_MAP_SWIZZLE_64B);
  make_tm(enc, &p.tmU, d_in[8], 1024, 3584, 128, 32, CU_TENSOR_MAP_SWIZZLE_64B);
  make_tm(enc, &p.tmDn, d_in[9], 3584, 1024, 32, 64, CU_TENSOR_MAP_SWIZZLE_128B);
  p.x = x; p.Dre = (const bf16*)d_in[3]; p.Dim = (const bf16*)d_in[4];
  p.wr = (const bf16*)d_in[6]; p.wdown = (const bf16*)d_in[9]; p.wgate = (const bf16*)d_in[7]; p.wup = (const bf16*)d_in[8];
  p.out = (bf16*)d_out; p.s = (Scratch*)abT;
  if (map == 1) fnet_moe_kernel<1><<<128, 384, SMEM_TOTAL>>>(p);
  else fnet_moe_kernel<0><<<132, 384, SMEM_TOTAL>>>(p);
}
```

```cpp
#include <cuda.h>
#include <cuda_runtime.h>
#include <cuda_bf16.h>
#include <stdint.h>
#include <type_traits>

typedef __nv_bfloat16 bf16;

constexpr int NX0 = 240;
constexpr int REG_C = 232, REG_P = 40;
__host__ __device__ constexpr int row_of(int p) { return (p & 1) * 1024 + ((p >> 1) & 1) * 512 + (p >> 2); }
__host__ __device__ constexpr int group_of(int row) { return (row & 511) >> 5; }
__device__ __forceinline__ int sigma_of(int tau, int r) { return r + (r >= tau); }
__device__ __forceinline__ int kblock(int tau, int j) {
  const int i = j - 4, c = (i * 37) >> 8;
  return j < 4 ? tau * 4 + j : sigma_of(tau, i - 7 * c) * 4 + c;
}
constexpr int AUX_AFTER = 1;
constexpr int PF_K0 = 8, PF_N0 = 2, PF_K1 = 24;
constexpr int WPF_K0 = 12, WPF_N = 10;
constexpr int WPF2_K = 44, WPF2_N = 4;
constexpr int GU_K = 46;
constexpr int PUB_K1 = 22;
constexpr int NREG_H = 5;
constexpr int MR_K0 = 29, MR_P = 6;
constexpr int MINI_PF_K = 35, MINI_LOAD_K = 43, MINI_K = 42;
constexpr int RESET_K = 37;
constexpr int SEND_FIRST = 2;
constexpr int GATHER_NS = 400;
constexpr int MOE_PACE_CLK = 300;
constexpr int OUT_PACE_CLK = 70;
constexpr int HOP1_DELAY = 150, HOP3_DELAY = 450;
constexpr int SPEC_MIN = 10;
constexpr int IDLE_WAIT_CLK = 1200;
__host__ __device__ constexpr int mr_k(int h) { return MR_K0 + MR_P * (h >> 1) + 2 * (h & 1); }
constexpr int A_BYTES = 128 * 64 * 2;
constexpr int B_BYTES = 256 * 64 * 2;
constexpr int ST_BYTES = A_BYTES + B_BYTES;
constexpr int OFF_XCH = 4 * ST_BYTES;
constexpr int OFF_BAR = OFF_XCH + 32768;
constexpr int OFF_WR = OFF_BAR + 384;
constexpr int OFF_RS = OFF_WR + 384;
constexpr int OFF_PUB = OFF_RS + 640;
constexpr int OFF_MISC = OFF_PUB + 768;
constexpr int SMEM_TOTAL = OFF_MISC + 256;
constexpr int OFF_WSUM = OFF_MISC, OFF_TAG = OFF_MISC + 4;
constexpr int OFF_SEEN = OFF_MISC + 8;
constexpr int OFF_KV = OFF_MISC + 12;
constexpr int OFF_WKEY = OFF_MISC + 32;
constexpr int OFF_MINI = OFF_XCH + 16384;
constexpr int OFF_EXA = OFF_XCH;
constexpr int OFF_EXB = OFF_XCH + 4096;
__host__ __device__ constexpr int chunk_off(int c, int w) { return (c < 2 ? (c + 2) * ST_BYTES : OFF_XCH + (c - 2) * 16384) + w * 8192; }
__host__ __device__ constexpr int late_off(int i) { return i < 4 ? i * 16384 : 2 * ST_BYTES + A_BYTES + (i - 4) * 16384; }
__host__ __device__ constexpr int round_off(int h) { return h < NREG_H + 2 ? OFF_XCH + (h & 1) * 16384 : late_off(h - NREG_H - 2); }
__host__ __device__ constexpr int down_off(int i) { return late_off(6 - NREG_H + i); }
constexpr int OFF_PEER = ST_BYTES + A_BYTES;
constexpr int OFF_OUT = 3 * ST_BYTES + A_BYTES;
constexpr int OFF_XSEL = OFF_PEER;
constexpr int OFF_HSEL = OFF_PEER + 4096;
constexpr int OFF_GP = OFF_PEER + 8192;
constexpr int OFF_FIN = OFF_PEER + 9216;
__device__ __forceinline__ int slot_of(int k) { return k & 3; }
__device__ __forceinline__ int use_of(int k) { return k >> 2; }
enum { B_FULL = 0, B_EMPTY = 4, B_EPI = 8, B_STD = 12, B_EPI0B = 16, B_LATE = 17, B_STAT = 18, B_XCH = 19, B_MR = 20  , B_GU = 22,
       B_DN = 23, B_AUX = 24  , B_OUT = 26, B_KEY = 27, B_XS = 28, B_A20 = 29, B_STDA = 30, B_PUB1 = 31, B_COUNT = 32 };
enum { NB_TURN0 = 1, NB_TURN1 = 2, NB_WG0 = 3, NB_BOTH = 5, NB_AUX = 6 };

struct Scratch {
  bf16 abT[2048 * 2048];
  uint2 xstat[2048];
  uint2 dsum[2048];
  uint4 abflag[16 * 8 * 2];
  uint4 hflag[16 * 2];
  uint4 hstat[16 * 8 * 128];
  uint4 cand[16 * 256];
  uint4 key[8 * 16 * 2];
  uint4 ypart[128 * 256];
  uint32_t epoch;
};
__device__ __align__(1024) Scratch g_scratch;

struct Params {
  Scratch* s; bf16* out;
  const bf16* x; const bf16* Dre; const bf16* Dim; const bf16* wr; const bf16* wdown; const bf16* wgate; const bf16* wup;
  CUtensorMap tmX, tmD0, tmD1, tmXr, tmAbS, tmAbL, tmW0, tmW1, tmOut, tmG, tmU, tmDn, tmXh, tmAbM, tmWM0, tmWM1;
};

#define SPIN_LIMIT (1u << 14)
#define MBAR_LIMIT (1u << 10)
__device__ __forceinline__ uint32_t smem_u32(const void* p) { return (uint32_t)__cvta_generic_to_shared(p); }
__device__ __forceinline__ void mbar_init(uint32_t bar, uint32_t cnt) { asm volatile("mbarrier.init.shared::cta.b64 [%0], %1;" :: "r"(bar), "r"(cnt) : "memory"); }
__device__ __forceinline__ void mbar_expect_tx(uint32_t bar, uint32_t bytes) { asm volatile("mbarrier.arrive.expect_tx.shared::cta.b64 _, [%0], %1;" :: "r"(bar), "r"(bytes) : "memory"); }
__device__ __forceinline__ void mbar_arrive(uint32_t bar) { asm volatile("mbarrier.arrive.shared::cta.b64 _, [%0];" :: "r"(bar) : "memory"); }
__device__ __forceinline__ void mbar_wait(uint32_t bar, uint32_t parity) {
  uint32_t ok, n = 0;
  do {
    asm volatile("{\n.reg .pred p;\nmbarrier.try_wait.parity.shared::cta.b64 p, [%1], %2;\nselp.u32 %0, 1, 0, p;\n}\n" : "=r"(ok) : "r"(bar), "r"(parity) : "memory");
  } while (!ok && ++n < MBAR_LIMIT);
}
__device__ __forceinline__ void mbar_wait_cluster(uint32_t bar, uint32_t parity) {
  uint32_t ok, n = 0;
  do {
    asm volatile("{\n.reg .pred p;\nmbarrier.try_wait.parity.acquire.cluster.shared::cta.b64 p, [%1], %2;\nselp.u32 %0, 1, 0, p;\n}\n" : "=r"(ok) : "r"(bar), "r"(parity) : "memory");
  } while (!ok && ++n < MBAR_LIMIT);
}
__device__ __forceinline__ void tma_load_2d(uint32_t dst, const CUtensorMap* tm, uint32_t bar, int c0, int c1) {
  asm volatile("cp.async.bulk.tensor.2d.shared::cluster.global.mbarrier::complete_tx::bytes [%0], [%1, {%3, %4}], [%2];"
    :: "r"(dst), "l"(tm), "r"(bar), "r"(c0), "r"(c1) : "memory");
}
__device__ __forceinline__ void tma_load_2d_hint(uint32_t dst, const CUtensorMap* tm, uint32_t bar, int c0, int c1, uint64_t pol) {
  asm volatile("cp.async.bulk.tensor.2d.shared::cluster.global.mbarrier::complete_tx::bytes.L2::cache_hint [%0], [%1, {%3, %4}], [%2], %5;"
    :: "r"(dst), "l"(tm), "r"(bar), "r"(c0), "r"(c1), "l"(pol) : "memory");
}
__device__ __forceinline__ uint64_t policy_evict_first() { uint64_t p; asm volatile("createpolicy.fractional.L2::evict_first.b64 %0, 1.0;" : "=l"(p)); return p; }
__device__ __forceinline__ void tma_store_2d(const CUtensorMap* tm, uint32_t src, int c0, int c1) {
  asm volatile("cp.async.bulk.tensor.2d.global.shared::cta.bulk_group [%0, {%2, %3}], [%1];" :: "l"(tm), "r"(src), "r"(c0), "r"(c1) : "memory");
}
__device__ __forceinline__ void tma_prefetch_2d(const CUtensorMap* tm, int c0, int c1) {
  asm volatile("cp.async.bulk.prefetch.tensor.2d.L2.global.tile [%0, {%1, %2}];" :: "l"(tm), "r"(c0), "r"(c1) : "memory");
}
__device__ __forceinline__ void bulk_load(uint32_t dst, const void* src, uint32_t bytes, uint32_t bar) {
  asm volatile("cp.async.bulk.shared::cluster.global.mbarrier::complete_tx::bytes [%0], [%1], %2, [%3];" :: "r"(dst), "l"(src), "r"(bytes), "r"(bar) : "memory");
}
__device__ __forceinline__ void bulk_commit() { asm volatile("cp.async.bulk.commit_group;" ::: "memory"); }
__device__ __forceinline__ void bulk_wait_all() { asm volatile("cp.async.bulk.wait_group 0;" ::: "memory"); }
__device__ __forceinline__ void fence_async_smem() { asm volatile("fence.proxy.async.shared::cta;" ::: "memory"); }
__device__ __forceinline__ void wgmma_fence() { asm volatile("wgmma.fence.sync.aligned;" ::: "memory"); }
__device__ __forceinline__ void wgmma_commit() { asm volatile("wgmma.commit_group.sync.aligned;" ::: "memory"); }
__device__ __forceinline__ void wgmma_wait0() { asm volatile("wgmma.wait_group.sync.aligned 0;" ::: "memory"); }
__device__ __forceinline__ void bar_sync(int id, int n) { asm volatile("bar.sync %0, %1;" :: "r"(id), "r"(n) : "memory"); }
__device__ __forceinline__ void bar_arrive(int id, int n) { asm volatile("bar.arrive %0, %1;" :: "r"(id), "r"(n) : "memory"); }
template<int R> __device__ __forceinline__ void reg_inc() { asm volatile("setmaxnreg.inc.sync.aligned.u32 %0;" :: "n"(R)); }
template<int R> __device__ __forceinline__ void reg_dec() { asm volatile("setmaxnreg.dec.sync.aligned.u32 %0;" :: "n"(R)); }
__device__ __forceinline__ bool elect_one() {
  uint32_t p;
  asm volatile("{\n.reg .pred q;\nelect.sync _|q, 0xffffffff;\nselp.u32 %0, 1, 0, q;\n}\n" : "=r"(p));
  return p != 0;
}
__device__ __forceinline__ uint32_t mapa(uint32_t addr, uint32_t cta) { uint32_t r; asm volatile("mapa.shared::cluster.u32 %0, %1, %2;" : "=r"(r) : "r"(addr), "r"(cta)); return r; }
__device__ __forceinline__ void st_async_v4(uint32_t addr, uint32_t bar, uint32_t a, uint32_t b, uint32_t c, uint32_t d) {
  asm volatile("st.async.weak.shared::cluster.mbarrier::complete_tx::bytes.v4.b32 [%0], {%2, %3, %4, %5}, [%1];" :: "r"(addr), "r"(bar), "r"(a), "r"(b), "r"(c), "r"(d) : "memory");
}
__device__ __forceinline__ void stsm_x4(uint32_t addr, uint32_t a, uint32_t b, uint32_t c, uint32_t d) {
  asm volatile("stmatrix.sync.aligned.m8n8.x4.shared.b16 [%0], {%1, %2, %3, %4};" :: "r"(addr), "r"(a), "r"(b), "r"(c), "r"(d));
}
__device__ __forceinline__ uint4 lds128_v(uint32_t addr) { uint4 v; asm volatile("ld.shared.v4.b32 {%0, %1, %2, %3}, [%4];" : "=r"(v.x), "=r"(v.y), "=r"(v.z), "=r"(v.w) : "r"(addr)); return v; }
extern __shared__ __align__(1024) uint8_t smem_raw[];
template<class T> __device__ __forceinline__ T& smem_at(uint32_t addr) { return *reinterpret_cast<T*>(__cvta_shared_to_generic(addr)); }
#define SM_(T, off) smem_at<T>(sb + (off))
__device__ __forceinline__ uint4 ldg_nc128(const void* p) { uint4 v; asm volatile("ld.global.nc.v4.b32 {%0, %1, %2, %3}, [%4];" : "=r"(v.x), "=r"(v.y), "=r"(v.z), "=r"(v.w) : "l"(p)); return v; }
__device__ __forceinline__ void pkt_st128(void* p, uint32_t a, uint32_t b, uint32_t c, uint32_t d) {
  asm volatile("{\n.reg .b128 v;\n.reg .b64 lo, hi;\nmov.b64 lo, {%1, %2};\nmov.b64 hi, {%3, %4};\nmov.b128 v, {lo, hi};\nst.relaxed.gpu.global.b128 [%0], v;\n}\n"
    :: "l"(p), "r"(a), "r"(b), "r"(c), "r"(d) : "memory");
}
__device__ __forceinline__ uint4 pkt_ld128(const void* p) {
  uint4 r;
  asm volatile("{\n.reg .b128 v;\n.reg .b64 lo, hi;\nld.relaxed.gpu.global.b128 v, [%4];\nmov.b128 {lo, hi}, v;\nmov.b64 {%0, %1}, lo;\nmov.b64 {%2, %3}, hi;\n}\n"
    : "=r"(r.x), "=r"(r.y), "=r"(r.z), "=r"(r.w) : "l"(p) : "memory");
  return r;
}
__device__ __forceinline__ void pkt_ld128_if(uint4& r, const void* p, bool cond) {
  asm volatile("{\n.reg .pred q;\n.reg .b64 lo, hi;\nsetp.ne.b32 q, %5, 0;\nmov.b64 lo, {%0, %1};\nmov.b64 hi, {%2, %3};\n"
               "@q ld.relaxed.gpu.global.v2.b64 {lo, hi}, [%4];\nmov.b64 {%0, %1}, lo;\nmov.b64 {%2, %3}, hi;\n}\n"
    : "+r"(r.x), "+r"(r.y), "+r"(r.z), "+r"(r.w) : "l"(p), "r"((uint32_t)cond) : "memory");
}
__device__ __forceinline__ void pkt_st64(void* p, uint32_t a, uint32_t b) {
  asm volatile("{\n.reg .b64 v;\nmov.b64 v, {%1, %2};\nst.relaxed.gpu.global.b64 [%0], v;\n}\n" :: "l"(p), "r"(a), "r"(b) : "memory");
}
__device__ __forceinline__ uint2 pkt_ld64(const void* p) {
  uint2 r;
  asm volatile("{\n.reg .b64 v;\nld.relaxed.gpu.global.b64 v, [%2];\nmov.b64 {%0, %1}, v;\n}\n" : "=r"(r.x), "=r"(r.y) : "l"(p) : "memory");
  return r;
}
__device__ __forceinline__ uint32_t ld_relaxed32(const void* p) { uint32_t v; asm volatile("ld.relaxed.gpu.global.b32 %0, [%1];" : "=r"(v) : "l"(p) : "memory"); return v; }
__device__ __forceinline__ void st_relaxed32(void* p, uint32_t v) { asm volatile("st.relaxed.gpu.global.b32 [%0], %1;" :: "l"(p), "r"(v) : "memory"); }
__device__ __forceinline__ uint32_t code_of(uint32_t tag) { return tag % 3u + 1u; }
__device__ __forceinline__ uint32_t with_bit(float v, uint32_t bit) { return (__float_as_uint(v) & ~1u) | (bit & 1u); }
__device__ __forceinline__ uint32_t pair_code(uint32_t a, uint32_t b) { return (a & 1u) | ((b & 1u) << 1); }
__device__ __forceinline__ uint32_t pack_bf16(float lo, float hi) { uint32_t r; asm("cvt.rn.bf16x2.f32 %0, %1, %2;" : "=r"(r) : "f"(hi), "f"(lo)); return r; }
__device__ __forceinline__ float bf_lo(uint32_t v) { return __uint_as_float(v << 16); }
__device__ __forceinline__ float bf_hi(uint32_t v) { return __uint_as_float(v & 0xFFFF0000u); }
__device__ __forceinline__ float bf16r(float x) { return __uint_as_float(pack_bf16(0.f, x)); }
__device__ __forceinline__ uint32_t badd2(uint32_t a, uint32_t b) { uint32_t r; asm("add.rn.bf16x2 %0, %1, %2;" : "=r"(r) : "r"(a), "r"(b)); return r; }
__device__ __forceinline__ uint32_t bmul2(uint32_t a, uint32_t b) { uint32_t r; asm("mul.rn.bf16x2 %0, %1, %2;" : "=r"(r) : "r"(a), "r"(b)); return r; }
__device__ __forceinline__ float warp_sum(float v) {
#pragma unroll
  for (int o = 16; o > 0; o >>= 1) v += __shfl_xor_sync(0xffffffffu, v, o);
  return v;
}
__device__ __forceinline__ uint64_t make_desc(uint32_t addr) {
  return (uint64_t)((addr & 0x3FFFF) >> 4) | ((uint64_t)1 << 16) | ((uint64_t)64 << 32) | ((uint64_t)1 << 62);
}
__device__ __forceinline__ uint64_t make_desc_noswz(uint32_t addr) {
  return (uint64_t)((addr & 0x3FFFF) >> 4) | ((uint64_t)8 << 16) | ((uint64_t)16 << 32);
}
__device__ __forceinline__ uint64_t make_desc_32b(uint32_t addr) {
  return (uint64_t)((addr & 0x3FFFF) >> 4) | ((uint64_t)1 << 16) | ((uint64_t)16 << 32) | ((uint64_t)3 << 62);
}
__device__ __forceinline__ void wgmma_n256(float (&d)[128], uint64_t da, uint64_t db, int scale_d) {
  asm volatile("{\n.reg .pred p;\nsetp.ne.b32 p, %130, 0;\n"
    "wgmma.mma_async.sync.aligned.m64n256k16.f32.bf16.bf16 "
    "{%0, %1, %2, %3, %4, %5, %6, %7, %8, %9, %10, %11, %12, %13, %14, %15, %16, %17, %18, %19, %20, %21, %22, %23, %24, %25, %26, %27, %28, %29, %30, %31, "
    "%32, %33, %34, %35, %36, %37, %38, %39, %40, %41, %42, %43, %44, %45, %46, %47, %48, %49, %50, %51, %52, %53, %54, %55, %56, %57, %58, %59, %60, %61, %62, %63, "
    "%64, %65, %66, %67, %68, %69, %70, %71, %72, %73, %74, %75, %76, %77, %78, %79, %80, %81, %82, %83, %84, %85, %86, %87, %88, %89, %90, %91, %92, %93, %94, %95, "
    "%96, %97, %98, %99, %100, %101, %102, %103, %104, %105, %106, %107, %108, %109, %110, %111, %112, %113, %114, %115, %116, %117, %118, %119, %120, %121, %122, %123, %124, %125, %126, %127}, "
    "%128, %129, p, 1, 1, 0, 0;\n}\n"
    : "+f"(d[0]), "+f"(d[1]), "+f"(d[2]), "+f"(d[3]), "+f"(d[4]), "+f"(d[5]), "+f"(d[6]), "+f"(d[7]),
      "+f"(d[8]), "+f"(d[9]), "+f"(d[10]), "+f"(d[11]), "+f"(d[12]), "+f"(d[13]), "+f"(d[14]), "+f"(d[15]),
      "+f"(d[16]), "+f"(d[17]), "+f"(d[18]), "+f"(d[19]), "+f"(d[20]), "+f"(d[21]), "+f"(d[22]), "+f"(d[23]),
      "+f"(d[24]), "+f"(d[25]), "+f"(d[26]), "+f"(d[27]), "+f"(d[28]), "+f"(d[29]), "+f"(d[30]), "+f"(d[31]),
      "+f"(d[32]), "+f"(d[33]), "+f"(d[34]), "+f"(d[35]), "+f"(d[36]), "+f"(d[37]), "+f"(d[38]), "+f"(d[39]),
      "+f"(d[40]), "+f"(d[41]), "+f"(d[42]), "+f"(d[43]), "+f"(d[44]), "+f"(d[45]), "+f"(d[46]), "+f"(d[47]),
      "+f"(d[48]), "+f"(d[49]), "+f"(d[50]), "+f"(d[51]), "+f"(d[52]), "+f"(d[53]), "+f"(d[54]), "+f"(d[55]),
      "+f"(d[56]), "+f"(d[57]), "+f"(d[58]), "+f"(d[59]), "+f"(d[60]), "+f"(d[61]), "+f"(d[62]), "+f"(d[63]),
      "+f"(d[64]), "+f"(d[65]), "+f"(d[66]), "+f"(d[67]), "+f"(d[68]), "+f"(d[69]), "+f"(d[70]), "+f"(d[71]),
      "+f"(d[72]), "+f"(d[73]), "+f"(d[74]), "+f"(d[75]), "+f"(d[76]), "+f"(d[77]), "+f"(d[78]), "+f"(d[79]),
      "+f"(d[80]), "+f"(d[81]), "+f"(d[82]), "+f"(d[83]), "+f"(d[84]), "+f"(d[85]), "+f"(d[86]), "+f"(d[87]),
      "+f"(d[88]), "+f"(d[89]), "+f"(d[90]), "+f"(d[91]), "+f"(d[92]), "+f"(d[93]), "+f"(d[94]), "+f"(d[95]),
      "+f"(d[96]), "+f"(d[97]), "+f"(d[98]), "+f"(d[99]), "+f"(d[100]), "+f"(d[101]), "+f"(d[102]), "+f"(d[103]),
      "+f"(d[104]), "+f"(d[105]), "+f"(d[106]), "+f"(d[107]), "+f"(d[108]), "+f"(d[109]), "+f"(d[110]), "+f"(d[111]),
      "+f"(d[112]), "+f"(d[113]), "+f"(d[114]), "+f"(d[115]), "+f"(d[116]), "+f"(d[117]), "+f"(d[118]), "+f"(d[119]),
      "+f"(d[120]), "+f"(d[121]), "+f"(d[122]), "+f"(d[123]), "+f"(d[124]), "+f"(d[125]), "+f"(d[126]), "+f"(d[127])
    : "l"(da), "l"(db), "r"(scale_d));
}
__device__ __forceinline__ void wgmma_g1(float (&d)[128], uint64_t da, uint64_t db, int scale_d) { wgmma_n256(d, da, db, scale_d); }
__device__ __forceinline__ void wgmma_g1(float (&d)[120], uint64_t da, uint64_t db, int scale_d) {
  asm volatile("{\n.reg .pred p;\nsetp.ne.b32 p, %122, 0;\n"
    "wgmma.mma_async.sync.aligned.m64n240k16.f32.bf16.bf16 "
    "{%0, %1, %2, %3, %4, %5, %6, %7, %8, %9, %10, %11, %12, %13, %14, %15, %16, %17, %18, %19, %20, %21, %22, %23, %24, %25, %26, %27, %28, %29, %30, %31, %32, %33, %34, %35, %36, %37, %38, %39, %40, %41, %42, %43, %44, %45, %46, %47, %48, %49, %50, %51, %52, %53, %54, %55, %56, %57, %58, %59, %60, %61, %62, %63, %64, %65, %66, %67, %68, %69, %70, %71, %72, %73, %74, %75, %76, %77, %78, %79, %80, %81, %82, %83, %84, %85, %86, %87, %88, %89, %90, %91, %92, %93, %94, %95, %96, %97, %98, %99, %100, %101, %102, %103, %104, %105, %106, %107, %108, %109, %110, %111, %112, %113, %114, %115, %116, %117, %118, %119}, "
    "%120, %121, p, 1, 1, 0, 0;\n}\n"
    : "+f"(d[0]), "+f"(d[1]), "+f"(d[2]), "+f"(d[3]), "+f"(d[4]), "+f"(d[5]), "+f"(d[6]), "+f"(d[7]), "+f"(d[8]), "+f"(d[9]), "+f"(d[10]), "+f"(d[11]), "+f"(d[12]), "+f"(d[13]), "+f"(d[14]), "+f"(d[15]), "+f"(d[16]), "+f"(d[17]), "+f"(d[18]), "+f"(d[19]), "+f"(d[20]), "+f"(d[21]), "+f"(d[22]), "+f"(d[23]), "+f"(d[24]), "+f"(d[25]), "+f"(d[26]), "+f"(d[27]), "+f"(d[28]), "+f"(d[29]), "+f"(d[30]), "+f"(d[31]), "+f"(d[32]), "+f"(d[33]), "+f"(d[34]), "+f"(d[35]), "+f"(d[36]), "+f"(d[37]), "+f"(d[38]), "+f"(d[39]), "+f"(d[40]), "+f"(d[41]), "+f"(d[42]), "+f"(d[43]), "+f"(d[44]), "+f"(d[45]), "+f"(d[46]), "+f"(d[47]), "+f"(d[48]), "+f"(d[49]), "+f"(d[50]), "+f"(d[51]), "+f"(d[52]), "+f"(d[53]), "+f"(d[54]), "+f"(d[55]), "+f"(d[56]), "+f"(d[57]), "+f"(d[58]), "+f"(d[59]), "+f"(d[60]), "+f"(d[61]), "+f"(d[62]), "+f"(d[63]), "+f"(d[64]), "+f"(d[65]), "+f"(d[66]), "+f"(d[67]), "+f"(d[68]), "+f"(d[69]), "+f"(d[70]), "+f"(d[71]), "+f"(d[72]), "+f"(d[73]), "+f"(d[74]), "+f"(d[75]), "+f"(d[76]), "+f"(d[77]), "+f"(d[78]), "+f"(d[79]), "+f"(d[80]), "+f"(d[81]), "+f"(d[82]), "+f"(d[83]), "+f"(d[84]), "+f"(d[85]), "+f"(d[86]), "+f"(d[87]), "+f"(d[88]), "+f"(d[89]), "+f"(d[90]), "+f"(d[91]), "+f"(d[92]), "+f"(d[93]), "+f"(d[94]), "+f"(d[95]), "+f"(d[96]), "+f"(d[97]), "+f"(d[98]), "+f"(d[99]), "+f"(d[100]), "+f"(d[101]), "+f"(d[102]), "+f"(d[103]), "+f"(d[104]), "+f"(d[105]), "+f"(d[106]), "+f"(d[107]), "+f"(d[108]), "+f"(d[109]), "+f"(d[110]), "+f"(d[111]), "+f"(d[112]), "+f"(d[113]), "+f"(d[114]), "+f"(d[115]), "+f"(d[116]), "+f"(d[117]), "+f"(d[118]), "+f"(d[119])
    : "l"(da), "l"(db), "r"(scale_d));
}
__device__ __forceinline__ void wgmma_n256_rs(float (&d)[128], uint32_t a0, uint32_t a1, uint32_t a2, uint32_t a3, uint64_t db, int scale_d) {
  asm volatile("{\n.reg .pred p;\nsetp.ne.b32 p, %133, 0;\n"
    "wgmma.mma_async.sync.aligned.m64n256k16.f32.bf16.bf16 "
    "{%0, %1, %2, %3, %4, %5, %6, %7, %8, %9, %10, %11, %12, %13, %14, %15, %16, %17, %18, %19, %20, %21, %22, %23, %24, %25, %26, %27, %28, %29, %30, %31, "
    "%32, %33, %34, %35, %36, %37, %38, %39, %40, %41, %42, %43, %44, %45, %46, %47, %48, %49, %50, %51, %52, %53, %54, %55, %56, %57, %58, %59, %60, %61, %62, %63, "
    "%64, %65, %66, %67, %68, %69, %70, %71, %72, %73, %74, %75, %76, %77, %78, %79, %80, %81, %82, %83, %84, %85, %86, %87, %88, %89, %90, %91, %92, %93, %94, %95, "
    "%96, %97, %98, %99, %100, %101, %102, %103, %104, %105, %106, %107, %108, %109, %110, %111, %112, %113, %114, %115, %116, %117, %118, %119, %120, %121, %122, %123, %124, %125, %126, %127}, "
    "{%128, %129, %130, %131}, %132, p, 1, 1, 0;\n}\n"
    : "+f"(d[0]), "+f"(d[1]), "+f"(d[2]), "+f"(d[3]), "+f"(d[4]), "+f"(d[5]), "+f"(d[6]), "+f"(d[7]),
      "+f"(d[8]), "+f"(d[9]), "+f"(d[10]), "+f"(d[11]), "+f"(d[12]), "+f"(d[13]), "+f"(d[14]), "+f"(d[15]),
      "+f"(d[16]), "+f"(d[17]), "+f"(d[18]), "+f"(d[19]), "+f"(d[20]), "+f"(d[21]), "+f"(d[22]), "+f"(d[23]),
      "+f"(d[24]), "+f"(d[25]), "+f"(d[26]), "+f"(d[27]), "+f"(d[28]), "+f"(d[29]), "+f"(d[30]), "+f"(d[31]),
      "+f"(d[32]), "+f"(d[33]), "+f"(d[34]), "+f"(d[35]), "+f"(d[36]), "+f"(d[37]), "+f"(d[38]), "+f"(d[39]),
      "+f"(d[40]), "+f"(d[41]), "+f"(d[42]), "+f"(d[43]), "+f"(d[44]), "+f"(d[45]), "+f"(d[46]), "+f"(d[47]),
      "+f"(d[48]), "+f"(d[49]), "+f"(d[50]), "+f"(d[51]), "+f"(d[52]), "+f"(d[53]), "+f"(d[54]), "+f"(d[55]),
      "+f"(d[56]), "+f"(d[57]), "+f"(d[58]), "+f"(d[59]), "+f"(d[60]), "+f"(d[61]), "+f"(d[62]), "+f"(d[63]),
      "+f"(d[64]), "+f"(d[65]), "+f"(d[66]), "+f"(d[67]), "+f"(d[68]), "+f"(d[69]), "+f"(d[70]), "+f"(d[71]),
      "+f"(d[72]), "+f"(d[73]), "+f"(d[74]), "+f"(d[75]), "+f"(d[76]), "+f"(d[77]), "+f"(d[78]), "+f"(d[79]),
      "+f"(d[80]), "+f"(d[81]), "+f"(d[82]), "+f"(d[83]), "+f"(d[84]), "+f"(d[85]), "+f"(d[86]), "+f"(d[87]),
      "+f"(d[88]), "+f"(d[89]), "+f"(d[90]), "+f"(d[91]), "+f"(d[92]), "+f"(d[93]), "+f"(d[94]), "+f"(d[95]),
      "+f"(d[96]), "+f"(d[97]), "+f"(d[98]), "+f"(d[99]), "+f"(d[100]), "+f"(d[101]), "+f"(d[102]), "+f"(d[103]),
      "+f"(d[104]), "+f"(d[105]), "+f"(d[106]), "+f"(d[107]), "+f"(d[108]), "+f"(d[109]), "+f"(d[110]), "+f"(d[111]),
      "+f"(d[112]), "+f"(d[113]), "+f"(d[114]), "+f"(d[115]), "+f"(d[116]), "+f"(d[117]), "+f"(d[118]), "+f"(d[119]),
      "+f"(d[120]), "+f"(d[121]), "+f"(d[122]), "+f"(d[123]), "+f"(d[124]), "+f"(d[125]), "+f"(d[126]), "+f"(d[127])
    : "r"(a0), "r"(a1), "r"(a2), "r"(a3), "l"(db), "r"(scale_d));
}
__device__ __forceinline__ void wgmma_n128(float (&d)[64], uint64_t da, uint64_t db, int scale_d = 1) {
  asm volatile("{\n.reg .pred p;\nsetp.ne.b32 p, %66, 0;\n"
    "wgmma.mma_async.sync.aligned.m64n128k16.f32.bf16.bf16 "
    "{%0, %1, %2, %3, %4, %5, %6, %7, %8, %9, %10, %11, %12, %13, %14, %15, %16, %17, %18, %19, %20, %21, %22, %23, %24, %25, %26, %27, %28, %29, %30, %31, %32, %33, %34, %35, %36, %37, %38, %39, %40, %41, %42, %43, %44, %45, %46, %47, %48, %49, %50, %51, %52, %53, %54, %55, %56, %57, %58, %59, %60, %61, %62, %63}, "
    "%64, %65, p, 1, 1, 0, 0;\n}\n"
    : "+f"(d[0]), "+f"(d[1]), "+f"(d[2]), "+f"(d[3]), "+f"(d[4]), "+f"(d[5]), "+f"(d[6]), "+f"(d[7]), "+f"(d[8]), "+f"(d[9]), "+f"(d[10]), "+f"(d[11]), "+f"(d[12]), "+f"(d[13]), "+f"(d[14]), "+f"(d[15]), "+f"(d[16]), "+f"(d[17]), "+f"(d[18]), "+f"(d[19]), "+f"(d[20]), "+f"(d[21]), "+f"(d[22]), "+f"(d[23]), "+f"(d[24]), "+f"(d[25]), "+f"(d[26]), "+f"(d[27]), "+f"(d[28]), "+f"(d[29]), "+f"(d[30]), "+f"(d[31]), "+f"(d[32]), "+f"(d[33]), "+f"(d[34]), "+f"(d[35]), "+f"(d[36]), "+f"(d[37]), "+f"(d[38]), "+f"(d[39]), "+f"(d[40]), "+f"(d[41]), "+f"(d[42]), "+f"(d[43]), "+f"(d[44]), "+f"(d[45]), "+f"(d[46]), "+f"(d[47]), "+f"(d[48]), "+f"(d[49]), "+f"(d[50]), "+f"(d[51]), "+f"(d[52]), "+f"(d[53]), "+f"(d[54]), "+f"(d[55]), "+f"(d[56]), "+f"(d[57]), "+f"(d[58]), "+f"(d[59]), "+f"(d[60]), "+f"(d[61]), "+f"(d[62]), "+f"(d[63])
    : "l"(da), "l"(db), "r"(scale_d));
}
template<int N> __device__ __forceinline__ void fence_acc(float (&d)[N]) {
#pragma unroll
  for (int i = 0; i < N; i++) asm volatile("" : "+f"(d[i]) :: "memory");
}

template<int N, int I = 0, class F> __device__ __forceinline__ void static_for(F&& f) {
  if constexpr (I < N) { f(std::integral_constant<int, I>()); static_for<N, I + 1>(f); }
}

__device__ __forceinline__ void ldsm_x4_t(uint32_t addr, uint32_t& a, uint32_t& b, uint32_t& c, uint32_t& d) {
  asm volatile("ldmatrix.sync.aligned.m8n8.x4.trans.shared.b16 {%0, %1, %2, %3}, [%4];" : "=r"(a), "=r"(b), "=r"(c), "=r"(d) : "r"(addr));
}
__device__ __forceinline__ void sts128(uint32_t addr, uint32_t a, uint32_t b, uint32_t c, uint32_t d) {
  asm volatile("st.shared.v4.b32 [%0], {%1, %2, %3, %4};" :: "r"(addr), "r"(a), "r"(b), "r"(c), "r"(d));
}
__device__ __forceinline__ void mma16816(float (&c)[4], uint32_t a0, uint32_t a1, uint32_t a2, uint32_t a3, uint32_t b0, uint32_t b1) {
  asm volatile("mma.sync.aligned.m16n8k16.row.col.f32.bf16.bf16.f32 {%0, %1, %2, %3}, {%4, %5, %6, %7}, {%8, %9}, {%0, %1, %2, %3};"
      : "+f"(c[0]), "+f"(c[1]), "+f"(c[2]), "+f"(c[3]) : "r"(a0), "r"(a1), "r"(a2), "r"(a3), "r"(b0), "r"(b1));
}
__device__ __forceinline__ void mma1688(float (&c)[4], uint32_t a0, uint32_t a1, uint32_t b0) {
  asm volatile("mma.sync.aligned.m16n8k8.row.col.f32.bf16.bf16.f32 {%0, %1, %2, %3}, {%4, %5}, {%6}, {%0, %1, %2, %3};"
      : "+f"(c[0]), "+f"(c[1]), "+f"(c[2]), "+f"(c[3]) : "r"(a0), "r"(a1), "r"(b0));
}
__device__ __forceinline__ uint32_t keep_awake() {
  float c0;
  asm volatile("{\n.reg .f32 c1, c2, c3, z;\n.reg .b32 a;\nmov.b32 a, 0;\nmov.f32 z, 0f00000000;\n"
               "mma.sync.aligned.m16n8k8.row.col.f32.bf16.bf16.f32 {%0, c1, c2, c3}, {a, a}, {a}, {z, z, z, z};\n}\n" : "=f"(c0));
  return __float_as_uint(c0);
}
__device__ __forceinline__ void pin(uint32_t& v) { asm volatile("shfl.sync.bfly.b32 %0, %0, 0, 0x1f, 0xffffffff;" : "+r"(v)); }
template<class T> __device__ __forceinline__ void pin(T*& v) {
  uint32_t lo = (uint32_t)(uint64_t)v, hi = (uint32_t)((uint64_t)v >> 32);
  pin(lo); pin(hi);
  v = (T*)(((uint64_t)hi << 32) | lo);
}
__device__ __forceinline__ float sel4(int q, float a, float b, float c, float d) {
  float r;
  asm("{\n.reg .pred p, o;\n.reg .f32 x, y;\n.reg .b32 t;\nand.b32 t, %1, 1;\nsetp.ne.b32 p, t, 0;\nsetp.gt.s32 o, %1, 1;\n"
      "selp.f32 x, %3, %2, p;\nselp.f32 y, %5, %4, p;\nselp.f32 %0, y, x, o;\n}\n" : "=f"(r) : "r"(q), "f"(a), "f"(b), "f"(c), "f"(d));
  return r;
}
__device__ __forceinline__ uint32_t bfma2(uint32_t a, uint32_t b, uint32_t c) { uint32_t r; asm("fma.rn.bf16x2 %0, %1, %2, %3;" : "=r"(r) : "r"(a), "r"(b), "r"(c)); return r; }
__device__ __forceinline__ void tma_load_5d(uint32_t dst, const CUtensorMap* tm, uint32_t bar, int c0, int c4) {
  asm volatile("cp.async.bulk.tensor.5d.shared::cluster.global.mbarrier::complete_tx::bytes [%0], [%1, {%3, %4, %4, %4, %5}], [%2];"
    :: "r"(dst), "l"(tm), "r"(bar), "r"(c0), "r"(0), "r"(c4) : "memory");
}
__device__ __forceinline__ void tma_load_4d(uint32_t dst, const CUtensorMap* tm, uint32_t bar, int c0, int c3) {
  asm volatile("cp.async.bulk.tensor.4d.shared::cluster.global.mbarrier::complete_tx::bytes [%0], [%1, {%3, %4, %4, %5}], [%2];"
    :: "r"(dst), "l"(tm), "r"(bar), "r"(c0), "r"(0), "r"(c3) : "memory");
}
__device__ __forceinline__ void tma_load_4d_hint(uint32_t dst, const CUtensorMap* tm, uint32_t bar, int c0, int c3, uint64_t pol) {
  asm volatile("cp.async.bulk.tensor.4d.shared::cluster.global.mbarrier::complete_tx::bytes.L2::cache_hint [%0], [%1, {%3, %4, %4, %5}], [%2], %6;"
    :: "r"(dst), "l"(tm), "r"(bar), "r"(c0), "r"(0), "r"(c3), "l"(pol) : "memory");
}
__device__ __forceinline__ void tma_prefetch_4d(const CUtensorMap* tm, int c0, int c3) {
  asm volatile("cp.async.bulk.prefetch.tensor.4d.L2.global.tile [%0, {%1, %2, %2, %3}];" :: "l"(tm), "r"(c0), "r"(0), "r"(c3) : "memory");
}
__device__ __forceinline__ void tma_store_5d(const CUtensorMap* tm, uint32_t src, int c0, int c4) {
  asm volatile("cp.async.bulk.tensor.5d.global.shared::cta.bulk_group [%0, {%2, %3, %3, %3, %4}], [%1];" :: "l"(tm), "r"(src), "r"(c0), "r"(0), "r"(c4) : "memory");
}
__device__ __forceinline__ float rcp_fast(float x) { float r; asm("rcp.approx.ftz.f32 %0, %1;" : "=f"(r) : "f"(x)); return r; }
__device__ __forceinline__ float sigmoid_fast(float x) { float e; asm("ex2.approx.ftz.f32 %0, %1;" : "=f"(e) : "f"(x * -1.4426950408889634f)); return rcp_fast(1.f + e); }
__device__ __forceinline__ float sqrt_fast(float x) { float r; asm("sqrt.approx.ftz.f32 %0, %1;" : "=f"(r) : "f"(x)); return r; }
__device__ __forceinline__ float ln_sd(float var) { return bf16r(sqrt_fast(bf16r(bf16r(fmaxf(var, 0.f)) + 1e-5f))); }
__device__ __forceinline__ uint32_t norm2(uint32_t h, uint32_t neg_mean2, float inv_sd) {
  const uint32_t d = badd2(h, neg_mean2);
  return pack_bf16(bf_lo(d) * inv_sd, bf_hi(d) * inv_sd);
}
template<int N> __device__ __forceinline__ void delay_clk() {
  if constexpr (N > 0) { const uint32_t t0 = clock(); while ((uint32_t)clock() - t0 < N) {} }
}
__device__ __forceinline__ void put_xstat(uint32_t rs, uint32_t exb, int col, uint32_t mean_rstd, int m) {
  smem_at<uint16_t>(rs + ((col & 7) >> 1) * 144 + (col >> 3) * 4 + (col & 1) * 2) = (uint16_t)(mean_rstd ^ (m << 15));
  const uint32_t nm = (mean_rstd >> 16) ^ 0x8000u;
  smem_at<uint4>(exb + (col >> 3) * 256 + (col & 7) * 16) = make_uint4(nm | (nm << 16), nm, 0, 0);
  smem_at<uint4>(exb + (col >> 3) * 256 + 128 + (col & 7) * 16) = make_uint4(0, 0, 0, 0);
}
__device__ __forceinline__ void put_dsum(uint32_t exa, int e, float c) {
  const float hi = bf16r(c), mid = bf16r(c - hi), lo = bf16r((c - hi) - mid);
  smem_at<uint4>(exa + (e >> 3) * 256 + (e & 7) * 16) = make_uint4((__float_as_uint(hi) >> 16) | (__float_as_uint(mid) & 0xFFFF0000u), __float_as_uint(lo) >> 16, 0, 0);
  smem_at<uint4>(exa + (e >> 3) * 256 + 128 + (e & 7) * 16) = make_uint4(0, 0, 0, 0);
}
__host__ __device__ constexpr int min_c(int a, int b) { return a < b ? a : b; }
template<int V> using IC = std::integral_constant<int, V>;

#define CT(slot) do {} while (0)
#define PT(slot) do {} while (0)

template<int MAP>
__global__ void __cluster_dims__(2, 1, 1) __launch_bounds__(384, 1)
fnet_moe_kernel(const __grid_constant__ Params p) {
  constexpr int NX = MAP == 0 ? NX0 : 256;
  constexpr int G1_BYTES = A_BYTES + NX * 128;
  uint32_t sb;
  asm volatile("mov.u32 %0, %1;" : "=r"(sb) : "r"(smem_u32(smem_raw)));
  const int m = blockIdx.x & 1;
  int tau, eps;
  bool helper = false;
  if (MAP == 0) {
    uint32_t smid;
    asm volatile("mov.u32 %0, %%smid;" : "=r"(smid));
    const int c = smid >> 1, e7 = ((c - 32) * 37) >> 8;
    helper = c == 60 || c == 61;
    tau = c < 32 ? (c & 7) : (c < 60 ? c - 31 - 7 * e7 : 0);
    eps = c < 32 ? (c >> 3) : (c < 60 ? 4 + e7 : c - 58);
  } else {
    tau = (blockIdx.x >> 1) & 7; eps = blockIdx.x >> 4;
  }
  const int cid = tau * 16 + eps * 2 + m;
  const bool moe = tau > 0;
  auto BAR = [&](int i) { return sb + OFF_BAR + 8 * i; };
  const CUtensorMap* tmD = m ? &p.tmD1 : &p.tmD0;
  const uint64_t pol_ef = policy_evict_first();
#define LOAD_STREAM(d, tm, bar, c0, c1) tma_load_2d_hint(d, tm, bar, c0, c1, pol_ef)
#define LOAD_W(d, tm, bar, c0, grp) tma_load_4d_hint(d, tm, bar, c0, (grp) * 32, pol_ef)
  auto helper_load = [&](int k) {
    const uint32_t sa = sb + slot_of(k) * ST_BYTES, bar = BAR(B_FULL + slot_of(k));
    const CUtensorMap* tm = eps == 3 ? &p.tmD1 : &p.tmD0;
    tma_load_5d(sa, &p.tmXh, bar, (k & 15) * 64, 0);
    tma_load_2d(sa + A_BYTES, tm, bar, (k & 15) * 64, m * 512 + (k >> 4) * 256);
    tma_load_2d(sa + A_BYTES + 16384, tm, bar, (k & 15) * 64, m * 512 + (k >> 4) * 256 + 128);
  };
  if (threadIdx.x < 32 && elect_one()) {
    mbar_init(BAR(B_FULL), 1);
    asm volatile("fence.mbarrier_init.release.cluster;" ::: "memory");
    if (!helper) {
      tma_load_2d(sb + A_BYTES, &p.tmX, BAR(B_FULL), 0, tau * 256);
      tma_load_2d(sb, tmD, BAR(B_FULL), 0, eps * 128);
    }
    PT(52);
#pragma unroll
    for (int k = 1; k < 4; k++) mbar_init(BAR(B_FULL + k), 1);
    asm volatile("fence.mbarrier_init.release.cluster;" ::: "memory");
#pragma unroll
    for (int k = 0; k < 4; k++) mbar_expect_tx(BAR(B_FULL + k), helper ? ST_BYTES : G1_BYTES);
    if (!helper) {
#pragma unroll
      for (int k = 1; k < 4; k++) {
        tma_load_2d(sb + k * ST_BYTES + A_BYTES, &p.tmX, BAR(B_FULL + k), k * 64, tau * 256);
        LOAD_STREAM(sb + k * ST_BYTES, tmD, BAR(B_FULL + k), k * 64, eps * 128);
      }
    } else {
#pragma unroll 1
      for (int k = 0; k < 4; k++) helper_load(k);
    }
    PT(0);
  }
  __syncwarp();
  const int warp = __shfl_sync(0xffffffffu, threadIdx.x >> 5, 0);
  if (warp == 8) {
    if (elect_one()) {
#pragma unroll
      for (int b = B_EMPTY; b < B_COUNT; b++)
        mbar_init(BAR(b), b < B_EPI ? 2 : (b == B_EPI || b == B_EPI0B) ? 4 : (b < B_STD || b == B_OUT) ? 8 : (b == B_STAT || b == B_XS) ? 3 : 1);
      asm volatile("fence.mbarrier_init.release.cluster;" ::: "memory");
      mbar_expect_tx(BAR(B_XCH), 32768);
      SM_(uint32_t, OFF_SEEN) = 0;
    }
  }
  __syncthreads();

  if (warp >= 8) {
    reg_dec<REG_P>();
    asm volatile("barrier.cluster.arrive.relaxed.aligned;" ::: "memory");
    const int abrow = m * 1024 + eps * 128;
    const int f0 = (cid - 16) * 32;
    const CUtensorMap* tmWM = m ? &p.tmWM1 : &p.tmWM0;
    auto side_first = [&](int k) {
      if (NX < 256 && k == MINI_LOAD_K) {
        static_assert(NX == 256 || (mr_k(NREG_H) == MINI_LOAD_K && (NREG_H & 1) == 1), "second half of the staging buffer must be free");
        mbar_wait(BAR(B_STD + 3), 0);
        uint32_t n = 0;
        while (!((*(volatile uint32_t*)&SM_(uint32_t, OFF_SEEN) >> (4 * tau + 1)) & 1) && ++n < SPIN_LIMIT * 16) {}
        if (elect_one()) {
          mbar_expect_tx(BAR(B_A20), 12288);
          tma_load_2d(sb + OFF_MINI, &p.tmAbM, BAR(B_A20), tau * 256 + 240, abrow);
          LOAD_W(sb + OFF_MINI + 4096, tmWM, BAR(B_A20), tau * 256 + 240, tau * 2 + m);
          LOAD_W(sb + OFF_MINI + 8192, tmWM, BAR(B_A20), tau * 256 + 240, tau * 2 + 1 - m);
        }
      }
    };
    auto side = [&](int k) {
      if (NX < 256 && k == MINI_PF_K && elect_one()) tma_prefetch_4d(tmWM, tau * 256 + 240, tau * 64 + (eps & 1) * 32);
      if (k == WPF2_K && eps < WPF2_N && elect_one()) tma_prefetch_4d(m ? &p.tmW1 : &p.tmW0, kblock(tau, 31 - (eps >> 1)) * 64, tau * 64 + (eps & 1) * 32);
      if (!moe) return;
      const int i = k - MR_K0, r6 = i / MR_P, u = i - MR_P * r6, h = 2 * r6 + (u >> 1);
      if (i >= 0 && u < 4 && h < NREG_H) {
        if (h < 2) mbar_wait(BAR(B_STD + 2 + h), 0);
        if (elect_one()) {
          if (!(u & 1)) mbar_expect_tx(BAR(B_MR + (h & 1)), 16384);
          LOAD_STREAM(sb + OFF_XCH + u * 8192, (u & 1) ? &p.tmU : &p.tmG, BAR(B_MR + (h & 1)), f0, h * 128);
        }
      }
      if (k >= GU_K && k < GU_K + 2 && elect_one()) {
        static_assert(mr_k(NREG_H + 1) <= GU_K + 1 && MINI_K + 4 <= GU_K && GU_K < 47, "staging buffer must be free");
        LOAD_STREAM(sb + round_off(NREG_H + k - GU_K), &p.tmG, BAR(B_GU), f0, (NREG_H + k - GU_K) * 128);
        LOAD_STREAM(sb + round_off(NREG_H + k - GU_K) + 8192, &p.tmU, BAR(B_GU), f0, (NREG_H + k - GU_K) * 128);
      }
      if (k >= PF_K1 && !(k & 1) && elect_one()) {
        const int j = PF_N0 + ((k - PF_K1) >> 1);
        if (j < 8) tma_prefetch_2d(m ? &p.tmU : &p.tmG, f0, j * 128);
        else if (j < 12) asm volatile("cp.async.bulk.prefetch.L2.global [%0], %1;" :: "l"(p.wdown + (size_t)f0 * 1024 + (j - 8) * 8192), "r"(16384) : "memory");
      }
    };
    if (MAP == 0 && helper) {
      if (warp == 8) {
#pragma unroll 1
        for (int k = 4; k < 32; k++) {
          mbar_wait(BAR(B_EMPTY + slot_of(k)), (use_of(k) & 1) ^ 1);
          if (elect_one()) { mbar_expect_tx(BAR(B_FULL + slot_of(k)), ST_BYTES); helper_load(k); }
        }
      } else {
        const int i0 = threadIdx.x - 288, lane = threadIdx.x & 31, col0 = (eps - 2) * 8 + m * 4;
#pragma unroll 1
        for (int u = 0; u < 3; u++) mbar_wait(BAR(B_EMPTY + 0), u & 1);
        const uint32_t tag = ld_relaxed32(&p.s->epoch) + 1;
        if (i0 < 8) pkt_st128(&p.s->hflag[col0 * 2 + i0], 0, 0, 0, 0);
        SM_(uint32_t, OFF_TAG) = tag;
#pragma unroll 1
        for (int j0 = i0; j0 < 768; j0 += 384) {
          uint2 v[4]; uint32_t n = 0;
          while (true) {
#pragma unroll
            for (int z = 0; z < 4; z++) {
              const int j = j0 + 96 * z;
              v[z] = pkt_ld64(p.s->xstat + (j < 128 ? 256 * (j >> 4) + 240 + 2 * (j & 6) + ((j >> 2) & 2) + (j & 1)
                                          : j < 640 ? 2048 + col0 * 128 + j - 128 : (j - 640) * 16));
            }
            if (__all_sync(0xffffffffu, v[0].y == tag && v[1].y == tag && v[2].y == tag && v[3].y == tag) || ++n > SPIN_LIMIT) break;
            __nanosleep(300);
          }
#pragma unroll
          for (int z = 0; z < 4; z++) {
            const int j = j0 + 96 * z;
            if (j < 128) put_xstat(sb + OFF_RS, sb + OFF_XCH + 16384, j, v[z].x, eps - 2);
            else if (j < 640) put_dsum(sb + OFF_XCH, j - 128, __uint_as_float(v[z].x));
          }
        }
        fence_async_smem();
        __syncwarp();
        if (lane == 0) mbar_arrive(BAR(B_STAT));
      }
    } else if (warp == 8) {
      const CUtensorMap* tmW = m ? &p.tmW1 : &p.tmW0;
      const int gA = tau * 2 + m, gB = tau * 2 + 1 - m;
      auto wait_slot = [&](int k) {
        mbar_wait(BAR(B_EMPTY + slot_of(k)), (use_of(k) & 1) ^ 1);
        PT(64 + k);
      };
#pragma unroll 1
      for (int k = 4; k < 24; k++) {
        const int s = slot_of(k);
        const uint32_t sa = sb + s * ST_BYTES, sbb = sa + A_BYTES;
        const int kb = kblock(tau, k - 16);
        wait_slot(k);
        if (elect_one()) {
          mbar_expect_tx(BAR(B_FULL + s), k < 16 ? G1_BYTES : (k >> 1) == 9 ? B_BYTES : k == 20 ? ST_BYTES - 8192 : ST_BYTES);
          if (k < 16) {
            LOAD_STREAM(sa, tmD, BAR(B_FULL + s), k * 64, eps * 128);
            tma_load_2d(sbb, &p.tmX, BAR(B_FULL + s), k * 64, tau * 256);
          } else {
            LOAD_W(sbb, tmW, BAR(B_FULL + s), kb * 64, gA);
            LOAD_W(sbb + 16384, tmW, BAR(B_FULL + s), kb * 64, gB);
            if (k < 18) {
              tma_load_4d(sa, &p.tmXr, BAR(B_FULL + s), eps * 128, gA * 32 + s * 16);
              tma_load_4d(sa + 8192, &p.tmXr, BAR(B_FULL + s), eps * 128 + 64, gA * 32 + s * 16);
            }
          }
          if (k == PUB_K1) mbar_arrive(BAR(B_LATE));
          if (k >= WPF_K0 && k < WPF_K0 + WPF_N && (eps >> 1) == ((k - WPF_K0) & 3))
            tma_prefetch_4d(tmW, kblock(tau, k - WPF_K0) * 64, tau * 64 + (eps & 1) * 32);
          if (moe && k >= PF_K0 && k < PF_K0 + 2 * PF_N0 && !(k & 1)) tma_prefetch_2d(m ? &p.tmU : &p.tmG, f0, (k - PF_K0) * 64);
        }
      }
      uint32_t seen = 0;
#pragma unroll 1
      for (int k = 24; k < 48; k++) {
        const int s = slot_of(k);
        const uint32_t sa = sb + s * ST_BYTES, sbb = sa + A_BYTES;
        const int kb = kblock(tau, k - 16);
        const uint32_t need = (1u << kb) | ((kb & 3) == 3 ? 2u << (4 * tau) : 0u);
        wait_slot(k);
        side_first(k);
        if (elect_one()) {
          mbar_expect_tx(BAR(B_FULL + s), ST_BYTES);
          LOAD_W(sbb, tmW, BAR(B_FULL + s), kb * 64, gA);
          LOAD_W(sbb + 16384, tmW, BAR(B_FULL + s), kb * 64, gB);
        }
        uint32_t n = 0;
        while ((seen & need) != need && ++n < SPIN_LIMIT * 16) seen = *(volatile uint32_t*)&SM_(uint32_t, OFF_SEEN);
        if (elect_one()) tma_load_2d(sa, &p.tmAbL, BAR(B_FULL + s), kb * 64, abrow);
        side(k);
      }
      if (moe) {
        mbar_wait(BAR(B_EMPTY + 0), 1);
        if (elect_one()) { mbar_expect_tx(BAR(B_GU), (8 - NREG_H) * 16384); mbar_expect_tx(BAR(B_DN), 65536); }
#pragma unroll 1
        for (int i = 0; i < 10 - NREG_H; i++) {
          if (i == 3) mbar_wait(BAR(B_EMPTY + 1), 1);
          if (i == 4) {
            mbar_wait(BAR(B_EMPTY + 2), 1);
            mbar_wait(BAR(B_XCH), 0);
            PT(53);
          }
          const uint32_t dst = sb + late_off(i);
          if (elect_one()) {
            if (i < 6 - NREG_H) {
              LOAD_STREAM(dst, &p.tmG, BAR(B_GU), f0, (NREG_H + 2 + i) * 128);
              LOAD_STREAM(dst + 8192, &p.tmU, BAR(B_GU), f0, (NREG_H + 2 + i) * 128);
            } else {
#pragma unroll
              for (int b = 0; b < 4; b++) LOAD_STREAM(dst + b * 4096, &p.tmDn, BAR(B_DN), (4 * (i - 6 + NREG_H) + b) * 64, f0);
            }
          }
          const long long t0 = clock64();
          while (i < 9 - NREG_H && clock64() - t0 < MOE_PACE_CLK) {}
        }
      }
      const int lane = threadIdx.x & 31;
      mbar_wait(BAR(B_OUT), 0);
      const uint32_t km = SM_(uint32_t, OFF_WKEY + (lane & 7) * 8);
      const uint32_t bk = __reduce_max_sync(0xffffffffu, km);
      const int ww = __ffs(__ballot_sync(0xffffffffu, km == bk)) - 1;
#pragma unroll 1
      for (int i = 1; i <= 8; i++) {
        const int W = (ww + i) & 7;
        if (i == 8) {
          mbar_wait(BAR(B_XS), 0);
          if (SM_(uint32_t, OFF_KV) == bk) {
#pragma unroll 2
            for (int j = lane; j < 256; j += 32) {
              const int rho = j >> 4, row = row_of(gA * 128 + 32 * (W >> 1) + 8 * ((rho & 7) >> 1) + 4 * (W & 1) + 2 * (rho >> 3) + (rho & 1));
              const uint4 v = lds128_v(sb + OFF_OUT + (j & 8) * 2048 + (16 * W + rho) * 128 + (((j ^ rho) & 7) << 4));
              if (row != 0xFFFF - (int)(bk & 0xFFFFu))
                asm volatile("st.global.v4.b32 [%0], {%1, %2, %3, %4};" :: "l"(p.out + (size_t)row * 1024 + eps * 128 + (j & 15) * 8), "r"(v.x), "r"(v.y), "r"(v.z), "r"(v.w));
            }
            break;
          }
        }
        if (lane == 0) {
          tma_store_5d(&p.tmOut, sb + OFF_OUT + W * 2048, eps * 128, row_of(gA * 128 + 32 * (W >> 1) + 4 * (W & 1)));
          tma_store_5d(&p.tmOut, sb + OFF_OUT + 16384 + W * 2048, eps * 128 + 64, row_of(gA * 128 + 32 * (W >> 1) + 4 * (W & 1)));
        }
        const long long t0 = clock64();
        while (i < 7 && clock64() - t0 < OUT_PACE_CLK) {}
      }
      if (lane == 0) { bulk_commit(); bulk_wait_all(); }
      PT(22);
    } else {
      const int a = warp - 9;
      const int lane = threadIdx.x & 31;
      auto stage = [&](const bf16* src, int g) {
        if (elect_one()) {
          mbar_expect_tx(BAR(B_AUX + g), 16384);
          bulk_load(sb + OFF_XCH + g * 16384, src + g * 8192, 16384, BAR(B_AUX + g));
        }
      };
      uint32_t tag = 0;
#pragma unroll 1
      for (int i = 0; i < 3; i++) { i += keep_awake(); delay_clk<300>(); }
      mbar_wait(BAR(B_FULL + AUX_AFTER), 0);
      if (a == 0) PT(1);
      if (a == 1) mbar_wait(BAR(B_AUX + 0), 0);
      if (a < 2) stage(p.x + (size_t)cid * 16 * 1024, a);
#pragma unroll 1
      for (int it = 0; it < 4; it++) {
        const int g = it & 1;
        mbar_wait(BAR(B_AUX + g), it >> 1);
        if (a == 0) PT(2 + it);
        if (it == 2) tag = ld_relaxed32(&p.s->epoch) + 1;
        if (it == 2 && a == 2 && lane < 16) asm volatile("prefetch.global.L2 [%0];" :: "l"(p.wr + lane * 64));
        const uint32_t ad = sb + OFF_XCH + g * 16384 + (lane >> 2) * 2048;
        float s0 = 0.f, s1 = 0.f, q0 = 0.f, q1 = 0.f;
        auto row = [&](auto sq) {
#pragma unroll
          for (int i = 0; i < 11; i++) {
            if (i == 10 && a == 2) break;
            const uint4 v = lds128_v(ad + (((a * 44 + 4 * i + lane) & 127) << 4));
            const uint32_t ww[4] = {v.x, v.y, v.z, v.w};
#pragma unroll
            for (int z = 0; z < 4; z++) {
              const float d0 = bf_lo(ww[z]), d1 = bf_hi(ww[z]);
              s0 += d0; s1 += d1;
              if (decltype(sq)::value) { q0 = fmaf(d0, d0, q0); q1 = fmaf(d1, d1, q1); }
            }
          }
        };
        if (it < 2) row(IC<1>()); else row(IC<0>());
        s0 += s1; q0 += q1;
#pragma unroll
        for (int o = 1; o < 4; o <<= 1) { s0 += __shfl_xor_sync(0xffffffffu, s0, o); q0 += __shfl_xor_sync(0xffffffffu, q0, o); }
        if ((lane & 3) == 0) SM_(float2, OFF_PUB + a * 256 + it * 64 + (lane >> 2) * 8) = make_float2(s0, q0);
        if (it != 2) bar_sync(NB_AUX, 96);
        if (it < 2 && a == 2) stage(cid < 64 ? p.Dre + (size_t)cid * 16 * 1024 : p.Dim + (size_t)(cid - 64) * 16 * 1024, g);
      }
      if (a == 1) {
        const float2 v0 = SM_(float2, OFF_PUB + lane * 8), v1 = SM_(float2, OFF_PUB + 256 + lane * 8), v2 = SM_(float2, OFF_PUB + 512 + lane * 8);
        const float s = v0.x + v1.x + v2.x, mean = s * (1.f / 1024.f);
        const float rs = rcp_fast(ln_sd((v0.y + v1.y + v2.y) * (1.f / 1024.f) - mean * mean));
        pkt_st64((lane < 16 ? p.s->xstat : p.s->dsum) + cid * 16 + (lane & 15), lane < 16 ? pack_bf16(rs, mean) : __float_as_uint(s), tag);
        PT(6);
      }
      if (a == 2) {
        float s = 0.f;
#pragma unroll
        for (int q = 0; q < 4; q++) {
          const uint4 v = ldg_nc128(p.wr + (q * 32 + lane) * 8);
          s += ((bf_lo(v.x) + bf_hi(v.x)) + (bf_lo(v.y) + bf_hi(v.y))) + ((bf_lo(v.z) + bf_hi(v.z)) + (bf_lo(v.w) + bf_hi(v.w)));
          const int ch = q * 32 + lane - eps * 16;
          if (ch >= 0 && ch < 16) {
            SM_(uint32_t, OFF_WR + ch * 4) = v.x; SM_(uint32_t, OFF_WR + 80 + ch * 4) = v.y;
            SM_(uint32_t, OFF_WR + 160 + ch * 4) = v.z; SM_(uint32_t, OFF_WR + 240 + ch * 4) = v.w;
          }
        }
        s = warp_sum(s);
        if (lane == 0) { SM_(float, OFF_WSUM) = s; SM_(uint32_t, OFF_TAG) = tag; }
      }
      if (a < 2) __nanosleep(GATHER_NS);
      {
        const int i0 = a * 32 + lane;
        uint2 v[3], c0, c1; uint32_t n = 0;
        const uint2* dp = &p.s->dsum[abrow];
        while (true) {
#pragma unroll
          for (int q = 0; q < 3; q++) v[q] = pkt_ld64(&p.s->xstat[tau * 256 + min(i0 + 96 * q, 255)]);
          c0 = pkt_ld64(dp + i0); c1 = pkt_ld64(dp + min(i0 + 96, 127));
          if (__all_sync(0xffffffffu, v[0].y == tag && v[1].y == tag && v[2].y == tag && c0.y == tag && c1.y == tag) || ++n > SPIN_LIMIT) break;
          __nanosleep(200);
        }
#pragma unroll
        for (int q = 0; q < 3; q++) put_xstat(sb + OFF_RS, sb + OFF_EXB, min(i0 + 96 * q, 255), v[q].x, m);
        put_dsum(sb + OFF_EXA, i0, __uint_as_float(c0.x));
        put_dsum(sb + OFF_EXA, min(i0 + 96, 127), __uint_as_float(c1.x));
        fence_async_smem();
      }
      __syncwarp();
      if (lane == 0) mbar_arrive(BAR(B_STAT));
      if (a == 0) PT(7);
      if (a == 0) {
        const int sg = (lane >> 2) == tau ? sigma_of(tau, 0) : lane >> 2;
        const uint32_t* flg = reinterpret_cast<const uint32_t*>(&p.s->abflag[((eps * 2 + m) * 8 + sg) * 2]) + ((lane >> 2) == tau ? 4 : lane & 3);
        if (NX < 256 && lane == 4 * tau + 1) flg = reinterpret_cast<const uint32_t*>(&p.s->hflag[(m * 8 + eps) * 2]);
        uint32_t seen = 0;
        auto until = [&](int tile) {
          uint32_t n = 0;
          while (!((seen >> (4 * tile)) & 1) && ++n < SPIN_LIMIT) seen = __ballot_sync(0xffffffffu, ld_relaxed32(flg) == tag);
        };
        const int s0 = sigma_of(tau, 0), s1 = sigma_of(tau, 1), s2 = sigma_of(tau, 2), s3 = sigma_of(tau, 3);
        mbar_wait(BAR(B_EPI), 0);
        mbar_wait(BAR(B_FULL + 0), 0);
        mbar_wait(BAR(B_FULL + 1), 0);
        if (elect_one()) mbar_expect_tx(BAR(B_A20), 8192);
        mbar_wait(BAR(B_STDA), 0);
        PT(49);
        until(tau);
        mbar_wait(BAR(B_EPI0B), 0);
        PT(48);
        if (elect_one()) tma_load_2d(sb + OFF_XCH, &p.tmAbS, BAR(B_FULL + 0), s0 * 256, abrow);
        mbar_wait(BAR(B_FULL + 2), 0);
        mbar_wait(BAR(B_STD + 0), 0);
        until(s0);
        PT(16);
        if (elect_one()) tma_load_2d(sb + OFF_XCH + 8192, &p.tmAbS, BAR(B_A20), s0 * 256, abrow + 64);
        until(s1);
        PT(17);
        if (elect_one()) tma_load_2d(sb + OFF_XCH + 16384, &p.tmAbL, BAR(B_FULL + 1), s1 * 256, abrow);
        until(s2);
        PT(18);
        if (elect_one()) {
          tma_load_2d(sb + 2 * ST_BYTES, &p.tmAbL, BAR(B_FULL + 2), s2 * 256, abrow);
          mbar_arrive(BAR(B_PUB1));
        }
        until(s3);
        mbar_wait(BAR(B_FULL + 3), 0);
        mbar_wait(BAR(B_STD + 1), 0);
        PT(19);
        if (elect_one()) tma_load_2d(sb + 3 * ST_BYTES, &p.tmAbL, BAR(B_FULL + 3), s3 * 256, abrow);
        uint32_t n = 0;
        while (true) {
          asm volatile("fence.proxy.async.global;" ::: "memory");
          *(volatile uint32_t*)&SM_(uint32_t, OFF_SEEN) = seen;
          if (seen == 0xFFFFFFFFu || ++n > SPIN_LIMIT) break;
          seen = __ballot_sync(0xffffffffu, ld_relaxed32(flg) == tag);
          __nanosleep(100);
        }
      } else {
        uint32_t* flag = reinterpret_cast<uint32_t*>(&p.s->abflag[((eps * 2 + m) * 8 + tau) * 2]);
        mbar_wait(BAR(a == 1 ? B_EPI : B_EPI0B), 0);
        if (a == 1) PT(8);
        if (lane == 0) {
          tma_store_2d(&p.tmAbS, sb + chunk_off(0, a - 1), tau * 256, abrow + (a - 1) * 64);
          bulk_commit();
          bulk_wait_all();
        }
        if (a == 2) mbar_wait(BAR(B_STDA), 0);
        if (lane == 0) {
          st_relaxed32(flag + (a == 1 ? 4 : 0), tag);
          mbar_arrive(BAR(a == 1 ? B_STDA : B_STD));
        }
        if (a == 2) PT(12);
        if (a == 1) {
          mbar_wait(BAR(B_EPI + 1), 0);
          mbar_wait(BAR(B_LATE), 0);
          mbar_wait(BAR(B_PUB1), 0);
          PT(9);
          if (lane == 0) {
            tma_store_2d(&p.tmAbS, sb + chunk_off(1, 0), tau * 256 + 64, abrow);
            tma_store_2d(&p.tmAbS, sb + chunk_off(1, 1), tau * 256 + 64, abrow + 64);
            bulk_commit();
            bulk_wait_all();
            st_relaxed32(flag + 1, tag);
            mbar_arrive(BAR(B_STD + 1));
          }
          PT(13);
        }
        auto copy_out = [&](int c) {
          mbar_wait(BAR(B_EPI + c), 0);
          PT(8 + c);
          bf16* dst = p.s->abT + (size_t)(abrow + (lane >> 3)) * 2048 + tau * 256 + c * 64 + (lane & 7) * 8;
          const uint32_t src = sb + chunk_off(c, 0) + (lane >> 3) * 128 + (((lane & 7) ^ (lane >> 3)) << 4);
          const uint32_t on = c * 64 + (lane & 7) * 8 < NX;
#pragma unroll 4
          for (int i = 0; i < 32; i++) {
            const uint4 v = lds128_v((src ^ ((i & 1) << 6)) + i * 512);
            asm volatile("{\n.reg .pred p;\nsetp.ne.b32 p, %5, 0;\n@p st.global.v4.b32 [%0], {%1, %2, %3, %4};\n}\n"
                         :: "l"(dst + i * 4 * 2048), "r"(v.x), "r"(v.y), "r"(v.z), "r"(v.w), "r"(on));
          }
          __syncwarp();
          if (lane == 0) mbar_arrive(BAR(B_STD + c));
        };
        if (a == 2) {
#pragma unroll 1
          for (int c = 2; c < 4; c++) copy_out(c);
          asm volatile("fence.acq_rel.gpu;" ::: "memory");
          __syncwarp();
          if (lane < 2) st_relaxed32(flag + 2 + lane, tag);
          PT(15);
        }
      }
      {
        mbar_wait(BAR(B_LATE), 1);
        const int grp = tau * 2 + m;
#pragma unroll 1
        for (int i = a; i < 14; i += 3) {
          uint4* dst = i < 8 ? &p.s->ypart[cid * 256 + i * 32 + lane] : i < 12 ? &p.s->hstat[(grp * 8 + eps) * 128 + (i - 8) * 32 + lane]
                     : i == 12 ? &p.s->cand[grp * 256 + eps * 32 + lane] : &p.s->key[(((lane >> 1) & 7) * 16 + grp) * 2 + (lane & 1)];
          if (i < 13 || eps == 0) pkt_st128(dst, 0, 0, 0, 0);
          __nanosleep(200);
        }
        __syncwarp();
        if (lane == 0) mbar_arrive(BAR(B_STAT));
      }
      {
        const uint4* kp = &p.s->key[(tau * 16 + (lane & 15)) * 2];
        const int i0 = a * 32 + lane;
        mbar_wait(BAR(B_KEY), 0);
        if (a == 0) PT(43);
        uint4 kq = pkt_ld128(kp), cv[3] = {};
        uint32_t n = 0, kv;
        int gspec = -1;
        while (true) {
          const bool ok = kq.y == tag && kq.w == tag;
          kv = __reduce_max_sync(0xffffffffu, ok ? kq.x : 0u);
          const int gs = group_of(0xFFFF - (int)(kv & 0xFFFFu));
          const bool cok = gs == gspec && cv[0].y == tag && cv[0].w == tag && cv[1].y == tag && cv[1].w == tag && cv[2].y == tag && cv[2].w == tag;
          if (__all_sync(0xffffffffu, ok && cok) || ++n > SPIN_LIMIT) break;
          if (!ok) kq = pkt_ld128(kp);
          n += keep_awake();
          const bool spec = __popc(__ballot_sync(0xffffffffu, ok)) >= 2 * SPEC_MIN;
          if (!cok && spec) {
#pragma unroll
            for (int i = 0; i < 3; i++) cv[i] = pkt_ld128(&p.s->cand[gs * 256 + min(i0 + 96 * i, 255)]);
          }
          if (spec) gspec = gs;
        }
        if (a == 0) PT(45);
        const uint32_t ms = __shfl_sync(0xffffffffu, kq.z, gspec);
        const uint32_t nm = ((ms & 0xFFFFu) ^ 0x8000u) * 0x10001u;
        const float is = rcp_fast(bf_hi(ms));
#pragma unroll
        for (int i = 0; i < 3; i++) {
          const int j = min(i0 + 96 * i, 255);
          SM_(uint2, OFF_XSEL + j * 8) = make_uint2(norm2(cv[i].x, nm, is), norm2(cv[i].z, nm, is));
        }
#pragma unroll
        for (int i = 0; i < 3; i++) SM_(uint2, OFF_HSEL + min(i0 + 96 * i, 255) * 8) = make_uint2(cv[i].x, cv[i].z);
        SM_(uint32_t, OFF_KV) = kv;
        __syncwarp();
        if (lane == 0) mbar_arrive(BAR(B_XS));
      }
    }
    asm volatile("barrier.cluster.wait.aligned;" ::: "memory");
  } else {
    reg_inc<REG_C>();
    const int tid = __shfl_sync(0xffffffffu, threadIdx.x, threadIdx.x & 31), lane = tid & 31;
    const int w = warp >> 2, wi = warp & 3, t = tid & 127;
    const int g = lane >> 2, q = lane & 3;
    const int turn_me = NB_TURN0 + w, turn_other = NB_TURN1 - w;
    auto release = [&](int s) { if (t == 0) mbar_arrive(BAR(B_EMPTY + s)); };
    if (MAP == 0 && helper) {
      asm volatile("barrier.cluster.arrive.relaxed.aligned;" ::: "memory");
      float s0[64], s1[64];
#pragma unroll
      for (int i = 0; i < 64; i++) { s0[i] = 0.f; s1[i] = 0.f; }
      if (w == 1) bar_arrive(NB_TURN0, 256);
      uint32_t o[32][2] = {};
      const int col = (eps - 2) * 8 + m * 4 + w;
      auto put = [&](auto tc, uint32_t buf) {
        constexpr int tl = decltype(tc)::value;
#pragma unroll
        for (int i = 0; i < 4; i++)
          smem_at<uint2>(buf + ((i >> 1) * 64 + wi * 16 + (i & 1) * 8 + g) * 32 + ((q * 8) ^ ((g & 4) << 2))) = make_uint2(o[8 * i + tl][0], o[8 * i + tl][1]);
      };
      auto publish = [&](int c) { if (t == 0) { bulk_wait_all(); st_relaxed32(&p.s->hflag[c * 2], SM_(uint32_t, OFF_TAG)); } };
#pragma unroll 1
      for (int pass = 0; pass < 2; pass++) {
#pragma unroll 1
        for (int k = 16 * pass; k < 16 * pass + 16; k++) {
          const int s = slot_of(k);
          mbar_wait(BAR(B_FULL + s), use_of(k) & 1);
          bar_sync(turn_me, 256);
          const uint64_t da = make_desc(sb + s * ST_BYTES + A_BYTES + w * 16384), db = make_desc(sb + s * ST_BYTES);
          wgmma_fence();
#pragma unroll
          for (int kk = 0; kk < 4; kk++) {
            wgmma_n128(s0, da + kk * 2, db + kk * 2, kk > 0 || (k & 15));
            wgmma_n128(s1, da + 512 + kk * 2, db + kk * 2, kk > 0 || (k & 15));
          }
          wgmma_commit();
          if (k < 31 || w == 0) bar_arrive(turn_other, 256);
          if (pass && !(k & 1)) {
            const uint32_t buf = sb + OFF_XCH + 20480 + w * 4096;
            static_for<8>([&](auto ic) { if (k == 16 + 2 * decltype(ic)::value) put(ic, buf); });
            fence_async_smem();
            bar_sync(NB_WG0 + w, 128);
            if (t == 0) { tma_store_2d(&p.tmAbM, buf, (k - 16) * 128 + 240, col * 128); bulk_commit(); }
          }
          wgmma_wait0();
          release(s);
          if ((k & 1) && t == 0) asm volatile("cp.async.bulk.wait_group.read 0;" ::: "memory");
        }
        if (pass) publish(col);
        mbar_wait(BAR(B_STAT), 0);
        wgmma_fence();
        wgmma_n128(s0, make_desc_noswz(sb + OFF_XCH + pass * 8192 + w * 4096), make_desc_noswz(sb + OFF_XCH + 16384));
        wgmma_n128(s1, make_desc_noswz(sb + OFF_XCH + pass * 8192 + w * 4096 + 2048), make_desc_noswz(sb + OFF_XCH + 16384));
        wgmma_commit();
        uint4 rs[4];
#pragma unroll
        for (int i = 0; i < 4; i++) rs[i] = lds128_v(sb + OFF_RS + q * 144 + i * 16);
        wgmma_wait0();
        fence_acc(s0); fence_acc(s1);
#pragma unroll
        for (int i = 0; i < 32; i++) {
          const int tl = i & 7, hr = (i >> 3) & 1;
          const float* ac = (i >> 4) ? &s1[8 * tl + 2 * hr] : &s0[8 * tl + 2 * hr];
          o[i][0] = bmul2(pack_bf16(ac[0], ac[1]), (tl & 1) ? rs[tl >> 1].z : rs[tl >> 1].x);
          o[i][1] = bmul2(pack_bf16(ac[4], ac[5]), (tl & 1) ? rs[tl >> 1].w : rs[tl >> 1].y);
        }
      }
      static_for<8>([&](auto ic) { put(ic, sb + (w * 8 + decltype(ic)::value) * 4096); });
      fence_async_smem();
      bar_sync(NB_WG0 + w, 128);
      if (t == 0) {
#pragma unroll 1
        for (int i = 0; i < 8; i++) tma_store_2d(&p.tmAbM, sb + (w * 8 + i) * 4096, i * 256 + 240, (col + 2) * 128);
        bulk_commit();
      }
      publish(col + 2);
      asm volatile("barrier.cluster.wait.aligned;" ::: "memory");
      return;
    }
    float acc[128], a1[NX / 2];
#pragma unroll
    for (int i = 0; i < NX / 2; i++) a1[i] = 0.f;
    if (w == 1) bar_arrive(NB_TURN0, 256);
    auto kstep = [&](auto& d, int k, bool first, bool a_in_xch = false, bool mini = false) {
      const int s = slot_of(k);
      mbar_wait(BAR(B_FULL + s), use_of(k) & 1);
      CT(64 + k);
      bar_sync(turn_me, 256);
      const uint64_t da = make_desc(sb + (a_in_xch ? OFF_XCH + s * 16384 : s * ST_BYTES) + w * 8192), db = make_desc(sb + s * ST_BYTES + A_BYTES);
      wgmma_fence();
      wgmma_g1(d, da, db, !first);
#pragma unroll
      for (int kk = 1; kk < 4; kk++) wgmma_g1(d, da + kk * 2, db + kk * 2, 1);
      wgmma_commit();
      if (mini) {
        CT(29);
        mbar_wait(BAR(B_A20), 1);
        CT(30);
        wgmma_fence();
        wgmma_g1(d, make_desc_32b(sb + OFF_MINI + w * 2048), make_desc_32b(sb + OFF_MINI + 4096), 1);
        wgmma_commit();
      }
      bar_arrive(turn_other, 256);
    };
    auto kdone = [&](int k) { wgmma_wait0(); release(slot_of(k)); };
    auto wgmma_wait1 = [&]() { asm volatile("wgmma.wait_group.sync.aligned 1;" ::: "memory"); };

#pragma unroll 1
    for (int k = 0; k < 14; k++) {
      kstep(a1, k, k == 0);
      if (k == 0) CT(0);
      if (k == 8 && warp == 2 && lane < 2) pkt_st128(&p.s->abflag[((eps * 2 + m) * 8 + tau) * 2 + lane], 0, 0, 0, 0);
      kdone(k);
    }
    uint32_t R[64];
    uint32_t tag;
    {
      const uint32_t rsa = sb + OFF_RS + q * 144;
      const uint64_t da2 = make_desc(sb + 2 * ST_BYTES + w * 8192), db2 = make_desc(sb + 2 * ST_BYTES + A_BYTES);
      const uint64_t da3 = make_desc(sb + 3 * ST_BYTES + w * 8192), db3 = make_desc(sb + 3 * ST_BYTES + A_BYTES);
      mbar_wait(BAR(B_FULL + 2), 1);
      CT(64 + 14);
      bar_sync(turn_me, 256);
      wgmma_fence();
#pragma unroll
      for (int kk = 0; kk < 4; kk++) wgmma_g1(a1, da2 + kk * 2, db2 + kk * 2, 1);
      wgmma_commit();
      mbar_wait(BAR(B_FULL + 3), 1);
      CT(64 + 15);
      wgmma_fence();
      wgmma_g1(a1, da3, db3, 1);
      wgmma_g1(a1, da3 + 2, db3 + 2, 1);
      wgmma_commit();
      mbar_wait(BAR(B_STAT), 0);
      tag = SM_(uint32_t, OFF_TAG);
#pragma unroll
      for (int i = 0; i < 8; i++) { const uint4 v = lds128_v(rsa + i * 16); R[8 * i] = v.x; R[8 * i + 2] = v.y; R[8 * i + 4] = v.z; R[8 * i + 6] = v.w; }
      wgmma_wait1();
      release(2);
      wgmma_fence();
      wgmma_g1(a1, da3 + 4, db3 + 4, 1);
      wgmma_g1(a1, da3 + 6, db3 + 6, 1);
      wgmma_g1(a1, make_desc_noswz(sb + OFF_EXA + w * 2048), make_desc_noswz(sb + OFF_EXB), 1);
      wgmma_commit();
      bar_arrive(turn_other, 256);
      kdone(15);
      mbar_wait(BAR(B_STAT), 0);
    }
    fence_acc(a1);
    CT(1);
    auto pack = [&](auto cc) {
      constexpr int c = decltype(cc)::value;
#pragma unroll
      for (int j = 8 * c; j < min_c(8 * c + 8, NX / 8); j++) {
        const uint32_t rs = R[2 * j];
        const float* ac = &a1[4 * j];
        R[2 * j] = bmul2(pack_bf16(ac[0], ac[1]), rs);
        R[2 * j + 1] = bmul2(pack_bf16(ac[2], ac[3]), rs);
      }
    };
    auto put_chunk = [&](auto cc) {
      constexpr int c = decltype(cc)::value;
      const int rho = 16 * wi + (lane & 15);
#pragma unroll
      for (int j = 8 * c; j < min_c(8 * c + 8, NX / 8); j += 2) {
        const int chunk = (j & 7) + (lane >> 4);
        stsm_x4(sb + chunk_off(c, w) + rho * 128 + ((chunk ^ (lane & 7)) << 4), R[2 * j], R[2 * j + 1], R[2 * j + 2], R[2 * j + 3]);
      }
    };
    auto staged = [&](int bar) {
      fence_async_smem();
      __syncwarp();
      if (lane == 0) mbar_arrive(BAR(bar));
    };
    auto mma_rs = [&](auto cc, auto k0, auto k1) {
      constexpr int c = decltype(cc)::value;
      const uint64_t db = make_desc(sb + c * ST_BYTES + A_BYTES);
#pragma unroll
      for (int kk = decltype(k0)::value; kk < decltype(k1)::value; kk++)
        wgmma_n256_rs(acc, R[16 * c + 4 * kk], R[16 * c + 4 * kk + 1], R[16 * c + 4 * kk + 2], R[16 * c + 4 * kk + 3], db + kk * 2, c + kk > 0);
      wgmma_commit();
    };
    auto kdone_x = [&](int k, auto ic) {
      constexpr int i = decltype(ic)::value;
      uint32_t r[8];
#pragma unroll
      for (int z = 0; z < 2; z++) {
        const int tr = 32 * (i & 1) + 16 * z + 8 * (lane >> 4) + (lane & 7), chunk = 2 * wi + ((lane >> 3) & 1);
        ldsm_x4_t(sb + (i >> 1) * ST_BYTES + w * 8192 + tr * 128 + ((chunk ^ (lane & 7)) << 4), r[4 * z], r[4 * z + 1], r[4 * z + 2], r[4 * z + 3]);
      }
      float f[16];
#pragma unroll
      for (int z = 0; z < 8; z++) { f[2 * z] = bf_lo(r[z]); f[2 * z + 1] = bf_hi(r[z]); }
#pragma unroll
      for (int z = 0; z < 16; z++) asm volatile("" : "+f"(f[z]));
      kdone(k);
#pragma unroll
      for (int z = 0; z < 16; z++) asm volatile("add.f32 %0, %0, %1;" : "+f"(acc[16 * i + z]) : "f"(f[z]));
    };
    pack(IC<0>());
    put_chunk(IC<0>());
    staged(w ? B_EPI0B : B_EPI);
    mbar_wait(BAR(B_STAT), 0);
    CT(21);
    pack(IC<1>());
    pack(IC<2>());
    pack(IC<3>());
#pragma unroll
    for (int i = 16; i < NX / 4; i++) asm volatile("" : "+r"(R[i]));
#pragma unroll
    for (int i = 0; i < 128; i++) asm volatile("" : "=f"(acc[i]));
    mbar_wait(BAR(B_FULL + 0), 0);
    CT(2);
    CT(64 + 16);
    bar_sync(turn_me, 256);
    wgmma_fence();
    mma_rs(IC<0>(), IC<0>(), IC<4>());
    mbar_wait(BAR(B_FULL + 1), 0);
    CT(64 + 17);
    wgmma_fence();
    mma_rs(IC<1>(), IC<0>(), IC<2>());
    wgmma_wait1();
    release(0);
    mma_rs(IC<1>(), IC<2>(), IC<4>());
    bar_arrive(turn_other, 256);
    kdone_x(17, IC<0>());
    static_for<2>([&](auto ic) {
      constexpr int c = 2 + decltype(ic)::value;
      mbar_wait(BAR(B_FULL + c), 0);
      CT(64 + 16 + c);
      bar_sync(turn_me, 256);
      wgmma_fence();
      mma_rs(IC<c>(), IC<0>(), IC<min_c(4, NX / 16 - 4 * c)>());
      bar_arrive(turn_other, 256);
      if (c == 2) { put_chunk(IC<1>()); staged(B_EPI + 1); }
      kdone_x(16 + c, IC<c - 1>());
    });
#pragma unroll 1
    for (int k = 20; k < 23; k++) {
      if (w == 1) mbar_wait(BAR(B_A20), 0);
      kstep(acc, k, false, k < 22);
      if (k == 20) {
        kdone_x(k, IC<3>());
      } else {
        if (k == 21) put_chunk(IC<2>()); else put_chunk(IC<3>());
        __syncwarp();
        if (lane == 0) mbar_arrive(BAR(B_EPI + k - 19));
        kdone(k);
      }
    }
    uint32_t wf[32][4];
    auto load_wf = [&](auto hc) {
      constexpr int h = decltype(hc)::value;
      const int d = w * 64 + (lane >> 4) * 8 + (lane & 7);
      const uint32_t ad = sb + round_off(h) + (lane & 8) * 1024 + d * 64 + ((wi ^ ((lane >> 1) & 3)) << 4);
#pragma unroll
      for (int i = 0; i < 4; i++) ldsm_x4_t(ad + i * 1024, wf[4 * h + i][0], wf[4 * h + i][1], wf[4 * h + i][2], wf[4 * h + i][3]);
    };
    auto load_wf_rest = [&]() { static_for<8 - NREG_H>([&](auto ic) { load_wf(IC<NREG_H + decltype(ic)::value>()); }); };
#pragma unroll
    for (int i = 0; i < 4 * NREG_H; i++) { wf[i][0] = 0; wf[i][1] = 0; wf[i][2] = 0; wf[i][3] = 0; }
    const int grp = tau * 2 + m;
#pragma unroll 1
    for (int k = 23; k < 46; k++) {
      kstep(acc, k, false, false, NX < 256 && k == MINI_K);
      if (moe) {
        static_for<NREG_H>([&](auto hc) {
          constexpr int h = decltype(hc)::value;
          if (k == mr_k(h) + 1) { mbar_wait(BAR(B_MR + (h & 1)), (h >> 1) & 1); CT(32 + h); load_wf(hc); }
        });
      }
      if (k == RESET_K && tid == 0) mbar_arrive(BAR(B_LATE));
      kdone(k);
    }
    asm volatile("barrier.cluster.arrive.relaxed.aligned;" ::: "memory");
    mbar_wait(BAR(B_STAT), 1);
    uint32_t wa[16][2];
    uint32_t cd = code_of(tag);
    uint4* hp_pub = &p.s->hstat[(grp * 8 + eps) * 128 + warp * 16 + g];
    const uint4* hp_poll = &p.s->hstat[(grp * 8 + 2 * q) * 128 + warp * 16 + g];
    const uint32_t vec_off = (2 * wi) * 512 + q * 128 + ((g ^ (2 * q)) << 4);
    {
      float as[64], ak[64];
      fence_acc(acc);
#pragma unroll
      for (int i = 0; i < 64; i++) asm volatile("mov.b32 %0, %1;" : "=f"(as[i]) : "f"(acc[64 + i]));
#pragma unroll
      for (int i = 0; i < 64; i++) asm volatile("mov.b32 %0, %1;" : "=f"(ak[i]) : "f"(acc[i]));
      const uint64_t da1 = make_desc(sb + 2 * ST_BYTES + w * 8192), db1 = make_desc(sb + 2 * ST_BYTES + A_BYTES);
      const uint64_t da2 = make_desc(sb + 3 * ST_BYTES + w * 8192), db2 = make_desc(sb + 3 * ST_BYTES + A_BYTES);
      mbar_wait(BAR(B_FULL + 2), 1);
      CT(64 + 46);
      bar_sync(turn_me, 256);
      wgmma_fence();
#pragma unroll
      for (int kk = 0; kk < 4; kk++) wgmma_n128(as, da1 + kk * 2, db1 + 1024 + kk * 2);
      wgmma_commit();
      mbar_wait(BAR(B_FULL + 3), 1);
      CT(64 + 47);
      wgmma_fence();
#pragma unroll
      for (int kk = 0; kk < 4; kk++) wgmma_n128(as, da2 + kk * 2, db2 + 1024 + kk * 2);
      wgmma_commit();
      bar_arrive(turn_other, 256);
      const uint32_t rx = mapa(sb + OFF_PEER + w * 4096 + vec_off, 1 - m), rb = mapa(BAR(B_XCH), 1 - m);
      asm volatile("barrier.cluster.wait.aligned;" ::: "memory");
      CT(24);
      wgmma_wait0();
      fence_acc(as);
      CT(25);
      auto keep = [&]() {
        bar_sync(turn_me, 256);
        wgmma_fence();
#pragma unroll
        for (int kk = 0; kk < 4; kk++) wgmma_n128(ak, da1 + kk * 2, db1 + kk * 2);
        wgmma_commit();
#pragma unroll
        for (int kk = 0; kk < 4; kk++) wgmma_n128(ak, da2 + kk * 2, db2 + kk * 2);
        wgmma_commit();
        if (w == 0) bar_arrive(turn_other, 256);
      };
#pragma unroll
      for (int i = 0; i < 8; i++) {
        if (i == SEND_FIRST) keep();
        const float* ac = &as[16 * (i >> 1) + 2 * (i & 1)];
        st_async_v4(rx + (i >> 1) * 8192 + (i & 1) * 512, rb, pack_bf16(ac[0], ac[1]), pack_bf16(ac[4], ac[5]), pack_bf16(ac[8], ac[9]), pack_bf16(ac[12], ac[13]));
      }
      CT(26);
#pragma unroll
      for (int i = 0; i < 4; i++) {
        const uint4 v = lds128_v(sb + OFF_WR + q * 80 + i * 16);
        const uint32_t vv[4] = {v.x, v.y, v.z, v.w};
#pragma unroll
        for (int z = 0; z < 4; z++) {
          asm volatile("{\n.reg .pred p;\nsetp.ne.b32 p, %2, 0;\nselp.b32 %0, %1, 0x3F803F80, p;\n}" : "=r"(wa[4 * i + z][0]) : "r"(vv[z]), "r"(g & 1));
          asm volatile("{\n.reg .pred p;\nsetp.ne.b32 p, %2, 0;\nselp.b32 %0, %1, 0x3F803F80, p;\n}" : "=r"(wa[4 * i + z][1]) : "r"(vv[z]), "r"(g & 1));
        }
      }
      pin(cd); pin(hp_pub); pin(hp_poll);
      CT(27);
      wgmma_wait1();
      release(2);
      wgmma_wait0();
      fence_acc(ak);
      CT(3);
#pragma unroll
      for (int i = 0; i < 8; i++) {
        const float* ac = &ak[16 * (i >> 1) + 2 * (i & 1)];
        sts128(sb + (2 + (i >> 2)) * ST_BYTES + w * 8192 + ((i >> 1) & 1) * 4096 + (i & 1) * 512 + vec_off,
               pack_bf16(ac[0], ac[1]), pack_bf16(ac[4], ac[5]), pack_bf16(ac[8], ac[9]), pack_bf16(ac[12], ac[13]));
      }
    }
    uint32_t h[8][4];
    {
      const int qq = 2 * (warp & 1) + ((lane >> 3) & 1);
      const uint32_t lo = (lane >> 4) * 512 + qq * 128 + (((lane & 7) ^ (2 * qq)) << 4);
      bar_sync(NB_BOTH, 256);
#pragma unroll
      for (int ks = 0; ks < 8; ks++)
        ldsm_x4_t(sb + (2 + w) * ST_BYTES + (ks >> 2) * 8192 + (wi >> 1) * 4096 + (ks & 3) * 1024 + lo, h[ks][0], h[ks][1], h[ks][2], h[ks][3]);
      CT(28);
      mbar_wait_cluster(BAR(B_XCH), 0);
      CT(4);
      uint32_t r[8][4];
#pragma unroll
      for (int ks = 0; ks < 8; ks++) ldsm_x4_t(sb + OFF_PEER + (warp >> 1) * 8192 + ks * 1024 + lo, r[ks][0], r[ks][1], r[ks][2], r[ks][3]);
      float d[4][4] = {};
#pragma unroll
      for (int ks = 0; ks < 8; ks++) {
#pragma unroll
        for (int i = 0; i < 4; i++) {
          h[ks][i] = badd2(h[ks][i], r[ks][i]);
          mma1688(d[i], h[ks][i], wa[2 * ks + (i >> 1)][i & 1], h[ks][i]);
        }
      }
#pragma unroll
      for (int i = 0; i < 2; i++) {
        const float sq = (g & 1) ? d[i][1] + d[i + 2][1] : d[i][0] + d[i + 2][0];
        const float e0 = d[i][2] + d[i + 2][2], e1 = d[i][3] + d[i + 2][3];
        const float other = __shfl_xor_sync(0xffffffffu, (g & 1) ? e0 : e1, 4);
        if (q == (g >> 1)) pkt_st128(hp_pub + 8 * i, with_bit((g & 1) ? other : e0, cd), with_bit(sq, cd >> 1), __float_as_uint((g & 1) ? e1 : other), tag);
      }
    }
    CT(5);
    if (tid == 0) mbar_arrive(BAR(B_KEY));
    delay_clk<HOP1_DELAY>();
    float m_bf, sd, inv_sd, r_bf;
    uint4* key_pub = &p.s->key[((lane & 7) * 16 + grp) * 2];
    uint4* cand_pub = &p.s->cand[grp * 256 + eps * 32 + q];
    uint32_t trow_inv = 0xFFFFu - (uint32_t)row_of(grp * 128 + 32 * (warp >> 1) + 8 * (g >> 1) + 4 * (warp & 1) + (q & 2) + (g & 1));
    {
      uint4 u[4];
#pragma unroll
      for (int i = 0; i < 4; i++) u[i] = pkt_ld128(hp_poll + (i & 1) * 128 + (i >> 1) * 8);
      const float wsum = SM_(float, OFF_WSUM);
      pin(key_pub); pin(cand_pub); pin(trow_inv);
      uint32_t n = 0;
      while (true) {
        bool ok[4];
#pragma unroll
        for (int i = 0; i < 4; i++) ok[i] = u[i].w == tag && pair_code(u[i].x, u[i].y) == cd;
        const bool all = __all_sync(0xffffffffu, ok[0] && ok[1] && ok[2] && ok[3]);
        if (all || ++n > SPIN_LIMIT) break;
#pragma unroll
        for (int i = 0; i < 4; i++) pkt_ld128_if(u[i], hp_poll + (i & 1) * 128 + (i >> 1) * 8, !ok[i]);
      }
      CT(6);
      float a[3], b[3];
      a[0] = __uint_as_float(u[0].x & ~1u) + __uint_as_float(u[1].x & ~1u); b[0] = __uint_as_float(u[2].x & ~1u) + __uint_as_float(u[3].x & ~1u);
      a[1] = __uint_as_float(u[0].y & ~1u) + __uint_as_float(u[1].y & ~1u); b[1] = __uint_as_float(u[2].y & ~1u) + __uint_as_float(u[3].y & ~1u);
      a[2] = __uint_as_float(u[0].z) + __uint_as_float(u[1].z); b[2] = __uint_as_float(u[2].z) + __uint_as_float(u[3].z);
#pragma unroll
      for (int i = 0; i < 3; i++) {
        a[i] = ((q & 2) ? b[i] : a[i]) + __shfl_xor_sync(0xffffffffu, (q & 2) ? a[i] : b[i], 2);
        a[i] += __shfl_xor_sync(0xffffffffu, a[i], 1);
      }
      const float mu = a[0] * (1.f / 1024.f);
      m_bf = bf16r(mu);
      sd = ln_sd(a[1] * (1.f / 1024.f) - mu * mu);
      inv_sd = rcp_fast(sd);
      r_bf = bf16r((a[2] - m_bf * wsum) * inv_sd);
    }
    {
      const uint32_t u = __float_as_uint(r_bf);
      const uint32_t ord = (u & 0x80000000u) ? ~u : (u | 0x80000000u);
      const uint32_t key = (ord & 0xFFFF0000u) | trow_inv;
      const uint32_t wk = __reduce_max_sync(0xffffffffu, key);
      if (key == wk) SM_(uint2, OFF_WKEY + warp * 8) = make_uint2(wk, (__float_as_uint(m_bf) >> 16) | __float_as_uint(sd));
      const uint32_t wmask = __ballot_sync(0xffffffffu, key == wk);
      const bool hi = (wmask & 0xCCCCCCCCu) != 0;
      uint32_t c[16];
#pragma unroll
      for (int ks = 0; ks < 8; ks++) { c[2 * ks] = hi ? h[ks][1] : h[ks][0]; c[2 * ks + 1] = hi ? h[ks][3] : h[ks][2]; }
      bar_sync(NB_BOTH, 256);
      const uint2 km = SM_(uint2, OFF_WKEY + (lane & 7) * 8);
      const uint32_t bk = __reduce_max_sync(0xffffffffu, km.x);
      if (wk == bk) {
        if ((wmask >> (lane & 28)) & 15) {
#pragma unroll
          for (int ks = 0; ks < 8; ks++) pkt_st128(cand_pub + ks * 4, c[2 * ks], tag, c[2 * ks + 1], tag);
        }
      } else if (eps == 0) {
        const uint32_t kx = __shfl_sync(0xffffffffu, km.x, warp ^ 1), ms = __shfl_sync(0xffffffffu, km.y, warp ^ 1);
        if (kx == bk && lane < 8) pkt_st128(key_pub, bk, tag, ms, tag);
      }
      CT(7);
    }
    {
      const float ih = bf16r(inv_sd);
      const uint32_t nm = pack_bf16(-m_bf, -m_bf), iv = pack_bf16(ih, inv_sd - ih);
      const uint32_t nm_o = __shfl_xor_sync(0xffffffffu, nm, 2), iv_o = __shfl_xor_sync(0xffffffffu, iv, 2);
      const uint32_t nm2[2] = {(q & 2) ? nm_o : nm, (q & 2) ? nm : nm_o}, iv2[2] = {(q & 2) ? iv_o : iv, (q & 2) ? iv : iv_o};
      const uint32_t hi2[2] = {__byte_perm(iv2[0], 0, 0x1010), __byte_perm(iv2[1], 0, 0x1010)}, lo2[2] = {__byte_perm(iv2[0], 0, 0x3232), __byte_perm(iv2[1], 0, 0x3232)};
      const uint32_t oa = sb + OFF_OUT + (warp * 16 + (lane & 15)) * 128;
#pragma unroll
      for (int ks = 0; ks < 8; ks++) {
        uint32_t o[4];
#pragma unroll
        for (int i = 0; i < 4; i++) {
          const uint32_t dd = badd2(h[ks][i], nm2[i & 1]);
          o[i] = badd2(h[ks][i], bfma2(dd, hi2[i & 1], bmul2(dd, lo2[i & 1])));
        }
        stsm_x4(oa + (ks >> 2) * 16384 + (((2 * (ks & 3) + (lane >> 4)) ^ (lane & 7)) << 4), o[0], o[1], o[2], o[3]);
      }
      staged(B_OUT);
    }
    CT(8);
    uint32_t df[16][4];
    auto load_df = [&]() {
      const int frow = (lane & 7) + ((lane >> 4) << 3), hi = (lane >> 3) & 1;
      const uint32_t base = sb + down_off(warp >> 1) + (warp & 1) * 8192 + frow * 128;
#pragma unroll
      for (int mt = 0; mt < 8; mt++) {
#pragma unroll
        for (int ks = 0; ks < 2; ks++)
          ldsm_x4_t(base + (mt >> 2) * 4096 + ks * 2048 + (((2 * (mt & 3) + hi) ^ (lane & 7)) << 4),
                    df[2 * mt + ks][0], df[2 * mt + ks][1], df[2 * mt + ks][2], df[2 * mt + ks][3]);
      }
    };
    if (moe) {
      mbar_wait(BAR(B_GU), 0);
      load_wf_rest();
      mbar_wait(BAR(B_DN), 0);
      load_df();
    }
    uint4* y_pub = &p.s->ypart[cid * 256 + tid];
    uint32_t xs_ad = sb + OFF_XSEL + (8 * (g >> 2) + 4 * w + (g & 3)) * 32 + q * 8, gp_ad = sb + OFF_GP + (wi * 8 + g) * 16 + w * 8 + (q >> 1) * 4;
    pin(y_pub); pin(xs_ad); pin(gp_ad);
    mbar_wait(BAR(B_XS), 0);
    CT(9);
    if (moe) {
      float gd[8][4] = {};
      uint2 bx[4];
#pragma unroll
      for (int r = 0; r < 4; r++) bx[r] = smem_at<uint2>(xs_ad + r * 512);
#pragma unroll
      for (int r = 0; r < 4; r++) {
#pragma unroll
        for (int i = 0; i < 8; i++) mma16816(gd[i], wf[8 * r + i][0], wf[8 * r + i][1], wf[8 * r + i][2], wf[8 * r + i][3], bx[r].x, bx[r].y);
      }
      const float gs = sel4(q, gd[0][0] + gd[1][1], gd[2][0] + gd[3][1], gd[4][0] + gd[5][1], gd[6][0] + gd[7][1]);
      const float us = sel4(q, gd[0][2] + gd[1][3], gd[2][2] + gd[3][3], gd[4][2] + gd[5][3], gd[6][2] + gd[7][3]);
      float v = ((q & 2) ? us : gs) + __shfl_xor_sync(0xffffffffu, (q & 2) ? gs : us, 2);
      v += __shfl_xor_sync(0xffffffffu, v, 1);
      smem_at<float>(gp_ad) = v;
      CT(10);
      bar_sync(NB_BOTH, 256);
      uint32_t bq[4];
      {
        const float4 p0 = SM_(float4, OFF_GP + lane * 16);
        const float gt = bf16r(p0.x + p0.z), up = bf16r(p0.y + p0.w);
        const float act = bf16r(gt * sigmoid_fast(gt)) * up;
        const uint32_t pr = pack_bf16(act, __shfl_down_sync(0xffffffffu, act, 1));
#pragma unroll
        for (int i = 0; i < 4; i++) bq[i] = __shfl_sync(0xffffffffu, pr, 8 * i + 2 * q);
      }
      CT(11);
      float yd[8][4] = {};
#pragma unroll
      for (int ks = 0; ks < 2; ks++) {
#pragma unroll
        for (int mt = 0; mt < 8; mt++) mma16816(yd[mt], df[2 * mt + ks][0], df[2 * mt + ks][1], df[2 * mt + ks][2], df[2 * mt + ks][3], bq[2 * ks], bq[2 * ks + 1]);
      }
      pkt_st128(y_pub, with_bit(sel4(q, yd[0][0], yd[2][0], yd[4][0], yd[6][0]), cd), with_bit(sel4(q, yd[0][2], yd[2][2], yd[4][2], yd[6][2]), cd >> 1),
                with_bit(sel4(q, yd[1][0], yd[3][0], yd[5][0], yd[7][0]), cd), with_bit(sel4(q, yd[1][2], yd[3][2], yd[5][2], yd[7][2]), cd >> 1));
    } else {
      const long long tw = clock64();
      while (clock64() - tw < IDLE_WAIT_CLK) __nanosleep(100);
    }
    CT(12);
    const uint32_t kv = SM_(uint32_t, OFF_KV);
    const int tsel = (int)(~kv & 2047u);
    const float r_sel = __uint_as_float((kv & 0x80000000u) ? (kv & 0x7FFF0000u) : (~kv & 0xFFFF0000u));
    const float sig = bf16r(sigmoid_fast(r_sel));
    const int pfin = 2 * cid + (tid & 1);
    const int col_fin = (pfin >> 5) * 128 + (pfin & 3) * 32 + ((pfin & 31) >> 2) + 8 * ((tid >> 1) & 3);
    const int sel_off = (col_fin >> 4) * 32 + ((col_fin & 7) >> 1) * 8 + ((col_fin >> 3) & 1) * 4 + (col_fin & 1) * 2;
    const float hn_fin = __uint_as_float((uint32_t)SM_(uint16_t, OFF_XSEL + sel_off) << 16), h_fin = __uint_as_float((uint32_t)SM_(uint16_t, OFF_HSEL + sel_off) << 16);
    bf16* out_fin = p.out + (size_t)tsel * 1024 + col_fin;
    {
      const uint4* src = &p.s->ypart[(16 + (tid >> 1)) * 256 + pfin];
      pin(src); pin(out_fin);
      uint4 v = make_uint4(0, 0, 0, 0);
      if (warp < 7) {
        delay_clk<HOP3_DELAY>();
        uint32_t n = 0;
        bool ok = false;
        do {
          pkt_ld128_if(v, src, !ok);
          ok = pair_code(v.x, v.y) == cd && pair_code(v.z, v.w) == cd;
        } while (!__all_sync(0xffffffffu, ok) && ++n < SPIN_LIMIT);
      }
      CT(13);
      const float y0 = __uint_as_float(v.x & ~1u), y1 = __uint_as_float(v.y & ~1u), y2 = __uint_as_float(v.z & ~1u), y3 = __uint_as_float(v.w & ~1u);
      const float a0 = ((lane & 2) ? y1 : y0) + __shfl_xor_sync(0xffffffffu, (lane & 2) ? y0 : y1, 2);
      const float a1 = ((lane & 2) ? y3 : y2) + __shfl_xor_sync(0xffffffffu, (lane & 2) ? y2 : y3, 2);
      float b = ((lane & 4) ? a1 : a0) + __shfl_xor_sync(0xffffffffu, (lane & 4) ? a0 : a1, 4);
      b += __shfl_xor_sync(0xffffffffu, b, 8);
      b += __shfl_xor_sync(0xffffffffu, b, 16);
      if (lane < 8) SM_(float, OFF_FIN + lane * 32 + warp * 4) = b;
    }
    bar_sync(NB_BOTH, 256);
    if (tid < 8) {
      const float4 y0 = SM_(float4, OFF_FIN + tid * 32), y1 = SM_(float4, OFF_FIN + tid * 32 + 16);
      const float y = ((y0.x + y0.y) + (y0.z + y0.w)) + ((y1.x + y1.y) + y1.z);
      *out_fin = __float2bfloat16_rn(h_fin + bf16r(hn_fin + bf16r(bf16r(y) * sig)));
      if (cid == 0 && tid == 0) st_relaxed32(&p.s->epoch, tag);
    }
    CT(14);
  }
}

__global__ void __launch_bounds__(384, 1) occupancy_probe_kernel() {}

typedef CUresult (*EncodeFn)(CUtensorMap*, CUtensorMapDataType, cuuint32_t, void*, const cuuint64_t*, const cuuint64_t*, const cuuint32_t*, const cuuint32_t*,
                             CUtensorMapInterleave, CUtensorMapSwizzle, CUtensorMapL2promotion, CUtensorMapFloatOOBfill);

static void make_tm(EncodeFn enc, CUtensorMap* tm, const void* ptr, uint64_t rows, uint64_t cols, uint32_t brows, uint32_t bcols, CUtensorMapSwizzle sw,
                    CUtensorMapL2promotion promo = CU_TENSOR_MAP_L2_PROMOTION_L2_128B) {
  cuuint64_t dims[2] = {cols, rows};
  cuuint64_t strides[1] = {cols * 2};
  cuuint32_t box[2] = {bcols, brows};
  cuuint32_t es[2] = {1, 1};
  enc(tm, CU_TENSOR_MAP_DATA_TYPE_BFLOAT16, 2, const_cast<void*>(ptr), dims, strides, box, es, CU_TENSOR_MAP_INTERLEAVE_NONE, sw,
      promo, CU_TENSOR_MAP_FLOAT_OOB_FILL_NONE);
}

static void make_tm_rows(EncodeFn enc, CUtensorMap* tm, const void* ptr, uint64_t cols, uint32_t brows, uint32_t bcols, CUtensorMapSwizzle sw,
                         CUtensorMapL2promotion promo = CU_TENSOR_MAP_L2_PROMOTION_L2_128B) {
  cuuint64_t dims[4] = {cols, 2, 2, 512};
  cuuint64_t strides[3] = {row_of(1) * cols * 2, row_of(2) * cols * 2, row_of(4) * cols * 2};
  cuuint32_t box[4] = {bcols, 2, 2, brows / 4};
  cuuint32_t es[4] = {1, 1, 1, 1};
  enc(tm, CU_TENSOR_MAP_DATA_TYPE_BFLOAT16, 4, const_cast<void*>(ptr), dims, strides, box, es, CU_TENSOR_MAP_INTERLEAVE_NONE, sw, promo,
      CU_TENSOR_MAP_FLOAT_OOB_FILL_NONE);
}

extern "C" void kernel_launch(void* const* d_in, const int* in_sizes, int n_in, void* d_out, int out_size) {
  (void)in_sizes; (void)n_in; (void)out_size;
  static EncodeFn enc = nullptr;
  static void* abT = nullptr;
  static int map = 0;
  if (!enc) {
    void* fn = nullptr; cudaDriverEntryPointQueryResult st;
    cudaGetDriverEntryPoint("cuTensorMapEncodeTiled", &fn, cudaEnableDefault, &st);
    enc = (EncodeFn)fn;
    cudaGetSymbolAddress(&abT, g_scratch);
    cudaFuncSetAttribute(fnet_moe_kernel<0>, cudaFuncAttributeMaxDynamicSharedMemorySize, SMEM_TOTAL);
    cudaFuncSetAttribute(fnet_moe_kernel<1>, cudaFuncAttributeMaxDynamicSharedMemorySize, SMEM_TOTAL);
    cudaFuncSetAttribute(occupancy_probe_kernel, cudaFuncAttributeMaxDynamicSharedMemorySize, SMEM_TOTAL);
    cudaFuncSetAttribute(occupancy_probe_kernel, cudaFuncAttributeNonPortableClusterSizeAllowed, 1);
    auto max_clusters = [&](int size) {
      cudaLaunchConfig_t cfg = {};
      cfg.gridDim = dim3(128); cfg.blockDim = dim3(384); cfg.dynamicSmemBytes = SMEM_TOTAL;
      cudaLaunchAttribute at[1];
      at[0].id = cudaLaunchAttributeClusterDimension; at[0].val.clusterDim.x = size; at[0].val.clusterDim.y = 1; at[0].val.clusterDim.z = 1;
      cfg.attrs = at; cfg.numAttrs = 1;
      int ncl = 0;
      return cudaOccupancyMaxActiveClusters(&ncl, occupancy_probe_kernel, &cfg) == cudaSuccess ? ncl : 0;
    };
    int dev = 0, sms = 0;
    cudaGetDevice(&dev);
    cudaDeviceGetAttribute(&sms, cudaDevAttrMultiProcessorCount, dev);
    map = (sms == 132 && max_clusters(2) == 66 && max_clusters(16) == 7) ? 0 : 1;
    (void)cudaGetLastError();
  }
  Params p;
  const bf16* x = (const bf16*)d_in[0];
  make_tm(enc, &p.tmD0, d_in[3], 1024, 1024, 128, 64, CU_TENSOR_MAP_SWIZZLE_128B);
  make_tm(enc, &p.tmD1, d_in[4], 1024, 1024, 128, 64, CU_TENSOR_MAP_SWIZZLE_128B);
  make_tm(enc, &p.tmX, x, 2048, 1024, map == 0 ? NX0 : 256, 64, CU_TENSOR_MAP_SWIZZLE_128B);
  make_tm_rows(enc, &p.tmXr, x, 1024, 64, 64, CU_TENSOR_MAP_SWIZZLE_128B);
  make_tm(enc, &p.tmAbS, abT, 2048, 2048, 64, 64, CU_TENSOR_MAP_SWIZZLE_128B);
  make_tm(enc, &p.tmAbL, abT, 2048, 2048, 128, 64, CU_TENSOR_MAP_SWIZZLE_128B);
  make_tm_rows(enc, &p.tmW0, d_in[1], 2048, 128, 64, CU_TENSOR_MAP_SWIZZLE_128B);
  make_tm_rows(enc, &p.tmW1, d_in[2], 2048, 128, 64, CU_TENSOR_MAP_SWIZZLE_128B);
  {
    cuuint64_t dims[5] = {1024, 2, 4, 2, 2048};
    cuuint64_t strides[4] = {row_of(1) * 2048, row_of(8) * 2048, row_of(2) * 2048, 2048};
    cuuint32_t box[5] = {64, 2, 4, 2, 1};
    cuuint32_t es[5] = {1, 1, 1, 1, 1};
    enc(&p.tmOut, CU_TENSOR_MAP_DATA_TYPE_BFLOAT16, 5, d_out, dims, strides, box, es, CU_TENSOR_MAP_INTERLEAVE_NONE, CU_TENSOR_MAP_SWIZZLE_128B,
        CU_TENSOR_MAP_L2_PROMOTION_NONE, CU_TENSOR_MAP_FLOAT_OOB_FILL_NONE);
  }
  {
    cuuint64_t dims[5] = {1024, 2, 4, 2, 8};
    cuuint64_t strides[4] = {2048, 4 * 2048, 2 * 2048, 256 * 2048};
    cuuint32_t box[5] = {64, 2, 4, 2, 8};
    cuuint32_t es[5] = {1, 1, 1, 1, 1};
    enc(&p.tmXh, CU_TENSOR_MAP_DATA_TYPE_BFLOAT16, 5, const_cast<bf16*>(x) + 240 * 1024, dims, strides, box, es, CU_TENSOR_MAP_INTERLEAVE_NONE,
        CU_TENSOR_MAP_SWIZZLE_128B, CU_TENSOR_MAP_L2_PROMOTION_L2_128B, CU_TENSOR_MAP_FLOAT_OOB_FILL_NONE);
  }
  make_tm(enc, &p.tmAbM, abT, 2048, 2048, 128, 16, CU_TENSOR_MAP_SWIZZLE_32B, CU_TENSOR_MAP_L2_PROMOTION_NONE);
  make_tm_rows(enc, &p.tmWM0, d_in[1], 2048, 128, 16, CU_TENSOR_MAP_SWIZZLE_32B);
  make_tm_rows(enc, &p.tmWM1, d_in[2], 2048, 128, 16, CU_TENSOR_MAP_SWIZZLE_32B);
  make_tm(enc, &p.tmG, d_in[7], 1024, 3584, 128, 32, CU_TENSOR_MAP_SWIZZLE_64B);
  make_tm(enc, &p.tmU, d_in[8], 1024, 3584, 128, 32, CU_TENSOR_MAP_SWIZZLE_64B);
  make_tm(enc, &p.tmDn, d_in[9], 3584, 1024, 32, 64, CU_TENSOR_MAP_SWIZZLE_128B);
  p.x = x; p.Dre = (const bf16*)d_in[3]; p.Dim = (const bf16*)d_in[4];
  p.wr = (const bf16*)d_in[6]; p.wdown = (const bf16*)d_in[9]; p.wgate = (const bf16*)d_in[7]; p.wup = (const bf16*)d_in[8];
  p.out = (bf16*)d_out; p.s = (Scratch*)abT;
  if (map == 1) fnet_moe_kernel<1><<<128, 384, SMEM_TOTAL>>>(p);
  else fnet_moe_kernel<0><<<132, 384, SMEM_TOTAL>>>(p);
}
```

```cpp
#include <cuda.h>
#include <cuda_runtime.h>
#include <cuda_bf16.h>
#include <stdint.h>
#include <type_traits>

typedef __nv_bfloat16 bf16;

constexpr int NX0 = 240;
constexpr int REG_C = 232, REG_P = 40;
__host__ __device__ constexpr int row_of(int p) { return (p & 1) * 1024 + ((p >> 1) & 1) * 512 + (p >> 2); }
__host__ __device__ constexpr int group_of(int row) { return (row & 511) >> 5; }
__device__ __forceinline__ int sigma_of(int tau, int r) { return r + (r >= tau); }
__device__ __forceinline__ int kblock(int tau, int j) {
  const int i = j - 4, c = (i * 37) >> 8;
  return j < 4 ? tau * 4 + j : sigma_of(tau, i - 7 * c) * 4 + c;
}
constexpr int AUX_AFTER = 1;
constexpr int PF_K0 = 8, PF_N0 = 2, PF_K1 = 24;
constexpr int WPF_K0 = 12, WPF_N = 10;
constexpr int WPF2_K = 44, WPF2_N = 4;
constexpr int GU_K = 46;
constexpr int PUB_K1 = 22;
constexpr int NREG_H = 5;
constexpr int MR_K0 = 29, MR_P = 6;
constexpr int MINI_PF_K = 35, MINI_LOAD_K = 43, MINI_K = 42;
constexpr int RESET_K = 37;
constexpr int SEND_FIRST = 2;
constexpr int GATHER_NS = 400;
constexpr int MOE_PACE_CLK = 300;
constexpr int OUT_PACE_CLK = 70;
constexpr int HOP1_DELAY = 150, HOP3_DELAY = 450;
constexpr int SPEC_MIN = 10;
constexpr int IDLE_WAIT_CLK = 1200;
__host__ __device__ constexpr int mr_k(int h) { return MR_K0 + MR_P * (h >> 1) + 2 * (h & 1); }
constexpr int A_BYTES = 128 * 64 * 2;
constexpr int B_BYTES = 256 * 64 * 2;
constexpr int ST_BYTES = A_BYTES + B_BYTES;
constexpr int OFF_XCH = 4 * ST_BYTES;
constexpr int OFF_BAR = OFF_XCH + 32768;
constexpr int OFF_WR = OFF_BAR + 384;
constexpr int OFF_RS = OFF_WR + 384;
constexpr int OFF_PUB = OFF_RS + 640;
constexpr int OFF_MISC = OFF_PUB + 768;
constexpr int SMEM_TOTAL = OFF_MISC + 256;
constexpr int OFF_WSUM = OFF_MISC, OFF_TAG = OFF_MISC + 4;
constexpr int OFF_SEEN = OFF_MISC + 8;
constexpr int OFF_KV = OFF_MISC + 12;
constexpr int OFF_WKEY = OFF_MISC + 32;
constexpr int OFF_MINI = OFF_XCH + 16384;
constexpr int OFF_EXA = OFF_XCH;
constexpr int OFF_EXB = OFF_XCH + 4096;
__host__ __device__ constexpr int chunk_off(int c, int w) { return (c < 2 ? (c + 2) * ST_BYTES : OFF_XCH + (c - 2) * 16384) + w * 8192; }
__host__ __device__ constexpr int late_off(int i) { return i < 4 ? i * 16384 : 2 * ST_BYTES + A_BYTES + (i - 4) * 16384; }
__host__ __device__ constexpr int round_off(int h) { return h < NREG_H + 2 ? OFF_XCH + (h & 1) * 16384 : late_off(h - NREG_H - 2); }
__host__ __device__ constexpr int down_off(int i) { return late_off(6 - NREG_H + i); }
constexpr int OFF_PEER = ST_BYTES + A_BYTES;
constexpr int OFF_OUT = 3 * ST_BYTES + A_BYTES;
constexpr int OFF_XSEL = OFF_PEER;
constexpr int OFF_HSEL = OFF_PEER + 4096;
constexpr int OFF_GP = OFF_PEER + 8192;
constexpr int OFF_FIN = OFF_PEER + 9216;
__device__ __forceinline__ int slot_of(int k) { return k & 3; }
__device__ __forceinline__ int use_of(int k) { return k >> 2; }
enum { B_FULL = 0, B_EMPTY = 4, B_EPI = 8, B_STD = 12, B_EPI0B = 16, B_LATE = 17, B_STAT = 18, B_XCH = 19, B_MR = 20  , B_GU = 22,
       B_DN = 23, B_AUX = 24  , B_OUT = 26, B_KEY = 27, B_XS = 28, B_A20 = 29, B_STDA = 30, B_PUB1 = 31, B_COUNT = 32 };
enum { NB_TURN0 = 1, NB_TURN1 = 2, NB_WG0 = 3, NB_BOTH = 5, NB_AUX = 6 };

struct Scratch {
  bf16 abT[2048 * 2048];
  uint2 xstat[2048];
  uint2 dsum[2048];
  uint4 abflag[16 * 8 * 2];
  uint4 hflag[16 * 2];
  uint4 hstat[16 * 8 * 128];
  uint4 cand[16 * 256];
  uint4 key[8 * 16 * 2];
  uint4 ypart[128 * 256];
  uint32_t epoch;
};
__device__ __align__(1024) Scratch g_scratch;

struct Params {
  Scratch* s; bf16* out;
  const bf16* x; const bf16* Dre; const bf16* Dim; const bf16* wr; const bf16* wdown; const bf16* wgate; const bf16* wup;
  CUtensorMap tmX, tmD0, tmD1, tmXr, tmAbS, tmAbL, tmW0, tmW1, tmOut, tmG, tmU, tmDn, tmXh, tmAbM, tmWM0, tmWM1;
};

#define SPIN_LIMIT (1u << 14)
#define MBAR_LIMIT (1u << 10)
__device__ __forceinline__ uint32_t smem_u32(const void* p) { return (uint32_t)__cvta_generic_to_shared(p); }
__device__ __forceinline__ void mbar_init(uint32_t bar, uint32_t cnt) { asm volatile("mbarrier.init.shared::cta.b64 [%0], %1;" :: "r"(bar), "r"(cnt) : "memory"); }
__device__ __forceinline__ void mbar_expect_tx(uint32_t bar, uint32_t bytes) { asm volatile("mbarrier.arrive.expect_tx.shared::cta.b64 _, [%0], %1;" :: "r"(bar), "r"(bytes) : "memory"); }
__device__ __forceinline__ void mbar_arrive(uint32_t bar) { asm volatile("mbarrier.arrive.shared::cta.b64 _, [%0];" :: "r"(bar) : "memory"); }
__device__ __forceinline__ void mbar_wait(uint32_t bar, uint32_t parity) {
  uint32_t ok, n = 0;
  do {
    asm volatile("{\n.reg .pred p;\nmbarrier.try_wait.parity.shared::cta.b64 p, [%1], %2;\nselp.u32 %0, 1, 0, p;\n}\n" : "=r"(ok) : "r"(bar), "r"(parity) : "memory");
  } while (!ok && ++n < MBAR_LIMIT);
}
__device__ __forceinline__ void mbar_wait_cluster(uint32_t bar, uint32_t parity) {
  uint32_t ok, n = 0;
  do {
    asm volatile("{\n.reg .pred p;\nmbarrier.try_wait.parity.acquire.cluster.shared::cta.b64 p, [%1], %2;\nselp.u32 %0, 1, 0, p;\n}\n" : "=r"(ok) : "r"(bar), "r"(parity) : "memory");
  } while (!ok && ++n < MBAR_LIMIT);
}
__device__ __forceinline__ void tma_load_2d(uint32_t dst, const CUtensorMap* tm, uint32_t bar, int c0, int c1) {
  asm volatile("cp.async.bulk.tensor.2d.shared::cluster.global.mbarrier::complete_tx::bytes [%0], [%1, {%3, %4}], [%2];"
    :: "r"(dst), "l"(tm), "r"(bar), "r"(c0), "r"(c1) : "memory");
}
__device__ __forceinline__ void tma_load_2d_hint(uint32_t dst, const CUtensorMap* tm, uint32_t bar, int c0, int c1, uint64_t pol) {
  asm volatile("cp.async.bulk.tensor.2d.shared::cluster.global.mbarrier::complete_tx::bytes.L2::cache_hint [%0], [%1, {%3, %4}], [%2], %5;"
    :: "r"(dst), "l"(tm), "r"(bar), "r"(c0), "r"(c1), "l"(pol) : "memory");
}
__device__ __forceinline__ uint64_t policy_evict_first() { uint64_t p; asm volatile("createpolicy.fractional.L2::evict_first.b64 %0, 1.0;" : "=l"(p)); return p; }
__device__ __forceinline__ void tma_store_2d(const CUtensorMap* tm, uint32_t src, int c0, int c1) {
  asm volatile("cp.async.bulk.tensor.2d.global.shared::cta.bulk_group [%0, {%2, %3}], [%1];" :: "l"(tm), "r"(src), "r"(c0), "r"(c1) : "memory");
}
__device__ __forceinline__ void tma_prefetch_2d(const CUtensorMap* tm, int c0, int c1) {
  asm volatile("cp.async.bulk.prefetch.tensor.2d.L2.global.tile [%0, {%1, %2}];" :: "l"(tm), "r"(c0), "r"(c1) : "memory");
}
__device__ __forceinline__ void bulk_load(uint32_t dst, const void* src, uint32_t bytes, uint32_t bar) {
  asm volatile("cp.async.bulk.shared::cluster.global.mbarrier::complete_tx::bytes [%0], [%1], %2, [%3];" :: "r"(dst), "l"(src), "r"(bytes), "r"(bar) : "memory");
}
__device__ __forceinline__ void bulk_commit() { asm volatile("cp.async.bulk.commit_group;" ::: "memory"); }
__device__ __forceinline__ void bulk_wait_all() { asm volatile("cp.async.bulk.wait_group 0;" ::: "memory"); }
__device__ __forceinline__ void fence_async_smem() { asm volatile("fence.proxy.async.shared::cta;" ::: "memory"); }
__device__ __forceinline__ void wgmma_fence() { asm volatile("wgmma.fence.sync.aligned;" ::: "memory"); }
__device__ __forceinline__ void wgmma_commit() { asm volatile("wgmma.commit_group.sync.aligned;" ::: "memory"); }
__device__ __forceinline__ void wgmma_wait0() { asm volatile("wgmma.wait_group.sync.aligned 0;" ::: "memory"); }
__device__ __forceinline__ void bar_sync(int id, int n) { asm volatile("bar.sync %0, %1;" :: "r"(id), "r"(n) : "memory"); }
__device__ __forceinline__ void bar_arrive(int id, int n) { asm volatile("bar.arrive %0, %1;" :: "r"(id), "r"(n) : "memory"); }
template<int R> __device__ __forceinline__ void reg_inc() { asm volatile("setmaxnreg.inc.sync.aligned.u32 %0;" :: "n"(R)); }
template<int R> __device__ __forceinline__ void reg_dec() { asm volatile("setmaxnreg.dec.sync.aligned.u32 %0;" :: "n"(R)); }
__device__ __forceinline__ bool elect_one() {
  uint32_t p;
  asm volatile("{\n.reg .pred q;\nelect.sync _|q, 0xffffffff;\nselp.u32 %0, 1, 0, q;\n}\n" : "=r"(p));
  return p != 0;
}
__device__ __forceinline__ uint32_t mapa(uint32_t addr, uint32_t cta) { uint32_t r; asm volatile("mapa.shared::cluster.u32 %0, %1, %2;" : "=r"(r) : "r"(addr), "r"(cta)); return r; }
__device__ __forceinline__ void st_async_v4(uint32_t addr, uint32_t bar, uint32_t a, uint32_t b, uint32_t c, uint32_t d) {
  asm volatile("st.async.weak.shared::cluster.mbarrier::complete_tx::bytes.v4.b32 [%0], {%2, %3, %4, %5}, [%1];" :: "r"(addr), "r"(bar), "r"(a), "r"(b), "r"(c), "r"(d) : "memory");
}
__device__ __forceinline__ void stsm_x4(uint32_t addr, uint32_t a, uint32_t b, uint32_t c, uint32_t d) {
  asm volatile("stmatrix.sync.aligned.m8n8.x4.shared.b16 [%0], {%1, %2, %3, %4};" :: "r"(addr), "r"(a), "r"(b), "r"(c), "r"(d));
}
__device__ __forceinline__ uint4 lds128_v(uint32_t addr) { uint4 v; asm volatile("ld.shared.v4.b32 {%0, %1, %2, %3}, [%4];" : "=r"(v.x), "=r"(v.y), "=r"(v.z), "=r"(v.w) : "r"(addr)); return v; }
extern __shared__ __align__(1024) uint8_t smem_raw[];
template<class T> __device__ __forceinline__ T& smem_at(uint32_t addr) { return *reinterpret_cast<T*>(__cvta_shared_to_generic(addr)); }
#define SM_(T, off) smem_at<T>(sb + (off))
__device__ __forceinline__ uint4 ldg_nc128(const void* p) { uint4 v; asm volatile("ld.global.nc.v4.b32 {%0, %1, %2, %3}, [%4];" : "=r"(v.x), "=r"(v.y), "=r"(v.z), "=r"(v.w) : "l"(p)); return v; }
__device__ __forceinline__ void pkt_st128(void* p, uint32_t a, uint32_t b, uint32_t c, uint32_t d) {
  asm volatile("{\n.reg .b128 v;\n.reg .b64 lo, hi;\nmov.b64 lo, {%1, %2};\nmov.b64 hi, {%3, %4};\nmov.b128 v, {lo, hi};\nst.relaxed.gpu.global.b128 [%0], v;\n}\n"
    :: "l"(p), "r"(a), "r"(b), "r"(c), "r"(d) : "memory");
}
__device__ __forceinline__ uint4 pkt_ld128(const void* p) {
  uint4 r;
  asm volatile("{\n.reg .b128 v;\n.reg .b64 lo, hi;\nld.relaxed.gpu.global.b128 v, [%4];\nmov.b128 {lo, hi}, v;\nmov.b64 {%0, %1}, lo;\nmov.b64 {%2, %3}, hi;\n}\n"
    : "=r"(r.x), "=r"(r.y), "=r"(r.z), "=r"(r.w) : "l"(p) : "memory");
  return r;
}
__device__ __forceinline__ void pkt_ld128_if(uint4& r, const void* p, bool cond) {
  asm volatile("{\n.reg .pred q;\n.reg .b64 lo, hi;\nsetp.ne.b32 q, %5, 0;\nmov.b64 lo, {%0, %1};\nmov.b64 hi, {%2, %3};\n"
               "@q ld.relaxed.gpu.global.v2.b64 {lo, hi}, [%4];\nmov.b64 {%0, %1}, lo;\nmov.b64 {%2, %3}, hi;\n}\n"
    : "+r"(r.x), "+r"(r.y), "+r"(r.z), "+r"(r.w) : "l"(p), "r"((uint32_t)cond) : "memory");
}
__device__ __forceinline__ void pkt_st64(void* p, uint32_t a, uint32_t b) {
  asm volatile("{\n.reg .b64 v;\nmov.b64 v, {%1, %2};\nst.relaxed.gpu.global.b64 [%0], v;\n}\n" :: "l"(p), "r"(a), "r"(b) : "memory");
}
__device__ __forceinline__ uint2 pkt_ld64(const void* p) {
  uint2 r;
  asm volatile("{\n.reg .b64 v;\nld.relaxed.gpu.global.b64 v, [%2];\nmov.b64 {%0, %1}, v;\n}\n" : "=r"(r.x), "=r"(r.y) : "l"(p) : "memory");
  return r;
}
__device__ __forceinline__ uint32_t ld_relaxed32(const void* p) { uint32_t v; asm volatile("ld.relaxed.gpu.global.b32 %0, [%1];" : "=r"(v) : "l"(p) : "memory"); return v; }
__device__ __forceinline__ void st_relaxed32(void* p, uint32_t v) { asm volatile("st.relaxed.gpu.global.b32 [%0], %1;" :: "l"(p), "r"(v) : "memory"); }
__device__ __forceinline__ uint32_t code_of(uint32_t tag) { return tag % 3u + 1u; }
__device__ __forceinline__ uint32_t with_bit(float v, uint32_t bit) { return (__float_as_uint(v) & ~1u) | (bit & 1u); }
__device__ __forceinline__ uint32_t pair_code(uint32_t a, uint32_t b) { return (a & 1u) | ((b & 1u) << 1); }
__device__ __forceinline__ uint32_t pack_bf16(float lo, float hi) { uint32_t r; asm("cvt.rn.bf16x2.f32 %0, %1, %2;" : "=r"(r) : "f"(hi), "f"(lo)); return r; }
__device__ __forceinline__ float bf_lo(uint32_t v) { return __uint_as_float(v << 16); }
__device__ __forceinline__ float bf_hi(uint32_t v) { return __uint_as_float(v & 0xFFFF0000u); }
__device__ __forceinline__ float bf16r(float x) { return __uint_as_float(pack_bf16(0.f, x)); }
__device__ __forceinline__ uint32_t badd2(uint32_t a, uint32_t b) { uint32_t r; asm("add.rn.bf16x2 %0, %1, %2;" : "=r"(r) : "r"(a), "r"(b)); return r; }
__device__ __forceinline__ uint32_t bmul2(uint32_t a, uint32_t b) { uint32_t r; asm("mul.rn.bf16x2 %0, %1, %2;" : "=r"(r) : "r"(a), "r"(b)); return r; }
__device__ __forceinline__ float warp_sum(float v) {
#pragma unroll
  for (int o = 16; o > 0; o >>= 1) v += __shfl_xor_sync(0xffffffffu, v, o);
  return v;
}
__device__ __forceinline__ uint64_t make_desc(uint32_t addr) {
  return (uint64_t)((addr & 0x3FFFF) >> 4) | ((uint64_t)1 << 16) | ((uint64_t)64 << 32) | ((uint64_t)1 << 62);
}
__device__ __forceinline__ uint64_t make_desc_noswz(uint32_t addr) {
  return (uint64_t)((addr & 0x3FFFF) >> 4) | ((uint64_t)8 << 16) | ((uint64_t)16 << 32);
}
__device__ __forceinline__ uint64_t make_desc_32b(uint32_t addr) {
  return (uint64_t)((addr & 0x3FFFF) >> 4) | ((uint64_t)1 << 16) | ((uint64_t)16 << 32) | ((uint64_t)3 << 62);
}
__device__ __forceinline__ void wgmma_n256(float (&d)[128], uint64_t da, uint64_t db, int scale_d) {
  asm volatile("{\n.reg .pred p;\nsetp.ne.b32 p, %130, 0;\n"
    "wgmma.mma_async.sync.aligned.m64n256k16.f32.bf16.bf16 "
    "{%0, %1, %2, %3, %4, %5, %6, %7, %8, %9, %10, %11, %12, %13, %14, %15, %16, %17, %18, %19, %20, %21, %22, %23, %24, %25, %26, %27, %28, %29, %30, %31, "
    "%32, %33, %34, %35, %36, %37, %38, %39, %40, %41, %42, %43, %44, %45, %46, %47, %48, %49, %50, %51, %52, %53, %54, %55, %56, %57, %58, %59, %60, %61, %62, %63, "
    "%64, %65, %66, %67, %68, %69, %70, %71, %72, %73, %74, %75, %76, %77, %78, %79, %80, %81, %82, %83, %84, %85, %86, %87, %88, %89, %90, %91, %92, %93, %94, %95, "
    "%96, %97, %98, %99, %100, %101, %102, %103, %104, %105, %106, %107, %108, %109, %110, %111, %112, %113, %114, %115, %116, %117, %118, %119, %120, %121, %122, %123, %124, %125, %126, %127}, "
    "%128, %129, p, 1, 1, 0, 0;\n}\n"
    : "+f"(d[0]), "+f"(d[1]), "+f"(d[2]), "+f"(d[3]), "+f"(d[4]), "+f"(d[5]), "+f"(d[6]), "+f"(d[7]),
      "+f"(d[8]), "+f"(d[9]), "+f"(d[10]), "+f"(d[11]), "+f"(d[12]), "+f"(d[13]), "+f"(d[14]), "+f"(d[15]),
      "+f"(d[16]), "+f"(d[17]), "+f"(d[18]), "+f"(d[19]), "+f"(d[20]), "+f"(d[21]), "+f"(d[22]), "+f"(d[23]),
      "+f"(d[24]), "+f"(d[25]), "+f"(d[26]), "+f"(d[27]), "+f"(d[28]), "+f"(d[29]), "+f"(d[30]), "+f"(d[31]),
      "+f"(d[32]), "+f"(d[33]), "+f"(d[34]), "+f"(d[35]), "+f"(d[36]), "+f"(d[37]), "+f"(d[38]), "+f"(d[39]),
      "+f"(d[40]), "+f"(d[41]), "+f"(d[42]), "+f"(d[43]), "+f"(d[44]), "+f"(d[45]), "+f"(d[46]), "+f"(d[47]),
      "+f"(d[48]), "+f"(d[49]), "+f"(d[50]), "+f"(d[51]), "+f"(d[52]), "+f"(d[53]), "+f"(d[54]), "+f"(d[55]),
      "+f"(d[56]), "+f"(d[57]), "+f"(d[58]), "+f"(d[59]), "+f"(d[60]), "+f"(d[61]), "+f"(d[62]), "+f"(d[63]),
      "+f"(d[64]), "+f"(d[65]), "+f"(d[66]), "+f"(d[67]), "+f"(d[68]), "+f"(d[69]), "+f"(d[70]), "+f"(d[71]),
      "+f"(d[72]), "+f"(d[73]), "+f"(d[74]), "+f"(d[75]), "+f"(d[76]), "+f"(d[77]), "+f"(d[78]), "+f"(d[79]),
      "+f"(d[80]), "+f"(d[81]), "+f"(d[82]), "+f"(d[83]), "+f"(d[84]), "+f"(d[85]), "+f"(d[86]), "+f"(d[87]),
      "+f"(d[88]), "+f"(d[89]), "+f"(d[90]), "+f"(d[91]), "+f"(d[92]), "+f"(d[93]), "+f"(d[94]), "+f"(d[95]),
      "+f"(d[96]), "+f"(d[97]), "+f"(d[98]), "+f"(d[99]), "+f"(d[100]), "+f"(d[101]), "+f"(d[102]), "+f"(d[103]),
      "+f"(d[104]), "+f"(d[105]), "+f"(d[106]), "+f"(d[107]), "+f"(d[108]), "+f"(d[109]), "+f"(d[110]), "+f"(d[111]),
      "+f"(d[112]), "+f"(d[113]), "+f"(d[114]), "+f"(d[115]), "+f"(d[116]), "+f"(d[117]), "+f"(d[118]), "+f"(d[119]),
      "+f"(d[120]), "+f"(d[121]), "+f"(d[122]), "+f"(d[123]), "+f"(d[124]), "+f"(d[125]), "+f"(d[126]), "+f"(d[127])
    : "l"(da), "l"(db), "r"(scale_d));
}
__device__ __forceinline__ void wgmma_g1(float (&d)[128], uint64_t da, uint64_t db, int scale_d) { wgmma_n256(d, da, db, scale_d); }
__device__ __forceinline__ void wgmma_g1(float (&d)[120], uint64_t da, uint64_t db, int scale_d) {
  asm volatile("{\n.reg .pred p;\nsetp.ne.b32 p, %122, 0;\n"
    "wgmma.mma_async.sync.aligned.m64n240k16.f32.bf16.bf16 "
    "{%0, %1, %2, %3, %4, %5, %6, %7, %8, %9, %10, %11, %12, %13, %14, %15, %16, %17, %18, %19, %20, %21, %22, %23, %24, %25, %26, %27, %28, %29, %30, %31, %32, %33, %34, %35, %36, %37, %38, %39, %40, %41, %42, %43, %44, %45, %46, %47, %48, %49, %50, %51, %52, %53, %54, %55, %56, %57, %58, %59, %60, %61, %62, %63, %64, %65, %66, %67, %68, %69, %70, %71, %72, %73, %74, %75, %76, %77, %78, %79, %80, %81, %82, %83, %84, %85, %86, %87, %88, %89, %90, %91, %92, %93, %94, %95, %96, %97, %98, %99, %100, %101, %102, %103, %104, %105, %106, %107, %108, %109, %110, %111, %112, %113, %114, %115, %116, %117, %118, %119}, "
    "%120, %121, p, 1, 1, 0, 0;\n}\n"
    : "+f"(d[0]), "+f"(d[1]), "+f"(d[2]), "+f"(d[3]), "+f"(d[4]), "+f"(d[5]), "+f"(d[6]), "+f"(d[7]), "+f"(d[8]), "+f"(d[9]), "+f"(d[10]), "+f"(d[11]), "+f"(d[12]), "+f"(d[13]), "+f"(d[14]), "+f"(d[15]), "+f"(d[16]), "+f"(d[17]), "+f"(d[18]), "+f"(d[19]), "+f"(d[20]), "+f"(d[21]), "+f"(d[22]), "+f"(d[23]), "+f"(d[24]), "+f"(d[25]), "+f"(d[26]), "+f"(d[27]), "+f"(d[28]), "+f"(d[29]), "+f"(d[30]), "+f"(d[31]), "+f"(d[32]), "+f"(d[33]), "+f"(d[34]), "+f"(d[35]), "+f"(d[36]), "+f"(d[37]), "+f"(d[38]), "+f"(d[39]), "+f"(d[40]), "+f"(d[41]), "+f"(d[42]), "+f"(d[43]), "+f"(d[44]), "+f"(d[45]), "+f"(d[46]), "+f"(d[47]), "+f"(d[48]), "+f"(d[49]), "+f"(d[50]), "+f"(d[51]), "+f"(d[52]), "+f"(d[53]), "+f"(d[54]), "+f"(d[55]), "+f"(d[56]), "+f"(d[57]), "+f"(d[58]), "+f"(d[59]), "+f"(d[60]), "+f"(d[61]), "+f"(d[62]), "+f"(d[63]), "+f"(d[64]), "+f"(d[65]), "+f"(d[66]), "+f"(d[67]), "+f"(d[68]), "+f"(d[69]), "+f"(d[70]), "+f"(d[71]), "+f"(d[72]), "+f"(d[73]), "+f"(d[74]), "+f"(d[75]), "+f"(d[76]), "+f"(d[77]), "+f"(d[78]), "+f"(d[79]), "+f"(d[80]), "+f"(d[81]), "+f"(d[82]), "+f"(d[83]), "+f"(d[84]), "+f"(d[85]), "+f"(d[86]), "+f"(d[87]), "+f"(d[88]), "+f"(d[89]), "+f"(d[90]), "+f"(d[91]), "+f"(d[92]), "+f"(d[93]), "+f"(d[94]), "+f"(d[95]), "+f"(d[96]), "+f"(d[97]), "+f"(d[98]), "+f"(d[99]), "+f"(d[100]), "+f"(d[101]), "+f"(d[102]), "+f"(d[103]), "+f"(d[104]), "+f"(d[105]), "+f"(d[106]), "+f"(d[107]), "+f"(d[108]), "+f"(d[109]), "+f"(d[110]), "+f"(d[111]), "+f"(d[112]), "+f"(d[113]), "+f"(d[114]), "+f"(d[115]), "+f"(d[116]), "+f"(d[117]), "+f"(d[118]), "+f"(d[119])
    : "l"(da), "l"(db), "r"(scale_d));
}
__device__ __forceinline__ void wgmma_n256_rs(float (&d)[128], uint32_t a0, uint32_t a1, uint32_t a2, uint32_t a3, uint64_t db, int scale_d) {
  asm volatile("{\n.reg .pred p;\nsetp.ne.b32 p, %133, 0;\n"
    "wgmma.mma_async.sync.aligned.m64n256k16.f32.bf16.bf16 "
    "{%0, %1, %2, %3, %4, %5, %6, %7, %8, %9, %10, %11, %12, %13, %14, %15, %16, %17, %18, %19, %20, %21, %22, %23, %24, %25, %26, %27, %28, %29, %30, %31, "
    "%32, %33, %34, %35, %36, %37, %38, %39, %40, %41, %42, %43, %44, %45, %46, %47, %48, %49, %50, %51, %52, %53, %54, %55, %56, %57, %58, %59, %60, %61, %62, %63, "
    "%64, %65, %66, %67, %68, %69, %70, %71, %72, %73, %74, %75, %76, %77, %78, %79, %80, %81, %82, %83, %84, %85, %86, %87, %88, %89, %90, %91, %92, %93, %94, %95, "
    "%96, %97, %98, %99, %100, %101, %102, %103, %104, %105, %106, %107, %108, %109, %110, %111, %112, %113, %114, %115, %116, %117, %118, %119, %120, %121, %122, %123, %124, %125, %126, %127}, "
    "{%128, %129, %130, %131}, %132, p, 1, 1, 0;\n}\n"
    : "+f"(d[0]), "+f"(d[1]), "+f"(d[2]), "+f"(d[3]), "+f"(d[4]), "+f"(d[5]), "+f"(d[6]), "+f"(d[7]),
      "+f"(d[8]), "+f"(d[9]), "+f"(d[10]), "+f"(d[11]), "+f"(d[12]), "+f"(d[13]), "+f"(d[14]), "+f"(d[15]),
      "+f"(d[16]), "+f"(d[17]), "+f"(d[18]), "+f"(d[19]), "+f"(d[20]), "+f"(d[21]), "+f"(d[22]), "+f"(d[23]),
      "+f"(d[24]), "+f"(d[25]), "+f"(d[26]), "+f"(d[27]), "+f"(d[28]), "+f"(d[29]), "+f"(d[30]), "+f"(d[31]),
      "+f"(d[32]), "+f"(d[33]), "+f"(d[34]), "+f"(d[35]), "+f"(d[36]), "+f"(d[37]), "+f"(d[38]), "+f"(d[39]),
      "+f"(d[40]), "+f"(d[41]), "+f"(d[42]), "+f"(d[43]), "+f"(d[44]), "+f"(d[45]), "+f"(d[46]), "+f"(d[47]),
      "+f"(d[48]), "+f"(d[49]), "+f"(d[50]), "+f"(d[51]), "+f"(d[52]), "+f"(d[53]), "+f"(d[54]), "+f"(d[55]),
      "+f"(d[56]), "+f"(d[57]), "+f"(d[58]), "+f"(d[59]), "+f"(d[60]), "+f"(d[61]), "+f"(d[62]), "+f"(d[63]),
      "+f"(d[64]), "+f"(d[65]), "+f"(d[66]), "+f"(d[67]), "+f"(d[68]), "+f"(d[69]), "+f"(d[70]), "+f"(d[71]),
      "+f"(d[72]), "+f"(d[73]), "+f"(d[74]), "+f"(d[75]), "+f"(d[76]), "+f"(d[77]), "+f"(d[78]), "+f"(d[79]),
      "+f"(d[80]), "+f"(d[81]), "+f"(d[82]), "+f"(d[83]), "+f"(d[84]), "+f"(d[85]), "+f"(d[86]), "+f"(d[87]),
      "+f"(d[88]), "+f"(d[89]), "+f"(d[90]), "+f"(d[91]), "+f"(d[92]), "+f"(d[93]), "+f"(d[94]), "+f"(d[95]),
      "+f"(d[96]), "+f"(d[97]), "+f"(d[98]), "+f"(d[99]), "+f"(d[100]), "+f"(d[101]), "+f"(d[102]), "+f"(d[103]),
      "+f"(d[104]), "+f"(d[105]), "+f"(d[106]), "+f"(d[107]), "+f"(d[108]), "+f"(d[109]), "+f"(d[110]), "+f"(d[111]),
      "+f"(d[112]), "+f"(d[113]), "+f"(d[114]), "+f"(d[115]), "+f"(d[116]), "+f"(d[117]), "+f"(d[118]), "+f"(d[119]),
      "+f"(d[120]), "+f"(d[121]), "+f"(d[122]), "+f"(d[123]), "+f"(d[124]), "+f"(d[125]), "+f"(d[126]), "+f"(d[127])
    : "r"(a0), "r"(a1), "r"(a2), "r"(a3), "l"(db), "r"(scale_d));
}
__device__ __forceinline__ void wgmma_n128(float (&d)[64], uint64_t da, uint64_t db, int scale_d = 1) {
  asm volatile("{\n.reg .pred p;\nsetp.ne.b32 p, %66, 0;\n"
    "wgmma.mma_async.sync.aligned.m64n128k16.f32.bf16.bf16 "
    "{%0, %1, %2, %3, %4, %5, %6, %7, %8, %9, %10, %11, %12, %13, %14, %15, %16, %17, %18, %19, %20, %21, %22, %23, %24, %25, %26, %27, %28, %29, %30, %31, %32, %33, %34, %35, %36, %37, %38, %39, %40, %41, %42, %43, %44, %45, %46, %47, %48, %49, %50, %51, %52, %53, %54, %55, %56, %57, %58, %59, %60, %61, %62, %63}, "
    "%64, %65, p, 1, 1, 0, 0;\n}\n"
    : "+f"(d[0]), "+f"(d[1]), "+f"(d[2]), "+f"(d[3]), "+f"(d[4]), "+f"(d[5]), "+f"(d[6]), "+f"(d[7]), "+f"(d[8]), "+f"(d[9]), "+f"(d[10]), "+f"(d[11]), "+f"(d[12]), "+f"(d[13]), "+f"(d[14]), "+f"(d[15]), "+f"(d[16]), "+f"(d[17]), "+f"(d[18]), "+f"(d[19]), "+f"(d[20]), "+f"(d[21]), "+f"(d[22]), "+f"(d[23]), "+f"(d[24]), "+f"(d[25]), "+f"(d[26]), "+f"(d[27]), "+f"(d[28]), "+f"(d[29]), "+f"(d[30]), "+f"(d[31]), "+f"(d[32]), "+f"(d[33]), "+f"(d[34]), "+f"(d[35]), "+f"(d[36]), "+f"(d[37]), "+f"(d[38]), "+f"(d[39]), "+f"(d[40]), "+f"(d[41]), "+f"(d[42]), "+f"(d[43]), "+f"(d[44]), "+f"(d[45]), "+f"(d[46]), "+f"(d[47]), "+f"(d[48]), "+f"(d[49]), "+f"(d[50]), "+f"(d[51]), "+f"(d[52]), "+f"(d[53]), "+f"(d[54]), "+f"(d[55]), "+f"(d[56]), "+f"(d[57]), "+f"(d[58]), "+f"(d[59]), "+f"(d[60]), "+f"(d[61]), "+f"(d[62]), "+f"(d[63])
    : "l"(da), "l"(db), "r"(scale_d));
}
template<int N> __device__ __forceinline__ void fence_acc(float (&d)[N]) {
#pragma unroll
  for (int i = 0; i < N; i++) asm volatile("" : "+f"(d[i]) :: "memory");
}

template<int N, int I = 0, class F> __device__ __forceinline__ void static_for(F&& f) {
  if constexpr (I < N) { f(std::integral_constant<int, I>()); static_for<N, I + 1>(f); }
}

__device__ __forceinline__ void ldsm_x4_t(uint32_t addr, uint32_t& a, uint32_t& b, uint32_t& c, uint32_t& d) {
  asm volatile("ldmatrix.sync.aligned.m8n8.x4.trans.shared.b16 {%0, %1, %2, %3}, [%4];" : "=r"(a), "=r"(b), "=r"(c), "=r"(d) : "r"(addr));
}
__device__ __forceinline__ void sts128(uint32_t addr, uint32_t a, uint32_t b, uint32_t c, uint32_t d) {
  asm volatile("st.shared.v4.b32 [%0], {%1, %2, %3, %4};" :: "r"(addr), "r"(a), "r"(b), "r"(c), "r"(d));
}
__device__ __forceinline__ void mma16816(float (&c)[4], uint32_t a0, uint32_t a1, uint32_t a2, uint32_t a3, uint32_t b0, uint32_t b1) {
  asm volatile("mma.sync.aligned.m16n8k16.row.col.f32.bf16.bf16.f32 {%0, %1, %2, %3}, {%4, %5, %6, %7}, {%8, %9}, {%0, %1, %2, %3};"
      : "+f"(c[0]), "+f"(c[1]), "+f"(c[2]), "+f"(c[3]) : "r"(a0), "r"(a1), "r"(a2), "r"(a3), "r"(b0), "r"(b1));
}
__device__ __forceinline__ void mma1688(float (&c)[4], uint32_t a0, uint32_t a1, uint32_t b0) {
  asm volatile("mma.sync.aligned.m16n8k8.row.col.f32.bf16.bf16.f32 {%0, %1, %2, %3}, {%4, %5}, {%6}, {%0, %1, %2, %3};"
      : "+f"(c[0]), "+f"(c[1]), "+f"(c[2]), "+f"(c[3]) : "r"(a0), "r"(a1), "r"(b0));
}
__device__ __forceinline__ uint32_t keep_awake() {
  float c0;
  asm volatile("{\n.reg .f32 c1, c2, c3, z;\n.reg .b32 a;\nmov.b32 a, 0;\nmov.f32 z, 0f00000000;\n"
               "mma.sync.aligned.m16n8k8.row.col.f32.bf16.bf16.f32 {%0, c1, c2, c3}, {a, a}, {a}, {z, z, z, z};\n}\n" : "=f"(c0));
  return __float_as_uint(c0);
}
__device__ __forceinline__ void pin(uint32_t& v) { asm volatile("shfl.sync.bfly.b32 %0, %0, 0, 0x1f, 0xffffffff;" : "+r"(v)); }
template<class T> __device__ __forceinline__ void pin(T*& v) {
  uint32_t lo = (uint32_t)(uint64_t)v, hi = (uint32_t)((uint64_t)v >> 32);
  pin(lo); pin(hi);
  v = (T*)(((uint64_t)hi << 32) | lo);
}
__device__ __forceinline__ float sel4(int q, float a, float b, float c, float d) {
  float r;
  asm("{\n.reg .pred p, o;\n.reg .f32 x, y;\n.reg .b32 t;\nand.b32 t, %1, 1;\nsetp.ne.b32 p, t, 0;\nsetp.gt.s32 o, %1, 1;\n"
      "selp.f32 x, %3, %2, p;\nselp.f32 y, %5, %4, p;\nselp.f32 %0, y, x, o;\n}\n" : "=f"(r) : "r"(q), "f"(a), "f"(b), "f"(c), "f"(d));
  return r;
}
__device__ __forceinline__ uint32_t bfma2(uint32_t a, uint32_t b, uint32_t c) { uint32_t r; asm("fma.rn.bf16x2 %0, %1, %2, %3;" : "=r"(r) : "r"(a), "r"(b), "r"(c)); return r; }
__device__ __forceinline__ void tma_load_5d(uint32_t dst, const CUtensorMap* tm, uint32_t bar, int c0, int c4) {
  asm volatile("cp.async.bulk.tensor.5d.shared::cluster.global.mbarrier::complete_tx::bytes [%0], [%1, {%3, %4, %4, %4, %5}], [%2];"
    :: "r"(dst), "l"(tm), "r"(bar), "r"(c0), "r"(0), "r"(c4) : "memory");
}
__device__ __forceinline__ void tma_load_4d(uint32_t dst, const CUtensorMap* tm, uint32_t bar, int c0, int c3) {
  asm volatile("cp.async.bulk.tensor.4d.shared::cluster.global.mbarrier::complete_tx::bytes [%0], [%1, {%3, %4, %4, %5}], [%2];"
    :: "r"(dst), "l"(tm), "r"(bar), "r"(c0), "r"(0), "r"(c3) : "memory");
}
__device__ __forceinline__ void tma_load_4d_hint(uint32_t dst, const CUtensorMap* tm, uint32_t bar, int c0, int c3, uint64_t pol) {
  asm volatile("cp.async.bulk.tensor.4d.shared::cluster.global.mbarrier::complete_tx::bytes.L2::cache_hint [%0], [%1, {%3, %4, %4, %5}], [%2], %6;"
    :: "r"(dst), "l"(tm), "r"(bar), "r"(c0), "r"(0), "r"(c3), "l"(pol) : "memory");
}
__device__ __forceinline__ void tma_prefetch_4d(const CUtensorMap* tm, int c0, int c3) {
  asm volatile("cp.async.bulk.prefetch.tensor.4d.L2.global.tile [%0, {%1, %2, %2, %3}];" :: "l"(tm), "r"(c0), "r"(0), "r"(c3) : "memory");
}
__device__ __forceinline__ void tma_store_5d(const CUtensorMap* tm, uint32_t src, int c0, int c4) {
  asm volatile("cp.async.bulk.tensor.5d.global.shared::cta.bulk_group [%0, {%2, %3, %3, %3, %4}], [%1];" :: "l"(tm), "r"(src), "r"(c0), "r"(0), "r"(c4) : "memory");
}
__device__ __forceinline__ float rcp_fast(float x) { float r; asm("rcp.approx.ftz.f32 %0, %1;" : "=f"(r) : "f"(x)); return r; }
__device__ __forceinline__ float sigmoid_fast(float x) { float e; asm("ex2.approx.ftz.f32 %0, %1;" : "=f"(e) : "f"(x * -1.4426950408889634f)); return rcp_fast(1.f + e); }
__device__ __forceinline__ float sqrt_fast(float x) { float r; asm("sqrt.approx.ftz.f32 %0, %1;" : "=f"(r) : "f"(x)); return r; }
__device__ __forceinline__ float ln_sd(float var) { return bf16r(sqrt_fast(bf16r(bf16r(fmaxf(var, 0.f)) + 1e-5f))); }
__device__ __forceinline__ uint32_t norm2(uint32_t h, uint32_t neg_mean2, float inv_sd) {
  const uint32_t d = badd2(h, neg_mean2);
  return pack_bf16(bf_lo(d) * inv_sd, bf_hi(d) * inv_sd);
}
template<int N> __device__ __forceinline__ void delay_clk() {
  if constexpr (N > 0) { const uint32_t t0 = clock(); while ((uint32_t)clock() - t0 < N) {} }
}
__device__ __forceinline__ void put_xstat(uint32_t rs, uint32_t exb, int col, uint32_t mean_rstd, int m) {
  smem_at<uint16_t>(rs + ((col & 7) >> 1) * 144 + (col >> 3) * 4 + (col & 1) * 2) = (uint16_t)(mean_rstd ^ (m << 15));
  const uint32_t nm = (mean_rstd >> 16) ^ 0x8000u;
  smem_at<uint4>(exb + (col >> 3) * 256 + (col & 7) * 16) = make_uint4(nm | (nm << 16), nm, 0, 0);
  smem_at<uint4>(exb + (col >> 3) * 256 + 128 + (col & 7) * 16) = make_uint4(0, 0, 0, 0);
}
__device__ __forceinline__ void put_dsum(uint32_t exa, int e, float c) {
  const float hi = bf16r(c), mid = bf16r(c - hi), lo = bf16r((c - hi) - mid);
  smem_at<uint4>(exa + (e >> 3) * 256 + (e & 7) * 16) = make_uint4((__float_as_uint(hi) >> 16) | (__float_as_uint(mid) & 0xFFFF0000u), __float_as_uint(lo) >> 16, 0, 0);
  smem_at<uint4>(exa + (e >> 3) * 256 + 128 + (e & 7) * 16) = make_uint4(0, 0, 0, 0);
}
__host__ __device__ constexpr int min_c(int a, int b) { return a < b ? a : b; }
template<int V> using IC = std::integral_constant<int, V>;

#define CT(slot) do {} while (0)
#define PT(slot) do {} while (0)

template<int MAP>
__global__ void __cluster_dims__(2, 1, 1) __launch_bounds__(384, 1)
fnet_moe_kernel(const __grid_constant__ Params p) {
  constexpr int NX = MAP == 0 ? NX0 : 256;
  constexpr int G1_BYTES = A_BYTES + NX * 128;
  uint32_t sb;
  asm volatile("mov.u32 %0, %1;" : "=r"(sb) : "r"(smem_u32(smem_raw)));
  const int m = blockIdx.x & 1;
  int tau, eps;
  bool helper = false;
  if (MAP == 0) {
    uint32_t smid;
    asm volatile("mov.u32 %0, %%smid;" : "=r"(smid));
    const int c = smid >> 1, e7 = ((c - 32) * 37) >> 8;
    helper = c == 60 || c == 61;
    tau = c < 32 ? (c & 7) : (c < 60 ? c - 31 - 7 * e7 : 0);
    eps = c < 32 ? (c >> 3) : (c < 60 ? 4 + e7 : c - 58);
  } else {
    tau = (blockIdx.x >> 1) & 7; eps = blockIdx.x >> 4;
  }
  const int cid = tau * 16 + eps * 2 + m;
  const bool moe = tau > 0;
  auto BAR = [&](int i) { return sb + OFF_BAR + 8 * i; };
  const CUtensorMap* tmD = m ? &p.tmD1 : &p.tmD0;
  const uint64_t pol_ef = policy_evict_first();
#define LOAD_STREAM(d, tm, bar, c0, c1) tma_load_2d_hint(d, tm, bar, c0, c1, pol_ef)
#define LOAD_W(d, tm, bar, c0, grp) tma_load_4d_hint(d, tm, bar, c0, (grp) * 32, pol_ef)
  auto helper_load = [&](int k) {
    const uint32_t sa = sb + slot_of(k) * ST_BYTES, bar = BAR(B_FULL + slot_of(k));
    const CUtensorMap* tm = eps == 3 ? &p.tmD1 : &p.tmD0;
    tma_load_5d(sa, &p.tmXh, bar, (k & 15) * 64, 0);
    tma_load_2d(sa + A_BYTES, tm, bar, (k & 15) * 64, m * 512 + (k >> 4) * 256);
    tma_load_2d(sa + A_BYTES + 16384, tm, bar, (k & 15) * 64, m * 512 + (k >> 4) * 256 + 128);
  };
  if (threadIdx.x < 32 && elect_one()) {
    mbar_init(BAR(B_FULL), 1);
    asm volatile("fence.mbarrier_init.release.cluster;" ::: "memory");
    if (!helper) {
      tma_load_2d(sb + A_BYTES, &p.tmX, BAR(B_FULL), 0, tau * 256);
      tma_load_2d(sb, tmD, BAR(B_FULL), 0, eps * 128);
    }
    PT(52);
#pragma unroll
    for (int k = 1; k < 4; k++) mbar_init(BAR(B_FULL + k), 1);
    asm volatile("fence.mbarrier_init.release.cluster;" ::: "memory");
#pragma unroll
    for (int k = 0; k < 4; k++) mbar_expect_tx(BAR(B_FULL + k), helper ? ST_BYTES : G1_BYTES);
    if (!helper) {
#pragma unroll
      for (int k = 1; k < 4; k++) {
        tma_load_2d(sb + k * ST_BYTES + A_BYTES, &p.tmX, BAR(B_FULL + k), k * 64, tau * 256);
        LOAD_STREAM(sb + k * ST_BYTES, tmD, BAR(B_FULL + k), k * 64, eps * 128);
      }
    } else {
#pragma unroll 1
      for (int k = 0; k < 4; k++) helper_load(k);
    }
    PT(0);
  }
  __syncwarp();
  const int warp = __shfl_sync(0xffffffffu, threadIdx.x >> 5, 0);
  if (warp == 8) {
    if (elect_one()) {
#pragma unroll
      for (int b = B_EMPTY; b < B_COUNT; b++)
        mbar_init(BAR(b), b < B_EPI ? 2 : (b == B_EPI || b == B_EPI0B) ? 4 : (b < B_STD || b == B_OUT) ? 8 : (b == B_STAT || b == B_XS) ? 3 : 1);
      asm volatile("fence.mbarrier_init.release.cluster;" ::: "memory");
      mbar_expect_tx(BAR(B_XCH), 32768);
      SM_(uint32_t, OFF_SEEN) = 0;
    }
  }
  __syncthreads();

  if (warp >= 8) {
    reg_dec<REG_P>();
    asm volatile("barrier.cluster.arrive.relaxed.aligned;" ::: "memory");
    const int abrow = m * 1024 + eps * 128;
    const int f0 = (cid - 16) * 32;
    const CUtensorMap* tmWM = m ? &p.tmWM1 : &p.tmWM0;
    auto side_first = [&](int k) {
      if (NX < 256 && k == MINI_LOAD_K) {
        static_assert(NX == 256 || (mr_k(NREG_H) == MINI_LOAD_K && (NREG_H & 1) == 1), "second half of the staging buffer must be free");
        mbar_wait(BAR(B_STD + 3), 0);
        uint32_t n = 0;
        while (!((*(volatile uint32_t*)&SM_(uint32_t, OFF_SEEN) >> (4 * tau + 1)) & 1) && ++n < SPIN_LIMIT * 16) {}
        if (elect_one()) {
          mbar_expect_tx(BAR(B_A20), 12288);
          tma_load_2d(sb + OFF_MINI, &p.tmAbM, BAR(B_A20), tau * 256 + 240, abrow);
          LOAD_W(sb + OFF_MINI + 4096, tmWM, BAR(B_A20), tau * 256 + 240, tau * 2 + m);
          LOAD_W(sb + OFF_MINI + 8192, tmWM, BAR(B_A20), tau * 256 + 240, tau * 2 + 1 - m);
        }
      }
    };
    auto side = [&](int k) {
      if (NX < 256 && k == MINI_PF_K && elect_one()) tma_prefetch_4d(tmWM, tau * 256 + 240, tau * 64 + (eps & 1) * 32);
      if (k == WPF2_K && eps < WPF2_N && elect_one()) tma_prefetch_4d(m ? &p.tmW1 : &p.tmW0, kblock(tau, 31 - (eps >> 1)) * 64, tau * 64 + (eps & 1) * 32);
      if (!moe) return;
      const int i = k - MR_K0, r6 = i / MR_P, u = i - MR_P * r6, h = 2 * r6 + (u >> 1);
      if (i >= 0 && u < 4 && h < NREG_H) {
        if (h < 2) mbar_wait(BAR(B_STD + 2 + h), 0);
        if (elect_one()) {
          if (!(u & 1)) mbar_expect_tx(BAR(B_MR + (h & 1)), 16384);
          LOAD_STREAM(sb + OFF_XCH + u * 8192, (u & 1) ? &p.tmU : &p.tmG, BAR(B_MR + (h & 1)), f0, h * 128);
        }
      }
      if (k >= GU_K && k < GU_K + 2 && elect_one()) {
        static_assert(mr_k(NREG_H + 1) <= GU_K + 1 && MINI_K + 4 <= GU_K && GU_K < 47, "staging buffer must be free");
        LOAD_STREAM(sb + round_off(NREG_H + k - GU_K), &p.tmG, BAR(B_GU), f0, (NREG_H + k - GU_K) * 128);
        LOAD_STREAM(sb + round_off(NREG_H + k - GU_K) + 8192, &p.tmU, BAR(B_GU), f0, (NREG_H + k - GU_K) * 128);
      }
      if (k >= PF_K1 && !(k & 1) && elect_one()) {
        const int j = PF_N0 + ((k - PF_K1) >> 1);
        if (j < 8) tma_prefetch_2d(m ? &p.tmU : &p.tmG, f0, j * 128);
        else if (j < 12) asm volatile("cp.async.bulk.prefetch.L2.global [%0], %1;" :: "l"(p.wdown + (size_t)f0 * 1024 + (j - 8) * 8192), "r"(16384) : "memory");
      }
    };
    if (MAP == 0 && helper) {
      if (warp == 8) {
#pragma unroll 1
        for (int k = 4; k < 32; k++) {
          mbar_wait(BAR(B_EMPTY + slot_of(k)), (use_of(k) & 1) ^ 1);
          if (elect_one()) {
            mbar_expect_tx(BAR(B_FULL + slot_of(k)), ST_BYTES);
            helper_load(k);
            if (k == 12) mbar_arrive(BAR(B_LATE));
          }
        }
      } else {
        const int i0 = threadIdx.x - 288, lane = threadIdx.x & 31, col0 = (eps - 2) * 8 + m * 4;
        mbar_wait(BAR(B_LATE), 0);
        const uint32_t tag = ld_relaxed32(&p.s->epoch) + 1;
        if (i0 < 8) pkt_st128(&p.s->hflag[col0 * 2 + i0], 0, 0, 0, 0);
        SM_(uint32_t, OFF_TAG) = tag;
#pragma unroll 1
        for (int j0 = i0; j0 < 768; j0 += 384) {
          uint2 v[4]; uint32_t n = 0;
          while (true) {
#pragma unroll
            for (int z = 0; z < 4; z++) {
              const int j = j0 + 96 * z;
              v[z] = pkt_ld64(p.s->xstat + (j < 128 ? 256 * (j >> 4) + 240 + 2 * (j & 6) + ((j >> 2) & 2) + (j & 1)
                                          : j < 640 ? 2048 + col0 * 128 + j - 128 : (j - 640) * 16));
            }
            if (__all_sync(0xffffffffu, v[0].y == tag && v[1].y == tag && v[2].y == tag && v[3].y == tag) || ++n > SPIN_LIMIT) break;
            __nanosleep(300);
          }
#pragma unroll
          for (int z = 0; z < 4; z++) {
            const int j = j0 + 96 * z;
            if (j < 128) put_xstat(sb + OFF_RS, sb + OFF_XCH + 16384, j, v[z].x, eps - 2);
            else if (j < 640) put_dsum(sb + OFF_XCH, j - 128, __uint_as_float(v[z].x));
          }
        }
        fence_async_smem();
        __syncwarp();
        if (lane == 0) mbar_arrive(BAR(B_STAT));
      }
    } else if (warp == 8) {
      const CUtensorMap* tmW = m ? &p.tmW1 : &p.tmW0;
      const int gA = tau * 2 + m, gB = tau * 2 + 1 - m;
      auto wait_slot = [&](int k) {
        mbar_wait(BAR(B_EMPTY + slot_of(k)), (use_of(k) & 1) ^ 1);
        PT(64 + k);
      };
#pragma unroll 1
      for (int k = 4; k < 24; k++) {
        const int s = slot_of(k);
        const uint32_t sa = sb + s * ST_BYTES, sbb = sa + A_BYTES;
        const int kb = kblock(tau, k - 16);
        wait_slot(k);
        if (elect_one()) {
          mbar_expect_tx(BAR(B_FULL + s), k < 16 ? G1_BYTES : (k >> 1) == 9 ? B_BYTES : k == 20 ? ST_BYTES - 8192 : ST_BYTES);
          if (k < 16) {
            LOAD_STREAM(sa, tmD, BAR(B_FULL + s), k * 64, eps * 128);
            tma_load_2d(sbb, &p.tmX, BAR(B_FULL + s), k * 64, tau * 256);
          } else {
            LOAD_W(sbb, tmW, BAR(B_FULL + s), kb * 64, gA);
            LOAD_W(sbb + 16384, tmW, BAR(B_FULL + s), kb * 64, gB);
            if (k < 18) {
              tma_load_4d(sa, &p.tmXr, BAR(B_FULL + s), eps * 128, gA * 32 + s * 16);
              tma_load_4d(sa + 8192, &p.tmXr, BAR(B_FULL + s), eps * 128 + 64, gA * 32 + s * 16);
            }
          }
          if (k == PUB_K1) mbar_arrive(BAR(B_LATE));
          if (k >= WPF_K0 && k < WPF_K0 + WPF_N && (eps >> 1) == ((k - WPF_K0) & 3))
            tma_prefetch_4d(tmW, kblock(tau, k - WPF_K0) * 64, tau * 64 + (eps & 1) * 32);
          if (moe && k >= PF_K0 && k < PF_K0 + 2 * PF_N0 && !(k & 1)) tma_prefetch_2d(m ? &p.tmU : &p.tmG, f0, (k - PF_K0) * 64);
        }
      }
      uint32_t seen = 0;
#pragma unroll 1
      for (int k = 24; k < 48; k++) {
        const int s = slot_of(k);
        const uint32_t sa = sb + s * ST_BYTES, sbb = sa + A_BYTES;
        const int kb = kblock(tau, k - 16);
        const uint32_t need = (1u << kb) | ((kb & 3) == 3 ? 2u << (4 * tau) : 0u);
        wait_slot(k);
        side_first(k);
        if (elect_one()) {
          mbar_expect_tx(BAR(B_FULL + s), ST_BYTES);
          LOAD_W(sbb, tmW, BAR(B_FULL + s), kb * 64, gA);
          LOAD_W(sbb + 16384, tmW, BAR(B_FULL + s), kb * 64, gB);
        }
        uint32_t n = 0;
        while ((seen & need) != need && ++n < SPIN_LIMIT * 16) seen = *(volatile uint32_t*)&SM_(uint32_t, OFF_SEEN);
        if (elect_one()) tma_load_2d(sa, &p.tmAbL, BAR(B_FULL + s), kb * 64, abrow);
        side(k);
      }
      if (moe) {
        mbar_wait(BAR(B_EMPTY + 0), 1);
        if (elect_one()) { mbar_expect_tx(BAR(B_GU), (8 - NREG_H) * 16384); mbar_expect_tx(BAR(B_DN), 65536); }
#pragma unroll 1
        for (int i = 0; i < 10 - NREG_H; i++) {
          if (i == 3) mbar_wait(BAR(B_EMPTY + 1), 1);
          if (i == 4) {
            mbar_wait(BAR(B_EMPTY + 2), 1);
            mbar_wait(BAR(B_XCH), 0);
            PT(53);
          }
          const uint32_t dst = sb + late_off(i);
          if (elect_one()) {
            if (i < 6 - NREG_H) {
              LOAD_STREAM(dst, &p.tmG, BAR(B_GU), f0, (NREG_H + 2 + i) * 128);
              LOAD_STREAM(dst + 8192, &p.tmU, BAR(B_GU), f0, (NREG_H + 2 + i) * 128);
            } else {
#pragma unroll
              for (int b = 0; b < 4; b++) LOAD_STREAM(dst + b * 4096, &p.tmDn, BAR(B_DN), (4 * (i - 6 + NREG_H) + b) * 64, f0);
            }
          }
          const long long t0 = clock64();
          while (i < 9 - NREG_H && clock64() - t0 < MOE_PACE_CLK) {}
        }
      }
      const int lane = threadIdx.x & 31;
      mbar_wait(BAR(B_OUT), 0);
      const uint32_t km = SM_(uint32_t, OFF_WKEY + (lane & 7) * 8);
      const uint32_t bk = __reduce_max_sync(0xffffffffu, km);
      const int ww = __ffs(__ballot_sync(0xffffffffu, km == bk)) - 1;
#pragma unroll 1
      for (int i = 1; i <= 8; i++) {
        const int W = (ww + i) & 7;
        if (i == 8) {
          mbar_wait(BAR(B_XS), 0);
          if (SM_(uint32_t, OFF_KV) == bk) {
#pragma unroll 2
            for (int j = lane; j < 256; j += 32) {
              const int rho = j >> 4, row = row_of(gA * 128 + 32 * (W >> 1) + 8 * ((rho & 7) >> 1) + 4 * (W & 1) + 2 * (rho >> 3) + (rho & 1));
              const uint4 v = lds128_v(sb + OFF_OUT + (j & 8) * 2048 + (16 * W + rho) * 128 + (((j ^ rho) & 7) << 4));
              if (row != 0xFFFF - (int)(bk & 0xFFFFu))
                asm volatile("st.global.v4.b32 [%0], {%1, %2, %3, %4};" :: "l"(p.out + (size_t)row * 1024 + eps * 128 + (j & 15) * 8), "r"(v.x), "r"(v.y), "r"(v.z), "r"(v.w));
            }
            break;
          }
        }
        if (lane == 0) {
          tma_store_5d(&p.tmOut, sb + OFF_OUT + W * 2048, eps * 128, row_of(gA * 128 + 32 * (W >> 1) + 4 * (W & 1)));
          tma_store_5d(&p.tmOut, sb + OFF_OUT + 16384 + W * 2048, eps * 128 + 64, row_of(gA * 128 + 32 * (W >> 1) + 4 * (W & 1)));
        }
        const long long t0 = clock64();
        while (i < 7 && clock64() - t0 < OUT_PACE_CLK) {}
      }
      if (lane == 0) { bulk_commit(); bulk_wait_all(); }
      PT(22);
    } else {
      const int a = warp - 9;
      const int lane = threadIdx.x & 31;
      auto stage = [&](const bf16* src, int g) {
        if (elect_one()) {
          mbar_expect_tx(BAR(B_AUX + g), 16384);
          bulk_load(sb + OFF_XCH + g * 16384, src + g * 8192, 16384, BAR(B_AUX + g));
        }
      };
      uint32_t tag = 0;
#pragma unroll 1
      for (int i = 0; i < 3; i++) { i += keep_awake(); delay_clk<300>(); }
      mbar_wait(BAR(B_FULL + AUX_AFTER), 0);
      if (a == 0) PT(1);
      if (a == 1) mbar_wait(BAR(B_AUX + 0), 0);
      if (a < 2) stage(p.x + (size_t)cid * 16 * 1024, a);
#pragma unroll 1
      for (int it = 0; it < 4; it++) {
        const int g = it & 1;
        mbar_wait(BAR(B_AUX + g), it >> 1);
        if (a == 0) PT(2 + it);
        if (it == 2) tag = ld_relaxed32(&p.s->epoch) + 1;
        if (it == 2 && a == 2 && lane < 16) asm volatile("prefetch.global.L2 [%0];" :: "l"(p.wr + lane * 64));
        const uint32_t ad = sb + OFF_XCH + g * 16384 + (lane >> 2) * 2048;
        float s0 = 0.f, s1 = 0.f, q0 = 0.f, q1 = 0.f;
        auto row = [&](auto sq) {
#pragma unroll
          for (int i = 0; i < 11; i++) {
            if (i == 10 && a == 2) break;
            const uint4 v = lds128_v(ad + (((a * 44 + 4 * i + lane) & 127) << 4));
            const uint32_t ww[4] = {v.x, v.y, v.z, v.w};
#pragma unroll
            for (int z = 0; z < 4; z++) {
              const float d0 = bf_lo(ww[z]), d1 = bf_hi(ww[z]);
              s0 += d0; s1 += d1;
              if (decltype(sq)::value) { q0 = fmaf(d0, d0, q0); q1 = fmaf(d1, d1, q1); }
            }
          }
        };
        if (it < 2) row(IC<1>()); else row(IC<0>());
        s0 += s1; q0 += q1;
#pragma unroll
        for (int o = 1; o < 4; o <<= 1) { s0 += __shfl_xor_sync(0xffffffffu, s0, o); q0 += __shfl_xor_sync(0xffffffffu, q0, o); }
        if ((lane & 3) == 0) SM_(float2, OFF_PUB + a * 256 + it * 64 + (lane >> 2) * 8) = make_float2(s0, q0);
        if (it != 2) bar_sync(NB_AUX, 96);
        if (it < 2 && a == 2) stage(cid < 64 ? p.Dre + (size_t)cid * 16 * 1024 : p.Dim + (size_t)(cid - 64) * 16 * 1024, g);
      }
      if (a == 1) {
        const float2 v0 = SM_(float2, OFF_PUB + lane * 8), v1 = SM_(float2, OFF_PUB + 256 + lane * 8), v2 = SM_(float2, OFF_PUB + 512 + lane * 8);
        const float s = v0.x + v1.x + v2.x, mean = s * (1.f / 1024.f);
        const float rs = rcp_fast(ln_sd((v0.y + v1.y + v2.y) * (1.f / 1024.f) - mean * mean));
        pkt_st64((lane < 16 ? p.s->xstat : p.s->dsum) + cid * 16 + (lane & 15), lane < 16 ? pack_bf16(rs, mean) : __float_as_uint(s), tag);
        PT(6);
      }
      if (a == 2) {
        float s = 0.f;
#pragma unroll
        for (int q = 0; q < 4; q++) {
          const uint4 v = ldg_nc128(p.wr + (q * 32 + lane) * 8);
          s += ((bf_lo(v.x) + bf_hi(v.x)) + (bf_lo(v.y) + bf_hi(v.y))) + ((bf_lo(v.z) + bf_hi(v.z)) + (bf_lo(v.w) + bf_hi(v.w)));
          const int ch = q * 32 + lane - eps * 16;
          if (ch >= 0 && ch < 16) {
            SM_(uint32_t, OFF_WR + ch * 4) = v.x; SM_(uint32_t, OFF_WR + 80 + ch * 4) = v.y;
            SM_(uint32_t, OFF_WR + 160 + ch * 4) = v.z; SM_(uint32_t, OFF_WR + 240 + ch * 4) = v.w;
          }
        }
        s = warp_sum(s);
        if (lane == 0) { SM_(float, OFF_WSUM) = s; SM_(uint32_t, OFF_TAG) = tag; }
      }
      if (a < 2) __nanosleep(GATHER_NS);
      {
        const int i0 = a * 32 + lane;
        uint2 v[3], c0, c1; uint32_t n = 0;
        const uint2* dp = &p.s->dsum[abrow];
        while (true) {
#pragma unroll
          for (int q = 0; q < 3; q++) v[q] = pkt_ld64(&p.s->xstat[tau * 256 + min(i0 + 96 * q, 255)]);
          c0 = pkt_ld64(dp + i0); c1 = pkt_ld64(dp + min(i0 + 96, 127));
          if (__all_sync(0xffffffffu, v[0].y == tag && v[1].y == tag && v[2].y == tag && c0.y == tag && c1.y == tag) || ++n > SPIN_LIMIT) break;
          __nanosleep(200);
        }
#pragma unroll
        for (int q = 0; q < 3; q++) put_xstat(sb + OFF_RS, sb + OFF_EXB, min(i0 + 96 * q, 255), v[q].x, m);
        put_dsum(sb + OFF_EXA, i0, __uint_as_float(c0.x));
        put_dsum(sb + OFF_EXA, min(i0 + 96, 127), __uint_as_float(c1.x));
        fence_async_smem();
      }
      __syncwarp();
      if (lane == 0) mbar_arrive(BAR(B_STAT));
      if (a == 0) PT(7);
      if (a == 0) {
        const int sg = (lane >> 2) == tau ? sigma_of(tau, 0) : lane >> 2;
        const uint32_t* flg = reinterpret_cast<const uint32_t*>(&p.s->abflag[((eps * 2 + m) * 8 + sg) * 2]) + ((lane >> 2) == tau ? 4 : lane & 3);
        if (NX < 256 && lane == 4 * tau + 1) flg = reinterpret_cast<const uint32_t*>(&p.s->hflag[(m * 8 + eps) * 2]);
        uint32_t seen = 0;
        auto until = [&](int tile) {
          uint32_t n = 0;
          while (!((seen >> (4 * tile)) & 1) && ++n < SPIN_LIMIT) seen = __ballot_sync(0xffffffffu, ld_relaxed32(flg) == tag);
        };
        const int s0 = sigma_of(tau, 0), s1 = sigma_of(tau, 1), s2 = sigma_of(tau, 2), s3 = sigma_of(tau, 3);
        mbar_wait(BAR(B_EPI), 0);
        mbar_wait(BAR(B_FULL + 0), 0);
        mbar_wait(BAR(B_FULL + 1), 0);
        if (elect_one()) mbar_expect_tx(BAR(B_A20), 8192);
        mbar_wait(BAR(B_STDA), 0);
        PT(49);
        until(tau);
        mbar_wait(BAR(B_EPI0B), 0);
        PT(48);
        if (elect_one()) tma_load_2d(sb + OFF_XCH, &p.tmAbS, BAR(B_FULL + 0), s0 * 256, abrow);
        mbar_wait(BAR(B_FULL + 2), 0);
        mbar_wait(BAR(B_STD + 0), 0);
        until(s0);
        PT(16);
        if (elect_one()) tma_load_2d(sb + OFF_XCH + 8192, &p.tmAbS, BAR(B_A20), s0 * 256, abrow + 64);
        until(s1);
        PT(17);
        if (elect_one()) tma_load_2d(sb + OFF_XCH + 16384, &p.tmAbL, BAR(B_FULL + 1), s1 * 256, abrow);
        until(s2);
        PT(18);
        if (elect_one()) {
          tma_load_2d(sb + 2 * ST_BYTES, &p.tmAbL, BAR(B_FULL + 2), s2 * 256, abrow);
          mbar_arrive(BAR(B_PUB1));
        }
        until(s3);
        mbar_wait(BAR(B_FULL + 3), 0);
        mbar_wait(BAR(B_STD + 1), 0);
        PT(19);
        if (elect_one()) tma_load_2d(sb + 3 * ST_BYTES, &p.tmAbL, BAR(B_FULL + 3), s3 * 256, abrow);
        uint32_t n = 0;
        while (true) {
          asm volatile("fence.proxy.async.global;" ::: "memory");
          *(volatile uint32_t*)&SM_(uint32_t, OFF_SEEN) = seen;
          if (seen == 0xFFFFFFFFu || ++n > SPIN_LIMIT) break;
          seen = __ballot_sync(0xffffffffu, ld_relaxed32(flg) == tag);
          __nanosleep(100);
        }
      } else {
        uint32_t* flag = reinterpret_cast<uint32_t*>(&p.s->abflag[((eps * 2 + m) * 8 + tau) * 2]);
        mbar_wait(BAR(a == 1 ? B_EPI : B_EPI0B), 0);
        if (a == 1) PT(8);
        if (lane == 0) {
          tma_store_2d(&p.tmAbS, sb + chunk_off(0, a - 1), tau * 256, abrow + (a - 1) * 64);
          bulk_commit();
          bulk_wait_all();
        }
        if (a == 2) mbar_wait(BAR(B_STDA), 0);
        if (lane == 0) {
          st_relaxed32(flag + (a == 1 ? 4 : 0), tag);
          mbar_arrive(BAR(a == 1 ? B_STDA : B_STD));
        }
        if (a == 2) PT(12);
        if (a == 1) {
          mbar_wait(BAR(B_EPI + 1), 0);
          mbar_wait(BAR(B_LATE), 0);
          mbar_wait(BAR(B_PUB1), 0);
          PT(9);
          if (lane == 0) {
            tma_store_2d(&p.tmAbS, sb + chunk_off(1, 0), tau * 256 + 64, abrow);
            tma_store_2d(&p.tmAbS, sb + chunk_off(1, 1), tau * 256 + 64, abrow + 64);
            bulk_commit();
            bulk_wait_all();
            st_relaxed32(flag + 1, tag);
            mbar_arrive(BAR(B_STD + 1));
          }
          PT(13);
        }
        auto copy_out = [&](int c) {
          mbar_wait(BAR(B_EPI + c), 0);
          PT(8 + c);
          bf16* dst = p.s->abT + (size_t)(abrow + (lane >> 3)) * 2048 + tau * 256 + c * 64 + (lane & 7) * 8;
          const uint32_t src = sb + chunk_off(c, 0) + (lane >> 3) * 128 + (((lane & 7) ^ (lane >> 3)) << 4);
          const uint32_t on = c * 64 + (lane & 7) * 8 < NX;
#pragma unroll 4
          for (int i = 0; i < 32; i++) {
            const uint4 v = lds128_v((src ^ ((i & 1) << 6)) + i * 512);
            asm volatile("{\n.reg .pred p;\nsetp.ne.b32 p, %5, 0;\n@p st.global.v4.b32 [%0], {%1, %2, %3, %4};\n}\n"
                         :: "l"(dst + i * 4 * 2048), "r"(v.x), "r"(v.y), "r"(v.z), "r"(v.w), "r"(on));
          }
          __syncwarp();
          if (lane == 0) mbar_arrive(BAR(B_STD + c));
        };
        if (a == 2) {
#pragma unroll 1
          for (int c = 2; c < 4; c++) copy_out(c);
          asm volatile("fence.acq_rel.gpu;" ::: "memory");
          __syncwarp();
          if (lane < 2) st_relaxed32(flag + 2 + lane, tag);
          PT(15);
        }
      }
      {
        mbar_wait(BAR(B_LATE), 1);
        const int grp = tau * 2 + m;
#pragma unroll 1
        for (int i = a; i < 14; i += 3) {
          uint4* dst = i < 8 ? &p.s->ypart[cid * 256 + i * 32 + lane] : i < 12 ? &p.s->hstat[(grp * 8 + eps) * 128 + (i - 8) * 32 + lane]
                     : i == 12 ? &p.s->cand[grp * 256 + eps * 32 + lane] : &p.s->key[(((lane >> 1) & 7) * 16 + grp) * 2 + (lane & 1)];
          if (i < 13 || eps == 0) pkt_st128(dst, 0, 0, 0, 0);
          __nanosleep(200);
        }
        __syncwarp();
        if (lane == 0) mbar_arrive(BAR(B_STAT));
      }
      {
        const uint4* kp = &p.s->key[(tau * 16 + (lane & 15)) * 2];
        const int i0 = a * 32 + lane;
        mbar_wait(BAR(B_KEY), 0);
        if (a == 0) PT(43);
        uint4 kq = pkt_ld128(kp), cv[3] = {};
        uint32_t n = 0, kv;
        int gspec = -1;
        while (true) {
          const bool ok = kq.y == tag && kq.w == tag;
          kv = __reduce_max_sync(0xffffffffu, ok ? kq.x : 0u);
          const int gs = group_of(0xFFFF - (int)(kv & 0xFFFFu));
          const bool cok = gs == gspec && cv[0].y == tag && cv[0].w == tag && cv[1].y == tag && cv[1].w == tag && cv[2].y == tag && cv[2].w == tag;
          if (__all_sync(0xffffffffu, ok && cok) || ++n > SPIN_LIMIT) break;
          if (!ok) kq = pkt_ld128(kp);
          n += keep_awake();
          const bool spec = __popc(__ballot_sync(0xffffffffu, ok)) >= 2 * SPEC_MIN;
          if (!cok && spec) {
#pragma unroll
            for (int i = 0; i < 3; i++) cv[i] = pkt_ld128(&p.s->cand[gs * 256 + min(i0 + 96 * i, 255)]);
          }
          if (spec) gspec = gs;
        }
        if (a == 0) PT(45);
        const uint32_t ms = __shfl_sync(0xffffffffu, kq.z, gspec);
        const uint32_t nm = ((ms & 0xFFFFu) ^ 0x8000u) * 0x10001u;
        const float is = rcp_fast(bf_hi(ms));
#pragma unroll
        for (int i = 0; i < 3; i++) {
          const int j = min(i0 + 96 * i, 255);
          SM_(uint2, OFF_XSEL + j * 8) = make_uint2(norm2(cv[i].x, nm, is), norm2(cv[i].z, nm, is));
        }
#pragma unroll
        for (int i = 0; i < 3; i++) SM_(uint2, OFF_HSEL + min(i0 + 96 * i, 255) * 8) = make_uint2(cv[i].x, cv[i].z);
        SM_(uint32_t, OFF_KV) = kv;
        __syncwarp();
        if (lane == 0) mbar_arrive(BAR(B_XS));
      }
    }
    asm volatile("barrier.cluster.wait.aligned;" ::: "memory");
  } else {
    reg_inc<REG_C>();
    const int tid = __shfl_sync(0xffffffffu, threadIdx.x, threadIdx.x & 31), lane = tid & 31;
    const int w = warp >> 2, wi = warp & 3, t = tid & 127;
    const int g = lane >> 2, q = lane & 3;
    const int turn_me = NB_TURN0 + w, turn_other = NB_TURN1 - w;
    auto release = [&](int s) { if (t == 0) mbar_arrive(BAR(B_EMPTY + s)); };
    if (MAP == 0 && helper) {
      asm volatile("barrier.cluster.arrive.relaxed.aligned;" ::: "memory");
      float s0[64], s1[64];
#pragma unroll
      for (int i = 0; i < 64; i++) { s0[i] = 0.f; s1[i] = 0.f; }
      if (w == 1) bar_arrive(NB_TURN0, 256);
      uint32_t o[32][2] = {};
      const int col = (eps - 2) * 8 + m * 4 + w;
      auto put = [&](auto tc, uint32_t buf) {
        constexpr int tl = decltype(tc)::value;
#pragma unroll
        for (int i = 0; i < 4; i++)
          smem_at<uint2>(buf + ((i >> 1) * 64 + wi * 16 + (i & 1) * 8 + g) * 32 + ((q * 8) ^ ((g & 4) << 2))) = make_uint2(o[8 * i + tl][0], o[8 * i + tl][1]);
      };
      auto publish = [&](int c) { if (t == 0) { bulk_wait_all(); st_relaxed32(&p.s->hflag[c * 2], SM_(uint32_t, OFF_TAG)); } };
#pragma unroll 1
      for (int pass = 0; pass < 2; pass++) {
#pragma unroll 1
        for (int k = 16 * pass; k < 16 * pass + 16; k++) {
          const int s = slot_of(k);
          mbar_wait(BAR(B_FULL + s), use_of(k) & 1);
          bar_sync(turn_me, 256);
          const uint64_t da = make_desc(sb + s * ST_BYTES + A_BYTES + w * 16384), db = make_desc(sb + s * ST_BYTES);
          wgmma_fence();
#pragma unroll
          for (int kk = 0; kk < 4; kk++) {
            wgmma_n128(s0, da + kk * 2, db + kk * 2, kk > 0 || (k & 15));
            wgmma_n128(s1, da + 512 + kk * 2, db + kk * 2, kk > 0 || (k & 15));
          }
          wgmma_commit();
          if (k < 31 || w == 0) bar_arrive(turn_other, 256);
          if (pass && !(k & 1)) {
            const uint32_t buf = sb + OFF_XCH + 20480 + w * 4096;
            static_for<8>([&](auto ic) { if (k == 16 + 2 * decltype(ic)::value) put(ic, buf); });
            fence_async_smem();
            bar_sync(NB_WG0 + w, 128);
            if (t == 0) { tma_store_2d(&p.tmAbM, buf, (k - 16) * 128 + 240, col * 128); bulk_commit(); }
          }
          wgmma_wait0();
          release(s);
          if ((k & 1) && t == 0) asm volatile("cp.async.bulk.wait_group.read 0;" ::: "memory");
        }
        if (pass) publish(col);
        mbar_wait(BAR(B_STAT), 0);
        wgmma_fence();
        wgmma_n128(s0, make_desc_noswz(sb + OFF_XCH + pass * 8192 + w * 4096), make_desc_noswz(sb + OFF_XCH + 16384));
        wgmma_n128(s1, make_desc_noswz(sb + OFF_XCH + pass * 8192 + w * 4096 + 2048), make_desc_noswz(sb + OFF_XCH + 16384));
        wgmma_commit();
        uint4 rs[4];
#pragma unroll
        for (int i = 0; i < 4; i++) rs[i] = lds128_v(sb + OFF_RS + q * 144 + i * 16);
        wgmma_wait0();
        fence_acc(s0); fence_acc(s1);
#pragma unroll
        for (int i = 0; i < 32; i++) {
          const int tl = i & 7, hr = (i >> 3) & 1;
          const float* ac = (i >> 4) ? &s1[8 * tl + 2 * hr] : &s0[8 * tl + 2 * hr];
          o[i][0] = bmul2(pack_bf16(ac[0], ac[1]), (tl & 1) ? rs[tl >> 1].z : rs[tl >> 1].x);
          o[i][1] = bmul2(pack_bf16(ac[4], ac[5]), (tl & 1) ? rs[tl >> 1].w : rs[tl >> 1].y);
        }
      }
      static_for<8>([&](auto ic) { put(ic, sb + (w * 8 + decltype(ic)::value) * 4096); });
      fence_async_smem();
      bar_sync(NB_WG0 + w, 128);
      if (t == 0) {
#pragma unroll 1
        for (int i = 0; i < 8; i++) tma_store_2d(&p.tmAbM, sb + (w * 8 + i) * 4096, i * 256 + 240, (col + 2) * 128);
        bulk_commit();
      }
      publish(col + 2);
      asm volatile("barrier.cluster.wait.aligned;" ::: "memory");
      return;
    }
    float acc[128], a1[NX / 2];
#pragma unroll
    for (int i = 0; i < NX / 2; i++) a1[i] = 0.f;
    if (w == 1) bar_arrive(NB_TURN0, 256);
    auto kstep = [&](auto& d, int k, bool first, bool a_in_xch = false, bool mini = false) {
      const int s = slot_of(k);
      mbar_wait(BAR(B_FULL + s), use_of(k) & 1);
      CT(64 + k);
      bar_sync(turn_me, 256);
      const uint64_t da = make_desc(sb + (a_in_xch ? OFF_XCH + s * 16384 : s * ST_BYTES) + w * 8192), db = make_desc(sb + s * ST_BYTES + A_BYTES);
      wgmma_fence();
      wgmma_g1(d, da, db, !first);
#pragma unroll
      for (int kk = 1; kk < 4; kk++) wgmma_g1(d, da + kk * 2, db + kk * 2, 1);
      wgmma_commit();
      if (mini) {
        CT(29);
        mbar_wait(BAR(B_A20), 1);
        CT(30);
        wgmma_fence();
        wgmma_g1(d, make_desc_32b(sb + OFF_MINI + w * 2048), make_desc_32b(sb + OFF_MINI + 4096), 1);
        wgmma_commit();
      }
      bar_arrive(turn_other, 256);
    };
    auto kdone = [&](int k) { wgmma_wait0(); release(slot_of(k)); };
    auto wgmma_wait1 = [&]() { asm volatile("wgmma.wait_group.sync.aligned 1;" ::: "memory"); };

#pragma unroll 1
    for (int k = 0; k < 14; k++) {
      kstep(a1, k, k == 0);
      if (k == 0) CT(0);
      if (k == 8 && warp == 2 && lane < 2) pkt_st128(&p.s->abflag[((eps * 2 + m) * 8 + tau) * 2 + lane], 0, 0, 0, 0);
      kdone(k);
    }
    uint32_t R[64];
    uint32_t tag;
    {
      const uint32_t rsa = sb + OFF_RS + q * 144;
      const uint64_t da2 = make_desc(sb + 2 * ST_BYTES + w * 8192), db2 = make_desc(sb + 2 * ST_BYTES + A_BYTES);
      const uint64_t da3 = make_desc(sb + 3 * ST_BYTES + w * 8192), db3 = make_desc(sb + 3 * ST_BYTES + A_BYTES);
      mbar_wait(BAR(B_FULL + 2), 1);
      CT(64 + 14);
      bar_sync(turn_me, 256);
      wgmma_fence();
#pragma unroll
      for (int kk = 0; kk < 4; kk++) wgmma_g1(a1, da2 + kk * 2, db2 + kk * 2, 1);
      wgmma_commit();
      mbar_wait(BAR(B_FULL + 3), 1);
      CT(64 + 15);
      wgmma_fence();
      wgmma_g1(a1, da3, db3, 1);
      wgmma_g1(a1, da3 + 2, db3 + 2, 1);
      wgmma_commit();
      mbar_wait(BAR(B_STAT), 0);
      tag = SM_(uint32_t, OFF_TAG);
#pragma unroll
      for (int i = 0; i < 8; i++) { const uint4 v = lds128_v(rsa + i * 16); R[8 * i] = v.x; R[8 * i + 2] = v.y; R[8 * i + 4] = v.z; R[8 * i + 6] = v.w; }
      wgmma_wait1();
      release(2);
      wgmma_fence();
      wgmma_g1(a1, da3 + 4, db3 + 4, 1);
      wgmma_g1(a1, da3 + 6, db3 + 6, 1);
      wgmma_g1(a1, make_desc_noswz(sb + OFF_EXA + w * 2048), make_desc_noswz(sb + OFF_EXB), 1);
      wgmma_commit();
      bar_arrive(turn_other, 256);
      kdone(15);
      mbar_wait(BAR(B_STAT), 0);
    }
    fence_acc(a1);
    CT(1);
    auto pack = [&](auto cc) {
      constexpr int c = decltype(cc)::value;
#pragma unroll
      for (int j = 8 * c; j < min_c(8 * c + 8, NX / 8); j++) {
        const uint32_t rs = R[2 * j];
        const float* ac = &a1[4 * j];
        R[2 * j] = bmul2(pack_bf16(ac[0], ac[1]), rs);
        R[2 * j + 1] = bmul2(pack_bf16(ac[2], ac[3]), rs);
      }
    };
    auto put_chunk = [&](auto cc) {
      constexpr int c = decltype(cc)::value;
      const int rho = 16 * wi + (lane & 15);
#pragma unroll
      for (int j = 8 * c; j < min_c(8 * c + 8, NX / 8); j += 2) {
        const int chunk = (j & 7) + (lane >> 4);
        stsm_x4(sb + chunk_off(c, w) + rho * 128 + ((chunk ^ (lane & 7)) << 4), R[2 * j], R[2 * j + 1], R[2 * j + 2], R[2 * j + 3]);
      }
    };
    auto staged = [&](int bar) {
      fence_async_smem();
      __syncwarp();
      if (lane == 0) mbar_arrive(BAR(bar));
    };
    auto mma_rs = [&](auto cc, auto k0, auto k1) {
      constexpr int c = decltype(cc)::value;
      const uint64_t db = make_desc(sb + c * ST_BYTES + A_BYTES);
#pragma unroll
      for (int kk = decltype(k0)::value; kk < decltype(k1)::value; kk++)
        wgmma_n256_rs(acc, R[16 * c + 4 * kk], R[16 * c + 4 * kk + 1], R[16 * c + 4 * kk + 2], R[16 * c + 4 * kk + 3], db + kk * 2, c + kk > 0);
      wgmma_commit();
    };
    auto kdone_x = [&](int k, auto ic) {
      constexpr int i = decltype(ic)::value;
      uint32_t r[8];
#pragma unroll
      for (int z = 0; z < 2; z++) {
        const int tr = 32 * (i & 1) + 16 * z + 8 * (lane >> 4) + (lane & 7), chunk = 2 * wi + ((lane >> 3) & 1);
        ldsm_x4_t(sb + (i >> 1) * ST_BYTES + w * 8192 + tr * 128 + ((chunk ^ (lane & 7)) << 4), r[4 * z], r[4 * z + 1], r[4 * z + 2], r[4 * z + 3]);
      }
      float f[16];
#pragma unroll
      for (int z = 0; z < 8; z++) { f[2 * z] = bf_lo(r[z]); f[2 * z + 1] = bf_hi(r[z]); }
#pragma unroll
      for (int z = 0; z < 16; z++) asm volatile("" : "+f"(f[z]));
      kdone(k);
#pragma unroll
      for (int z = 0; z < 16; z++) asm volatile("add.f32 %0, %0, %1;" : "+f"(acc[16 * i + z]) : "f"(f[z]));
    };
    pack(IC<0>());
    put_chunk(IC<0>());
    staged(w ? B_EPI0B : B_EPI);
    mbar_wait(BAR(B_STAT), 0);
    CT(21);
    pack(IC<1>());
    pack(IC<2>());
    pack(IC<3>());
#pragma unroll
    for (int i = 16; i < NX / 4; i++) asm volatile("" : "+r"(R[i]));
#pragma unroll
    for (int i = 0; i < 128; i++) asm volatile("" : "=f"(acc[i]));
    mbar_wait(BAR(B_FULL + 0), 0);
    CT(2);
    CT(64 + 16);
    bar_sync(turn_me, 256);
    wgmma_fence();
    mma_rs(IC<0>(), IC<0>(), IC<4>());
    mbar_wait(BAR(B_FULL + 1), 0);
    CT(64 + 17);
    wgmma_fence();
    mma_rs(IC<1>(), IC<0>(), IC<2>());
    wgmma_wait1();
    release(0);
    mma_rs(IC<1>(), IC<2>(), IC<4>());
    bar_arrive(turn_other, 256);
    kdone_x(17, IC<0>());
    static_for<2>([&](auto ic) {
      constexpr int c = 2 + decltype(ic)::value;
      mbar_wait(BAR(B_FULL + c), 0);
      CT(64 + 16 + c);
      bar_sync(turn_me, 256);
      wgmma_fence();
      mma_rs(IC<c>(), IC<0>(), IC<min_c(4, NX / 16 - 4 * c)>());
      bar_arrive(turn_other, 256);
      if (c == 2) { put_chunk(IC<1>()); staged(B_EPI + 1); }
      kdone_x(16 + c, IC<c - 1>());
    });
#pragma unroll 1
    for (int k = 20; k < 23; k++) {
      if (w == 1) mbar_wait(BAR(B_A20), 0);
      kstep(acc, k, false, k < 22);
      if (k == 20) {
        kdone_x(k, IC<3>());
      } else {
        if (k == 21) put_chunk(IC<2>()); else put_chunk(IC<3>());
        __syncwarp();
        if (lane == 0) mbar_arrive(BAR(B_EPI + k - 19));
        kdone(k);
      }
    }
    uint32_t wf[32][4];
    auto load_wf = [&](auto hc) {
      constexpr int h = decltype(hc)::value;
      const int d = w * 64 + (lane >> 4) * 8 + (lane & 7);
      const uint32_t ad = sb + round_off(h) + (lane & 8) * 1024 + d * 64 + ((wi ^ ((lane >> 1) & 3)) << 4);
#pragma unroll
      for (int i = 0; i < 4; i++) ldsm_x4_t(ad + i * 1024, wf[4 * h + i][0], wf[4 * h + i][1], wf[4 * h + i][2], wf[4 * h + i][3]);
    };
    auto load_wf_rest = [&]() { static_for<8 - NREG_H>([&](auto ic) { load_wf(IC<NREG_H + decltype(ic)::value>()); }); };
#pragma unroll
    for (int i = 0; i < 4 * NREG_H; i++) { wf[i][0] = 0; wf[i][1] = 0; wf[i][2] = 0; wf[i][3] = 0; }
    const int grp = tau * 2 + m;
#pragma unroll 1
    for (int k = 23; k < 46; k++) {
      kstep(acc, k, false, false, NX < 256 && k == MINI_K);
      if (moe) {
        static_for<NREG_H>([&](auto hc) {
          constexpr int h = decltype(hc)::value;
          if (k == mr_k(h) + 1) { mbar_wait(BAR(B_MR + (h & 1)), (h >> 1) & 1); CT(32 + h); load_wf(hc); }
        });
      }
      if (k == RESET_K && tid == 0) mbar_arrive(BAR(B_LATE));
      kdone(k);
    }
    asm volatile("barrier.cluster.arrive.relaxed.aligned;" ::: "memory");
    mbar_wait(BAR(B_STAT), 1);
    uint32_t wa[16][2];
    uint32_t cd = code_of(tag);
    uint4* hp_pub = &p.s->hstat[(grp * 8 + eps) * 128 + warp * 16 + g];
    const uint4* hp_poll = &p.s->hstat[(grp * 8 + 2 * q) * 128 + warp * 16 + g];
    const uint32_t vec_off = (2 * wi) * 512 + q * 128 + ((g ^ (2 * q)) << 4);
    {
      float as[64], ak[64];
      fence_acc(acc);
#pragma unroll
      for (int i = 0; i < 64; i++) asm volatile("mov.b32 %0, %1;" : "=f"(as[i]) : "f"(acc[64 + i]));
#pragma unroll
      for (int i = 0; i < 64; i++) asm volatile("mov.b32 %0, %1;" : "=f"(ak[i]) : "f"(acc[i]));
      const uint64_t da1 = make_desc(sb + 2 * ST_BYTES + w * 8192), db1 = make_desc(sb + 2 * ST_BYTES + A_BYTES);
      const uint64_t da2 = make_desc(sb + 3 * ST_BYTES + w * 8192), db2 = make_desc(sb + 3 * ST_BYTES + A_BYTES);
      mbar_wait(BAR(B_FULL + 2), 1);
      CT(64 + 46);
      bar_sync(turn_me, 256);
      wgmma_fence();
#pragma unroll
      for (int kk = 0; kk < 4; kk++) wgmma_n128(as, da1 + kk * 2, db1 + 1024 + kk * 2);
      wgmma_commit();
      mbar_wait(BAR(B_FULL + 3), 1);
      CT(64 + 47);
      wgmma_fence();
#pragma unroll
      for (int kk = 0; kk < 4; kk++) wgmma_n128(as, da2 + kk * 2, db2 + 1024 + kk * 2);
      wgmma_commit();
      bar_arrive(turn_other, 256);
      const uint32_t rx = mapa(sb + OFF_PEER + w * 4096 + vec_off, 1 - m), rb = mapa(BAR(B_XCH), 1 - m);
      asm volatile("barrier.cluster.wait.aligned;" ::: "memory");
      CT(24);
      wgmma_wait0();
      fence_acc(as);
      CT(25);
      auto keep = [&]() {
        bar_sync(turn_me, 256);
        wgmma_fence();
#pragma unroll
        for (int kk = 0; kk < 4; kk++) wgmma_n128(ak, da1 + kk * 2, db1 + kk * 2);
        wgmma_commit();
#pragma unroll
        for (int kk = 0; kk < 4; kk++) wgmma_n128(ak, da2 + kk * 2, db2 + kk * 2);
        wgmma_commit();
        if (w == 0) bar_arrive(turn_other, 256);
      };
#pragma unroll
      for (int i = 0; i < 8; i++) {
        if (i == SEND_FIRST) keep();
        const float* ac = &as[16 * (i >> 1) + 2 * (i & 1)];
        st_async_v4(rx + (i >> 1) * 8192 + (i & 1) * 512, rb, pack_bf16(ac[0], ac[1]), pack_bf16(ac[4], ac[5]), pack_bf16(ac[8], ac[9]), pack_bf16(ac[12], ac[13]));
      }
      CT(26);
#pragma unroll
      for (int i = 0; i < 4; i++) {
        const uint4 v = lds128_v(sb + OFF_WR + q * 80 + i * 16);
        const uint32_t vv[4] = {v.x, v.y, v.z, v.w};
#pragma unroll
        for (int z = 0; z < 4; z++) {
          asm volatile("{\n.reg .pred p;\nsetp.ne.b32 p, %2, 0;\nselp.b32 %0, %1, 0x3F803F80, p;\n}" : "=r"(wa[4 * i + z][0]) : "r"(vv[z]), "r"(g & 1));
          asm volatile("{\n.reg .pred p;\nsetp.ne.b32 p, %2, 0;\nselp.b32 %0, %1, 0x3F803F80, p;\n}" : "=r"(wa[4 * i + z][1]) : "r"(vv[z]), "r"(g & 1));
        }
      }
      pin(cd); pin(hp_pub); pin(hp_poll);
      CT(27);
      wgmma_wait1();
      release(2);
      wgmma_wait0();
      fence_acc(ak);
      CT(3);
#pragma unroll
      for (int i = 0; i < 8; i++) {
        const float* ac = &ak[16 * (i >> 1) + 2 * (i & 1)];
        sts128(sb + (2 + (i >> 2)) * ST_BYTES + w * 8192 + ((i >> 1) & 1) * 4096 + (i & 1) * 512 + vec_off,
               pack_bf16(ac[0], ac[1]), pack_bf16(ac[4], ac[5]), pack_bf16(ac[8], ac[9]), pack_bf16(ac[12], ac[13]));
      }
    }
    uint32_t h[8][4];
    {
      const int qq = 2 * (warp & 1) + ((lane >> 3) & 1);
      const uint32_t lo = (lane >> 4) * 512 + qq * 128 + (((lane & 7) ^ (2 * qq)) << 4);
      bar_sync(NB_BOTH, 256);
#pragma unroll
      for (int ks = 0; ks < 8; ks++)
        ldsm_x4_t(sb + (2 + w) * ST_BYTES + (ks >> 2) * 8192 + (wi >> 1) * 4096 + (ks & 3) * 1024 + lo, h[ks][0], h[ks][1], h[ks][2], h[ks][3]);
      CT(28);
      mbar_wait_cluster(BAR(B_XCH), 0);
      CT(4);
      uint32_t r[8][4];
#pragma unroll
      for (int ks = 0; ks < 8; ks++) ldsm_x4_t(sb + OFF_PEER + (warp >> 1) * 8192 + ks * 1024 + lo, r[ks][0], r[ks][1], r[ks][2], r[ks][3]);
      float d[4][4] = {};
#pragma unroll
      for (int ks = 0; ks < 8; ks++) {
#pragma unroll
        for (int i = 0; i < 4; i++) {
          h[ks][i] = badd2(h[ks][i], r[ks][i]);
          mma1688(d[i], h[ks][i], wa[2 * ks + (i >> 1)][i & 1], h[ks][i]);
        }
      }
#pragma unroll
      for (int i = 0; i < 2; i++) {
        const float sq = (g & 1) ? d[i][1] + d[i + 2][1] : d[i][0] + d[i + 2][0];
        const float e0 = d[i][2] + d[i + 2][2], e1 = d[i][3] + d[i + 2][3];
        const float other = __shfl_xor_sync(0xffffffffu, (g & 1) ? e0 : e1, 4);
        if (q == (g >> 1)) pkt_st128(hp_pub + 8 * i, with_bit((g & 1) ? other : e0, cd), with_bit(sq, cd >> 1), __float_as_uint((g & 1) ? e1 : other), tag);
      }
    }
    CT(5);
    if (tid == 0) mbar_arrive(BAR(B_KEY));
    delay_clk<HOP1_DELAY>();
    float m_bf, sd, inv_sd, r_bf;
    uint4* key_pub = &p.s->key[((lane & 7) * 16 + grp) * 2];
    uint4* cand_pub = &p.s->cand[grp * 256 + eps * 32 + q];
    uint32_t trow_inv = 0xFFFFu - (uint32_t)row_of(grp * 128 + 32 * (warp >> 1) + 8 * (g >> 1) + 4 * (warp & 1) + (q & 2) + (g & 1));
    {
      uint4 u[4];
#pragma unroll
      for (int i = 0; i < 4; i++) u[i] = pkt_ld128(hp_poll + (i & 1) * 128 + (i >> 1) * 8);
      const float wsum = SM_(float, OFF_WSUM);
      pin(key_pub); pin(cand_pub); pin(trow_inv);
      uint32_t n = 0;
      while (true) {
        bool ok[4];
#pragma unroll
        for (int i = 0; i < 4; i++) ok[i] = u[i].w == tag && pair_code(u[i].x, u[i].y) == cd;
        const bool all = __all_sync(0xffffffffu, ok[0] && ok[1] && ok[2] && ok[3]);
        if (all || ++n > SPIN_LIMIT) break;
#pragma unroll
        for (int i = 0; i < 4; i++) pkt_ld128_if(u[i], hp_poll + (i & 1) * 128 + (i >> 1) * 8, !ok[i]);
      }
      CT(6);
      float a[3], b[3];
      a[0] = __uint_as_float(u[0].x & ~1u) + __uint_as_float(u[1].x & ~1u); b[0] = __uint_as_float(u[2].x & ~1u) + __uint_as_float(u[3].x & ~1u);
      a[1] = __uint_as_float(u[0].y & ~1u) + __uint_as_float(u[1].y & ~1u); b[1] = __uint_as_float(u[2].y & ~1u) + __uint_as_float(u[3].y & ~1u);
      a[2] = __uint_as_float(u[0].z) + __uint_as_float(u[1].z); b[2] = __uint_as_float(u[2].z) + __uint_as_float(u[3].z);
#pragma unroll
      for (int i = 0; i < 3; i++) {
        a[i] = ((q & 2) ? b[i] : a[i]) + __shfl_xor_sync(0xffffffffu, (q & 2) ? a[i] : b[i], 2);
        a[i] += __shfl_xor_sync(0xffffffffu, a[i], 1);
      }
      const float mu = a[0] * (1.f / 1024.f);
      m_bf = bf16r(mu);
      sd = ln_sd(a[1] * (1.f / 1024.f) - mu * mu);
      inv_sd = rcp_fast(sd);
      r_bf = bf16r((a[2] - m_bf * wsum) * inv_sd);
    }
    {
      const uint32_t u = __float_as_uint(r_bf);
      const uint32_t ord = (u & 0x80000000u) ? ~u : (u | 0x80000000u);
      const uint32_t key = (ord & 0xFFFF0000u) | trow_inv;
      const uint32_t wk = __reduce_max_sync(0xffffffffu, key);
      if (key == wk) SM_(uint2, OFF_WKEY + warp * 8) = make_uint2(wk, (__float_as_uint(m_bf) >> 16) | __float_as_uint(sd));
      const uint32_t wmask = __ballot_sync(0xffffffffu, key == wk);
      const bool hi = (wmask & 0xCCCCCCCCu) != 0;
      uint32_t c[16];
#pragma unroll
      for (int ks = 0; ks < 8; ks++) { c[2 * ks] = hi ? h[ks][1] : h[ks][0]; c[2 * ks + 1] = hi ? h[ks][3] : h[ks][2]; }
      bar_sync(NB_BOTH, 256);
      const uint2 km = SM_(uint2, OFF_WKEY + (lane & 7) * 8);
      const uint32_t bk = __reduce_max_sync(0xffffffffu, km.x);
      if (wk == bk) {
        if ((wmask >> (lane & 28)) & 15) {
#pragma unroll
          for (int ks = 0; ks < 8; ks++) pkt_st128(cand_pub + ks * 4, c[2 * ks], tag, c[2 * ks + 1], tag);
        }
      } else if (eps == 0) {
        const uint32_t kx = __shfl_sync(0xffffffffu, km.x, warp ^ 1), ms = __shfl_sync(0xffffffffu, km.y, warp ^ 1);
        if (kx == bk && lane < 8) pkt_st128(key_pub, bk, tag, ms, tag);
      }
      CT(7);
    }
    {
      const float ih = bf16r(inv_sd);
      const uint32_t nm = pack_bf16(-m_bf, -m_bf), iv = pack_bf16(ih, inv_sd - ih);
      const uint32_t nm_o = __shfl_xor_sync(0xffffffffu, nm, 2), iv_o = __shfl_xor_sync(0xffffffffu, iv, 2);
      const uint32_t nm2[2] = {(q & 2) ? nm_o : nm, (q & 2) ? nm : nm_o}, iv2[2] = {(q & 2) ? iv_o : iv, (q & 2) ? iv : iv_o};
      const uint32_t hi2[2] = {__byte_perm(iv2[0], 0, 0x1010), __byte_perm(iv2[1], 0, 0x1010)}, lo2[2] = {__byte_perm(iv2[0], 0, 0x3232), __byte_perm(iv2[1], 0, 0x3232)};
      const uint32_t oa = sb + OFF_OUT + (warp * 16 + (lane & 15)) * 128;
#pragma unroll
      for (int ks = 0; ks < 8; ks++) {
        uint32_t o[4];
#pragma unroll
        for (int i = 0; i < 4; i++) {
          const uint32_t dd = badd2(h[ks][i], nm2[i & 1]);
          o[i] = badd2(h[ks][i], bfma2(dd, hi2[i & 1], bmul2(dd, lo2[i & 1])));
        }
        stsm_x4(oa + (ks >> 2) * 16384 + (((2 * (ks & 3) + (lane >> 4)) ^ (lane & 7)) << 4), o[0], o[1], o[2], o[3]);
      }
      staged(B_OUT);
    }
    CT(8);
    uint32_t df[16][4];
    auto load_df = [&]() {
      const int frow = (lane & 7) + ((lane >> 4) << 3), hi = (lane >> 3) & 1;
      const uint32_t base = sb + down_off(warp >> 1) + (warp & 1) * 8192 + frow * 128;
#pragma unroll
      for (int mt = 0; mt < 8; mt++) {
#pragma unroll
        for (int ks = 0; ks < 2; ks++)
          ldsm_x4_t(base + (mt >> 2) * 4096 + ks * 2048 + (((2 * (mt & 3) + hi) ^ (lane & 7)) << 4),
                    df[2 * mt + ks][0], df[2 * mt + ks][1], df[2 * mt + ks][2], df[2 * mt + ks][3]);
      }
    };
    if (moe) {
      mbar_wait(BAR(B_GU), 0);
      load_wf_rest();
      mbar_wait(BAR(B_DN), 0);
      load_df();
    }
    uint4* y_pub = &p.s->ypart[cid * 256 + tid];
    uint32_t xs_ad = sb + OFF_XSEL + (8 * (g >> 2) + 4 * w + (g & 3)) * 32 + q * 8, gp_ad = sb + OFF_GP + (wi * 8 + g) * 16 + w * 8 + (q >> 1) * 4;
    pin(y_pub); pin(xs_ad); pin(gp_ad);
    mbar_wait(BAR(B_XS), 0);
    CT(9);
    if (moe) {
      float gd[8][4] = {};
      uint2 bx[4];
#pragma unroll
      for (int r = 0; r < 4; r++) bx[r] = smem_at<uint2>(xs_ad + r * 512);
#pragma unroll
      for (int r = 0; r < 4; r++) {
#pragma unroll
        for (int i = 0; i < 8; i++) mma16816(gd[i], wf[8 * r + i][0], wf[8 * r + i][1], wf[8 * r + i][2], wf[8 * r + i][3], bx[r].x, bx[r].y);
      }
      const float gs = sel4(q, gd[0][0] + gd[1][1], gd[2][0] + gd[3][1], gd[4][0] + gd[5][1], gd[6][0] + gd[7][1]);
      const float us = sel4(q, gd[0][2] + gd[1][3], gd[2][2] + gd[3][3], gd[4][2] + gd[5][3], gd[6][2] + gd[7][3]);
      float v = ((q & 2) ? us : gs) + __shfl_xor_sync(0xffffffffu, (q & 2) ? gs : us, 2);
      v += __shfl_xor_sync(0xffffffffu, v, 1);
      smem_at<float>(gp_ad) = v;
      CT(10);
      bar_sync(NB_BOTH, 256);
      uint32_t bq[4];
      {
        const float4 p0 = SM_(float4, OFF_GP + lane * 16);
        const float gt = bf16r(p0.x + p0.z), up = bf16r(p0.y + p0.w);
        const float act = bf16r(gt * sigmoid_fast(gt)) * up;
        const uint32_t pr = pack_bf16(act, __shfl_down_sync(0xffffffffu, act, 1));
#pragma unroll
        for (int i = 0; i < 4; i++) bq[i] = __shfl_sync(0xffffffffu, pr, 8 * i + 2 * q);
      }
      CT(11);
      float yd[8][4] = {};
#pragma unroll
      for (int ks = 0; ks < 2; ks++) {
#pragma unroll
        for (int mt = 0; mt < 8; mt++) mma16816(yd[mt], df[2 * mt + ks][0], df[2 * mt + ks][1], df[2 * mt + ks][2], df[2 * mt + ks][3], bq[2 * ks], bq[2 * ks + 1]);
      }
      pkt_st128(y_pub, with_bit(sel4(q, yd[0][0], yd[2][0], yd[4][0], yd[6][0]), cd), with_bit(sel4(q, yd[0][2], yd[2][2], yd[4][2], yd[6][2]), cd >> 1),
                with_bit(sel4(q, yd[1][0], yd[3][0], yd[5][0], yd[7][0]), cd), with_bit(sel4(q, yd[1][2], yd[3][2], yd[5][2], yd[7][2]), cd >> 1));
    } else {
      const long long tw = clock64();
      while (clock64() - tw < IDLE_WAIT_CLK) __nanosleep(100);
    }
    CT(12);
    const uint32_t kv = SM_(uint32_t, OFF_KV);
    const int tsel = (int)(~kv & 2047u);
    const float r_sel = __uint_as_float((kv & 0x80000000u) ? (kv & 0x7FFF0000u) : (~kv & 0xFFFF0000u));
    const float sig = bf16r(sigmoid_fast(r_sel));
    const int pfin = 2 * cid + (tid & 1);
    const int col_fin = (pfin >> 5) * 128 + (pfin & 3) * 32 + ((pfin & 31) >> 2) + 8 * ((tid >> 1) & 3);
    const int sel_off = (col_fin >> 4) * 32 + ((col_fin & 7) >> 1) * 8 + ((col_fin >> 3) & 1) * 4 + (col_fin & 1) * 2;
    const float hn_fin = __uint_as_float((uint32_t)SM_(uint16_t, OFF_XSEL + sel_off) << 16), h_fin = __uint_as_float((uint32_t)SM_(uint16_t, OFF_HSEL + sel_off) << 16);
    bf16* out_fin = p.out + (size_t)tsel * 1024 + col_fin;
    {
      const uint4* src = &p.s->ypart[(16 + (tid >> 1)) * 256 + pfin];
      pin(src); pin(out_fin);
      uint4 v = make_uint4(0, 0, 0, 0);
      if (warp < 7) {
        delay_clk<HOP3_DELAY>();
        uint32_t n = 0;
        bool ok = false;
        do {
          pkt_ld128_if(v, src, !ok);
          ok = pair_code(v.x, v.y) == cd && pair_code(v.z, v.w) == cd;
        } while (!__all_sync(0xffffffffu, ok) && ++n < SPIN_LIMIT);
      }
      CT(13);
      const float y0 = __uint_as_float(v.x & ~1u), y1 = __uint_as_float(v.y & ~1u), y2 = __uint_as_float(v.z & ~1u), y3 = __uint_as_float(v.w & ~1u);
      const float a0 = ((lane & 2) ? y1 : y0) + __shfl_xor_sync(0xffffffffu, (lane & 2) ? y0 : y1, 2);
      const float a1 = ((lane & 2) ? y3 : y2) + __shfl_xor_sync(0xffffffffu, (lane & 2) ? y2 : y3, 2);
      float b = ((lane & 4) ? a1 : a0) + __shfl_xor_sync(0xffffffffu, (lane & 4) ? a0 : a1, 4);
      b += __shfl_xor_sync(0xffffffffu, b, 8);
      b += __shfl_xor_sync(0xffffffffu, b, 16);
      if (lane < 8) SM_(float, OFF_FIN + lane * 32 + warp * 4) = b;
    }
    bar_sync(NB_BOTH, 256);
    if (tid < 8) {
      const float4 y0 = SM_(float4, OFF_FIN + tid * 32), y1 = SM_(float4, OFF_FIN + tid * 32 + 16);
      const float y = ((y0.x + y0.y) + (y0.z + y0.w)) + ((y1.x + y1.y) + y1.z);
      *out_fin = __float2bfloat16_rn(h_fin + bf16r(hn_fin + bf16r(bf16r(y) * sig)));
      if (cid == 0 && tid == 0) st_relaxed32(&p.s->epoch, tag);
    }
    CT(14);
  }
}

__global__ void __launch_bounds__(384, 1) occupancy_probe_kernel() {}

typedef CUresult (*EncodeFn)(CUtensorMap*, CUtensorMapDataType, cuuint32_t, void*, const cuuint64_t*, const cuuint64_t*, const cuuint32_t*, const cuuint32_t*,
                             CUtensorMapInterleave, CUtensorMapSwizzle, CUtensorMapL2promotion, CUtensorMapFloatOOBfill);

static void make_tm(EncodeFn enc, CUtensorMap* tm, const void* ptr, uint64_t rows, uint64_t cols, uint32_t brows, uint32_t bcols, CUtensorMapSwizzle sw,
                    CUtensorMapL2promotion promo = CU_TENSOR_MAP_L2_PROMOTION_L2_128B) {
  cuuint64_t dims[2] = {cols, rows};
  cuuint64_t strides[1] = {cols * 2};
  cuuint32_t box[2] = {bcols, brows};
  cuuint32_t es[2] = {1, 1};
  enc(tm, CU_TENSOR_MAP_DATA_TYPE_BFLOAT16, 2, const_cast<void*>(ptr), dims, strides, box, es, CU_TENSOR_MAP_INTERLEAVE_NONE, sw,
      promo, CU_TENSOR_MAP_FLOAT_OOB_FILL_NONE);
}

static void make_tm_rows(EncodeFn enc, CUtensorMap* tm, const void* ptr, uint64_t cols, uint32_t brows, uint32_t bcols, CUtensorMapSwizzle sw,
                         CUtensorMapL2promotion promo = CU_TENSOR_MAP_L2_PROMOTION_L2_128B) {
  cuuint64_t dims[4] = {cols, 2, 2, 512};
  cuuint64_t strides[3] = {row_of(1) * cols * 2, row_of(2) * cols * 2, row_of(4) * cols * 2};
  cuuint32_t box[4] = {bcols, 2, 2, brows / 4};
  cuuint32_t es[4] = {1, 1, 1, 1};
  enc(tm, CU_TENSOR_MAP_DATA_TYPE_BFLOAT16, 4, const_cast<void*>(ptr), dims, strides, box, es, CU_TENSOR_MAP_INTERLEAVE_NONE, sw, promo,
      CU_TENSOR_MAP_FLOAT_OOB_FILL_NONE);
}

extern "C" void kernel_launch(void* const* d_in, const int* in_sizes, int n_in, void* d_out, int out_size) {
  (void)in_sizes; (void)n_in; (void)out_size;
  static EncodeFn enc = nullptr;
  static void* abT = nullptr;
  static int map = 0;
  if (!enc) {
    void* fn = nullptr; cudaDriverEntryPointQueryResult st;
    cudaGetDriverEntryPoint("cuTensorMapEncodeTiled", &fn, cudaEnableDefault, &st);
    enc = (EncodeFn)fn;
    cudaGetSymbolAddress(&abT, g_scratch);
    cudaFuncSetAttribute(fnet_moe_kernel<0>, cudaFuncAttributeMaxDynamicSharedMemorySize, SMEM_TOTAL);
    cudaFuncSetAttribute(fnet_moe_kernel<1>, cudaFuncAttributeMaxDynamicSharedMemorySize, SMEM_TOTAL);
    cudaFuncSetAttribute(occupancy_probe_kernel, cudaFuncAttributeMaxDynamicSharedMemorySize, SMEM_TOTAL);
    cudaFuncSetAttribute(occupancy_probe_kernel, cudaFuncAttributeNonPortableClusterSizeAllowed, 1);
    auto max_clusters = [&](int size) {
      cudaLaunchConfig_t cfg = {};
      cfg.gridDim = dim3(128); cfg.blockDim = dim3(384); cfg.dynamicSmemBytes = SMEM_TOTAL;
      cudaLaunchAttribute at[1];
      at[0].id = cudaLaunchAttributeClusterDimension; at[0].val.clusterDim.x = size; at[0].val.clusterDim.y = 1; at[0].val.clusterDim.z = 1;
      cfg.attrs = at; cfg.numAttrs = 1;
      int ncl = 0;
      return cudaOccupancyMaxActiveClusters(&ncl, occupancy_probe_kernel, &cfg) == cudaSuccess ? ncl : 0;
    };
    int dev = 0, sms = 0;
    cudaGetDevice(&dev);
    cudaDeviceGetAttribute(&sms, cudaDevAttrMultiProcessorCount, dev);
    map = (sms == 132 && max_clusters(2) == 66 && max_clusters(16) == 7) ? 0 : 1;
    (void)cudaGetLastError();
  }
  Params p;
  const bf16* x = (const bf16*)d_in[0];
  make_tm(enc, &p.tmD0, d_in[3], 1024, 1024, 128, 64, CU_TENSOR_MAP_SWIZZLE_128B);
  make_tm(enc, &p.tmD1, d_in[4], 1024, 1024, 128, 64, CU_TENSOR_MAP_SWIZZLE_128B);
  make_tm(enc, &p.tmX, x, 2048, 1024, map == 0 ? NX0 : 256, 64, CU_TENSOR_MAP_SWIZZLE_128B);
  make_tm_rows(enc, &p.tmXr, x, 1024, 64, 64, CU_TENSOR_MAP_SWIZZLE_128B);
  make_tm(enc, &p.tmAbS, abT, 2048, 2048, 64, 64, CU_TENSOR_MAP_SWIZZLE_128B);
  make_tm(enc, &p.tmAbL, abT, 2048, 2048, 128, 64, CU_TENSOR_MAP_SWIZZLE_128B);
  make_tm_rows(enc, &p.tmW0, d_in[1], 2048, 128, 64, CU_TENSOR_MAP_SWIZZLE_128B);
  make_tm_rows(enc, &p.tmW1, d_in[2], 2048, 128, 64, CU_TENSOR_MAP_SWIZZLE_128B);
  {
    cuuint64_t dims[5] = {1024, 2, 4, 2, 2048};
    cuuint64_t strides[4] = {row_of(1) * 2048, row_of(8) * 2048, row_of(2) * 2048, 2048};
    cuuint32_t box[5] = {64, 2, 4, 2, 1};
    cuuint32_t es[5] = {1, 1, 1, 1, 1};
    enc(&p.tmOut, CU_TENSOR_MAP_DATA_TYPE_BFLOAT16, 5, d_out, dims, strides, box, es, CU_TENSOR_MAP_INTERLEAVE_NONE, CU_TENSOR_MAP_SWIZZLE_128B,
        CU_TENSOR_MAP_L2_PROMOTION_NONE, CU_TENSOR_MAP_FLOAT_OOB_FILL_NONE);
  }
  {
    cuuint64_t dims[5] = {1024, 2, 4, 2, 8};
    cuuint64_t strides[4] = {2048, 4 * 2048, 2 * 2048, 256 * 2048};
    cuuint32_t box[5] = {64, 2, 4, 2, 8};
    cuuint32_t es[5] = {1, 1, 1, 1, 1};
    enc(&p.tmXh, CU_TENSOR_MAP_DATA_TYPE_BFLOAT16, 5, const_cast<bf16*>(x) + 240 * 1024, dims, strides, box, es, CU_TENSOR_MAP_INTERLEAVE_NONE,
        CU_TENSOR_MAP_SWIZZLE_128B, CU_TENSOR_MAP_L2_PROMOTION_L2_128B, CU_TENSOR_MAP_FLOAT_OOB_FILL_NONE);
  }
  make_tm(enc, &p.tmAbM, abT, 2048, 2048, 128, 16, CU_TENSOR_MAP_SWIZZLE_32B, CU_TENSOR_MAP_L2_PROMOTION_NONE);
  make_tm_rows(enc, &p.tmWM0, d_in[1], 2048, 128, 16, CU_TENSOR_MAP_SWIZZLE_32B);
  make_tm_rows(enc, &p.tmWM1, d_in[2], 2048, 128, 16, CU_TENSOR_MAP_SWIZZLE_32B);
  make_tm(enc, &p.tmG, d_in[7], 1024, 3584, 128, 32, CU_TENSOR_MAP_SWIZZLE_64B);
  make_tm(enc, &p.tmU, d_in[8], 1024, 3584, 128, 32, CU_TENSOR_MAP_SWIZZLE_64B);
  make_tm(enc, &p.tmDn, d_in[9], 3584, 1024, 32, 64, CU_TENSOR_MAP_SWIZZLE_128B);
  p.x = x; p.Dre = (const bf16*)d_in[3]; p.Dim = (const bf16*)d_in[4];
  p.wr = (const bf16*)d_in[6]; p.wdown = (const bf16*)d_in[9]; p.wgate = (const bf16*)d_in[7]; p.wup = (const bf16*)d_in[8];
  p.out = (bf16*)d_out; p.s = (Scratch*)abT;
  if (map == 1) fnet_moe_kernel<1><<<128, 384, SMEM_TOTAL>>>(p);
  else fnet_moe_kernel<0><<<132, 384, SMEM_TOTAL>>>(p);
}
```

```cpp
#include <cuda.h>
#include <cuda_runtime.h>
#include <cuda_bf16.h>
#include <stdint.h>
#include <type_traits>

typedef __nv_bfloat16 bf16;

constexpr int NX0 = 240;
constexpr int REG_C = 232, REG_P = 40;
__host__ __device__ constexpr int row_of(int p) { return (p & 1) * 1024 + ((p >> 1) & 1) * 512 + (p >> 2); }
__host__ __device__ constexpr int group_of(int row) { return (row & 511) >> 5; }
__device__ __forceinline__ int sigma_of(int tau, int r) { return r + (r >= tau); }
__device__ __forceinline__ int kblock(int tau, int j) {
  const int i = j - 4, c = (i * 37) >> 8;
  return j < 4 ? tau * 4 + j : sigma_of(tau, i - 7 * c) * 4 + c;
}
constexpr int AUX_AFTER = 1;
constexpr int PF_K0 = 8, PF_N0 = 2, PF_K1 = 24;
constexpr int WPF_K0 = 12, WPF_N = 10;
constexpr int WPF2_K = 44, WPF2_N = 4;
constexpr int GU_K = 46;
constexpr int PUB_K1 = 22;
constexpr int NREG_H = 5;
constexpr int MR_K0 = 29, MR_P = 6;
constexpr int MINI_PF_K = 35, MINI_LOAD_K = 43, MINI_K = 42;
constexpr int RESET_K = 37;
constexpr int SEND_FIRST = 2;
constexpr int GATHER_NS = 400;
constexpr int MOE_PACE_CLK = 300;
constexpr int OUT_PACE_CLK = 70;
constexpr int HOP1_DELAY = 150, HOP3_DELAY = 450;
constexpr int SPEC_MIN = 10;
constexpr int IDLE_WAIT_CLK = 1200;
__host__ __device__ constexpr int mr_k(int h) { return MR_K0 + MR_P * (h >> 1) + 2 * (h & 1); }
constexpr int A_BYTES = 128 * 64 * 2;
constexpr int B_BYTES = 256 * 64 * 2;
constexpr int ST_BYTES = A_BYTES + B_BYTES;
constexpr int OFF_XCH = 4 * ST_BYTES;
constexpr int OFF_BAR = OFF_XCH + 32768;
constexpr int OFF_WR = OFF_BAR + 384;
constexpr int OFF_RS = OFF_WR + 384;
constexpr int OFF_PUB = OFF_RS + 640;
constexpr int OFF_MISC = OFF_PUB + 768;
constexpr int SMEM_TOTAL = OFF_MISC + 256;
constexpr int OFF_WSUM = OFF_MISC, OFF_TAG = OFF_MISC + 4;
constexpr int OFF_SEEN = OFF_MISC + 8;
constexpr int OFF_KV = OFF_MISC + 12;
constexpr int OFF_WKEY = OFF_MISC + 32;
constexpr int OFF_MINI = OFF_XCH + 16384;
constexpr int OFF_EXA = OFF_XCH;
constexpr int OFF_EXB = OFF_XCH + 4096;
__host__ __device__ constexpr int chunk_off(int c, int w) { return (c < 2 ? (c + 2) * ST_BYTES : OFF_XCH + (c - 2) * 16384) + w * 8192; }
__host__ __device__ constexpr int late_off(int i) { return i < 4 ? i * 16384 : 2 * ST_BYTES + A_BYTES + (i - 4) * 16384; }
__host__ __device__ constexpr int round_off(int h) { return h < NREG_H + 2 ? OFF_XCH + (h & 1) * 16384 : late_off(h - NREG_H - 2); }
__host__ __device__ constexpr int down_off(int i) { return late_off(6 - NREG_H + i); }
constexpr int OFF_PEER = ST_BYTES + A_BYTES;
constexpr int OFF_OUT = 3 * ST_BYTES + A_BYTES;
constexpr int OFF_XSEL = OFF_PEER;
constexpr int OFF_HSEL = OFF_PEER + 4096;
constexpr int OFF_GP = OFF_PEER + 8192;
constexpr int OFF_FIN = OFF_PEER + 9216;
__device__ __forceinline__ int slot_of(int k) { return k & 3; }
__device__ __forceinline__ int use_of(int k) { return k >> 2; }
enum { B_FULL = 0, B_EMPTY = 4, B_EPI = 8, B_STD = 12, B_EPI0B = 16, B_LATE = 17, B_STAT = 18, B_XCH = 19, B_MR = 20  , B_GU = 22,
       B_DN = 23, B_AUX = 24  , B_OUT = 26, B_KEY = 27, B_XS = 28, B_A20 = 29, B_STDA = 30, B_PUB1 = 31, B_COUNT = 32 };
enum { NB_TURN0 = 1, NB_TURN1 = 2, NB_WG0 = 3, NB_BOTH = 5, NB_AUX = 6 };

struct Scratch {
  bf16 abT[2048 * 2048];
  uint2 xstat[2048];
  uint2 dsum[2048];
  uint4 abflag[16 * 8 * 2];
  uint4 hflag[16 * 2];
  uint4 hstat[16 * 8 * 128];
  uint4 cand[16 * 256];
  uint4 key[8 * 16 * 2];
  uint4 ypart[128 * 256];
  uint32_t epoch;
};
__device__ __align__(1024) Scratch g_scratch;

struct Params {
  Scratch* s; bf16* out;
  const bf16* x; const bf16* Dre; const bf16* Dim; const bf16* wr; const bf16* wdown; const bf16* wgate; const bf16* wup;
  CUtensorMap tmX, tmD0, tmD1, tmXr, tmAbS, tmAbL, tmW0, tmW1, tmOut, tmG, tmU, tmDn, tmXh, tmAbM, tmWM0, tmWM1;
};

#define SPIN_LIMIT (1u << 14)
#define MBAR_LIMIT (1u << 10)
__device__ __forceinline__ uint32_t smem_u32(const void* p) { return (uint32_t)__cvta_generic_to_shared(p); }
__device__ __forceinline__ void mbar_init(uint32_t bar, uint32_t cnt) { asm volatile("mbarrier.init.shared::cta.b64 [%0], %1;" :: "r"(bar), "r"(cnt) : "memory"); }
__device__ __forceinline__ void mbar_expect_tx(uint32_t bar, uint32_t bytes) { asm volatile("mbarrier.arrive.expect_tx.shared::cta.b64 _, [%0], %1;" :: "r"(bar), "r"(bytes) : "memory"); }
__device__ __forceinline__ void mbar_arrive(uint32_t bar) { asm volatile("mbarrier.arrive.shared::cta.b64 _, [%0];" :: "r"(bar) : "memory"); }
__device__ __forceinline__ void mbar_wait(uint32_t bar, uint32_t parity) {
  uint32_t ok, n = 0;
  do {
    asm volatile("{\n.reg .pred p;\nmbarrier.try_wait.parity.shared::cta.b64 p, [%1], %2;\nselp.u32 %0, 1, 0, p;\n}\n" : "=r"(ok) : "r"(bar), "r"(parity) : "memory");
  } while (!ok && ++n < MBAR_LIMIT);
}
__device__ __forceinline__ void mbar_wait_cluster(uint32_t bar, uint32_t parity) {
  uint32_t ok, n = 0;
  do {
    asm volatile("{\n.reg .pred p;\nmbarrier.try_wait.parity.acquire.cluster.shared::cta.b64 p, [%1], %2;\nselp.u32 %0, 1, 0, p;\n}\n" : "=r"(ok) : "r"(bar), "r"(parity) : "memory");
  } while (!ok && ++n < MBAR_LIMIT);
}
__device__ __forceinline__ void tma_load_2d(uint32_t dst, const CUtensorMap* tm, uint32_t bar, int c0, int c1) {
  asm volatile("cp.async.bulk.tensor.2d.shared::cluster.global.mbarrier::complete_tx::bytes [%0], [%1, {%3, %4}], [%2];"
    :: "r"(dst), "l"(tm), "r"(bar), "r"(c0), "r"(c1) : "memory");
}
__device__ __forceinline__ void tma_load_2d_hint(uint32_t dst, const CUtensorMap* tm, uint32_t bar, int c0, int c1, uint64_t pol) {
  asm volatile("cp.async.bulk.tensor.2d.shared::cluster.global.mbarrier::complete_tx::bytes.L2::cache_hint [%0], [%1, {%3, %4}], [%2], %5;"
    :: "r"(dst), "l"(tm), "r"(bar), "r"(c0), "r"(c1), "l"(pol) : "memory");
}
__device__ __forceinline__ uint64_t policy_evict_first() { uint64_t p; asm volatile("createpolicy.fractional.L2::evict_first.b64 %0, 1.0;" : "=l"(p)); return p; }
__device__ __forceinline__ void tma_store_2d(const CUtensorMap* tm, uint32_t src, int c0, int c1) {
  asm volatile("cp.async.bulk.tensor.2d.global.shared::cta.bulk_group [%0, {%2, %3}], [%1];" :: "l"(tm), "r"(src), "r"(c0), "r"(c1) : "memory");
}
__device__ __forceinline__ void tma_prefetch_2d(const CUtensorMap* tm, int c0, int c1) {
  asm volatile("cp.async.bulk.prefetch.tensor.2d.L2.global.tile [%0, {%1, %2}];" :: "l"(tm), "r"(c0), "r"(c1) : "memory");
}
__device__ __forceinline__ void bulk_load(uint32_t dst, const void* src, uint32_t bytes, uint32_t bar) {
  asm volatile("cp.async.bulk.shared::cluster.global.mbarrier::complete_tx::bytes [%0], [%1], %2, [%3];" :: "r"(dst), "l"(src), "r"(bytes), "r"(bar) : "memory");
}
__device__ __forceinline__ void bulk_commit() { asm volatile("cp.async.bulk.commit_group;" ::: "memory"); }
__device__ __forceinline__ void bulk_wait_all() { asm volatile("cp.async.bulk.wait_group 0;" ::: "memory"); }
__device__ __forceinline__ void bulk_wait_release() {
  bulk_wait_all();
  asm volatile("fence.proxy.async.global;" ::: "memory");
  asm volatile("fence.acq_rel.gpu;" ::: "memory");
}
__device__ __forceinline__ void fence_async_smem() { asm volatile("fence.proxy.async.shared::cta;" ::: "memory"); }
__device__ __forceinline__ void wgmma_fence() { asm volatile("wgmma.fence.sync.aligned;" ::: "memory"); }
__device__ __forceinline__ void wgmma_commit() { asm volatile("wgmma.commit_group.sync.aligned;" ::: "memory"); }
__device__ __forceinline__ void wgmma_wait0() { asm volatile("wgmma.wait_group.sync.aligned 0;" ::: "memory"); }
__device__ __forceinline__ void bar_sync(int id, int n) { asm volatile("bar.sync %0, %1;" :: "r"(id), "r"(n) : "memory"); }
__device__ __forceinline__ void bar_arrive(int id, int n) { asm volatile("bar.arrive %0, %1;" :: "r"(id), "r"(n) : "memory"); }
template<int R> __device__ __forceinline__ void reg_inc() { asm volatile("setmaxnreg.inc.sync.aligned.u32 %0;" :: "n"(R)); }
template<int R> __device__ __forceinline__ void reg_dec() { asm volatile("setmaxnreg.dec.sync.aligned.u32 %0;" :: "n"(R)); }
__device__ __forceinline__ bool elect_one() {
  uint32_t p;
  asm volatile("{\n.reg .pred q;\nelect.sync _|q, 0xffffffff;\nselp.u32 %0, 1, 0, q;\n}\n" : "=r"(p));
  return p != 0;
}
__device__ __forceinline__ uint32_t mapa(uint32_t addr, uint32_t cta) { uint32_t r; asm volatile("mapa.shared::cluster.u32 %0, %1, %2;" : "=r"(r) : "r"(addr), "r"(cta)); return r; }
__device__ __forceinline__ void st_async_v4(uint32_t addr, uint32_t bar, uint32_t a, uint32_t b, uint32_t c, uint32_t d) {
  asm volatile("st.async.weak.shared::cluster.mbarrier::complete_tx::bytes.v4.b32 [%0], {%2, %3, %4, %5}, [%1];" :: "r"(addr), "r"(bar), "r"(a), "r"(b), "r"(c), "r"(d) : "memory");
}
__device__ __forceinline__ void stsm_x4(uint32_t addr, uint32_t a, uint32_t b, uint32_t c, uint32_t d) {
  asm volatile("stmatrix.sync.aligned.m8n8.x4.shared.b16 [%0], {%1, %2, %3, %4};" :: "r"(addr), "r"(a), "r"(b), "r"(c), "r"(d));
}
__device__ __forceinline__ uint4 lds128_v(uint32_t addr) { uint4 v; asm volatile("ld.shared.v4.b32 {%0, %1, %2, %3}, [%4];" : "=r"(v.x), "=r"(v.y), "=r"(v.z), "=r"(v.w) : "r"(addr)); return v; }
extern __shared__ __align__(1024) uint8_t smem_raw[];
template<class T> __device__ __forceinline__ T& smem_at(uint32_t addr) { return *reinterpret_cast<T*>(__cvta_shared_to_generic(addr)); }
#define SM_(T, off) smem_at<T>(sb + (off))
__device__ __forceinline__ uint4 ldg_nc128(const void* p) { uint4 v; asm volatile("ld.global.nc.v4.b32 {%0, %1, %2, %3}, [%4];" : "=r"(v.x), "=r"(v.y), "=r"(v.z), "=r"(v.w) : "l"(p)); return v; }
__device__ __forceinline__ void pkt_st128(void* p, uint32_t a, uint32_t b, uint32_t c, uint32_t d) {
  asm volatile("{\n.reg .b128 v;\n.reg .b64 lo, hi;\nmov.b64 lo, {%1, %2};\nmov.b64 hi, {%3, %4};\nmov.b128 v, {lo, hi};\nst.relaxed.gpu.global.b128 [%0], v;\n}\n"
    :: "l"(p), "r"(a), "r"(b), "r"(c), "r"(d) : "memory");
}
__device__ __forceinline__ uint4 pkt_ld128(const void* p) {
  uint4 r;
  asm volatile("{\n.reg .b128 v;\n.reg .b64 lo, hi;\nld.relaxed.gpu.global.b128 v, [%4];\nmov.b128 {lo, hi}, v;\nmov.b64 {%0, %1}, lo;\nmov.b64 {%2, %3}, hi;\n}\n"
    : "=r"(r.x), "=r"(r.y), "=r"(r.z), "=r"(r.w) : "l"(p) : "memory");
  return r;
}
__device__ __forceinline__ void pkt_ld128_if(uint4& r, const void* p, bool cond) {
  asm volatile("{\n.reg .pred q;\n.reg .b64 lo, hi;\nsetp.ne.b32 q, %5, 0;\nmov.b64 lo, {%0, %1};\nmov.b64 hi, {%2, %3};\n"
               "@q ld.relaxed.gpu.global.v2.b64 {lo, hi}, [%4];\nmov.b64 {%0, %1}, lo;\nmov.b64 {%2, %3}, hi;\n}\n"
    : "+r"(r.x), "+r"(r.y), "+r"(r.z), "+r"(r.w) : "l"(p), "r"((uint32_t)cond) : "memory");
}
__device__ __forceinline__ void pkt_st64(void* p, uint32_t a, uint32_t b) {
  asm volatile("{\n.reg .b64 v;\nmov.b64 v, {%1, %2};\nst.relaxed.gpu.global.b64 [%0], v;\n}\n" :: "l"(p), "r"(a), "r"(b) : "memory");
}
__device__ __forceinline__ uint2 pkt_ld64(const void* p) {
  uint2 r;
  asm volatile("{\n.reg .b64 v;\nld.relaxed.gpu.global.b64 v, [%2];\nmov.b64 {%0, %1}, v;\n}\n" : "=r"(r.x), "=r"(r.y) : "l"(p) : "memory");
  return r;
}
__device__ __forceinline__ uint32_t ld_relaxed32(const void* p) { uint32_t v; asm volatile("ld.relaxed.gpu.global.b32 %0, [%1];" : "=r"(v) : "l"(p) : "memory"); return v; }
__device__ __forceinline__ void st_relaxed32(void* p, uint32_t v) { asm volatile("st.relaxed.gpu.global.b32 [%0], %1;" :: "l"(p), "r"(v) : "memory"); }
__device__ __forceinline__ uint32_t code_of(uint32_t tag) { return tag % 3u + 1u; }
__device__ __forceinline__ uint32_t with_bit(float v, uint32_t bit) { return (__float_as_uint(v) & ~1u) | (bit & 1u); }
__device__ __forceinline__ uint32_t pair_code(uint32_t a, uint32_t b) { return (a & 1u) | ((b & 1u) << 1); }
__device__ __forceinline__ uint32_t pack_bf16(float lo, float hi) { uint32_t r; asm("cvt.rn.bf16x2.f32 %0, %1, %2;" : "=r"(r) : "f"(hi), "f"(lo)); return r; }
__device__ __forceinline__ float bf_lo(uint32_t v) { return __uint_as_float(v << 16); }
__device__ __forceinline__ float bf_hi(uint32_t v) { return __uint_as_float(v & 0xFFFF0000u); }
__device__ __forceinline__ float bf16r(float x) { return __uint_as_float(pack_bf16(0.f, x)); }
__device__ __forceinline__ uint32_t badd2(uint32_t a, uint32_t b) { uint32_t r; asm("add.rn.bf16x2 %0, %1, %2;" : "=r"(r) : "r"(a), "r"(b)); return r; }
__device__ __forceinline__ uint32_t bmul2(uint32_t a, uint32_t b) { uint32_t r; asm("mul.rn.bf16x2 %0, %1, %2;" : "=r"(r) : "r"(a), "r"(b)); return r; }
__device__ __forceinline__ float warp_sum(float v) {
#pragma unroll
  for (int o = 16; o > 0; o >>= 1) v += __shfl_xor_sync(0xffffffffu, v, o);
  return v;
}
__device__ __forceinline__ uint64_t make_desc(uint32_t addr) {
  return (uint64_t)((addr & 0x3FFFF) >> 4) | ((uint64_t)1 << 16) | ((uint64_t)64 << 32) | ((uint64_t)1 << 62);
}
__device__ __forceinline__ uint64_t make_desc_noswz(uint32_t addr) {
  return (uint64_t)((addr & 0x3FFFF) >> 4) | ((uint64_t)8 << 16) | ((uint64_t)16 << 32);
}
__device__ __forceinline__ uint64_t make_desc_32b(uint32_t addr) {
  return (uint64_t)((addr & 0x3FFFF) >> 4) | ((uint64_t)1 << 16) | ((uint64_t)16 << 32) | ((uint64_t)3 << 62);
}
__device__ __forceinline__ void wgmma_n256(float (&d)[128], uint64_t da, uint64_t db, int scale_d) {
  asm volatile("{\n.reg .pred p;\nsetp.ne.b32 p, %130, 0;\n"
    "wgmma.mma_async.sync.aligned.m64n256k16.f32.bf16.bf16 "
    "{%0, %1, %2, %3, %4, %5, %6, %7, %8, %9, %10, %11, %12, %13, %14, %15, %16, %17, %18, %19, %20, %21, %22, %23, %24, %25, %26, %27, %28, %29, %30, %31, "
    "%32, %33, %34, %35, %36, %37, %38, %39, %40, %41, %42, %43, %44, %45, %46, %47, %48, %49, %50, %51, %52, %53, %54, %55, %56, %57, %58, %59, %60, %61, %62, %63, "
    "%64, %65, %66, %67, %68, %69, %70, %71, %72, %73, %74, %75, %76, %77, %78, %79, %80, %81, %82, %83, %84, %85, %86, %87, %88, %89, %90, %91, %92, %93, %94, %95, "
    "%96, %97, %98, %99, %100, %101, %102, %103, %104, %105, %106, %107, %108, %109, %110, %111, %112, %113, %114, %115, %116, %117, %118, %119, %120, %121, %122, %123, %124, %125, %126, %127}, "
    "%128, %129, p, 1, 1, 0, 0;\n}\n"
    : "+f"(d[0]), "+f"(d[1]), "+f"(d[2]), "+f"(d[3]), "+f"(d[4]), "+f"(d[5]), "+f"(d[6]), "+f"(d[7]),
      "+f"(d[8]), "+f"(d[9]), "+f"(d[10]), "+f"(d[11]), "+f"(d[12]), "+f"(d[13]), "+f"(d[14]), "+f"(d[15]),
      "+f"(d[16]), "+f"(d[17]), "+f"(d[18]), "+f"(d[19]), "+f"(d[20]), "+f"(d[21]), "+f"(d[22]), "+f"(d[23]),
      "+f"(d[24]), "+f"(d[25]), "+f"(d[26]), "+f"(d[27]), "+f"(d[28]), "+f"(d[29]), "+f"(d[30]), "+f"(d[31]),
      "+f"(d[32]), "+f"(d[33]), "+f"(d[34]), "+f"(d[35]), "+f"(d[36]), "+f"(d[37]), "+f"(d[38]), "+f"(d[39]),
      "+f"(d[40]), "+f"(d[41]), "+f"(d[42]), "+f"(d[43]), "+f"(d[44]), "+f"(d[45]), "+f"(d[46]), "+f"(d[47]),
      "+f"(d[48]), "+f"(d[49]), "+f"(d[50]), "+f"(d[51]), "+f"(d[52]), "+f"(d[53]), "+f"(d[54]), "+f"(d[55]),
      "+f"(d[56]), "+f"(d[57]), "+f"(d[58]), "+f"(d[59]), "+f"(d[60]), "+f"(d[61]), "+f"(d[62]), "+f"(d[63]),
      "+f"(d[64]), "+f"(d[65]), "+f"(d[66]), "+f"(d[67]), "+f"(d[68]), "+f"(d[69]), "+f"(d[70]), "+f"(d[71]),
      "+f"(d[72]), "+f"(d[73]), "+f"(d[74]), "+f"(d[75]), "+f"(d[76]), "+f"(d[77]), "+f"(d[78]), "+f"(d[79]),
      "+f"(d[80]), "+f"(d[81]), "+f"(d[82]), "+f"(d[83]), "+f"(d[84]), "+f"(d[85]), "+f"(d[86]), "+f"(d[87]),
      "+f"(d[88]), "+f"(d[89]), "+f"(d[90]), "+f"(d[91]), "+f"(d[92]), "+f"(d[93]), "+f"(d[94]), "+f"(d[95]),
      "+f"(d[96]), "+f"(d[97]), "+f"(d[98]), "+f"(d[99]), "+f"(d[100]), "+f"(d[101]), "+f"(d[102]), "+f"(d[103]),
      "+f"(d[104]), "+f"(d[105]), "+f"(d[106]), "+f"(d[107]), "+f"(d[108]), "+f"(d[109]), "+f"(d[110]), "+f"(d[111]),
      "+f"(d[112]), "+f"(d[113]), "+f"(d[114]), "+f"(d[115]), "+f"(d[116]), "+f"(d[117]), "+f"(d[118]), "+f"(d[119]),
      "+f"(d[120]), "+f"(d[121]), "+f"(d[122]), "+f"(d[123]), "+f"(d[124]), "+f"(d[125]), "+f"(d[126]), "+f"(d[127])
    : "l"(da), "l"(db), "r"(scale_d));
}
__device__ __forceinline__ void wgmma_g1(float (&d)[128], uint64_t da, uint64_t db, int scale_d) { wgmma_n256(d, da, db, scale_d); }
__device__ __forceinline__ void wgmma_g1(float (&d)[120], uint64_t da, uint64_t db, int scale_d) {
  asm volatile("{\n.reg .pred p;\nsetp.ne.b32 p, %122, 0;\n"
    "wgmma.mma_async.sync.aligned.m64n240k16.f32.bf16.bf16 "
    "{%0, %1, %2, %3, %4, %5, %6, %7, %8, %9, %10, %11, %12, %13, %14, %15, %16, %17, %18, %19, %20, %21, %22, %23, %24, %25, %26, %27, %28, %29, %30, %31, %32, %33, %34, %35, %36, %37, %38, %39, %40, %41, %42, %43, %44, %45, %46, %47, %48, %49, %50, %51, %52, %53, %54, %55, %56, %57, %58, %59, %60, %61, %62, %63, %64, %65, %66, %67, %68, %69, %70, %71, %72, %73, %74, %75, %76, %77, %78, %79, %80, %81, %82, %83, %84, %85, %86, %87, %88, %89, %90, %91, %92, %93, %94, %95, %96, %97, %98, %99, %100, %101, %102, %103, %104, %105, %106, %107, %108, %109, %110, %111, %112, %113, %114, %115, %116, %117, %118, %119}, "
    "%120, %121, p, 1, 1, 0, 0;\n}\n"
    : "+f"(d[0]), "+f"(d[1]), "+f"(d[2]), "+f"(d[3]), "+f"(d[4]), "+f"(d[5]), "+f"(d[6]), "+f"(d[7]), "+f"(d[8]), "+f"(d[9]), "+f"(d[10]), "+f"(d[11]), "+f"(d[12]), "+f"(d[13]), "+f"(d[14]), "+f"(d[15]), "+f"(d[16]), "+f"(d[17]), "+f"(d[18]), "+f"(d[19]), "+f"(d[20]), "+f"(d[21]), "+f"(d[22]), "+f"(d[23]), "+f"(d[24]), "+f"(d[25]), "+f"(d[26]), "+f"(d[27]), "+f"(d[28]), "+f"(d[29]), "+f"(d[30]), "+f"(d[31]), "+f"(d[32]), "+f"(d[33]), "+f"(d[34]), "+f"(d[35]), "+f"(d[36]), "+f"(d[37]), "+f"(d[38]), "+f"(d[39]), "+f"(d[40]), "+f"(d[41]), "+f"(d[42]), "+f"(d[43]), "+f"(d[44]), "+f"(d[45]), "+f"(d[46]), "+f"(d[47]), "+f"(d[48]), "+f"(d[49]), "+f"(d[50]), "+f"(d[51]), "+f"(d[52]), "+f"(d[53]), "+f"(d[54]), "+f"(d[55]), "+f"(d[56]), "+f"(d[57]), "+f"(d[58]), "+f"(d[59]), "+f"(d[60]), "+f"(d[61]), "+f"(d[62]), "+f"(d[63]), "+f"(d[64]), "+f"(d[65]), "+f"(d[66]), "+f"(d[67]), "+f"(d[68]), "+f"(d[69]), "+f"(d[70]), "+f"(d[71]), "+f"(d[72]), "+f"(d[73]), "+f"(d[74]), "+f"(d[75]), "+f"(d[76]), "+f"(d[77]), "+f"(d[78]), "+f"(d[79]), "+f"(d[80]), "+f"(d[81]), "+f"(d[82]), "+f"(d[83]), "+f"(d[84]), "+f"(d[85]), "+f"(d[86]), "+f"(d[87]), "+f"(d[88]), "+f"(d[89]), "+f"(d[90]), "+f"(d[91]), "+f"(d[92]), "+f"(d[93]), "+f"(d[94]), "+f"(d[95]), "+f"(d[96]), "+f"(d[97]), "+f"(d[98]), "+f"(d[99]), "+f"(d[100]), "+f"(d[101]), "+f"(d[102]), "+f"(d[103]), "+f"(d[104]), "+f"(d[105]), "+f"(d[106]), "+f"(d[107]), "+f"(d[108]), "+f"(d[109]), "+f"(d[110]), "+f"(d[111]), "+f"(d[112]), "+f"(d[113]), "+f"(d[114]), "+f"(d[115]), "+f"(d[116]), "+f"(d[117]), "+f"(d[118]), "+f"(d[119])
    : "l"(da), "l"(db), "r"(scale_d));
}
__device__ __forceinline__ void wgmma_n256_rs(float (&d)[128], uint32_t a0, uint32_t a1, uint32_t a2, uint32_t a3, uint64_t db, int scale_d) {
  asm volatile("{\n.reg .pred p;\nsetp.ne.b32 p, %133, 0;\n"
    "wgmma.mma_async.sync.aligned.m64n256k16.f32.bf16.bf16 "
    "{%0, %1, %2, %3, %4, %5, %6, %7, %8, %9, %10, %11, %12, %13, %14, %15, %16, %17, %18, %19, %20, %21, %22, %23, %24, %25, %26, %27, %28, %29, %30, %31, "
    "%32, %33, %34, %35, %36, %37, %38, %39, %40, %41, %42, %43, %44, %45, %46, %47, %48, %49, %50, %51, %52, %53, %54, %55, %56, %57, %58, %59, %60, %61, %62, %63, "
    "%64, %65, %66, %67, %68, %69, %70, %71, %72, %73, %74, %75, %76, %77, %78, %79, %80, %81, %82, %83, %84, %85, %86, %87, %88, %89, %90, %91, %92, %93, %94, %95, "
    "%96, %97, %98, %99, %100, %101, %102, %103, %104, %105, %106, %107, %108, %109, %110, %111, %112, %113, %114, %115, %116, %117, %118, %119, %120, %121, %122, %123, %124, %125, %126, %127}, "
    "{%128, %129, %130, %131}, %132, p, 1, 1, 0;\n}\n"
    : "+f"(d[0]), "+f"(d[1]), "+f"(d[2]), "+f"(d[3]), "+f"(d[4]), "+f"(d[5]), "+f"(d[6]), "+f"(d[7]),
      "+f"(d[8]), "+f"(d[9]), "+f"(d[10]), "+f"(d[11]), "+f"(d[12]), "+f"(d[13]), "+f"(d[14]), "+f"(d[15]),
      "+f"(d[16]), "+f"(d[17]), "+f"(d[18]), "+f"(d[19]), "+f"(d[20]), "+f"(d[21]), "+f"(d[22]), "+f"(d[23]),
      "+f"(d[24]), "+f"(d[25]), "+f"(d[26]), "+f"(d[27]), "+f"(d[28]), "+f"(d[29]), "+f"(d[30]), "+f"(d[31]),
      "+f"(d[32]), "+f"(d[33]), "+f"(d[34]), "+f"(d[35]), "+f"(d[36]), "+f"(d[37]), "+f"(d[38]), "+f"(d[39]),
      "+f"(d[40]), "+f"(d[41]), "+f"(d[42]), "+f"(d[43]), "+f"(d[44]), "+f"(d[45]), "+f"(d[46]), "+f"(d[47]),
      "+f"(d[48]), "+f"(d[49]), "+f"(d[50]), "+f"(d[51]), "+f"(d[52]), "+f"(d[53]), "+f"(d[54]), "+f"(d[55]),
      "+f"(d[56]), "+f"(d[57]), "+f"(d[58]), "+f"(d[59]), "+f"(d[60]), "+f"(d[61]), "+f"(d[62]), "+f"(d[63]),
      "+f"(d[64]), "+f"(d[65]), "+f"(d[66]), "+f"(d[67]), "+f"(d[68]), "+f"(d[69]), "+f"(d[70]), "+f"(d[71]),
      "+f"(d[72]), "+f"(d[73]), "+f"(d[74]), "+f"(d[75]), "+f"(d[76]), "+f"(d[77]), "+f"(d[78]), "+f"(d[79]),
      "+f"(d[80]), "+f"(d[81]), "+f"(d[82]), "+f"(d[83]), "+f"(d[84]), "+f"(d[85]), "+f"(d[86]), "+f"(d[87]),
      "+f"(d[88]), "+f"(d[89]), "+f"(d[90]), "+f"(d[91]), "+f"(d[92]), "+f"(d[93]), "+f"(d[94]), "+f"(d[95]),
      "+f"(d[96]), "+f"(d[97]), "+f"(d[98]), "+f"(d[99]), "+f"(d[100]), "+f"(d[101]), "+f"(d[102]), "+f"(d[103]),
      "+f"(d[104]), "+f"(d[105]), "+f"(d[106]), "+f"(d[107]), "+f"(d[108]), "+f"(d[109]), "+f"(d[110]), "+f"(d[111]),
      "+f"(d[112]), "+f"(d[113]), "+f"(d[114]), "+f"(d[115]), "+f"(d[116]), "+f"(d[117]), "+f"(d[118]), "+f"(d[119]),
      "+f"(d[120]), "+f"(d[121]), "+f"(d[122]), "+f"(d[123]), "+f"(d[124]), "+f"(d[125]), "+f"(d[126]), "+f"(d[127])
    : "r"(a0), "r"(a1), "r"(a2), "r"(a3), "l"(db), "r"(scale_d));
}
__device__ __forceinline__ void wgmma_n128(float (&d)[64], uint64_t da, uint64_t db, int scale_d = 1) {
  asm volatile("{\n.reg .pred p;\nsetp.ne.b32 p, %66, 0;\n"
    "wgmma.mma_async.sync.aligned.m64n128k16.f32.bf16.bf16 "
    "{%0, %1, %2, %3, %4, %5, %6, %7, %8, %9, %10, %11, %12, %13, %14, %15, %16, %17, %18, %19, %20, %21, %22, %23, %24, %25, %26, %27, %28, %29, %30, %31, %32, %33, %34, %35, %36, %37, %38, %39, %40, %41, %42, %43, %44, %45, %46, %47, %48, %49, %50, %51, %52, %53, %54, %55, %56, %57, %58, %59, %60, %61, %62, %63}, "
    "%64, %65, p, 1, 1, 0, 0;\n}\n"
    : "+f"(d[0]), "+f"(d[1]), "+f"(d[2]), "+f"(d[3]), "+f"(d[4]), "+f"(d[5]), "+f"(d[6]), "+f"(d[7]), "+f"(d[8]), "+f"(d[9]), "+f"(d[10]), "+f"(d[11]), "+f"(d[12]), "+f"(d[13]), "+f"(d[14]), "+f"(d[15]), "+f"(d[16]), "+f"(d[17]), "+f"(d[18]), "+f"(d[19]), "+f"(d[20]), "+f"(d[21]), "+f"(d[22]), "+f"(d[23]), "+f"(d[24]), "+f"(d[25]), "+f"(d[26]), "+f"(d[27]), "+f"(d[28]), "+f"(d[29]), "+f"(d[30]), "+f"(d[31]), "+f"(d[32]), "+f"(d[33]), "+f"(d[34]), "+f"(d[35]), "+f"(d[36]), "+f"(d[37]), "+f"(d[38]), "+f"(d[39]), "+f"(d[40]), "+f"(d[41]), "+f"(d[42]), "+f"(d[43]), "+f"(d[44]), "+f"(d[45]), "+f"(d[46]), "+f"(d[47]), "+f"(d[48]), "+f"(d[49]), "+f"(d[50]), "+f"(d[51]), "+f"(d[52]), "+f"(d[53]), "+f"(d[54]), "+f"(d[55]), "+f"(d[56]), "+f"(d[57]), "+f"(d[58]), "+f"(d[59]), "+f"(d[60]), "+f"(d[61]), "+f"(d[62]), "+f"(d[63])
    : "l"(da), "l"(db), "r"(scale_d));
}
template<int N> __device__ __forceinline__ void fence_acc(float (&d)[N]) {
#pragma unroll
  for (int i = 0; i < N; i++) asm volatile("" : "+f"(d[i]) :: "memory");
}

template<int N, int I = 0, class F> __device__ __forceinline__ void static_for(F&& f) {
  if constexpr (I < N) { f(std::integral_constant<int, I>()); static_for<N, I + 1>(f); }
}

__device__ __forceinline__ void ldsm_x4_t(uint32_t addr, uint32_t& a, uint32_t& b, uint32_t& c, uint32_t& d) {
  asm volatile("ldmatrix.sync.aligned.m8n8.x4.trans.shared.b16 {%0, %1, %2, %3}, [%4];" : "=r"(a), "=r"(b), "=r"(c), "=r"(d) : "r"(addr));
}
__device__ __forceinline__ void sts128(uint32_t addr, uint32_t a, uint32_t b, uint32_t c, uint32_t d) {
  asm volatile("st.shared.v4.b32 [%0], {%1, %2, %3, %4};" :: "r"(addr), "r"(a), "r"(b), "r"(c), "r"(d));
}
__device__ __forceinline__ void mma16816(float (&c)[4], uint32_t a0, uint32_t a1, uint32_t a2, uint32_t a3, uint32_t b0, uint32_t b1) {
  asm volatile("mma.sync.aligned.m16n8k16.row.col.f32.bf16.bf16.f32 {%0, %1, %2, %3}, {%4, %5, %6, %7}, {%8, %9}, {%0, %1, %2, %3};"
      : "+f"(c[0]), "+f"(c[1]), "+f"(c[2]), "+f"(c[3]) : "r"(a0), "r"(a1), "r"(a2), "r"(a3), "r"(b0), "r"(b1));
}
__device__ __forceinline__ void mma1688(float (&c)[4], uint32_t a0, uint32_t a1, uint32_t b0) {
  asm volatile("mma.sync.aligned.m16n8k8.row.col.f32.bf16.bf16.f32 {%0, %1, %2, %3}, {%4, %5}, {%6}, {%0, %1, %2, %3};"
      : "+f"(c[0]), "+f"(c[1]), "+f"(c[2]), "+f"(c[3]) : "r"(a0), "r"(a1), "r"(b0));
}
__device__ __forceinline__ uint32_t keep_awake() {
  float c0;
  asm volatile("{\n.reg .f32 c1, c2, c3, z;\n.reg .b32 a;\nmov.b32 a, 0;\nmov.f32 z, 0f00000000;\n"
               "mma.sync.aligned.m16n8k8.row.col.f32.bf16.bf16.f32 {%0, c1, c2, c3}, {a, a}, {a}, {z, z, z, z};\n}\n" : "=f"(c0));
  return __float_as_uint(c0);
}
__device__ __forceinline__ void pin(uint32_t& v) { asm volatile("shfl.sync.bfly.b32 %0, %0, 0, 0x1f, 0xffffffff;" : "+r"(v)); }
template<class T> __device__ __forceinline__ void pin(T*& v) {
  uint32_t lo = (uint32_t)(uint64_t)v, hi = (uint32_t)((uint64_t)v >> 32);
  pin(lo); pin(hi);
  v = (T*)(((uint64_t)hi << 32) | lo);
}
__device__ __forceinline__ float sel4(int q, float a, float b, float c, float d) {
  float r;
  asm("{\n.reg .pred p, o;\n.reg .f32 x, y;\n.reg .b32 t;\nand.b32 t, %1, 1;\nsetp.ne.b32 p, t, 0;\nsetp.gt.s32 o, %1, 1;\n"
      "selp.f32 x, %3, %2, p;\nselp.f32 y, %5, %4, p;\nselp.f32 %0, y, x, o;\n}\n" : "=f"(r) : "r"(q), "f"(a), "f"(b), "f"(c), "f"(d));
  return r;
}
__device__ __forceinline__ uint32_t bfma2(uint32_t a, uint32_t b, uint32_t c) { uint32_t r; asm("fma.rn.bf16x2 %0, %1, %2, %3;" : "=r"(r) : "r"(a), "r"(b), "r"(c)); return r; }
__device__ __forceinline__ void tma_load_5d(uint32_t dst, const CUtensorMap* tm, uint32_t bar, int c0, int c4) {
  asm volatile("cp.async.bulk.tensor.5d.shared::cluster.global.mbarrier::complete_tx::bytes [%0], [%1, {%3, %4, %4, %4, %5}], [%2];"
    :: "r"(dst), "l"(tm), "r"(bar), "r"(c0), "r"(0), "r"(c4) : "memory");
}
__device__ __forceinline__ void tma_load_4d(uint32_t dst, const CUtensorMap* tm, uint32_t bar, int c0, int c3) {
  asm volatile("cp.async.bulk.tensor.4d.shared::cluster.global.mbarrier::complete_tx::bytes [%0], [%1, {%3, %4, %4, %5}], [%2];"
    :: "r"(dst), "l"(tm), "r"(bar), "r"(c0), "r"(0), "r"(c3) : "memory");
}
__device__ __forceinline__ void tma_load_4d_hint(uint32_t dst, const CUtensorMap* tm, uint32_t bar, int c0, int c3, uint64_t pol) {
  asm volatile("cp.async.bulk.tensor.4d.shared::cluster.global.mbarrier::complete_tx::bytes.L2::cache_hint [%0], [%1, {%3, %4, %4, %5}], [%2], %6;"
    :: "r"(dst), "l"(tm), "r"(bar), "r"(c0), "r"(0), "r"(c3), "l"(pol) : "memory");
}
__device__ __forceinline__ void tma_prefetch_4d(const CUtensorMap* tm, int c0, int c3) {
  asm volatile("cp.async.bulk.prefetch.tensor.4d.L2.global.tile [%0, {%1, %2, %2, %3}];" :: "l"(tm), "r"(c0), "r"(0), "r"(c3) : "memory");
}
__device__ __forceinline__ void tma_store_5d(const CUtensorMap* tm, uint32_t src, int c0, int c4) {
  asm volatile("cp.async.bulk.tensor.5d.global.shared::cta.bulk_group [%0, {%2, %3, %3, %3, %4}], [%1];" :: "l"(tm), "r"(src), "r"(c0), "r"(0), "r"(c4) : "memory");
}
__device__ __forceinline__ float rcp_fast(float x) { float r; asm("rcp.approx.ftz.f32 %0, %1;" : "=f"(r) : "f"(x)); return r; }
__device__ __forceinline__ float sigmoid_fast(float x) { float e; asm("ex2.approx.ftz.f32 %0, %1;" : "=f"(e) : "f"(x * -1.4426950408889634f)); return rcp_fast(1.f + e); }
__device__ __forceinline__ float sqrt_fast(float x) { float r; asm("sqrt.approx.ftz.f32 %0, %1;" : "=f"(r) : "f"(x)); return r; }
__device__ __forceinline__ float ln_sd(float var) { return bf16r(sqrt_fast(bf16r(bf16r(fmaxf(var, 0.f)) + 1e-5f))); }
__device__ __forceinline__ uint32_t norm2(uint32_t h, uint32_t neg_mean2, float inv_sd) {
  const uint32_t d = badd2(h, neg_mean2);
  return pack_bf16(bf_lo(d) * inv_sd, bf_hi(d) * inv_sd);
}
template<int N> __device__ __forceinline__ void delay_clk() {
  if constexpr (N > 0) { const uint32_t t0 = clock(); while ((uint32_t)clock() - t0 < N) {} }
}
__device__ __forceinline__ void put_xstat(uint32_t rs, uint32_t exb, int col, uint32_t mean_rstd, int m) {
  smem_at<uint16_t>(rs + ((col & 7) >> 1) * 144 + (col >> 3) * 4 + (col & 1) * 2) = (uint16_t)(mean_rstd ^ (m << 15));
  const uint32_t nm = (mean_rstd >> 16) ^ 0x8000u;
  smem_at<uint4>(exb + (col >> 3) * 256 + (col & 7) * 16) = make_uint4(nm | (nm << 16), nm, 0, 0);
  smem_at<uint4>(exb + (col >> 3) * 256 + 128 + (col & 7) * 16) = make_uint4(0, 0, 0, 0);
}
__device__ __forceinline__ void put_dsum(uint32_t exa, int e, float c) {
  const float hi = bf16r(c), mid = bf16r(c - hi), lo = bf16r((c - hi) - mid);
  smem_at<uint4>(exa + (e >> 3) * 256 + (e & 7) * 16) = make_uint4((__float_as_uint(hi) >> 16) | (__float_as_uint(mid) & 0xFFFF0000u), __float_as_uint(lo) >> 16, 0, 0);
  smem_at<uint4>(exa + (e >> 3) * 256 + 128 + (e & 7) * 16) = make_uint4(0, 0, 0, 0);
}
__host__ __device__ constexpr int min_c(int a, int b) { return a < b ? a : b; }
template<int V> using IC = std::integral_constant<int, V>;

#define CT(slot) do {} while (0)
#define PT(slot) do {} while (0)

template<int MAP>
__global__ void __cluster_dims__(2, 1, 1) __launch_bounds__(384, 1)
fnet_moe_kernel(const __grid_constant__ Params p) {
  constexpr int NX = MAP == 0 ? NX0 : 256;
  constexpr int G1_BYTES = A_BYTES + NX * 128;
  uint32_t sb;
  asm volatile("mov.u32 %0, %1;" : "=r"(sb) : "r"(smem_u32(smem_raw)));
  const int m = blockIdx.x & 1;
  int tau, eps;
  bool helper = false;
  if (MAP == 0) {
    uint32_t smid;
    asm volatile("mov.u32 %0, %%smid;" : "=r"(smid));
    const int c = smid >> 1, e7 = ((c - 32) * 37) >> 8;
    helper = c == 60 || c == 61;
    tau = c < 32 ? (c & 7) : (c < 60 ? c - 31 - 7 * e7 : 0);
    eps = c < 32 ? (c >> 3) : (c < 60 ? 4 + e7 : c - 58);
  } else {
    tau = (blockIdx.x >> 1) & 7; eps = blockIdx.x >> 4;
  }
  const int cid = tau * 16 + eps * 2 + m;
  const bool moe = tau > 0;
  auto BAR = [&](int i) { return sb + OFF_BAR + 8 * i; };
  const CUtensorMap* tmD = m ? &p.tmD1 : &p.tmD0;
  const uint64_t pol_ef = policy_evict_first();
#define LOAD_STREAM(d, tm, bar, c0, c1) tma_load_2d_hint(d, tm, bar, c0, c1, pol_ef)
#define LOAD_W(d, tm, bar, c0, grp) tma_load_4d_hint(d, tm, bar, c0, (grp) * 32, pol_ef)
  auto helper_load = [&](int k) {
    const uint32_t sa = sb + slot_of(k) * ST_BYTES, bar = BAR(B_FULL + slot_of(k));
    const CUtensorMap* tm = eps == 3 ? &p.tmD1 : &p.tmD0;
    tma_load_5d(sa, &p.tmXh, bar, (k & 15) * 64, 0);
    tma_load_2d(sa + A_BYTES, tm, bar, (k & 15) * 64, m * 512 + (k >> 4) * 256);
    tma_load_2d(sa + A_BYTES + 16384, tm, bar, (k & 15) * 64, m * 512 + (k >> 4) * 256 + 128);
  };
  if (threadIdx.x < 32 && elect_one()) {
    mbar_init(BAR(B_FULL), 1);
    asm volatile("fence.mbarrier_init.release.cluster;" ::: "memory");
    if (!helper) {
      tma_load_2d(sb + A_BYTES, &p.tmX, BAR(B_FULL), 0, tau * 256);
      tma_load_2d(sb, tmD, BAR(B_FULL), 0, eps * 128);
    }
    PT(52);
#pragma unroll
    for (int k = 1; k < 4; k++) mbar_init(BAR(B_FULL + k), 1);
    asm volatile("fence.mbarrier_init.release.cluster;" ::: "memory");
#pragma unroll
    for (int k = 0; k < 4; k++) mbar_expect_tx(BAR(B_FULL + k), helper ? ST_BYTES : G1_BYTES);
    if (!helper) {
#pragma unroll
      for (int k = 1; k < 4; k++) {
        tma_load_2d(sb + k * ST_BYTES + A_BYTES, &p.tmX, BAR(B_FULL + k), k * 64, tau * 256);
        LOAD_STREAM(sb + k * ST_BYTES, tmD, BAR(B_FULL + k), k * 64, eps * 128);
      }
    } else {
#pragma unroll 1
      for (int k = 0; k < 4; k++) helper_load(k);
    }
    PT(0);
  }
  __syncwarp();
  const int warp = __shfl_sync(0xffffffffu, threadIdx.x >> 5, 0);
  if (warp == 8) {
    if (elect_one()) {
#pragma unroll
      for (int b = B_EMPTY; b < B_COUNT; b++)
        mbar_init(BAR(b), b < B_EPI ? 2 : (b == B_EPI || b == B_EPI0B) ? 4 : (b < B_STD || b == B_OUT) ? 8 : (b == B_STAT || b == B_XS) ? 3 : 1);
      asm volatile("fence.mbarrier_init.release.cluster;" ::: "memory");
      mbar_expect_tx(BAR(B_XCH), 32768);
      SM_(uint32_t, OFF_SEEN) = 0;
    }
  }
  __syncthreads();

  if (warp >= 8) {
    reg_dec<REG_P>();
    asm volatile("barrier.cluster.arrive.relaxed.aligned;" ::: "memory");
    const int abrow = m * 1024 + eps * 128;
    const int f0 = (cid - 16) * 32;
    const CUtensorMap* tmWM = m ? &p.tmWM1 : &p.tmWM0;
    auto side_first = [&](int k) {
      if (NX < 256 && k == MINI_LOAD_K) {
        static_assert(NX == 256 || (mr_k(NREG_H) == MINI_LOAD_K && (NREG_H & 1) == 1), "second half of the staging buffer must be free");
        mbar_wait(BAR(B_STD + 3), 0);
        uint32_t n = 0;
        while (!((*(volatile uint32_t*)&SM_(uint32_t, OFF_SEEN) >> (4 * tau + 1)) & 1) && ++n < SPIN_LIMIT * 16) {}
        if (elect_one()) {
          mbar_expect_tx(BAR(B_A20), 12288);
          tma_load_2d(sb + OFF_MINI, &p.tmAbM, BAR(B_A20), tau * 256 + 240, abrow);
          LOAD_W(sb + OFF_MINI + 4096, tmWM, BAR(B_A20), tau * 256 + 240, tau * 2 + m);
          LOAD_W(sb + OFF_MINI + 8192, tmWM, BAR(B_A20), tau * 256 + 240, tau * 2 + 1 - m);
        }
      }
    };
    auto side = [&](int k) {
      if (NX < 256 && k == MINI_PF_K && elect_one()) tma_prefetch_4d(tmWM, tau * 256 + 240, tau * 64 + (eps & 1) * 32);
      if (k == WPF2_K && eps < WPF2_N && elect_one()) tma_prefetch_4d(m ? &p.tmW1 : &p.tmW0, kblock(tau, 31 - (eps >> 1)) * 64, tau * 64 + (eps & 1) * 32);
      if (!moe) return;
      const int i = k - MR_K0, r6 = i / MR_P, u = i - MR_P * r6, h = 2 * r6 + (u >> 1);
      if (i >= 0 && u < 4 && h < NREG_H) {
        if (h < 2) mbar_wait(BAR(B_STD + 2 + h), 0);
        if (elect_one()) {
          if (!(u & 1)) mbar_expect_tx(BAR(B_MR + (h & 1)), 16384);
          LOAD_STREAM(sb + OFF_XCH + u * 8192, (u & 1) ? &p.tmU : &p.tmG, BAR(B_MR + (h & 1)), f0, h * 128);
        }
      }
      if (k >= GU_K && k < GU_K + 2 && elect_one()) {
        static_assert(mr_k(NREG_H + 1) <= GU_K + 1 && MINI_K + 4 <= GU_K && GU_K < 47, "staging buffer must be free");
        LOAD_STREAM(sb + round_off(NREG_H + k - GU_K), &p.tmG, BAR(B_GU), f0, (NREG_H + k - GU_K) * 128);
        LOAD_STREAM(sb + round_off(NREG_H + k - GU_K) + 8192, &p.tmU, BAR(B_GU), f0, (NREG_H + k - GU_K) * 128);
      }
      if (k >= PF_K1 && !(k & 1) && elect_one()) {
        const int j = PF_N0 + ((k - PF_K1) >> 1);
        if (j < 8) tma_prefetch_2d(m ? &p.tmU : &p.tmG, f0, j * 128);
        else if (j < 12) asm volatile("cp.async.bulk.prefetch.L2.global [%0], %1;" :: "l"(p.wdown + (size_t)f0 * 1024 + (j - 8) * 8192), "r"(16384) : "memory");
      }
    };
    if (MAP == 0 && helper) {
      if (warp == 8) {
#pragma unroll 1
        for (int k = 4; k < 32; k++) {
          mbar_wait(BAR(B_EMPTY + slot_of(k)), (use_of(k) & 1) ^ 1);
          if (elect_one()) {
            mbar_expect_tx(BAR(B_FULL + slot_of(k)), ST_BYTES);
            helper_load(k);
            if (k == 12) mbar_arrive(BAR(B_LATE));
          }
        }
      } else {
        const int i0 = threadIdx.x - 288, lane = threadIdx.x & 31, col0 = (eps - 2) * 8 + m * 4;
        mbar_wait(BAR(B_LATE), 0);
        const uint32_t tag = ld_relaxed32(&p.s->epoch) + 1;
        if (i0 < 8) pkt_st128(&p.s->hflag[col0 * 2 + i0], 0, 0, 0, 0);
        SM_(uint32_t, OFF_TAG) = tag;
#pragma unroll 1
        for (int j0 = i0; j0 < 768; j0 += 384) {
          uint2 v[4]; uint32_t n = 0;
          while (true) {
#pragma unroll
            for (int z = 0; z < 4; z++) {
              const int j = j0 + 96 * z;
              v[z] = pkt_ld64(p.s->xstat + (j < 128 ? 256 * (j >> 4) + 240 + 2 * (j & 6) + ((j >> 2) & 2) + (j & 1)
                                          : j < 640 ? 2048 + col0 * 128 + j - 128 : (j - 640) * 16));
            }
            if (__all_sync(0xffffffffu, v[0].y == tag && v[1].y == tag && v[2].y == tag && v[3].y == tag) || ++n > SPIN_LIMIT) break;
            __nanosleep(300);
          }
#pragma unroll
          for (int z = 0; z < 4; z++) {
            const int j = j0 + 96 * z;
            if (j < 128) put_xstat(sb + OFF_RS, sb + OFF_XCH + 16384, j, v[z].x, eps - 2);
            else if (j < 640) put_dsum(sb + OFF_XCH, j - 128, __uint_as_float(v[z].x));
          }
        }
        fence_async_smem();
        __syncwarp();
        if (lane == 0) mbar_arrive(BAR(B_STAT));
      }
    } else if (warp == 8) {
      const CUtensorMap* tmW = m ? &p.tmW1 : &p.tmW0;
      const int gA = tau * 2 + m, gB = tau * 2 + 1 - m;
      auto wait_slot = [&](int k) {
        mbar_wait(BAR(B_EMPTY + slot_of(k)), (use_of(k) & 1) ^ 1);
        PT(64 + k);
      };
#pragma unroll 1
      for (int k = 4; k < 24; k++) {
        const int s = slot_of(k);
        const uint32_t sa = sb + s * ST_BYTES, sbb = sa + A_BYTES;
        const int kb = kblock(tau, k - 16);
        wait_slot(k);
        if (elect_one()) {
          mbar_expect_tx(BAR(B_FULL + s), k < 16 ? G1_BYTES : (k >> 1) == 9 ? B_BYTES : k == 20 ? ST_BYTES - 8192 : ST_BYTES);
          if (k < 16) {
            LOAD_STREAM(sa, tmD, BAR(B_FULL + s), k * 64, eps * 128);
            tma_load_2d(sbb, &p.tmX, BAR(B_FULL + s), k * 64, tau * 256);
          } else {
            LOAD_W(sbb, tmW, BAR(B_FULL + s), kb * 64, gA);
            LOAD_W(sbb + 16384, tmW, BAR(B_FULL + s), kb * 64, gB);
            if (k < 18) {
              tma_load_4d(sa, &p.tmXr, BAR(B_FULL + s), eps * 128, gA * 32 + s * 16);
              tma_load_4d(sa + 8192, &p.tmXr, BAR(B_FULL + s), eps * 128 + 64, gA * 32 + s * 16);
            }
          }
          if (k == PUB_K1) mbar_arrive(BAR(B_LATE));
          if (k >= WPF_K0 && k < WPF_K0 + WPF_N && (eps >> 1) == ((k - WPF_K0) & 3))
            tma_prefetch_4d(tmW, kblock(tau, k - WPF_K0) * 64, tau * 64 + (eps & 1) * 32);
          if (moe && k >= PF_K0 && k < PF_K0 + 2 * PF_N0 && !(k & 1)) tma_prefetch_2d(m ? &p.tmU : &p.tmG, f0, (k - PF_K0) * 64);
        }
      }
      uint32_t seen = 0;
#pragma unroll 1
      for (int k = 24; k < 48; k++) {
        const int s = slot_of(k);
        const uint32_t sa = sb + s * ST_BYTES, sbb = sa + A_BYTES;
        const int kb = kblock(tau, k - 16);
        const uint32_t need = (1u << kb) | ((kb & 3) == 3 ? 2u << (4 * tau) : 0u);
        wait_slot(k);
        side_first(k);
        if (elect_one()) {
          mbar_expect_tx(BAR(B_FULL + s), ST_BYTES);
          LOAD_W(sbb, tmW, BAR(B_FULL + s), kb * 64, gA);
          LOAD_W(sbb + 16384, tmW, BAR(B_FULL + s), kb * 64, gB);
        }
        uint32_t n = 0;
        while ((seen & need) != need && ++n < SPIN_LIMIT * 16) seen = *(volatile uint32_t*)&SM_(uint32_t, OFF_SEEN);
        if (elect_one()) tma_load_2d(sa, &p.tmAbL, BAR(B_FULL + s), kb * 64, abrow);
        side(k);
      }
      if (moe) {
        mbar_wait(BAR(B_EMPTY + 0), 1);
        if (elect_one()) { mbar_expect_tx(BAR(B_GU), (8 - NREG_H) * 16384); mbar_expect_tx(BAR(B_DN), 65536); }
#pragma unroll 1
        for (int i = 0; i < 10 - NREG_H; i++) {
          if (i == 3) mbar_wait(BAR(B_EMPTY + 1), 1);
          if (i == 4) {
            mbar_wait(BAR(B_EMPTY + 2), 1);
            mbar_wait(BAR(B_XCH), 0);
            PT(53);
          }
          const uint32_t dst = sb + late_off(i);
          if (elect_one()) {
            if (i < 6 - NREG_H) {
              LOAD_STREAM(dst, &p.tmG, BAR(B_GU), f0, (NREG_H + 2 + i) * 128);
              LOAD_STREAM(dst + 8192, &p.tmU, BAR(B_GU), f0, (NREG_H + 2 + i) * 128);
            } else {
#pragma unroll
              for (int b = 0; b < 4; b++) LOAD_STREAM(dst + b * 4096, &p.tmDn, BAR(B_DN), (4 * (i - 6 + NREG_H) + b) * 64, f0);
            }
          }
          const long long t0 = clock64();
          while (i < 9 - NREG_H && clock64() - t0 < MOE_PACE_CLK) {}
        }
      }
      const int lane = threadIdx.x & 31;
      mbar_wait(BAR(B_OUT), 0);
      const uint32_t km = SM_(uint32_t, OFF_WKEY + (lane & 7) * 8);
      const uint32_t bk = __reduce_max_sync(0xffffffffu, km);
      const int ww = __ffs(__ballot_sync(0xffffffffu, km == bk)) - 1;
#pragma unroll 1
      for (int i = 1; i <= 8; i++) {
        const int W = (ww + i) & 7;
        if (i == 8) {
          mbar_wait(BAR(B_XS), 0);
          if (SM_(uint32_t, OFF_KV) == bk) {
#pragma unroll 2
            for (int j = lane; j < 256; j += 32) {
              const int rho = j >> 4, row = row_of(gA * 128 + 32 * (W >> 1) + 8 * ((rho & 7) >> 1) + 4 * (W & 1) + 2 * (rho >> 3) + (rho & 1));
              const uint4 v = lds128_v(sb + OFF_OUT + (j & 8) * 2048 + (16 * W + rho) * 128 + (((j ^ rho) & 7) << 4));
              if (row != 0xFFFF - (int)(bk & 0xFFFFu))
                asm volatile("st.global.v4.b32 [%0], {%1, %2, %3, %4};" :: "l"(p.out + (size_t)row * 1024 + eps * 128 + (j & 15) * 8), "r"(v.x), "r"(v.y), "r"(v.z), "r"(v.w));
            }
            break;
          }
        }
        if (lane == 0) {
          tma_store_5d(&p.tmOut, sb + OFF_OUT + W * 2048, eps * 128, row_of(gA * 128 + 32 * (W >> 1) + 4 * (W & 1)));
          tma_store_5d(&p.tmOut, sb + OFF_OUT + 16384 + W * 2048, eps * 128 + 64, row_of(gA * 128 + 32 * (W >> 1) + 4 * (W & 1)));
        }
        const long long t0 = clock64();
        while (i < 7 && clock64() - t0 < OUT_PACE_CLK) {}
      }
      if (lane == 0) { bulk_commit(); bulk_wait_all(); }
      PT(22);
    } else {
      const int a = warp - 9;
      const int lane = threadIdx.x & 31;
      auto stage = [&](const bf16* src, int g) {
        if (elect_one()) {
          mbar_expect_tx(BAR(B_AUX + g), 16384);
          bulk_load(sb + OFF_XCH + g * 16384, src + g * 8192, 16384, BAR(B_AUX + g));
        }
      };
      uint32_t tag = 0;
#pragma unroll 1
      for (int i = 0; i < 3; i++) { i += keep_awake(); delay_clk<300>(); }
      mbar_wait(BAR(B_FULL + AUX_AFTER), 0);
      if (a == 0) PT(1);
      if (a == 1) mbar_wait(BAR(B_AUX + 0), 0);
      if (a < 2) stage(p.x + (size_t)cid * 16 * 1024, a);
#pragma unroll 1
      for (int it = 0; it < 4; it++) {
        const int g = it & 1;
        mbar_wait(BAR(B_AUX + g), it >> 1);
        if (a == 0) PT(2 + it);
        if (it == 2) tag = ld_relaxed32(&p.s->epoch) + 1;
        if (it == 2 && a == 2 && lane < 16) asm volatile("prefetch.global.L2 [%0];" :: "l"(p.wr + lane * 64));
        const uint32_t ad = sb + OFF_XCH + g * 16384 + (lane >> 2) * 2048;
        float s0 = 0.f, s1 = 0.f, q0 = 0.f, q1 = 0.f;
        auto row = [&](auto sq) {
#pragma unroll
          for (int i = 0; i < 11; i++) {
            if (i == 10 && a == 2) break;
            const uint4 v = lds128_v(ad + (((a * 44 + 4 * i + lane) & 127) << 4));
            const uint32_t ww[4] = {v.x, v.y, v.z, v.w};
#pragma unroll
            for (int z = 0; z < 4; z++) {
              const float d0 = bf_lo(ww[z]), d1 = bf_hi(ww[z]);
              s0 += d0; s1 += d1;
              if (decltype(sq)::value) { q0 = fmaf(d0, d0, q0); q1 = fmaf(d1, d1, q1); }
            }
          }
        };
        if (it < 2) row(IC<1>()); else row(IC<0>());
        s0 += s1; q0 += q1;
#pragma unroll
        for (int o = 1; o < 4; o <<= 1) { s0 += __shfl_xor_sync(0xffffffffu, s0, o); q0 += __shfl_xor_sync(0xffffffffu, q0, o); }
        if ((lane & 3) == 0) SM_(float2, OFF_PUB + a * 256 + it * 64 + (lane >> 2) * 8) = make_float2(s0, q0);
        if (it != 2) bar_sync(NB_AUX, 96);
        if (it < 2 && a == 2) stage(cid < 64 ? p.Dre + (size_t)cid * 16 * 1024 : p.Dim + (size_t)(cid - 64) * 16 * 1024, g);
      }
      if (a == 1) {
        const float2 v0 = SM_(float2, OFF_PUB + lane * 8), v1 = SM_(float2, OFF_PUB + 256 + lane * 8), v2 = SM_(float2, OFF_PUB + 512 + lane * 8);
        const float s = v0.x + v1.x + v2.x, mean = s * (1.f / 1024.f);
        const float rs = rcp_fast(ln_sd((v0.y + v1.y + v2.y) * (1.f / 1024.f) - mean * mean));
        pkt_st64((lane < 16 ? p.s->xstat : p.s->dsum) + cid * 16 + (lane & 15), lane < 16 ? pack_bf16(rs, mean) : __float_as_uint(s), tag);
        PT(6);
      }
      if (a == 2) {
        float s = 0.f;
#pragma unroll
        for (int q = 0; q < 4; q++) {
          const uint4 v = ldg_nc128(p.wr + (q * 32 + lane) * 8);
          s += ((bf_lo(v.x) + bf_hi(v.x)) + (bf_lo(v.y) + bf_hi(v.y))) + ((bf_lo(v.z) + bf_hi(v.z)) + (bf_lo(v.w) + bf_hi(v.w)));
          const int ch = q * 32 + lane - eps * 16;
          if (ch >= 0 && ch < 16) {
            SM_(uint32_t, OFF_WR + ch * 4) = v.x; SM_(uint32_t, OFF_WR + 80 + ch * 4) = v.y;
            SM_(uint32_t, OFF_WR + 160 + ch * 4) = v.z; SM_(uint32_t, OFF_WR + 240 + ch * 4) = v.w;
          }
        }
        s = warp_sum(s);
        if (lane == 0) { SM_(float, OFF_WSUM) = s; SM_(uint32_t, OFF_TAG) = tag; }
      }
      if (a < 2) __nanosleep(GATHER_NS);
      {
        const int i0 = a * 32 + lane;
        uint2 v[3], c0, c1; uint32_t n = 0;
        const uint2* dp = &p.s->dsum[abrow];
        while (true) {
#pragma unroll
          for (int q = 0; q < 3; q++) v[q] = pkt_ld64(&p.s->xstat[tau * 256 + min(i0 + 96 * q, 255)]);
          c0 = pkt_ld64(dp + i0); c1 = pkt_ld64(dp + min(i0 + 96, 127));
          if (__all_sync(0xffffffffu, v[0].y == tag && v[1].y == tag && v[2].y == tag && c0.y == tag && c1.y == tag) || ++n > SPIN_LIMIT) break;
          __nanosleep(200);
        }
#pragma unroll
        for (int q = 0; q < 3; q++) put_xstat(sb + OFF_RS, sb + OFF_EXB, min(i0 + 96 * q, 255), v[q].x, m);
        put_dsum(sb + OFF_EXA, i0, __uint_as_float(c0.x));
        put_dsum(sb + OFF_EXA, min(i0 + 96, 127), __uint_as_float(c1.x));
        fence_async_smem();
      }
      __syncwarp();
      if (lane == 0) mbar_arrive(BAR(B_STAT));
      if (a == 0) PT(7);
      if (a == 0) {
        const int sg = (lane >> 2) == tau ? sigma_of(tau, 0) : lane >> 2;
        const uint32_t* flg = reinterpret_cast<const uint32_t*>(&p.s->abflag[((eps * 2 + m) * 8 + sg) * 2]) + ((lane >> 2) == tau ? 4 : lane & 3);
        if (NX < 256 && lane == 4 * tau + 1) flg = reinterpret_cast<const uint32_t*>(&p.s->hflag[(m * 8 + eps) * 2]);
        uint32_t seen = 0;
        auto until = [&](int tile) {
          uint32_t n = 0;
          while (!((seen >> (4 * tile)) & 1) && ++n < SPIN_LIMIT) seen = __ballot_sync(0xffffffffu, ld_relaxed32(flg) == tag);
        };
        const int s0 = sigma_of(tau, 0), s1 = sigma_of(tau, 1), s2 = sigma_of(tau, 2), s3 = sigma_of(tau, 3);
        mbar_wait(BAR(B_EPI), 0);
        mbar_wait(BAR(B_FULL + 0), 0);
        mbar_wait(BAR(B_FULL + 1), 0);
        if (elect_one()) mbar_expect_tx(BAR(B_A20), 8192);
        mbar_wait(BAR(B_STDA), 0);
        PT(49);
        until(tau);
        mbar_wait(BAR(B_EPI0B), 0);
        PT(48);
        if (elect_one()) tma_load_2d(sb + OFF_XCH, &p.tmAbS, BAR(B_FULL + 0), s0 * 256, abrow);
        mbar_wait(BAR(B_FULL + 2), 0);
        mbar_wait(BAR(B_STD + 0), 0);
        until(s0);
        PT(16);
        if (elect_one()) tma_load_2d(sb + OFF_XCH + 8192, &p.tmAbS, BAR(B_A20), s0 * 256, abrow + 64);
        until(s1);
        PT(17);
        if (elect_one()) tma_load_2d(sb + OFF_XCH + 16384, &p.tmAbL, BAR(B_FULL + 1), s1 * 256, abrow);
        until(s2);
        PT(18);
        if (elect_one()) {
          tma_load_2d(sb + 2 * ST_BYTES, &p.tmAbL, BAR(B_FULL + 2), s2 * 256, abrow);
          mbar_arrive(BAR(B_PUB1));
        }
        until(s3);
        mbar_wait(BAR(B_FULL + 3), 0);
        mbar_wait(BAR(B_STD + 1), 0);
        PT(19);
        if (elect_one()) tma_load_2d(sb + 3 * ST_BYTES, &p.tmAbL, BAR(B_FULL + 3), s3 * 256, abrow);
        uint32_t n = 0;
        while (true) {
          asm volatile("fence.proxy.async.global;" ::: "memory");
          *(volatile uint32_t*)&SM_(uint32_t, OFF_SEEN) = seen;
          if (seen == 0xFFFFFFFFu || ++n > SPIN_LIMIT) break;
          seen = __ballot_sync(0xffffffffu, ld_relaxed32(flg) == tag);
          __nanosleep(100);
        }
      } else {
        uint32_t* flag = reinterpret_cast<uint32_t*>(&p.s->abflag[((eps * 2 + m) * 8 + tau) * 2]);
        mbar_wait(BAR(a == 1 ? B_EPI : B_EPI0B), 0);
        if (a == 1) PT(8);
        if (lane == 0) {
          tma_store_2d(&p.tmAbS, sb + chunk_off(0, a - 1), tau * 256, abrow + (a - 1) * 64);
          bulk_commit();
          bulk_wait_release();
        }
        if (a == 2) mbar_wait(BAR(B_STDA), 0);
        if (lane == 0) {
          st_relaxed32(flag + (a == 1 ? 4 : 0), tag);
          mbar_arrive(BAR(a == 1 ? B_STDA : B_STD));
        }
        if (a == 2) PT(12);
        if (a == 1) {
          mbar_wait(BAR(B_EPI + 1), 0);
          mbar_wait(BAR(B_LATE), 0);
          mbar_wait(BAR(B_PUB1), 0);
          PT(9);
          if (lane == 0) {
            tma_store_2d(&p.tmAbS, sb + chunk_off(1, 0), tau * 256 + 64, abrow);
            tma_store_2d(&p.tmAbS, sb + chunk_off(1, 1), tau * 256 + 64, abrow + 64);
            bulk_commit();
            bulk_wait_all();
            mbar_arrive(BAR(B_STD + 1));
            bulk_wait_release();
            st_relaxed32(flag + 1, tag);
          }
          PT(13);
        }
        auto copy_out = [&](int c) {
          mbar_wait(BAR(B_EPI + c), 0);
          PT(8 + c);
          bf16* dst = p.s->abT + (size_t)(abrow + (lane >> 3)) * 2048 + tau * 256 + c * 64 + (lane & 7) * 8;
          const uint32_t src = sb + chunk_off(c, 0) + (lane >> 3) * 128 + (((lane & 7) ^ (lane >> 3)) << 4);
          const uint32_t on = c * 64 + (lane & 7) * 8 < NX;
#pragma unroll 4
          for (int i = 0; i < 32; i++) {
            const uint4 v = lds128_v((src ^ ((i & 1) << 6)) + i * 512);
            asm volatile("{\n.reg .pred p;\nsetp.ne.b32 p, %5, 0;\n@p st.global.v4.b32 [%0], {%1, %2, %3, %4};\n}\n"
                         :: "l"(dst + i * 4 * 2048), "r"(v.x), "r"(v.y), "r"(v.z), "r"(v.w), "r"(on));
          }
          __syncwarp();
          if (lane == 0) mbar_arrive(BAR(B_STD + c));
        };
        if (a == 2) {
#pragma unroll 1
          for (int c = 2; c < 4; c++) copy_out(c);
          asm volatile("fence.acq_rel.gpu;" ::: "memory");
          __syncwarp();
          if (lane < 2) st_relaxed32(flag + 2 + lane, tag);
          PT(15);
        }
      }
      {
        mbar_wait(BAR(B_LATE), 1);
        const int grp = tau * 2 + m;
#pragma unroll 1
        for (int i = a; i < 14; i += 3) {
          uint4* dst = i < 8 ? &p.s->ypart[cid * 256 + i * 32 + lane] : i < 12 ? &p.s->hstat[(grp * 8 + eps) * 128 + (i - 8) * 32 + lane]
                     : i == 12 ? &p.s->cand[grp * 256 + eps * 32 + lane] : &p.s->key[(((lane >> 1) & 7) * 16 + grp) * 2 + (lane & 1)];
          if (i < 13 || eps == 0) pkt_st128(dst, 0, 0, 0, 0);
          __nanosleep(200);
        }
        __syncwarp();
        if (lane == 0) mbar_arrive(BAR(B_STAT));
      }
      {
        const uint4* kp = &p.s->key[(tau * 16 + (lane & 15)) * 2];
        const int i0 = a * 32 + lane;
        mbar_wait(BAR(B_KEY), 0);
        if (a == 0) PT(43);
        uint4 kq = pkt_ld128(kp), cv[3] = {};
        uint32_t n = 0, kv;
        int gspec = -1;
        while (true) {
          const bool ok = kq.y == tag && kq.w == tag;
          kv = __reduce_max_sync(0xffffffffu, ok ? kq.x : 0u);
          const int gs = group_of(0xFFFF - (int)(kv & 0xFFFFu));
          const bool cok = gs == gspec && cv[0].y == tag && cv[0].w == tag && cv[1].y == tag && cv[1].w == tag && cv[2].y == tag && cv[2].w == tag;
          if (__all_sync(0xffffffffu, ok && cok) || ++n > SPIN_LIMIT) break;
          if (!ok) kq = pkt_ld128(kp);
          n += keep_awake();
          const bool spec = __popc(__ballot_sync(0xffffffffu, ok)) >= 2 * SPEC_MIN;
          if (!cok && spec) {
#pragma unroll
            for (int i = 0; i < 3; i++) cv[i] = pkt_ld128(&p.s->cand[gs * 256 + min(i0 + 96 * i, 255)]);
          }
          if (spec) gspec = gs;
        }
        if (a == 0) PT(45);
        const uint32_t ms = __shfl_sync(0xffffffffu, kq.z, gspec);
        const uint32_t nm = ((ms & 0xFFFFu) ^ 0x8000u) * 0x10001u;
        const float is = rcp_fast(bf_hi(ms));
#pragma unroll
        for (int i = 0; i < 3; i++) {
          const int j = min(i0 + 96 * i, 255);
          SM_(uint2, OFF_XSEL + j * 8) = make_uint2(norm2(cv[i].x, nm, is), norm2(cv[i].z, nm, is));
        }
#pragma unroll
        for (int i = 0; i < 3; i++) SM_(uint2, OFF_HSEL + min(i0 + 96 * i, 255) * 8) = make_uint2(cv[i].x, cv[i].z);
        SM_(uint32_t, OFF_KV) = kv;
        __syncwarp();
        if (lane == 0) mbar_arrive(BAR(B_XS));
      }
    }
    asm volatile("barrier.cluster.wait.aligned;" ::: "memory");
  } else {
    reg_inc<REG_C>();
    const int tid = __shfl_sync(0xffffffffu, threadIdx.x, threadIdx.x & 31), lane = tid & 31;
    const int w = warp >> 2, wi = warp & 3, t = tid & 127;
    const int g = lane >> 2, q = lane & 3;
    const int turn_me = NB_TURN0 + w, turn_other = NB_TURN1 - w;
    auto release = [&](int s) { if (t == 0) mbar_arrive(BAR(B_EMPTY + s)); };
    if (MAP == 0 && helper) {
      asm volatile("barrier.cluster.arrive.relaxed.aligned;" ::: "memory");
      float s0[64], s1[64];
#pragma unroll
      for (int i = 0; i < 64; i++) { s0[i] = 0.f; s1[i] = 0.f; }
      if (w == 1) bar_arrive(NB_TURN0, 256);
      uint32_t o[32][2] = {};
      const int col = (eps - 2) * 8 + m * 4 + w;
      auto put = [&](auto tc, uint32_t buf) {
        constexpr int tl = decltype(tc)::value;
#pragma unroll
        for (int i = 0; i < 4; i++)
          smem_at<uint2>(buf + ((i >> 1) * 64 + wi * 16 + (i & 1) * 8 + g) * 32 + ((q * 8) ^ ((g & 4) << 2))) = make_uint2(o[8 * i + tl][0], o[8 * i + tl][1]);
      };
      auto publish = [&](int c) { if (t == 0) { bulk_wait_release(); st_relaxed32(&p.s->hflag[c * 2], SM_(uint32_t, OFF_TAG)); } };
#pragma unroll 1
      for (int pass = 0; pass < 2; pass++) {
#pragma unroll 1
        for (int k = 16 * pass; k < 16 * pass + 16; k++) {
          const int s = slot_of(k);
          mbar_wait(BAR(B_FULL + s), use_of(k) & 1);
          bar_sync(turn_me, 256);
          const uint64_t da = make_desc(sb + s * ST_BYTES + A_BYTES + w * 16384), db = make_desc(sb + s * ST_BYTES);
          wgmma_fence();
#pragma unroll
          for (int kk = 0; kk < 4; kk++) {
            wgmma_n128(s0, da + kk * 2, db + kk * 2, kk > 0 || (k & 15));
            wgmma_n128(s1, da + 512 + kk * 2, db + kk * 2, kk > 0 || (k & 15));
          }
          wgmma_commit();
          if (k < 31 || w == 0) bar_arrive(turn_other, 256);
          if (pass && !(k & 1)) {
            const uint32_t buf = sb + OFF_XCH + 20480 + w * 4096;
            static_for<8>([&](auto ic) { if (k == 16 + 2 * decltype(ic)::value) put(ic, buf); });
            fence_async_smem();
            bar_sync(NB_WG0 + w, 128);
            if (t == 0) { tma_store_2d(&p.tmAbM, buf, (k - 16) * 128 + 240, col * 128); bulk_commit(); }
          }
          wgmma_wait0();
          release(s);
          if ((k & 1) && t == 0) asm volatile("cp.async.bulk.wait_group.read 0;" ::: "memory");
        }
        if (pass) publish(col);
        mbar_wait(BAR(B_STAT), 0);
        wgmma_fence();
        wgmma_n128(s0, make_desc_noswz(sb + OFF_XCH + pass * 8192 + w * 4096), make_desc_noswz(sb + OFF_XCH + 16384));
        wgmma_n128(s1, make_desc_noswz(sb + OFF_XCH + pass * 8192 + w * 4096 + 2048), make_desc_noswz(sb + OFF_XCH + 16384));
        wgmma_commit();
        uint4 rs[4];
#pragma unroll
        for (int i = 0; i < 4; i++) rs[i] = lds128_v(sb + OFF_RS + q * 144 + i * 16);
        wgmma_wait0();
        fence_acc(s0); fence_acc(s1);
#pragma unroll
        for (int i = 0; i < 32; i++) {
          const int tl = i & 7, hr = (i >> 3) & 1;
          const float* ac = (i >> 4) ? &s1[8 * tl + 2 * hr] : &s0[8 * tl + 2 * hr];
          o[i][0] = bmul2(pack_bf16(ac[0], ac[1]), (tl & 1) ? rs[tl >> 1].z : rs[tl >> 1].x);
          o[i][1] = bmul2(pack_bf16(ac[4], ac[5]), (tl & 1) ? rs[tl >> 1].w : rs[tl >> 1].y);
        }
      }
      static_for<8>([&](auto ic) { put(ic, sb + (w * 8 + decltype(ic)::value) * 4096); });
      fence_async_smem();
      bar_sync(NB_WG0 + w, 128);
      if (t == 0) {
#pragma unroll 1
        for (int i = 0; i < 8; i++) tma_store_2d(&p.tmAbM, sb + (w * 8 + i) * 4096, i * 256 + 240, (col + 2) * 128);
        bulk_commit();
      }
      publish(col + 2);
      asm volatile("barrier.cluster.wait.aligned;" ::: "memory");
      return;
    }
    float acc[128], a1[NX / 2];
#pragma unroll
    for (int i = 0; i < NX / 2; i++) a1[i] = 0.f;
    if (w == 1) bar_arrive(NB_TURN0, 256);
    auto kstep = [&](auto& d, int k, bool first, bool a_in_xch = false, bool mini = false) {
      const int s = slot_of(k);
      mbar_wait(BAR(B_FULL + s), use_of(k) & 1);
      CT(64 + k);
      bar_sync(turn_me, 256);
      const uint64_t da = make_desc(sb + (a_in_xch ? OFF_XCH + s * 16384 : s * ST_BYTES) + w * 8192), db = make_desc(sb + s * ST_BYTES + A_BYTES);
      wgmma_fence();
      wgmma_g1(d, da, db, !first);
#pragma unroll
      for (int kk = 1; kk < 4; kk++) wgmma_g1(d, da + kk * 2, db + kk * 2, 1);
      wgmma_commit();
      if (mini) {
        CT(29);
        mbar_wait(BAR(B_A20), 1);
        CT(30);
        wgmma_fence();
        wgmma_g1(d, make_desc_32b(sb + OFF_MINI + w * 2048), make_desc_32b(sb + OFF_MINI + 4096), 1);
        wgmma_commit();
      }
      bar_arrive(turn_other, 256);
    };
    auto kdone = [&](int k) { wgmma_wait0(); release(slot_of(k)); };
    auto wgmma_wait1 = [&]() { asm volatile("wgmma.wait_group.sync.aligned 1;" ::: "memory"); };

#pragma unroll 1
    for (int k = 0; k < 14; k++) {
      kstep(a1, k, k == 0);
      if (k == 0) CT(0);
      if (k == 8 && warp == 2 && lane < 2) pkt_st128(&p.s->abflag[((eps * 2 + m) * 8 + tau) * 2 + lane], 0, 0, 0, 0);
      kdone(k);
    }
    uint32_t R[64];
    uint32_t tag;
    {
      const uint32_t rsa = sb + OFF_RS + q * 144;
      const uint64_t da2 = make_desc(sb + 2 * ST_BYTES + w * 8192), db2 = make_desc(sb + 2 * ST_BYTES + A_BYTES);
      const uint64_t da3 = make_desc(sb + 3 * ST_BYTES + w * 8192), db3 = make_desc(sb + 3 * ST_BYTES + A_BYTES);
      mbar_wait(BAR(B_FULL + 2), 1);
      CT(64 + 14);
      bar_sync(turn_me, 256);
      wgmma_fence();
#pragma unroll
      for (int kk = 0; kk < 4; kk++) wgmma_g1(a1, da2 + kk * 2, db2 + kk * 2, 1);
      wgmma_commit();
      mbar_wait(BAR(B_FULL + 3), 1);
      CT(64 + 15);
      wgmma_fence();
      wgmma_g1(a1, da3, db3, 1);
      wgmma_g1(a1, da3 + 2, db3 + 2, 1);
      wgmma_commit();
      mbar_wait(BAR(B_STAT), 0);
      tag = SM_(uint32_t, OFF_TAG);
#pragma unroll
      for (int i = 0; i < 8; i++) { const uint4 v = lds128_v(rsa + i * 16); R[8 * i] = v.x; R[8 * i + 2] = v.y; R[8 * i + 4] = v.z; R[8 * i + 6] = v.w; }
      wgmma_wait1();
      release(2);
      wgmma_fence();
      wgmma_g1(a1, da3 + 4, db3 + 4, 1);
      wgmma_g1(a1, da3 + 6, db3 + 6, 1);
      wgmma_g1(a1, make_desc_noswz(sb + OFF_EXA + w * 2048), make_desc_noswz(sb + OFF_EXB), 1);
      wgmma_commit();
      bar_arrive(turn_other, 256);
      kdone(15);
      mbar_wait(BAR(B_STAT), 0);
    }
    fence_acc(a1);
    CT(1);
    auto pack = [&](auto cc) {
      constexpr int c = decltype(cc)::value;
#pragma unroll
      for (int j = 8 * c; j < min_c(8 * c + 8, NX / 8); j++) {
        const uint32_t rs = R[2 * j];
        const float* ac = &a1[4 * j];
        R[2 * j] = bmul2(pack_bf16(ac[0], ac[1]), rs);
        R[2 * j + 1] = bmul2(pack_bf16(ac[2], ac[3]), rs);
      }
    };
    auto put_chunk = [&](auto cc) {
      constexpr int c = decltype(cc)::value;
      const int rho = 16 * wi + (lane & 15);
#pragma unroll
      for (int j = 8 * c; j < min_c(8 * c + 8, NX / 8); j += 2) {
        const int chunk = (j & 7) + (lane >> 4);
        stsm_x4(sb + chunk_off(c, w) + rho * 128 + ((chunk ^ (lane & 7)) << 4), R[2 * j], R[2 * j + 1], R[2 * j + 2], R[2 * j + 3]);
      }
    };
    auto staged = [&](int bar) {
      fence_async_smem();
      __syncwarp();
      if (lane == 0) mbar_arrive(BAR(bar));
    };
    auto mma_rs = [&](auto cc, auto k0, auto k1) {
      constexpr int c = decltype(cc)::value;
      const uint64_t db = make_desc(sb + c * ST_BYTES + A_BYTES);
#pragma unroll
      for (int kk = decltype(k0)::value; kk < decltype(k1)::value; kk++)
        wgmma_n256_rs(acc, R[16 * c + 4 * kk], R[16 * c + 4 * kk + 1], R[16 * c + 4 * kk + 2], R[16 * c + 4 * kk + 3], db + kk * 2, c + kk > 0);
      wgmma_commit();
    };
    auto kdone_x = [&](int k, auto ic) {
      constexpr int i = decltype(ic)::value;
      uint32_t r[8];
#pragma unroll
      for (int z = 0; z < 2; z++) {
        const int tr = 32 * (i & 1) + 16 * z + 8 * (lane >> 4) + (lane & 7), chunk = 2 * wi + ((lane >> 3) & 1);
        ldsm_x4_t(sb + (i >> 1) * ST_BYTES + w * 8192 + tr * 128 + ((chunk ^ (lane & 7)) << 4), r[4 * z], r[4 * z + 1], r[4 * z + 2], r[4 * z + 3]);
      }
      float f[16];
#pragma unroll
      for (int z = 0; z < 8; z++) { f[2 * z] = bf_lo(r[z]); f[2 * z + 1] = bf_hi(r[z]); }
#pragma unroll
      for (int z = 0; z < 16; z++) asm volatile("" : "+f"(f[z]));
      kdone(k);
#pragma unroll
      for (int z = 0; z < 16; z++) asm volatile("add.f32 %0, %0, %1;" : "+f"(acc[16 * i + z]) : "f"(f[z]));
    };
    pack(IC<0>());
    put_chunk(IC<0>());
    staged(w ? B_EPI0B : B_EPI);
    mbar_wait(BAR(B_STAT), 0);
    CT(21);
    pack(IC<1>());
    pack(IC<2>());
    pack(IC<3>());
#pragma unroll
    for (int i = 16; i < NX / 4; i++) asm volatile("" : "+r"(R[i]));
#pragma unroll
    for (int i = 0; i < 128; i++) asm volatile("" : "=f"(acc[i]));
    mbar_wait(BAR(B_FULL + 0), 0);
    CT(2);
    CT(64 + 16);
    bar_sync(turn_me, 256);
    wgmma_fence();
    mma_rs(IC<0>(), IC<0>(), IC<4>());
    mbar_wait(BAR(B_FULL + 1), 0);
    CT(64 + 17);
    wgmma_fence();
    mma_rs(IC<1>(), IC<0>(), IC<2>());
    wgmma_wait1();
    release(0);
    mma_rs(IC<1>(), IC<2>(), IC<4>());
    bar_arrive(turn_other, 256);
    kdone_x(17, IC<0>());
    static_for<2>([&](auto ic) {
      constexpr int c = 2 + decltype(ic)::value;
      mbar_wait(BAR(B_FULL + c), 0);
      CT(64 + 16 + c);
      bar_sync(turn_me, 256);
      wgmma_fence();
      mma_rs(IC<c>(), IC<0>(), IC<min_c(4, NX / 16 - 4 * c)>());
      bar_arrive(turn_other, 256);
      if (c == 2) { put_chunk(IC<1>()); staged(B_EPI + 1); }
      kdone_x(16 + c, IC<c - 1>());
    });
#pragma unroll 1
    for (int k = 20; k < 23; k++) {
      if (w == 1) mbar_wait(BAR(B_A20), 0);
      kstep(acc, k, false, k < 22);
      if (k == 20) {
        kdone_x(k, IC<3>());
      } else {
        if (k == 21) put_chunk(IC<2>()); else put_chunk(IC<3>());
        __syncwarp();
        if (lane == 0) mbar_arrive(BAR(B_EPI + k - 19));
        kdone(k);
      }
    }
    uint32_t wf[32][4];
    auto load_wf = [&](auto hc) {
      constexpr int h = decltype(hc)::value;
      const int d = w * 64 + (lane >> 4) * 8 + (lane & 7);
      const uint32_t ad = sb + round_off(h) + (lane & 8) * 1024 + d * 64 + ((wi ^ ((lane >> 1) & 3)) << 4);
#pragma unroll
      for (int i = 0; i < 4; i++) ldsm_x4_t(ad + i * 1024, wf[4 * h + i][0], wf[4 * h + i][1], wf[4 * h + i][2], wf[4 * h + i][3]);
    };
    auto load_wf_rest = [&]() { static_for<8 - NREG_H>([&](auto ic) { load_wf(IC<NREG_H + decltype(ic)::value>()); }); };
#pragma unroll
    for (int i = 0; i < 4 * NREG_H; i++) { wf[i][0] = 0; wf[i][1] = 0; wf[i][2] = 0; wf[i][3] = 0; }
    const int grp = tau * 2 + m;
#pragma unroll 1
    for (int k = 23; k < 46; k++) {
      kstep(acc, k, false, false, NX < 256 && k == MINI_K);
      if (moe) {
        static_for<NREG_H>([&](auto hc) {
          constexpr int h = decltype(hc)::value;
          if (k == mr_k(h) + 1) { mbar_wait(BAR(B_MR + (h & 1)), (h >> 1) & 1); CT(32 + h); load_wf(hc); }
        });
      }
      if (k == RESET_K && tid == 0) mbar_arrive(BAR(B_LATE));
      kdone(k);
    }
    asm volatile("barrier.cluster.arrive.relaxed.aligned;" ::: "memory");
    mbar_wait(BAR(B_STAT), 1);
    uint32_t wa[16][2];
    uint32_t cd = code_of(tag);
    uint4* hp_pub = &p.s->hstat[(grp * 8 + eps) * 128 + warp * 16 + g];
    const uint4* hp_poll = &p.s->hstat[(grp * 8 + 2 * q) * 128 + warp * 16 + g];
    const uint32_t vec_off = (2 * wi) * 512 + q * 128 + ((g ^ (2 * q)) << 4);
    {
      float as[64], ak[64];
      fence_acc(acc);
#pragma unroll
      for (int i = 0; i < 64; i++) asm volatile("mov.b32 %0, %1;" : "=f"(as[i]) : "f"(acc[64 + i]));
#pragma unroll
      for (int i = 0; i < 64; i++) asm volatile("mov.b32 %0, %1;" : "=f"(ak[i]) : "f"(acc[i]));
      const uint64_t da1 = make_desc(sb + 2 * ST_BYTES + w * 8192), db1 = make_desc(sb + 2 * ST_BYTES + A_BYTES);
      const uint64_t da2 = make_desc(sb + 3 * ST_BYTES + w * 8192), db2 = make_desc(sb + 3 * ST_BYTES + A_BYTES);
      mbar_wait(BAR(B_FULL + 2), 1);
      CT(64 + 46);
      bar_sync(turn_me, 256);
      wgmma_fence();
#pragma unroll
      for (int kk = 0; kk < 4; kk++) wgmma_n128(as, da1 + kk * 2, db1 + 1024 + kk * 2);
      wgmma_commit();
      mbar_wait(BAR(B_FULL + 3), 1);
      CT(64 + 47);
      wgmma_fence();
#pragma unroll
      for (int kk = 0; kk < 4; kk++) wgmma_n128(as, da2 + kk * 2, db2 + 1024 + kk * 2);
      wgmma_commit();
      bar_arrive(turn_other, 256);
      const uint32_t rx = mapa(sb + OFF_PEER + w * 4096 + vec_off, 1 - m), rb = mapa(BAR(B_XCH), 1 - m);
      asm volatile("barrier.cluster.wait.aligned;" ::: "memory");
      CT(24);
      wgmma_wait0();
      fence_acc(as);
      CT(25);
      auto keep = [&]() {
        bar_sync(turn_me, 256);
        wgmma_fence();
#pragma unroll
        for (int kk = 0; kk < 4; kk++) wgmma_n128(ak, da1 + kk * 2, db1 + kk * 2);
        wgmma_commit();
#pragma unroll
        for (int kk = 0; kk < 4; kk++) wgmma_n128(ak, da2 + kk * 2, db2 + kk * 2);
        wgmma_commit();
        if (w == 0) bar_arrive(turn_other, 256);
      };
#pragma unroll
      for (int i = 0; i < 8; i++) {
        if (i == SEND_FIRST) keep();
        const float* ac = &as[16 * (i >> 1) + 2 * (i & 1)];
        st_async_v4(rx + (i >> 1) * 8192 + (i & 1) * 512, rb, pack_bf16(ac[0], ac[1]), pack_bf16(ac[4], ac[5]), pack_bf16(ac[8], ac[9]), pack_bf16(ac[12], ac[13]));
      }
      CT(26);
#pragma unroll
      for (int i = 0; i < 4; i++) {
        const uint4 v = lds128_v(sb + OFF_WR + q * 80 + i * 16);
        const uint32_t vv[4] = {v.x, v.y, v.z, v.w};
#pragma unroll
        for (int z = 0; z < 4; z++) {
          asm volatile("{\n.reg .pred p;\nsetp.ne.b32 p, %2, 0;\nselp.b32 %0, %1, 0x3F803F80, p;\n}" : "=r"(wa[4 * i + z][0]) : "r"(vv[z]), "r"(g & 1));
          asm volatile("{\n.reg .pred p;\nsetp.ne.b32 p, %2, 0;\nselp.b32 %0, %1, 0x3F803F80, p;\n}" : "=r"(wa[4 * i + z][1]) : "r"(vv[z]), "r"(g & 1));
        }
      }
      pin(cd); pin(hp_pub); pin(hp_poll);
      CT(27);
      wgmma_wait1();
      release(2);
      wgmma_wait0();
      fence_acc(ak);
      CT(3);
#pragma unroll
      for (int i = 0; i < 8; i++) {
        const float* ac = &ak[16 * (i >> 1) + 2 * (i & 1)];
        sts128(sb + (2 + (i >> 2)) * ST_BYTES + w * 8192 + ((i >> 1) & 1) * 4096 + (i & 1) * 512 + vec_off,
               pack_bf16(ac[0], ac[1]), pack_bf16(ac[4], ac[5]), pack_bf16(ac[8], ac[9]), pack_bf16(ac[12], ac[13]));
      }
    }
    uint32_t h[8][4];
    {
      const int qq = 2 * (warp & 1) + ((lane >> 3) & 1);
      const uint32_t lo = (lane >> 4) * 512 + qq * 128 + (((lane & 7) ^ (2 * qq)) << 4);
      bar_sync(NB_BOTH, 256);
#pragma unroll
      for (int ks = 0; ks < 8; ks++)
        ldsm_x4_t(sb + (2 + w) * ST_BYTES + (ks >> 2) * 8192 + (wi >> 1) * 4096 + (ks & 3) * 1024 + lo, h[ks][0], h[ks][1], h[ks][2], h[ks][3]);
      CT(28);
      mbar_wait_cluster(BAR(B_XCH), 0);
      CT(4);
      uint32_t r[8][4];
#pragma unroll
      for (int ks = 0; ks < 8; ks++) ldsm_x4_t(sb + OFF_PEER + (warp >> 1) * 8192 + ks * 1024 + lo, r[ks][0], r[ks][1], r[ks][2], r[ks][3]);
      float d[4][4] = {};
#pragma unroll
      for (int ks = 0; ks < 8; ks++) {
#pragma unroll
        for (int i = 0; i < 4; i++) {
          h[ks][i] = badd2(h[ks][i], r[ks][i]);
          mma1688(d[i], h[ks][i], wa[2 * ks + (i >> 1)][i & 1], h[ks][i]);
        }
      }
#pragma unroll
      for (int i = 0; i < 2; i++) {
        const float sq = (g & 1) ? d[i][1] + d[i + 2][1] : d[i][0] + d[i + 2][0];
        const float e0 = d[i][2] + d[i + 2][2], e1 = d[i][3] + d[i + 2][3];
        const float other = __shfl_xor_sync(0xffffffffu, (g & 1) ? e0 : e1, 4);
        if (q == (g >> 1)) pkt_st128(hp_pub + 8 * i, with_bit((g & 1) ? other : e0, cd), with_bit(sq, cd >> 1), __float_as_uint((g & 1) ? e1 : other), tag);
      }
    }
    CT(5);
    if (tid == 0) mbar_arrive(BAR(B_KEY));
    delay_clk<HOP1_DELAY>();
    float m_bf, sd, inv_sd, r_bf;
    uint4* key_pub = &p.s->key[((lane & 7) * 16 + grp) * 2];
    uint4* cand_pub = &p.s->cand[grp * 256 + eps * 32 + q];
    uint32_t trow_inv = 0xFFFFu - (uint32_t)row_of(grp * 128 + 32 * (warp >> 1) + 8 * (g >> 1) + 4 * (warp & 1) + (q & 2) + (g & 1));
    {
      uint4 u[4];
#pragma unroll
      for (int i = 0; i < 4; i++) u[i] = pkt_ld128(hp_poll + (i & 1) * 128 + (i >> 1) * 8);
      const float wsum = SM_(float, OFF_WSUM);
      pin(key_pub); pin(cand_pub); pin(trow_inv);
      uint32_t n = 0;
      while (true) {
        bool ok[4];
#pragma unroll
        for (int i = 0; i < 4; i++) ok[i] = u[i].w == tag && pair_code(u[i].x, u[i].y) == cd;
        const bool all = __all_sync(0xffffffffu, ok[0] && ok[1] && ok[2] && ok[3]);
        if (all || ++n > SPIN_LIMIT) break;
#pragma unroll
        for (int i = 0; i < 4; i++) pkt_ld128_if(u[i], hp_poll + (i & 1) * 128 + (i >> 1) * 8, !ok[i]);
      }
      CT(6);
      float a[3], b[3];
      a[0] = __uint_as_float(u[0].x & ~1u) + __uint_as_float(u[1].x & ~1u); b[0] = __uint_as_float(u[2].x & ~1u) + __uint_as_float(u[3].x & ~1u);
      a[1] = __uint_as_float(u[0].y & ~1u) + __uint_as_float(u[1].y & ~1u); b[1] = __uint_as_float(u[2].y & ~1u) + __uint_as_float(u[3].y & ~1u);
      a[2] = __uint_as_float(u[0].z) + __uint_as_float(u[1].z); b[2] = __uint_as_float(u[2].z) + __uint_as_float(u[3].z);
#pragma unroll
      for (int i = 0; i < 3; i++) {
        a[i] = ((q & 2) ? b[i] : a[i]) + __shfl_xor_sync(0xffffffffu, (q & 2) ? a[i] : b[i], 2);
        a[i] += __shfl_xor_sync(0xffffffffu, a[i], 1);
      }
      const float mu = a[0] * (1.f / 1024.f);
      m_bf = bf16r(mu);
      sd = ln_sd(a[1] * (1.f / 1024.f) - mu * mu);
      inv_sd = rcp_fast(sd);
      r_bf = bf16r((a[2] - m_bf * wsum) * inv_sd);
    }
    {
      const uint32_t u = __float_as_uint(r_bf);
      const uint32_t ord = (u & 0x80000000u) ? ~u : (u | 0x80000000u);
      const uint32_t key = (ord & 0xFFFF0000u) | trow_inv;
      const uint32_t wk = __reduce_max_sync(0xffffffffu, key);
      if (key == wk) SM_(uint2, OFF_WKEY + warp * 8) = make_uint2(wk, (__float_as_uint(m_bf) >> 16) | __float_as_uint(sd));
      const uint32_t wmask = __ballot_sync(0xffffffffu, key == wk);
      const bool hi = (wmask & 0xCCCCCCCCu) != 0;
      uint32_t c[16];
#pragma unroll
      for (int ks = 0; ks < 8; ks++) { c[2 * ks] = hi ? h[ks][1] : h[ks][0]; c[2 * ks + 1] = hi ? h[ks][3] : h[ks][2]; }
      bar_sync(NB_BOTH, 256);
      const uint2 km = SM_(uint2, OFF_WKEY + (lane & 7) * 8);
      const uint32_t bk = __reduce_max_sync(0xffffffffu, km.x);
      if (wk == bk) {
        if ((wmask >> (lane & 28)) & 15) {
#pragma unroll
          for (int ks = 0; ks < 8; ks++) pkt_st128(cand_pub + ks * 4, c[2 * ks], tag, c[2 * ks + 1], tag);
        }
      } else if (eps == 0) {
        const uint32_t kx = __shfl_sync(0xffffffffu, km.x, warp ^ 1), ms = __shfl_sync(0xffffffffu, km.y, warp ^ 1);
        if (kx == bk && lane < 8) pkt_st128(key_pub, bk, tag, ms, tag);
      }
      CT(7);
    }
    {
      const float ih = bf16r(inv_sd);
      const uint32_t nm = pack_bf16(-m_bf, -m_bf), iv = pack_bf16(ih, inv_sd - ih);
      const uint32_t nm_o = __shfl_xor_sync(0xffffffffu, nm, 2), iv_o = __shfl_xor_sync(0xffffffffu, iv, 2);
      const uint32_t nm2[2] = {(q & 2) ? nm_o : nm, (q & 2) ? nm : nm_o}, iv2[2] = {(q & 2) ? iv_o : iv, (q & 2) ? iv : iv_o};
      const uint32_t hi2[2] = {__byte_perm(iv2[0], 0, 0x1010), __byte_perm(iv2[1], 0, 0x1010)}, lo2[2] = {__byte_perm(iv2[0], 0, 0x3232), __byte_perm(iv2[1], 0, 0x3232)};
      const uint32_t oa = sb + OFF_OUT + (warp * 16 + (lane & 15)) * 128;
#pragma unroll
      for (int ks = 0; ks < 8; ks++) {
        uint32_t o[4];
#pragma unroll
        for (int i = 0; i < 4; i++) {
          const uint32_t dd = badd2(h[ks][i], nm2[i & 1]);
          o[i] = badd2(h[ks][i], bfma2(dd, hi2[i & 1], bmul2(dd, lo2[i & 1])));
        }
        stsm_x4(oa + (ks >> 2) * 16384 + (((2 * (ks & 3) + (lane >> 4)) ^ (lane & 7)) << 4), o[0], o[1], o[2], o[3]);
      }
      staged(B_OUT);
    }
    CT(8);
    uint32_t df[16][4];
    auto load_df = [&]() {
      const int frow = (lane & 7) + ((lane >> 4) << 3), hi = (lane >> 3) & 1;
      const uint32_t base = sb + down_off(warp >> 1) + (warp & 1) * 8192 + frow * 128;
#pragma unroll
      for (int mt = 0; mt < 8; mt++) {
#pragma unroll
        for (int ks = 0; ks < 2; ks++)
          ldsm_x4_t(base + (mt >> 2) * 4096 + ks * 2048 + (((2 * (mt & 3) + hi) ^ (lane & 7)) << 4),
                    df[2 * mt + ks][0], df[2 * mt + ks][1], df[2 * mt + ks][2], df[2 * mt + ks][3]);
      }
    };
    if (moe) {
      mbar_wait(BAR(B_GU), 0);
      load_wf_rest();
      mbar_wait(BAR(B_DN), 0);
      load_df();
    }
    uint4* y_pub = &p.s->ypart[cid * 256 + tid];
    uint32_t xs_ad = sb + OFF_XSEL + (8 * (g >> 2) + 4 * w + (g & 3)) * 32 + q * 8, gp_ad = sb + OFF_GP + (wi * 8 + g) * 16 + w * 8 + (q >> 1) * 4;
    pin(y_pub); pin(xs_ad); pin(gp_ad);
    mbar_wait(BAR(B_XS), 0);
    CT(9);
    if (moe) {
      float gd[8][4] = {};
      uint2 bx[4];
#pragma unroll
      for (int r = 0; r < 4; r++) bx[r] = smem_at<uint2>(xs_ad + r * 512);
#pragma unroll
      for (int r = 0; r < 4; r++) {
#pragma unroll
        for (int i = 0; i < 8; i++) mma16816(gd[i], wf[8 * r + i][0], wf[8 * r + i][1], wf[8 * r + i][2], wf[8 * r + i][3], bx[r].x, bx[r].y);
      }
      const float gs = sel4(q, gd[0][0] + gd[1][1], gd[2][0] + gd[3][1], gd[4][0] + gd[5][1], gd[6][0] + gd[7][1]);
      const float us = sel4(q, gd[0][2] + gd[1][3], gd[2][2] + gd[3][3], gd[4][2] + gd[5][3], gd[6][2] + gd[7][3]);
      float v = ((q & 2) ? us : gs) + __shfl_xor_sync(0xffffffffu, (q & 2) ? gs : us, 2);
      v += __shfl_xor_sync(0xffffffffu, v, 1);
      smem_at<float>(gp_ad) = v;
      CT(10);
      bar_sync(NB_BOTH, 256);
      uint32_t bq[4];
      {
        const float4 p0 = SM_(float4, OFF_GP + lane * 16);
        const float gt = bf16r(p0.x + p0.z), up = bf16r(p0.y + p0.w);
        const float act = bf16r(gt * sigmoid_fast(gt)) * up;
        const uint32_t pr = pack_bf16(act, __shfl_down_sync(0xffffffffu, act, 1));
#pragma unroll
        for (int i = 0; i < 4; i++) bq[i] = __shfl_sync(0xffffffffu, pr, 8 * i + 2 * q);
      }
      CT(11);
      float yd[8][4] = {};
#pragma unroll
      for (int ks = 0; ks < 2; ks++) {
#pragma unroll
        for (int mt = 0; mt < 8; mt++) mma16816(yd[mt], df[2 * mt + ks][0], df[2 * mt + ks][1], df[2 * mt + ks][2], df[2 * mt + ks][3], bq[2 * ks], bq[2 * ks + 1]);
      }
      pkt_st128(y_pub, with_bit(sel4(q, yd[0][0], yd[2][0], yd[4][0], yd[6][0]), cd), with_bit(sel4(q, yd[0][2], yd[2][2], yd[4][2], yd[6][2]), cd >> 1),
                with_bit(sel4(q, yd[1][0], yd[3][0], yd[5][0], yd[7][0]), cd), with_bit(sel4(q, yd[1][2], yd[3][2], yd[5][2], yd[7][2]), cd >> 1));
    } else {
      const long long tw = clock64();
      while (clock64() - tw < IDLE_WAIT_CLK) __nanosleep(100);
    }
    CT(12);
    const uint32_t kv = SM_(uint32_t, OFF_KV);
    const int tsel = (int)(~kv & 2047u);
    const float r_sel = __uint_as_float((kv & 0x80000000u) ? (kv & 0x7FFF0000u) : (~kv & 0xFFFF0000u));
    const float sig = bf16r(sigmoid_fast(r_sel));
    const int pfin = 2 * cid + (tid & 1);
    const int col_fin = (pfin >> 5) * 128 + (pfin & 3) * 32 + ((pfin & 31) >> 2) + 8 * ((tid >> 1) & 3);
    const int sel_off = (col_fin >> 4) * 32 + ((col_fin & 7) >> 1) * 8 + ((col_fin >> 3) & 1) * 4 + (col_fin & 1) * 2;
    const float hn_fin = __uint_as_float((uint32_t)SM_(uint16_t, OFF_XSEL + sel_off) << 16), h_fin = __uint_as_float((uint32_t)SM_(uint16_t, OFF_HSEL + sel_off) << 16);
    bf16* out_fin = p.out + (size_t)tsel * 1024 + col_fin;
    {
      const uint4* src = &p.s->ypart[(16 + (tid >> 1)) * 256 + pfin];
      pin(src); pin(out_fin);
      uint4 v = make_uint4(0, 0, 0, 0);
      if (warp < 7) {
        delay_clk<HOP3_DELAY>();
        uint32_t n = 0;
        bool ok = false;
        do {
          pkt_ld128_if(v, src, !ok);
          ok = pair_code(v.x, v.y) == cd && pair_code(v.z, v.w) == cd;
        } while (!__all_sync(0xffffffffu, ok) && ++n < SPIN_LIMIT);
      }
      CT(13);
      const float y0 = __uint_as_float(v.x & ~1u), y1 = __uint_as_float(v.y & ~1u), y2 = __uint_as_float(v.z & ~1u), y3 = __uint_as_float(v.w & ~1u);
      const float a0 = ((lane & 2) ? y1 : y0) + __shfl_xor_sync(0xffffffffu, (lane & 2) ? y0 : y1, 2);
      const float a1 = ((lane & 2) ? y3 : y2) + __shfl_xor_sync(0xffffffffu, (lane & 2) ? y2 : y3, 2);
      float b = ((lane & 4) ? a1 : a0) + __shfl_xor_sync(0xffffffffu, (lane & 4) ? a0 : a1, 4);
      b += __shfl_xor_sync(0xffffffffu, b, 8);
      b += __shfl_xor_sync(0xffffffffu, b, 16);
      if (lane < 8) SM_(float, OFF_FIN + lane * 32 + warp * 4) = b;
    }
    bar_sync(NB_BOTH, 256);
    if (tid < 8) {
      const float4 y0 = SM_(float4, OFF_FIN + tid * 32), y1 = SM_(float4, OFF_FIN + tid * 32 + 16);
      const float y = ((y0.x + y0.y) + (y0.z + y0.w)) + ((y1.x + y1.y) + y1.z);
      *out_fin = __float2bfloat16_rn(h_fin + bf16r(hn_fin + bf16r(bf16r(y) * sig)));
      if (cid == 0 && tid == 0) st_relaxed32(&p.s->epoch, tag);
    }
    CT(14);
  }
}

__global__ void __launch_bounds__(384, 1) occupancy_probe_kernel() {}

typedef CUresult (*EncodeFn)(CUtensorMap*, CUtensorMapDataType, cuuint32_t, void*, const cuuint64_t*, const cuuint64_t*, const cuuint32_t*, const cuuint32_t*,
                             CUtensorMapInterleave, CUtensorMapSwizzle, CUtensorMapL2promotion, CUtensorMapFloatOOBfill);

static void make_tm(EncodeFn enc, CUtensorMap* tm, const void* ptr, uint64_t rows, uint64_t cols, uint32_t brows, uint32_t bcols, CUtensorMapSwizzle sw,
                    CUtensorMapL2promotion promo = CU_TENSOR_MAP_L2_PROMOTION_L2_128B) {
  cuuint64_t dims[2] = {cols, rows};
  cuuint64_t strides[1] = {cols * 2};
  cuuint32_t box[2] = {bcols, brows};
  cuuint32_t es[2] = {1, 1};
  enc(tm, CU_TENSOR_MAP_DATA_TYPE_BFLOAT16, 2, const_cast<void*>(ptr), dims, strides, box, es, CU_TENSOR_MAP_INTERLEAVE_NONE, sw,
      promo, CU_TENSOR_MAP_FLOAT_OOB_FILL_NONE);
}

static void make_tm_rows(EncodeFn enc, CUtensorMap* tm, const void* ptr, uint64_t cols, uint32_t brows, uint32_t bcols, CUtensorMapSwizzle sw,
                         CUtensorMapL2promotion promo = CU_TENSOR_MAP_L2_PROMOTION_L2_128B) {
  cuuint64_t dims[4] = {cols, 2, 2, 512};
  cuuint64_t strides[3] = {row_of(1) * cols * 2, row_of(2) * cols * 2, row_of(4) * cols * 2};
  cuuint32_t box[4] = {bcols, 2, 2, brows / 4};
  cuuint32_t es[4] = {1, 1, 1, 1};
  enc(tm, CU_TENSOR_MAP_DATA_TYPE_BFLOAT16, 4, const_cast<void*>(ptr), dims, strides, box, es, CU_TENSOR_MAP_INTERLEAVE_NONE, sw, promo,
      CU_TENSOR_MAP_FLOAT_OOB_FILL_NONE);
}

extern "C" void kernel_launch(void* const* d_in, const int* in_sizes, int n_in, void* d_out, int out_size) {
  (void)in_sizes; (void)n_in; (void)out_size;
  static EncodeFn enc = nullptr;
  static void* abT = nullptr;
  static int map = 0;
  if (!enc) {
    void* fn = nullptr; cudaDriverEntryPointQueryResult st;
    cudaGetDriverEntryPoint("cuTensorMapEncodeTiled", &fn, cudaEnableDefault, &st);
    enc = (EncodeFn)fn;
    cudaGetSymbolAddress(&abT, g_scratch);
    cudaFuncSetAttribute(fnet_moe_kernel<0>, cudaFuncAttributeMaxDynamicSharedMemorySize, SMEM_TOTAL);
    cudaFuncSetAttribute(fnet_moe_kernel<1>, cudaFuncAttributeMaxDynamicSharedMemorySize, SMEM_TOTAL);
    cudaFuncSetAttribute(occupancy_probe_kernel, cudaFuncAttributeMaxDynamicSharedMemorySize, SMEM_TOTAL);
    cudaFuncSetAttribute(occupancy_probe_kernel, cudaFuncAttributeNonPortableClusterSizeAllowed, 1);
    auto max_clusters = [&](int size) {
      cudaLaunchConfig_t cfg = {};
      cfg.gridDim = dim3(128); cfg.blockDim = dim3(384); cfg.dynamicSmemBytes = SMEM_TOTAL;
      cudaLaunchAttribute at[1];
      at[0].id = cudaLaunchAttributeClusterDimension; at[0].val.clusterDim.x = size; at[0].val.clusterDim.y = 1; at[0].val.clusterDim.z = 1;
      cfg.attrs = at; cfg.numAttrs = 1;
      int ncl = 0;
      return cudaOccupancyMaxActiveClusters(&ncl, occupancy_probe_kernel, &cfg) == cudaSuccess ? ncl : 0;
    };
    int dev = 0, sms = 0;
    cudaGetDevice(&dev);
    cudaDeviceGetAttribute(&sms, cudaDevAttrMultiProcessorCount, dev);
    map = (sms == 132 && max_clusters(2) == 66 && max_clusters(16) == 7) ? 0 : 1;
    (void)cudaGetLastError();
  }
  Params p;
  const bf16* x = (const bf16*)d_in[0];
  make_tm(enc, &p.tmD0, d_in[3], 1024, 1024, 128, 64, CU_TENSOR_MAP_SWIZZLE_128B);
  make_tm(enc, &p.tmD1, d_in[4], 1024, 1024, 128, 64, CU_TENSOR_MAP_SWIZZLE_128B);
  make_tm(enc, &p.tmX, x, 2048, 1024, map == 0 ? NX0 : 256, 64, CU_TENSOR_MAP_SWIZZLE_128B);
  make_tm_rows(enc, &p.tmXr, x, 1024, 64, 64, CU_TENSOR_MAP_SWIZZLE_128B);
  make_tm(enc, &p.tmAbS, abT, 2048, 2048, 64, 64, CU_TENSOR_MAP_SWIZZLE_128B);
  make_tm(enc, &p.tmAbL, abT, 2048, 2048, 128, 64, CU_TENSOR_MAP_SWIZZLE_128B);
  make_tm_rows(enc, &p.tmW0, d_in[1], 2048, 128, 64, CU_TENSOR_MAP_SWIZZLE_128B);
  make_tm_rows(enc, &p.tmW1, d_in[2], 2048, 128, 64, CU_TENSOR_MAP_SWIZZLE_128B);
  {
    cuuint64_t dims[5] = {1024, 2, 4, 2, 2048};
    cuuint64_t strides[4] = {row_of(1) * 2048, row_of(8) * 2048, row_of(2) * 2048, 2048};
    cuuint32_t box[5] = {64, 2, 4, 2, 1};
    cuuint32_t es[5] = {1, 1, 1, 1, 1};
    enc(&p.tmOut, CU_TENSOR_MAP_DATA_TYPE_BFLOAT16, 5, d_out, dims, strides, box, es, CU_TENSOR_MAP_INTERLEAVE_NONE, CU_TENSOR_MAP_SWIZZLE_128B,
        CU_TENSOR_MAP_L2_PROMOTION_NONE, CU_TENSOR_MAP_FLOAT_OOB_FILL_NONE);
  }
  {
    cuuint64_t dims[5] = {1024, 2, 4, 2, 8};
    cuuint64_t strides[4] = {2048, 4 * 2048, 2 * 2048, 256 * 2048};
    cuuint32_t box[5] = {64, 2, 4, 2, 8};
    cuuint32_t es[5] = {1, 1, 1, 1, 1};
    enc(&p.tmXh, CU_TENSOR_MAP_DATA_TYPE_BFLOAT16, 5, const_cast<bf16*>(x) + 240 * 1024, dims, strides, box, es, CU_TENSOR_MAP_INTERLEAVE_NONE,
        CU_TENSOR_MAP_SWIZZLE_128B, CU_TENSOR_MAP_L2_PROMOTION_L2_128B, CU_TENSOR_MAP_FLOAT_OOB_FILL_NONE);
  }
  make_tm(enc, &p.tmAbM, abT, 2048, 2048, 128, 16, CU_TENSOR_MAP_SWIZZLE_32B, CU_TENSOR_MAP_L2_PROMOTION_NONE);
  make_tm_rows(enc, &p.tmWM0, d_in[1], 2048, 128, 16, CU_TENSOR_MAP_SWIZZLE_32B);
  make_tm_rows(enc, &p.tmWM1, d_in[2], 2048, 128, 16, CU_TENSOR_MAP_SWIZZLE_32B);
  make_tm(enc, &p.tmG, d_in[7], 1024, 3584, 128, 32, CU_TENSOR_MAP_SWIZZLE_64B);
  make_tm(enc, &p.tmU, d_in[8], 1024, 3584, 128, 32, CU_TENSOR_MAP_SWIZZLE_64B);
  make_tm(enc, &p.tmDn, d_in[9], 3584, 1024, 32, 64, CU_TENSOR_MAP_SWIZZLE_128B);
  p.x = x; p.Dre = (const bf16*)d_in[3]; p.Dim = (const bf16*)d_in[4];
  p.wr = (const bf16*)d_in[6]; p.wdown = (const bf16*)d_in[9]; p.wgate = (const bf16*)d_in[7]; p.wup = (const bf16*)d_in[8];
  p.out = (bf16*)d_out; p.s = (Scratch*)abT;
  if (map == 1) fnet_moe_kernel<1><<<128, 384, SMEM_TOTAL>>>(p);
  else fnet_moe_kernel<0><<<132, 384, SMEM_TOTAL>>>(p);
}
```

```cpp
#include <cuda.h>
#include <cuda_runtime.h>
#include <cuda_bf16.h>
#include <stdint.h>
#include <type_traits>

typedef __nv_bfloat16 bf16;

constexpr int NX0 = 240;
constexpr int REG_C = 232, REG_P = 40;
__host__ __device__ constexpr int row_of(int p) { return (p & 1) * 1024 + ((p >> 1) & 1) * 512 + (p >> 2); }
__host__ __device__ constexpr int group_of(int row) { return (row & 511) >> 5; }
__device__ __forceinline__ int sigma_of(int tau, int r) { return r + (r >= tau); }
__device__ __forceinline__ int kblock(int tau, int j) {
  const int i = j - 4, c = (i * 37) >> 8;
  return j < 4 ? tau * 4 + j : sigma_of(tau, i - 7 * c) * 4 + c;
}
constexpr int AUX_AFTER = 1;
constexpr int PF_K0 = 8, PF_N0 = 2, PF_K1 = 24;
constexpr int WPF_K0 = 12, WPF_N = 10;
constexpr int WPF2_K = 44, WPF2_N = 4;
constexpr int GU_K = 46;
constexpr int PUB_K1 = 22;
constexpr int NREG_H = 5;
constexpr int MR_K0 = 29, MR_P = 6;
constexpr int MINI_PF_K = 35, MINI_LOAD_K = 43, MINI_K = 42;
constexpr int RESET_K = 37;
constexpr int SEND_FIRST = 2;
constexpr int GATHER_NS = 400;
constexpr int MOE_PACE_CLK = 300;
constexpr int OUT_PACE_CLK = 70;
constexpr int HOP1_DELAY = 150, HOP3_DELAY = 450;
constexpr int SPEC_MIN = 10;
constexpr int IDLE_WAIT_CLK = 1200;
__host__ __device__ constexpr int mr_k(int h) { return MR_K0 + MR_P * (h >> 1) + 2 * (h & 1); }
constexpr int A_BYTES = 128 * 64 * 2;
constexpr int B_BYTES = 256 * 64 * 2;
constexpr int ST_BYTES = A_BYTES + B_BYTES;
constexpr int OFF_XCH = 4 * ST_BYTES;
constexpr int OFF_BAR = OFF_XCH + 32768;
constexpr int OFF_WR = OFF_BAR + 384;
constexpr int OFF_RS = OFF_WR + 384;
constexpr int OFF_PUB = OFF_RS + 640;
constexpr int OFF_MISC = OFF_PUB + 768;
constexpr int SMEM_TOTAL = OFF_MISC + 256;
constexpr int OFF_WSUM = OFF_MISC, OFF_TAG = OFF_MISC + 4;
constexpr int OFF_SEEN = OFF_MISC + 8;
constexpr int OFF_KV = OFF_MISC + 12;
constexpr int OFF_WKEY = OFF_MISC + 32;
constexpr int OFF_MINI = OFF_XCH + 16384;
constexpr int OFF_EXA = OFF_XCH;
constexpr int OFF_EXB = OFF_XCH + 4096;
__host__ __device__ constexpr int chunk_off(int c, int w) { return (c == 1 ? 3 * ST_BYTES : c == 2 ? OFF_XCH : OFF_XCH + 16384) + w * 8192; }
__host__ __device__ constexpr int late_off(int i) { return i < 4 ? i * 16384 : 2 * ST_BYTES + A_BYTES + (i - 4) * 16384; }
__host__ __device__ constexpr int round_off(int h) { return h < NREG_H + 2 ? OFF_XCH + (h & 1) * 16384 : late_off(h - NREG_H - 2); }
__host__ __device__ constexpr int down_off(int i) { return late_off(6 - NREG_H + i); }
constexpr int OFF_PEER = ST_BYTES + A_BYTES;
constexpr int OFF_OUT = 3 * ST_BYTES + A_BYTES;
constexpr int OFF_XSEL = OFF_PEER;
constexpr int OFF_HSEL = OFF_PEER + 4096;
constexpr int OFF_GP = OFF_PEER + 8192;
constexpr int OFF_FIN = OFF_PEER + 9216;
__device__ __forceinline__ int slot_of(int k) { return k & 3; }
__device__ __forceinline__ int use_of(int k) { return k >> 2; }
enum { B_FULL = 0, B_EMPTY = 4, B_EPI = 8, B_STD = 12, B_EPI0B = 16, B_LATE = 17, B_STAT = 18, B_XCH = 19, B_MR = 20  , B_GU = 22,
       B_DN = 23, B_AUX = 24  , B_OUT = 26, B_KEY = 27, B_XS = 28, B_MINI = 29, B_PUB1 = 30, B_COUNT = 31 };
enum { NB_TURN0 = 1, NB_TURN1 = 2, NB_WG0 = 3, NB_BOTH = 5, NB_AUX = 6 };

struct Scratch {
  bf16 abT[2048 * 2048];
  uint2 xstat[2048];
  uint2 dsum[2048];
  uint4 abflag[16 * 8 * 2];
  uint4 hflag[16 * 2];
  uint4 hstat[16 * 8 * 128];
  uint4 cand[16 * 256];
  uint4 key[8 * 16 * 2];
  uint4 ypart[128 * 256];
  uint32_t epoch;
};
__device__ __align__(1024) Scratch g_scratch;

struct Params {
  Scratch* s; bf16* out;
  const bf16* x; const bf16* Dre; const bf16* Dim; const bf16* wr; const bf16* wdown; const bf16* wgate; const bf16* wup;
  CUtensorMap tmX, tmD0, tmD1, tmXr, tmAbS, tmAbL, tmW0, tmW1, tmOut, tmG, tmU, tmDn, tmXh, tmAbM, tmWM0, tmWM1;
};

#define SPIN_LIMIT (1u << 14)
#define MBAR_LIMIT (1u << 10)
__device__ __forceinline__ uint32_t smem_u32(const void* p) { return (uint32_t)__cvta_generic_to_shared(p); }
__device__ __forceinline__ void mbar_init(uint32_t bar, uint32_t cnt) { asm volatile("mbarrier.init.shared::cta.b64 [%0], %1;" :: "r"(bar), "r"(cnt) : "memory"); }
__device__ __forceinline__ void mbar_expect_tx(uint32_t bar, uint32_t bytes) { asm volatile("mbarrier.arrive.expect_tx.shared::cta.b64 _, [%0], %1;" :: "r"(bar), "r"(bytes) : "memory"); }
__device__ __forceinline__ void mbar_arrive(uint32_t bar) { asm volatile("mbarrier.arrive.shared::cta.b64 _, [%0];" :: "r"(bar) : "memory"); }
__device__ __forceinline__ void mbar_wait(uint32_t bar, uint32_t parity) {
  uint32_t ok, n = 0;
  do {
    asm volatile("{\n.reg .pred p;\nmbarrier.try_wait.parity.shared::cta.b64 p, [%1], %2;\nselp.u32 %0, 1, 0, p;\n}\n" : "=r"(ok) : "r"(bar), "r"(parity) : "memory");
  } while (!ok && ++n < MBAR_LIMIT);
}
__device__ __forceinline__ void mbar_wait_cluster(uint32_t bar, uint32_t parity) {
  uint32_t ok, n = 0;
  do {
    asm volatile("{\n.reg .pred p;\nmbarrier.try_wait.parity.acquire.cluster.shared::cta.b64 p, [%1], %2;\nselp.u32 %0, 1, 0, p;\n}\n" : "=r"(ok) : "r"(bar), "r"(parity) : "memory");
  } while (!ok && ++n < MBAR_LIMIT);
}
__device__ __forceinline__ void tma_load_2d(uint32_t dst, const CUtensorMap* tm, uint32_t bar, int c0, int c1) {
  asm volatile("cp.async.bulk.tensor.2d.shared::cluster.global.mbarrier::complete_tx::bytes [%0], [%1, {%3, %4}], [%2];"
    :: "r"(dst), "l"(tm), "r"(bar), "r"(c0), "r"(c1) : "memory");
}
__device__ __forceinline__ void tma_load_2d_hint(uint32_t dst, const CUtensorMap* tm, uint32_t bar, int c0, int c1, uint64_t pol) {
  asm volatile("cp.async.bulk.tensor.2d.shared::cluster.global.mbarrier::complete_tx::bytes.L2::cache_hint [%0], [%1, {%3, %4}], [%2], %5;"
    :: "r"(dst), "l"(tm), "r"(bar), "r"(c0), "r"(c1), "l"(pol) : "memory");
}
__device__ __forceinline__ uint64_t policy_evict_first() { uint64_t p; asm volatile("createpolicy.fractional.L2::evict_first.b64 %0, 1.0;" : "=l"(p)); return p; }
__device__ __forceinline__ void tma_store_2d(const CUtensorMap* tm, uint32_t src, int c0, int c1) {
  asm volatile("cp.async.bulk.tensor.2d.global.shared::cta.bulk_group [%0, {%2, %3}], [%1];" :: "l"(tm), "r"(src), "r"(c0), "r"(c1) : "memory");
}
__device__ __forceinline__ void tma_prefetch_2d(const CUtensorMap* tm, int c0, int c1) {
  asm volatile("cp.async.bulk.prefetch.tensor.2d.L2.global.tile [%0, {%1, %2}];" :: "l"(tm), "r"(c0), "r"(c1) : "memory");
}
__device__ __forceinline__ void bulk_load(uint32_t dst, const void* src, uint32_t bytes, uint32_t bar) {
  asm volatile("cp.async.bulk.shared::cluster.global.mbarrier::complete_tx::bytes [%0], [%1], %2, [%3];" :: "r"(dst), "l"(src), "r"(bytes), "r"(bar) : "memory");
}
__device__ __forceinline__ void bulk_commit() { asm volatile("cp.async.bulk.commit_group;" ::: "memory"); }
__device__ __forceinline__ void bulk_wait_all() { asm volatile("cp.async.bulk.wait_group 0;" ::: "memory"); }
__device__ __forceinline__ void bulk_wait_release() {
  bulk_wait_all();
  asm volatile("fence.proxy.async.global;" ::: "memory");
  asm volatile("fence.acq_rel.gpu;" ::: "memory");
}
__device__ __forceinline__ void fence_async_smem() { asm volatile("fence.proxy.async.shared::cta;" ::: "memory"); }
__device__ __forceinline__ void wgmma_fence() { asm volatile("wgmma.fence.sync.aligned;" ::: "memory"); }
__device__ __forceinline__ void wgmma_commit() { asm volatile("wgmma.commit_group.sync.aligned;" ::: "memory"); }
__device__ __forceinline__ void wgmma_wait0() { asm volatile("wgmma.wait_group.sync.aligned 0;" ::: "memory"); }
__device__ __forceinline__ void bar_sync(int id, int n) { asm volatile("bar.sync %0, %1;" :: "r"(id), "r"(n) : "memory"); }
__device__ __forceinline__ void bar_arrive(int id, int n) { asm volatile("bar.arrive %0, %1;" :: "r"(id), "r"(n) : "memory"); }
template<int R> __device__ __forceinline__ void reg_inc() { asm volatile("setmaxnreg.inc.sync.aligned.u32 %0;" :: "n"(R)); }
template<int R> __device__ __forceinline__ void reg_dec() { asm volatile("setmaxnreg.dec.sync.aligned.u32 %0;" :: "n"(R)); }
__device__ __forceinline__ bool elect_one() {
  uint32_t p;
  asm volatile("{\n.reg .pred q;\nelect.sync _|q, 0xffffffff;\nselp.u32 %0, 1, 0, q;\n}\n" : "=r"(p));
  return p != 0;
}
__device__ __forceinline__ uint32_t mapa(uint32_t addr, uint32_t cta) { uint32_t r; asm volatile("mapa.shared::cluster.u32 %0, %1, %2;" : "=r"(r) : "r"(addr), "r"(cta)); return r; }
__device__ __forceinline__ void st_async_v4(uint32_t addr, uint32_t bar, uint32_t a, uint32_t b, uint32_t c, uint32_t d) {
  asm volatile("st.async.weak.shared::cluster.mbarrier::complete_tx::bytes.v4.b32 [%0], {%2, %3, %4, %5}, [%1];" :: "r"(addr), "r"(bar), "r"(a), "r"(b), "r"(c), "r"(d) : "memory");
}
__device__ __forceinline__ void stsm_x4(uint32_t addr, uint32_t a, uint32_t b, uint32_t c, uint32_t d) {
  asm volatile("stmatrix.sync.aligned.m8n8.x4.shared.b16 [%0], {%1, %2, %3, %4};" :: "r"(addr), "r"(a), "r"(b), "r"(c), "r"(d));
}
__device__ __forceinline__ uint4 lds128_v(uint32_t addr) { uint4 v; asm volatile("ld.shared.v4.b32 {%0, %1, %2, %3}, [%4];" : "=r"(v.x), "=r"(v.y), "=r"(v.z), "=r"(v.w) : "r"(addr)); return v; }
extern __shared__ __align__(1024) uint8_t smem_raw[];
template<class T> __device__ __forceinline__ T& smem_at(uint32_t addr) { return *reinterpret_cast<T*>(__cvta_shared_to_generic(addr)); }
#define SM_(T, off) smem_at<T>(sb + (off))
__device__ __forceinline__ uint4 ldg_nc128(const void* p) { uint4 v; asm volatile("ld.global.nc.v4.b32 {%0, %1, %2, %3}, [%4];" : "=r"(v.x), "=r"(v.y), "=r"(v.z), "=r"(v.w) : "l"(p)); return v; }
__device__ __forceinline__ void pkt_st128(void* p, uint32_t a, uint32_t b, uint32_t c, uint32_t d) {
  asm volatile("{\n.reg .b128 v;\n.reg .b64 lo, hi;\nmov.b64 lo, {%1, %2};\nmov.b64 hi, {%3, %4};\nmov.b128 v, {lo, hi};\nst.relaxed.gpu.global.b128 [%0], v;\n}\n"
    :: "l"(p), "r"(a), "r"(b), "r"(c), "r"(d) : "memory");
}
__device__ __forceinline__ uint4 pkt_ld128(const void* p) {
  uint4 r;
  asm volatile("{\n.reg .b128 v;\n.reg .b64 lo, hi;\nld.relaxed.gpu.global.b128 v, [%4];\nmov.b128 {lo, hi}, v;\nmov.b64 {%0, %1}, lo;\nmov.b64 {%2, %3}, hi;\n}\n"
    : "=r"(r.x), "=r"(r.y), "=r"(r.z), "=r"(r.w) : "l"(p) : "memory");
  return r;
}
__device__ __forceinline__ void pkt_ld128_if(uint4& r, const void* p, bool cond) {
  asm volatile("{\n.reg .pred q;\n.reg .b64 lo, hi;\nsetp.ne.b32 q, %5, 0;\nmov.b64 lo, {%0, %1};\nmov.b64 hi, {%2, %3};\n"
               "@q ld.relaxed.gpu.global.v2.b64 {lo, hi}, [%4];\nmov.b64 {%0, %1}, lo;\nmov.b64 {%2, %3}, hi;\n}\n"
    : "+r"(r.x), "+r"(r.y), "+r"(r.z), "+r"(r.w) : "l"(p), "r"((uint32_t)cond) : "memory");
}
__device__ __forceinline__ void pkt_st64(void* p, uint32_t a, uint32_t b) {
  asm volatile("{\n.reg .b64 v;\nmov.b64 v, {%1, %2};\nst.relaxed.gpu.global.b64 [%0], v;\n}\n" :: "l"(p), "r"(a), "r"(b) : "memory");
}
__device__ __forceinline__ uint2 pkt_ld64(const void* p) {
  uint2 r;
  asm volatile("{\n.reg .b64 v;\nld.relaxed.gpu.global.b64 v, [%2];\nmov.b64 {%0, %1}, v;\n}\n" : "=r"(r.x), "=r"(r.y) : "l"(p) : "memory");
  return r;
}
__device__ __forceinline__ uint32_t ld_relaxed32(const void* p) { uint32_t v; asm volatile("ld.relaxed.gpu.global.b32 %0, [%1];" : "=r"(v) : "l"(p) : "memory"); return v; }
__device__ __forceinline__ uint32_t ld_acquire32(const void* p) { uint32_t v; asm volatile("ld.acquire.gpu.global.b32 %0, [%1];" : "=r"(v) : "l"(p) : "memory"); return v; }
__device__ __forceinline__ void st_relaxed32(void* p, uint32_t v) { asm volatile("st.relaxed.gpu.global.b32 [%0], %1;" :: "l"(p), "r"(v) : "memory"); }
__device__ __forceinline__ uint32_t code_of(uint32_t tag) { return tag % 3u + 1u; }
__device__ __forceinline__ uint32_t with_bit(float v, uint32_t bit) { return (__float_as_uint(v) & ~1u) | (bit & 1u); }
__device__ __forceinline__ uint32_t pair_code(uint32_t a, uint32_t b) { return (a & 1u) | ((b & 1u) << 1); }
__device__ __forceinline__ uint32_t pack_bf16(float lo, float hi) { uint32_t r; asm("cvt.rn.bf16x2.f32 %0, %1, %2;" : "=r"(r) : "f"(hi), "f"(lo)); return r; }
__device__ __forceinline__ float bf_lo(uint32_t v) { return __uint_as_float(v << 16); }
__device__ __forceinline__ float bf_hi(uint32_t v) { return __uint_as_float(v & 0xFFFF0000u); }
__device__ __forceinline__ float bf16r(float x) { return __uint_as_float(pack_bf16(0.f, x)); }
__device__ __forceinline__ uint32_t badd2(uint32_t a, uint32_t b) { uint32_t r; asm("add.rn.bf16x2 %0, %1, %2;" : "=r"(r) : "r"(a), "r"(b)); return r; }
__device__ __forceinline__ uint32_t bmul2(uint32_t a, uint32_t b) { uint32_t r; asm("mul.rn.bf16x2 %0, %1, %2;" : "=r"(r) : "r"(a), "r"(b)); return r; }
__device__ __forceinline__ float warp_sum(float v) {
#pragma unroll
  for (int o = 16; o > 0; o >>= 1) v += __shfl_xor_sync(0xffffffffu, v, o);
  return v;
}
__device__ __forceinline__ uint64_t make_desc(uint32_t addr) {
  return (uint64_t)((addr & 0x3FFFF) >> 4) | ((uint64_t)1 << 16) | ((uint64_t)64 << 32) | ((uint64_t)1 << 62);
}
__device__ __forceinline__ uint64_t make_desc_noswz(uint32_t addr) {
  return (uint64_t)((addr & 0x3FFFF) >> 4) | ((uint64_t)8 << 16) | ((uint64_t)16 << 32);
}
__device__ __forceinline__ uint64_t make_desc_32b(uint32_t addr) {
  return (uint64_t)((addr & 0x3FFFF) >> 4) | ((uint64_t)1 << 16) | ((uint64_t)16 << 32) | ((uint64_t)3 << 62);
}
__device__ __forceinline__ void wgmma_n256(float (&d)[128], uint64_t da, uint64_t db, int scale_d) {
  asm volatile("{\n.reg .pred p;\nsetp.ne.b32 p, %130, 0;\n"
    "wgmma.mma_async.sync.aligned.m64n256k16.f32.bf16.bf16 "
    "{%0, %1, %2, %3, %4, %5, %6, %7, %8, %9, %10, %11, %12, %13, %14, %15, %16, %17, %18, %19, %20, %21, %22, %23, %24, %25, %26, %27, %28, %29, %30, %31, "
    "%32, %33, %34, %35, %36, %37, %38, %39, %40, %41, %42, %43, %44, %45, %46, %47, %48, %49, %50, %51, %52, %53, %54, %55, %56, %57, %58, %59, %60, %61, %62, %63, "
    "%64, %65, %66, %67, %68, %69, %70, %71, %72, %73, %74, %75, %76, %77, %78, %79, %80, %81, %82, %83, %84, %85, %86, %87, %88, %89, %90, %91, %92, %93, %94, %95, "
    "%96, %97, %98, %99, %100, %101, %102, %103, %104, %105, %106, %107, %108, %109, %110, %111, %112, %113, %114, %115, %116, %117, %118, %119, %120, %121, %122, %123, %124, %125, %126, %127}, "
    "%128, %129, p, 1, 1, 0, 0;\n}\n"
    : "+f"(d[0]), "+f"(d[1]), "+f"(d[2]), "+f"(d[3]), "+f"(d[4]), "+f"(d[5]), "+f"(d[6]), "+f"(d[7]),
      "+f"(d[8]), "+f"(d[9]), "+f"(d[10]), "+f"(d[11]), "+f"(d[12]), "+f"(d[13]), "+f"(d[14]), "+f"(d[15]),
      "+f"(d[16]), "+f"(d[17]), "+f"(d[18]), "+f"(d[19]), "+f"(d[20]), "+f"(d[21]), "+f"(d[22]), "+f"(d[23]),
      "+f"(d[24]), "+f"(d[25]), "+f"(d[26]), "+f"(d[27]), "+f"(d[28]), "+f"(d[29]), "+f"(d[30]), "+f"(d[31]),
      "+f"(d[32]), "+f"(d[33]), "+f"(d[34]), "+f"(d[35]), "+f"(d[36]), "+f"(d[37]), "+f"(d[38]), "+f"(d[39]),
      "+f"(d[40]), "+f"(d[41]), "+f"(d[42]), "+f"(d[43]), "+f"(d[44]), "+f"(d[45]), "+f"(d[46]), "+f"(d[47]),
      "+f"(d[48]), "+f"(d[49]), "+f"(d[50]), "+f"(d[51]), "+f"(d[52]), "+f"(d[53]), "+f"(d[54]), "+f"(d[55]),
      "+f"(d[56]), "+f"(d[57]), "+f"(d[58]), "+f"(d[59]), "+f"(d[60]), "+f"(d[61]), "+f"(d[62]), "+f"(d[63]),
      "+f"(d[64]), "+f"(d[65]), "+f"(d[66]), "+f"(d[67]), "+f"(d[68]), "+f"(d[69]), "+f"(d[70]), "+f"(d[71]),
      "+f"(d[72]), "+f"(d[73]), "+f"(d[74]), "+f"(d[75]), "+f"(d[76]), "+f"(d[77]), "+f"(d[78]), "+f"(d[79]),
      "+f"(d[80]), "+f"(d[81]), "+f"(d[82]), "+f"(d[83]), "+f"(d[84]), "+f"(d[85]), "+f"(d[86]), "+f"(d[87]),
      "+f"(d[88]), "+f"(d[89]), "+f"(d[90]), "+f"(d[91]), "+f"(d[92]), "+f"(d[93]), "+f"(d[94]), "+f"(d[95]),
      "+f"(d[96]), "+f"(d[97]), "+f"(d[98]), "+f"(d[99]), "+f"(d[100]), "+f"(d[101]), "+f"(d[102]), "+f"(d[103]),
      "+f"(d[104]), "+f"(d[105]), "+f"(d[106]), "+f"(d[107]), "+f"(d[108]), "+f"(d[109]), "+f"(d[110]), "+f"(d[111]),
      "+f"(d[112]), "+f"(d[113]), "+f"(d[114]), "+f"(d[115]), "+f"(d[116]), "+f"(d[117]), "+f"(d[118]), "+f"(d[119]),
      "+f"(d[120]), "+f"(d[121]), "+f"(d[122]), "+f"(d[123]), "+f"(d[124]), "+f"(d[125]), "+f"(d[126]), "+f"(d[127])
    : "l"(da), "l"(db), "r"(scale_d));
}
__device__ __forceinline__ void wgmma_g1(float (&d)[128], uint64_t da, uint64_t db, int scale_d) { wgmma_n256(d, da, db, scale_d); }
__device__ __forceinline__ void wgmma_g1(float (&d)[120], uint64_t da, uint64_t db, int scale_d) {
  asm volatile("{\n.reg .pred p;\nsetp.ne.b32 p, %122, 0;\n"
    "wgmma.mma_async.sync.aligned.m64n240k16.f32.bf16.bf16 "
    "{%0, %1, %2, %3, %4, %5, %6, %7, %8, %9, %10, %11, %12, %13, %14, %15, %16, %17, %18, %19, %20, %21, %22, %23, %24, %25, %26, %27, %28, %29, %30, %31, %32, %33, %34, %35, %36, %37, %38, %39, %40, %41, %42, %43, %44, %45, %46, %47, %48, %49, %50, %51, %52, %53, %54, %55, %56, %57, %58, %59, %60, %61, %62, %63, %64, %65, %66, %67, %68, %69, %70, %71, %72, %73, %74, %75, %76, %77, %78, %79, %80, %81, %82, %83, %84, %85, %86, %87, %88, %89, %90, %91, %92, %93, %94, %95, %96, %97, %98, %99, %100, %101, %102, %103, %104, %105, %106, %107, %108, %109, %110, %111, %112, %113, %114, %115, %116, %117, %118, %119}, "
    "%120, %121, p, 1, 1, 0, 0;\n}\n"
    : "+f"(d[0]), "+f"(d[1]), "+f"(d[2]), "+f"(d[3]), "+f"(d[4]), "+f"(d[5]), "+f"(d[6]), "+f"(d[7]), "+f"(d[8]), "+f"(d[9]), "+f"(d[10]), "+f"(d[11]), "+f"(d[12]), "+f"(d[13]), "+f"(d[14]), "+f"(d[15]), "+f"(d[16]), "+f"(d[17]), "+f"(d[18]), "+f"(d[19]), "+f"(d[20]), "+f"(d[21]), "+f"(d[22]), "+f"(d[23]), "+f"(d[24]), "+f"(d[25]), "+f"(d[26]), "+f"(d[27]), "+f"(d[28]), "+f"(d[29]), "+f"(d[30]), "+f"(d[31]), "+f"(d[32]), "+f"(d[33]), "+f"(d[34]), "+f"(d[35]), "+f"(d[36]), "+f"(d[37]), "+f"(d[38]), "+f"(d[39]), "+f"(d[40]), "+f"(d[41]), "+f"(d[42]), "+f"(d[43]), "+f"(d[44]), "+f"(d[45]), "+f"(d[46]), "+f"(d[47]), "+f"(d[48]), "+f"(d[49]), "+f"(d[50]), "+f"(d[51]), "+f"(d[52]), "+f"(d[53]), "+f"(d[54]), "+f"(d[55]), "+f"(d[56]), "+f"(d[57]), "+f"(d[58]), "+f"(d[59]), "+f"(d[60]), "+f"(d[61]), "+f"(d[62]), "+f"(d[63]), "+f"(d[64]), "+f"(d[65]), "+f"(d[66]), "+f"(d[67]), "+f"(d[68]), "+f"(d[69]), "+f"(d[70]), "+f"(d[71]), "+f"(d[72]), "+f"(d[73]), "+f"(d[74]), "+f"(d[75]), "+f"(d[76]), "+f"(d[77]), "+f"(d[78]), "+f"(d[79]), "+f"(d[80]), "+f"(d[81]), "+f"(d[82]), "+f"(d[83]), "+f"(d[84]), "+f"(d[85]), "+f"(d[86]), "+f"(d[87]), "+f"(d[88]), "+f"(d[89]), "+f"(d[90]), "+f"(d[91]), "+f"(d[92]), "+f"(d[93]), "+f"(d[94]), "+f"(d[95]), "+f"(d[96]), "+f"(d[97]), "+f"(d[98]), "+f"(d[99]), "+f"(d[100]), "+f"(d[101]), "+f"(d[102]), "+f"(d[103]), "+f"(d[104]), "+f"(d[105]), "+f"(d[106]), "+f"(d[107]), "+f"(d[108]), "+f"(d[109]), "+f"(d[110]), "+f"(d[111]), "+f"(d[112]), "+f"(d[113]), "+f"(d[114]), "+f"(d[115]), "+f"(d[116]), "+f"(d[117]), "+f"(d[118]), "+f"(d[119])
    : "l"(da), "l"(db), "r"(scale_d));
}
__device__ __forceinline__ void wgmma_g1(float (&d)[32], uint64_t da, uint64_t db, int scale_d) {
  asm volatile("{\n.reg .pred p;\nsetp.ne.b32 p, %34, 0;\n"
    "wgmma.mma_async.sync.aligned.m64n64k16.f32.bf16.bf16 "
    "{%0, %1, %2, %3, %4, %5, %6, %7, %8, %9, %10, %11, %12, %13, %14, %15, %16, %17, %18, %19, %20, %21, %22, %23, %24, %25, %26, %27, %28, %29, %30, %31}, "
    "%32, %33, p, 1, 1, 0, 0;\n}\n"
    : "+f"(d[0]), "+f"(d[1]), "+f"(d[2]), "+f"(d[3]), "+f"(d[4]), "+f"(d[5]), "+f"(d[6]), "+f"(d[7]), "+f"(d[8]), "+f"(d[9]), "+f"(d[10]), "+f"(d[11]), "+f"(d[12]), "+f"(d[13]), "+f"(d[14]), "+f"(d[15]), "+f"(d[16]), "+f"(d[17]), "+f"(d[18]), "+f"(d[19]), "+f"(d[20]), "+f"(d[21]), "+f"(d[22]), "+f"(d[23]), "+f"(d[24]), "+f"(d[25]), "+f"(d[26]), "+f"(d[27]), "+f"(d[28]), "+f"(d[29]), "+f"(d[30]), "+f"(d[31])
    : "l"(da), "l"(db), "r"(scale_d));
}
__device__ __forceinline__ void wgmma_g1(float (&d)[88], uint64_t da, uint64_t db, int scale_d) {
  asm volatile("{\n.reg .pred p;\nsetp.ne.b32 p, %90, 0;\n"
    "wgmma.mma_async.sync.aligned.m64n176k16.f32.bf16.bf16 "
    "{%0, %1, %2, %3, %4, %5, %6, %7, %8, %9, %10, %11, %12, %13, %14, %15, %16, %17, %18, %19, %20, %21, %22, %23, %24, %25, %26, %27, %28, %29, %30, %31, %32, %33, %34, %35, %36, %37, %38, %39, %40, %41, %42, %43, %44, %45, %46, %47, %48, %49, %50, %51, %52, %53, %54, %55, %56, %57, %58, %59, %60, %61, %62, %63, %64, %65, %66, %67, %68, %69, %70, %71, %72, %73, %74, %75, %76, %77, %78, %79, %80, %81, %82, %83, %84, %85, %86, %87}, "
    "%88, %89, p, 1, 1, 0, 0;\n}\n"
    : "+f"(d[0]), "+f"(d[1]), "+f"(d[2]), "+f"(d[3]), "+f"(d[4]), "+f"(d[5]), "+f"(d[6]), "+f"(d[7]), "+f"(d[8]), "+f"(d[9]), "+f"(d[10]), "+f"(d[11]), "+f"(d[12]), "+f"(d[13]), "+f"(d[14]), "+f"(d[15]), "+f"(d[16]), "+f"(d[17]), "+f"(d[18]), "+f"(d[19]), "+f"(d[20]), "+f"(d[21]), "+f"(d[22]), "+f"(d[23]), "+f"(d[24]), "+f"(d[25]), "+f"(d[26]), "+f"(d[27]), "+f"(d[28]), "+f"(d[29]), "+f"(d[30]), "+f"(d[31]), "+f"(d[32]), "+f"(d[33]), "+f"(d[34]), "+f"(d[35]), "+f"(d[36]), "+f"(d[37]), "+f"(d[38]), "+f"(d[39]), "+f"(d[40]), "+f"(d[41]), "+f"(d[42]), "+f"(d[43]), "+f"(d[44]), "+f"(d[45]), "+f"(d[46]), "+f"(d[47]), "+f"(d[48]), "+f"(d[49]), "+f"(d[50]), "+f"(d[51]), "+f"(d[52]), "+f"(d[53]), "+f"(d[54]), "+f"(d[55]), "+f"(d[56]), "+f"(d[57]), "+f"(d[58]), "+f"(d[59]), "+f"(d[60]), "+f"(d[61]), "+f"(d[62]), "+f"(d[63]), "+f"(d[64]), "+f"(d[65]), "+f"(d[66]), "+f"(d[67]), "+f"(d[68]), "+f"(d[69]), "+f"(d[70]), "+f"(d[71]), "+f"(d[72]), "+f"(d[73]), "+f"(d[74]), "+f"(d[75]), "+f"(d[76]), "+f"(d[77]), "+f"(d[78]), "+f"(d[79]), "+f"(d[80]), "+f"(d[81]), "+f"(d[82]), "+f"(d[83]), "+f"(d[84]), "+f"(d[85]), "+f"(d[86]), "+f"(d[87])
    : "l"(da), "l"(db), "r"(scale_d));
}
__device__ __forceinline__ void wgmma_g1(float (&d)[96], uint64_t da, uint64_t db, int scale_d) {
  asm volatile("{\n.reg .pred p;\nsetp.ne.b32 p, %98, 0;\n"
    "wgmma.mma_async.sync.aligned.m64n192k16.f32.bf16.bf16 "
    "{%0, %1, %2, %3, %4, %5, %6, %7, %8, %9, %10, %11, %12, %13, %14, %15, %16, %17, %18, %19, %20, %21, %22, %23, %24, %25, %26, %27, %28, %29, %30, %31, %32, %33, %34, %35, %36, %37, %38, %39, %40, %41, %42, %43, %44, %45, %46, %47, %48, %49, %50, %51, %52, %53, %54, %55, %56, %57, %58, %59, %60, %61, %62, %63, %64, %65, %66, %67, %68, %69, %70, %71, %72, %73, %74, %75, %76, %77, %78, %79, %80, %81, %82, %83, %84, %85, %86, %87, %88, %89, %90, %91, %92, %93, %94, %95}, "
    "%96, %97, p, 1, 1, 0, 0;\n}\n"
    : "+f"(d[0]), "+f"(d[1]), "+f"(d[2]), "+f"(d[3]), "+f"(d[4]), "+f"(d[5]), "+f"(d[6]), "+f"(d[7]), "+f"(d[8]), "+f"(d[9]), "+f"(d[10]), "+f"(d[11]), "+f"(d[12]), "+f"(d[13]), "+f"(d[14]), "+f"(d[15]), "+f"(d[16]), "+f"(d[17]), "+f"(d[18]), "+f"(d[19]), "+f"(d[20]), "+f"(d[21]), "+f"(d[22]), "+f"(d[23]), "+f"(d[24]), "+f"(d[25]), "+f"(d[26]), "+f"(d[27]), "+f"(d[28]), "+f"(d[29]), "+f"(d[30]), "+f"(d[31]), "+f"(d[32]), "+f"(d[33]), "+f"(d[34]), "+f"(d[35]), "+f"(d[36]), "+f"(d[37]), "+f"(d[38]), "+f"(d[39]), "+f"(d[40]), "+f"(d[41]), "+f"(d[42]), "+f"(d[43]), "+f"(d[44]), "+f"(d[45]), "+f"(d[46]), "+f"(d[47]), "+f"(d[48]), "+f"(d[49]), "+f"(d[50]), "+f"(d[51]), "+f"(d[52]), "+f"(d[53]), "+f"(d[54]), "+f"(d[55]), "+f"(d[56]), "+f"(d[57]), "+f"(d[58]), "+f"(d[59]), "+f"(d[60]), "+f"(d[61]), "+f"(d[62]), "+f"(d[63]), "+f"(d[64]), "+f"(d[65]), "+f"(d[66]), "+f"(d[67]), "+f"(d[68]), "+f"(d[69]), "+f"(d[70]), "+f"(d[71]), "+f"(d[72]), "+f"(d[73]), "+f"(d[74]), "+f"(d[75]), "+f"(d[76]), "+f"(d[77]), "+f"(d[78]), "+f"(d[79]), "+f"(d[80]), "+f"(d[81]), "+f"(d[82]), "+f"(d[83]), "+f"(d[84]), "+f"(d[85]), "+f"(d[86]), "+f"(d[87]), "+f"(d[88]), "+f"(d[89]), "+f"(d[90]), "+f"(d[91]), "+f"(d[92]), "+f"(d[93]), "+f"(d[94]), "+f"(d[95])
    : "l"(da), "l"(db), "r"(scale_d));
}
__device__ __forceinline__ void wgmma_n256_rs(float (&d)[128], uint32_t a0, uint32_t a1, uint32_t a2, uint32_t a3, uint64_t db, int scale_d) {
  asm volatile("{\n.reg .pred p;\nsetp.ne.b32 p, %133, 0;\n"
    "wgmma.mma_async.sync.aligned.m64n256k16.f32.bf16.bf16 "
    "{%0, %1, %2, %3, %4, %5, %6, %7, %8, %9, %10, %11, %12, %13, %14, %15, %16, %17, %18, %19, %20, %21, %22, %23, %24, %25, %26, %27, %28, %29, %30, %31, "
    "%32, %33, %34, %35, %36, %37, %38, %39, %40, %41, %42, %43, %44, %45, %46, %47, %48, %49, %50, %51, %52, %53, %54, %55, %56, %57, %58, %59, %60, %61, %62, %63, "
    "%64, %65, %66, %67, %68, %69, %70, %71, %72, %73, %74, %75, %76, %77, %78, %79, %80, %81, %82, %83, %84, %85, %86, %87, %88, %89, %90, %91, %92, %93, %94, %95, "
    "%96, %97, %98, %99, %100, %101, %102, %103, %104, %105, %106, %107, %108, %109, %110, %111, %112, %113, %114, %115, %116, %117, %118, %119, %120, %121, %122, %123, %124, %125, %126, %127}, "
    "{%128, %129, %130, %131}, %132, p, 1, 1, 0;\n}\n"
    : "+f"(d[0]), "+f"(d[1]), "+f"(d[2]), "+f"(d[3]), "+f"(d[4]), "+f"(d[5]), "+f"(d[6]), "+f"(d[7]),
      "+f"(d[8]), "+f"(d[9]), "+f"(d[10]), "+f"(d[11]), "+f"(d[12]), "+f"(d[13]), "+f"(d[14]), "+f"(d[15]),
      "+f"(d[16]), "+f"(d[17]), "+f"(d[18]), "+f"(d[19]), "+f"(d[20]), "+f"(d[21]), "+f"(d[22]), "+f"(d[23]),
      "+f"(d[24]), "+f"(d[25]), "+f"(d[26]), "+f"(d[27]), "+f"(d[28]), "+f"(d[29]), "+f"(d[30]), "+f"(d[31]),
      "+f"(d[32]), "+f"(d[33]), "+f"(d[34]), "+f"(d[35]), "+f"(d[36]), "+f"(d[37]), "+f"(d[38]), "+f"(d[39]),
      "+f"(d[40]), "+f"(d[41]), "+f"(d[42]), "+f"(d[43]), "+f"(d[44]), "+f"(d[45]), "+f"(d[46]), "+f"(d[47]),
      "+f"(d[48]), "+f"(d[49]), "+f"(d[50]), "+f"(d[51]), "+f"(d[52]), "+f"(d[53]), "+f"(d[54]), "+f"(d[55]),
      "+f"(d[56]), "+f"(d[57]), "+f"(d[58]), "+f"(d[59]), "+f"(d[60]), "+f"(d[61]), "+f"(d[62]), "+f"(d[63]),
      "+f"(d[64]), "+f"(d[65]), "+f"(d[66]), "+f"(d[67]), "+f"(d[68]), "+f"(d[69]), "+f"(d[70]), "+f"(d[71]),
      "+f"(d[72]), "+f"(d[73]), "+f"(d[74]), "+f"(d[75]), "+f"(d[76]), "+f"(d[77]), "+f"(d[78]), "+f"(d[79]),
      "+f"(d[80]), "+f"(d[81]), "+f"(d[82]), "+f"(d[83]), "+f"(d[84]), "+f"(d[85]), "+f"(d[86]), "+f"(d[87]),
      "+f"(d[88]), "+f"(d[89]), "+f"(d[90]), "+f"(d[91]), "+f"(d[92]), "+f"(d[93]), "+f"(d[94]), "+f"(d[95]),
      "+f"(d[96]), "+f"(d[97]), "+f"(d[98]), "+f"(d[99]), "+f"(d[100]), "+f"(d[101]), "+f"(d[102]), "+f"(d[103]),
      "+f"(d[104]), "+f"(d[105]), "+f"(d[106]), "+f"(d[107]), "+f"(d[108]), "+f"(d[109]), "+f"(d[110]), "+f"(d[111]),
      "+f"(d[112]), "+f"(d[113]), "+f"(d[114]), "+f"(d[115]), "+f"(d[116]), "+f"(d[117]), "+f"(d[118]), "+f"(d[119]),
      "+f"(d[120]), "+f"(d[121]), "+f"(d[122]), "+f"(d[123]), "+f"(d[124]), "+f"(d[125]), "+f"(d[126]), "+f"(d[127])
    : "r"(a0), "r"(a1), "r"(a2), "r"(a3), "l"(db), "r"(scale_d));
}
__device__ __forceinline__ void wgmma_n128(float (&d)[64], uint64_t da, uint64_t db, int scale_d = 1) {
  asm volatile("{\n.reg .pred p;\nsetp.ne.b32 p, %66, 0;\n"
    "wgmma.mma_async.sync.aligned.m64n128k16.f32.bf16.bf16 "
    "{%0, %1, %2, %3, %4, %5, %6, %7, %8, %9, %10, %11, %12, %13, %14, %15, %16, %17, %18, %19, %20, %21, %22, %23, %24, %25, %26, %27, %28, %29, %30, %31, %32, %33, %34, %35, %36, %37, %38, %39, %40, %41, %42, %43, %44, %45, %46, %47, %48, %49, %50, %51, %52, %53, %54, %55, %56, %57, %58, %59, %60, %61, %62, %63}, "
    "%64, %65, p, 1, 1, 0, 0;\n}\n"
    : "+f"(d[0]), "+f"(d[1]), "+f"(d[2]), "+f"(d[3]), "+f"(d[4]), "+f"(d[5]), "+f"(d[6]), "+f"(d[7]), "+f"(d[8]), "+f"(d[9]), "+f"(d[10]), "+f"(d[11]), "+f"(d[12]), "+f"(d[13]), "+f"(d[14]), "+f"(d[15]), "+f"(d[16]), "+f"(d[17]), "+f"(d[18]), "+f"(d[19]), "+f"(d[20]), "+f"(d[21]), "+f"(d[22]), "+f"(d[23]), "+f"(d[24]), "+f"(d[25]), "+f"(d[26]), "+f"(d[27]), "+f"(d[28]), "+f"(d[29]), "+f"(d[30]), "+f"(d[31]), "+f"(d[32]), "+f"(d[33]), "+f"(d[34]), "+f"(d[35]), "+f"(d[36]), "+f"(d[37]), "+f"(d[38]), "+f"(d[39]), "+f"(d[40]), "+f"(d[41]), "+f"(d[42]), "+f"(d[43]), "+f"(d[44]), "+f"(d[45]), "+f"(d[46]), "+f"(d[47]), "+f"(d[48]), "+f"(d[49]), "+f"(d[50]), "+f"(d[51]), "+f"(d[52]), "+f"(d[53]), "+f"(d[54]), "+f"(d[55]), "+f"(d[56]), "+f"(d[57]), "+f"(d[58]), "+f"(d[59]), "+f"(d[60]), "+f"(d[61]), "+f"(d[62]), "+f"(d[63])
    : "l"(da), "l"(db), "r"(scale_d));
}
template<int N> __device__ __forceinline__ void fence_acc(float (&d)[N]) {
#pragma unroll
  for (int i = 0; i < N; i++) asm volatile("" : "+f"(d[i]) :: "memory");
}

template<int N, int I = 0, class F> __device__ __forceinline__ void static_for(F&& f) {
  if constexpr (I < N) { f(std::integral_constant<int, I>()); static_for<N, I + 1>(f); }
}

__device__ __forceinline__ void ldsm_x4_t(uint32_t addr, uint32_t& a, uint32_t& b, uint32_t& c, uint32_t& d) {
  asm volatile("ldmatrix.sync.aligned.m8n8.x4.trans.shared.b16 {%0, %1, %2, %3}, [%4];" : "=r"(a), "=r"(b), "=r"(c), "=r"(d) : "r"(addr));
}
__device__ __forceinline__ void sts128(uint32_t addr, uint32_t a, uint32_t b, uint32_t c, uint32_t d) {
  asm volatile("st.shared.v4.b32 [%0], {%1, %2, %3, %4};" :: "r"(addr), "r"(a), "r"(b), "r"(c), "r"(d));
}
__device__ __forceinline__ void mma16816(float (&c)[4], uint32_t a0, uint32_t a1, uint32_t a2, uint32_t a3, uint32_t b0, uint32_t b1) {
  asm volatile("mma.sync.aligned.m16n8k16.row.col.f32.bf16.bf16.f32 {%0, %1, %2, %3}, {%4, %5, %6, %7}, {%8, %9}, {%0, %1, %2, %3};"
      : "+f"(c[0]), "+f"(c[1]), "+f"(c[2]), "+f"(c[3]) : "r"(a0), "r"(a1), "r"(a2), "r"(a3), "r"(b0), "r"(b1));
}
__device__ __forceinline__ void mma1688(float (&c)[4], uint32_t a0, uint32_t a1, uint32_t b0) {
  asm volatile("mma.sync.aligned.m16n8k8.row.col.f32.bf16.bf16.f32 {%0, %1, %2, %3}, {%4, %5}, {%6}, {%0, %1, %2, %3};"
      : "+f"(c[0]), "+f"(c[1]), "+f"(c[2]), "+f"(c[3]) : "r"(a0), "r"(a1), "r"(b0));
}
__device__ __forceinline__ uint32_t keep_awake() {
  float c0;
  asm volatile("{\n.reg .f32 c1, c2, c3, z;\n.reg .b32 a;\nmov.b32 a, 0;\nmov.f32 z, 0f00000000;\n"
               "mma.sync.aligned.m16n8k8.row.col.f32.bf16.bf16.f32 {%0, c1, c2, c3}, {a, a}, {a}, {z, z, z, z};\n}\n" : "=f"(c0));
  return __float_as_uint(c0);
}
__device__ __forceinline__ void pin(uint32_t& v) { asm volatile("shfl.sync.bfly.b32 %0, %0, 0, 0x1f, 0xffffffff;" : "+r"(v)); }
template<class T> __device__ __forceinline__ void pin(T*& v) {
  uint32_t lo = (uint32_t)(uint64_t)v, hi = (uint32_t)((uint64_t)v >> 32);
  pin(lo); pin(hi);
  v = (T*)(((uint64_t)hi << 32) | lo);
}
__device__ __forceinline__ float sel4(int q, float a, float b, float c, float d) {
  float r;
  asm("{\n.reg .pred p, o;\n.reg .f32 x, y;\n.reg .b32 t;\nand.b32 t, %1, 1;\nsetp.ne.b32 p, t, 0;\nsetp.gt.s32 o, %1, 1;\n"
      "selp.f32 x, %3, %2, p;\nselp.f32 y, %5, %4, p;\nselp.f32 %0, y, x, o;\n}\n" : "=f"(r) : "r"(q), "f"(a), "f"(b), "f"(c), "f"(d));
  return r;
}
__device__ __forceinline__ uint32_t bfma2(uint32_t a, uint32_t b, uint32_t c) { uint32_t r; asm("fma.rn.bf16x2 %0, %1, %2, %3;" : "=r"(r) : "r"(a), "r"(b), "r"(c)); return r; }
__device__ __forceinline__ void tma_load_5d(uint32_t dst, const CUtensorMap* tm, uint32_t bar, int c0, int c4) {
  asm volatile("cp.async.bulk.tensor.5d.shared::cluster.global.mbarrier::complete_tx::bytes [%0], [%1, {%3, %4, %4, %4, %5}], [%2];"
    :: "r"(dst), "l"(tm), "r"(bar), "r"(c0), "r"(0), "r"(c4) : "memory");
}
__device__ __forceinline__ void tma_load_4d(uint32_t dst, const CUtensorMap* tm, uint32_t bar, int c0, int c3) {
  asm volatile("cp.async.bulk.tensor.4d.shared::cluster.global.mbarrier::complete_tx::bytes [%0], [%1, {%3, %4, %4, %5}], [%2];"
    :: "r"(dst), "l"(tm), "r"(bar), "r"(c0), "r"(0), "r"(c3) : "memory");
}
__device__ __forceinline__ void tma_load_4d_hint(uint32_t dst, const CUtensorMap* tm, uint32_t bar, int c0, int c3, uint64_t pol) {
  asm volatile("cp.async.bulk.tensor.4d.shared::cluster.global.mbarrier::complete_tx::bytes.L2::cache_hint [%0], [%1, {%3, %4, %4, %5}], [%2], %6;"
    :: "r"(dst), "l"(tm), "r"(bar), "r"(c0), "r"(0), "r"(c3), "l"(pol) : "memory");
}
__device__ __forceinline__ void tma_prefetch_4d(const CUtensorMap* tm, int c0, int c3) {
  asm volatile("cp.async.bulk.prefetch.tensor.4d.L2.global.tile [%0, {%1, %2, %2, %3}];" :: "l"(tm), "r"(c0), "r"(0), "r"(c3) : "memory");
}
__device__ __forceinline__ void tma_store_5d(const CUtensorMap* tm, uint32_t src, int c0, int c4) {
  asm volatile("cp.async.bulk.tensor.5d.global.shared::cta.bulk_group [%0, {%2, %3, %3, %3, %4}], [%1];" :: "l"(tm), "r"(src), "r"(c0), "r"(0), "r"(c4) : "memory");
}
__device__ __forceinline__ float rcp_fast(float x) { float r; asm("rcp.approx.ftz.f32 %0, %1;" : "=f"(r) : "f"(x)); return r; }
__device__ __forceinline__ float sigmoid_fast(float x) { float e; asm("ex2.approx.ftz.f32 %0, %1;" : "=f"(e) : "f"(x * -1.4426950408889634f)); return rcp_fast(1.f + e); }
__device__ __forceinline__ float sqrt_fast(float x) { float r; asm("sqrt.approx.ftz.f32 %0, %1;" : "=f"(r) : "f"(x)); return r; }
__device__ __forceinline__ float ln_sd(float var) { return bf16r(sqrt_fast(bf16r(bf16r(fmaxf(var, 0.f)) + 1e-5f))); }
__device__ __forceinline__ uint32_t norm2(uint32_t h, uint32_t neg_mean2, float inv_sd) {
  const uint32_t d = badd2(h, neg_mean2);
  return pack_bf16(bf_lo(d) * inv_sd, bf_hi(d) * inv_sd);
}
template<int N> __device__ __forceinline__ void delay_clk() {
  if constexpr (N > 0) { const uint32_t t0 = clock(); while ((uint32_t)clock() - t0 < N) {} }
}
__device__ __forceinline__ void put_xstat(uint32_t rs, uint32_t exb, int col, uint32_t mean_rstd, int m) {
  smem_at<uint16_t>(rs + ((col & 7) >> 1) * 144 + (col >> 3) * 4 + (col & 1) * 2) = (uint16_t)(mean_rstd ^ (m << 15));
  const uint32_t nm = (mean_rstd >> 16) ^ 0x8000u;
  smem_at<uint4>(exb + (col >> 3) * 256 + (col & 7) * 16) = make_uint4(nm | (nm << 16), nm, 0, 0);
  smem_at<uint4>(exb + (col >> 3) * 256 + 128 + (col & 7) * 16) = make_uint4(0, 0, 0, 0);
}
__device__ __forceinline__ void put_dsum(uint32_t exa, int e, float c) {
  const float hi = bf16r(c), mid = bf16r(c - hi), lo = bf16r((c - hi) - mid);
  smem_at<uint4>(exa + (e >> 3) * 256 + (e & 7) * 16) = make_uint4((__float_as_uint(hi) >> 16) | (__float_as_uint(mid) & 0xFFFF0000u), __float_as_uint(lo) >> 16, 0, 0);
  smem_at<uint4>(exa + (e >> 3) * 256 + 128 + (e & 7) * 16) = make_uint4(0, 0, 0, 0);
}
__host__ __device__ constexpr int min_c(int a, int b) { return a < b ? a : b; }
template<int V> using IC = std::integral_constant<int, V>;

#define CT(slot) do {} while (0)
#define PT(slot) do {} while (0)

template<int MAP>
__global__ void __cluster_dims__(2, 1, 1) __launch_bounds__(384, 1)
fnet_moe_kernel(const __grid_constant__ Params p) {
  constexpr int NX = MAP == 0 ? NX0 : 256;
  constexpr int G1_BYTES = A_BYTES + NX * 128;
  uint32_t sb;
  asm volatile("mov.u32 %0, %1;" : "=r"(sb) : "r"(smem_u32(smem_raw)));
  const int m = blockIdx.x & 1;
  int tau, eps;
  bool helper = false;
  if (MAP == 0) {
    uint32_t smid;
    asm volatile("mov.u32 %0, %%smid;" : "=r"(smid));
    const int c = smid >> 1, e7 = ((c - 32) * 37) >> 8;
    helper = c == 60 || c == 61;
    tau = c < 32 ? (c & 7) : (c < 60 ? c - 31 - 7 * e7 : 0);
    eps = c < 32 ? (c >> 3) : (c < 60 ? 4 + e7 : c - 58);
  } else {
    tau = (blockIdx.x >> 1) & 7; eps = blockIdx.x >> 4;
  }
  const int cid = tau * 16 + eps * 2 + m;
  const bool moe = tau > 0;
  auto BAR = [&](int i) { return sb + OFF_BAR + 8 * i; };
  const CUtensorMap* tmD = m ? &p.tmD1 : &p.tmD0;
  const uint64_t pol_ef = policy_evict_first();
#define LOAD_STREAM(d, tm, bar, c0, c1) tma_load_2d_hint(d, tm, bar, c0, c1, pol_ef)
#define LOAD_W(d, tm, bar, c0, grp) tma_load_4d_hint(d, tm, bar, c0, (grp) * 32, pol_ef)
  auto helper_load = [&](int k) {
    const uint32_t sa = sb + slot_of(k) * ST_BYTES, bar = BAR(B_FULL + slot_of(k));
    const CUtensorMap* tm = eps == 3 ? &p.tmD1 : &p.tmD0;
    tma_load_5d(sa, &p.tmXh, bar, (k & 15) * 64, 0);
    tma_load_2d(sa + A_BYTES, tm, bar, (k & 15) * 64, m * 512 + (k >> 4) * 256);
    tma_load_2d(sa + A_BYTES + 16384, tm, bar, (k & 15) * 64, m * 512 + (k >> 4) * 256 + 128);
  };
  if (threadIdx.x < 32 && elect_one()) {
    mbar_init(BAR(B_FULL), 1);
    asm volatile("fence.mbarrier_init.release.cluster;" ::: "memory");
    if (!helper) {
      tma_load_2d(sb + A_BYTES, &p.tmX, BAR(B_FULL), 0, tau * 256);
      tma_load_2d(sb, tmD, BAR(B_FULL), 0, eps * 128);
    }
    PT(52);
#pragma unroll
    for (int k = 1; k < 4; k++) mbar_init(BAR(B_FULL + k), 1);
    asm volatile("fence.mbarrier_init.release.cluster;" ::: "memory");
#pragma unroll
    for (int k = 0; k < 4; k++) mbar_expect_tx(BAR(B_FULL + k), helper ? ST_BYTES : G1_BYTES);
    if (!helper) {
#pragma unroll
      for (int k = 1; k < 4; k++) {
        tma_load_2d(sb + k * ST_BYTES + A_BYTES, &p.tmX, BAR(B_FULL + k), k * 64, tau * 256);
        LOAD_STREAM(sb + k * ST_BYTES, tmD, BAR(B_FULL + k), k * 64, eps * 128);
      }
    } else {
#pragma unroll 1
      for (int k = 0; k < 4; k++) helper_load(k);
    }
    PT(0);
  }
  __syncwarp();
  const int warp = __shfl_sync(0xffffffffu, threadIdx.x >> 5, 0);
  if (warp == 8) {
    if (elect_one()) {
#pragma unroll
      for (int b = B_EMPTY; b < B_COUNT; b++)
        mbar_init(BAR(b), b < B_EPI ? 2 : (b == B_EPI || b == B_EPI0B) ? 4 : (b < B_STD || b == B_OUT) ? 8 : (b == B_STAT || b == B_XS) ? 3 : 1);
      asm volatile("fence.mbarrier_init.release.cluster;" ::: "memory");
      mbar_expect_tx(BAR(B_XCH), 32768);
      SM_(uint32_t, OFF_SEEN) = 0;
    }
  }
  __syncthreads();

  if (warp >= 8) {
    reg_dec<REG_P>();
    asm volatile("barrier.cluster.arrive.relaxed.aligned;" ::: "memory");
    const int abrow = m * 1024 + eps * 128;
    const int f0 = (cid - 16) * 32;
    const CUtensorMap* tmWM = m ? &p.tmWM1 : &p.tmWM0;
    auto side_first = [&](int k) {
      if (NX < 256 && k == MINI_LOAD_K) {
        static_assert(NX == 256 || (mr_k(NREG_H) == MINI_LOAD_K && (NREG_H & 1) == 1), "second half of the staging buffer must be free");
        mbar_wait(BAR(B_STD + 3), 0);
        uint32_t n = 0;
        while (!((*(volatile uint32_t*)&SM_(uint32_t, OFF_SEEN) >> (4 * tau + 1)) & 1) && ++n < SPIN_LIMIT * 16) {}
        if (elect_one()) {
          mbar_expect_tx(BAR(B_MINI), 12288);
          tma_load_2d(sb + OFF_MINI, &p.tmAbM, BAR(B_MINI), tau * 256 + 240, abrow);
          LOAD_W(sb + OFF_MINI + 4096, tmWM, BAR(B_MINI), tau * 256 + 240, tau * 2 + m);
          LOAD_W(sb + OFF_MINI + 8192, tmWM, BAR(B_MINI), tau * 256 + 240, tau * 2 + 1 - m);
        }
      }
    };
    auto side = [&](int k) {
      if (NX < 256 && k == MINI_PF_K && elect_one()) tma_prefetch_4d(tmWM, tau * 256 + 240, tau * 64 + (eps & 1) * 32);
      if (k == WPF2_K && eps < WPF2_N && elect_one()) tma_prefetch_4d(m ? &p.tmW1 : &p.tmW0, kblock(tau, 31 - (eps >> 1)) * 64, tau * 64 + (eps & 1) * 32);
      if (!moe) return;
      const int i = k - MR_K0, r6 = i / MR_P, u = i - MR_P * r6, h = 2 * r6 + (u >> 1);
      if (i >= 0 && u < 4 && h < NREG_H) {
        if (h < 2) mbar_wait(BAR(B_STD + 2 + h), 0);
        if (elect_one()) {
          if (!(u & 1)) mbar_expect_tx(BAR(B_MR + (h & 1)), 16384);
          LOAD_STREAM(sb + OFF_XCH + u * 8192, (u & 1) ? &p.tmU : &p.tmG, BAR(B_MR + (h & 1)), f0, h * 128);
        }
      }
      if (k >= GU_K && k < GU_K + 2 && elect_one()) {
        static_assert(mr_k(NREG_H + 1) <= GU_K + 1 && MINI_K + 4 <= GU_K && GU_K < 47, "staging buffer must be free");
        LOAD_STREAM(sb + round_off(NREG_H + k - GU_K), &p.tmG, BAR(B_GU), f0, (NREG_H + k - GU_K) * 128);
        LOAD_STREAM(sb + round_off(NREG_H + k - GU_K) + 8192, &p.tmU, BAR(B_GU), f0, (NREG_H + k - GU_K) * 128);
      }
      if (k >= PF_K1 && !(k & 1) && elect_one()) {
        const int j = PF_N0 + ((k - PF_K1) >> 1);
        if (j < 8) tma_prefetch_2d(m ? &p.tmU : &p.tmG, f0, j * 128);
        else if (j < 12) asm volatile("cp.async.bulk.prefetch.L2.global [%0], %1;" :: "l"(p.wdown + (size_t)f0 * 1024 + (j - 8) * 8192), "r"(16384) : "memory");
      }
    };
    if (MAP == 0 && helper) {
      if (warp == 8) {
#pragma unroll 1
        for (int k = 4; k < 32; k++) {
          mbar_wait(BAR(B_EMPTY + slot_of(k)), (use_of(k) & 1) ^ 1);
          if (elect_one()) {
            mbar_expect_tx(BAR(B_FULL + slot_of(k)), ST_BYTES);
            helper_load(k);
            if (k == 12) mbar_arrive(BAR(B_LATE));
          }
        }
      } else {
        const int i0 = threadIdx.x - 288, lane = threadIdx.x & 31, col0 = (eps - 2) * 8 + m * 4;
        mbar_wait(BAR(B_LATE), 0);
        const uint32_t tag = ld_relaxed32(&p.s->epoch) + 1;
        if (i0 < 8) pkt_st128(&p.s->hflag[col0 * 2 + i0], 0, 0, 0, 0);
        SM_(uint32_t, OFF_TAG) = tag;
#pragma unroll 1
        for (int j0 = i0; j0 < 768; j0 += 384) {
          uint2 v[4]; uint32_t n = 0;
          while (true) {
#pragma unroll
            for (int z = 0; z < 4; z++) {
              const int j = j0 + 96 * z;
              v[z] = pkt_ld64(p.s->xstat + (j < 128 ? 256 * (j >> 4) + 240 + 2 * (j & 6) + ((j >> 2) & 2) + (j & 1)
                                          : j < 640 ? 2048 + col0 * 128 + j - 128 : (j - 640) * 16));
            }
            if (__all_sync(0xffffffffu, v[0].y == tag && v[1].y == tag && v[2].y == tag && v[3].y == tag) || ++n > SPIN_LIMIT) break;
            __nanosleep(300);
          }
#pragma unroll
          for (int z = 0; z < 4; z++) {
            const int j = j0 + 96 * z;
            if (j < 128) put_xstat(sb + OFF_RS, sb + OFF_XCH + 16384, j, v[z].x, eps - 2);
            else if (j < 640) put_dsum(sb + OFF_XCH, j - 128, __uint_as_float(v[z].x));
          }
        }
        fence_async_smem();
        __syncwarp();
        if (lane == 0) mbar_arrive(BAR(B_STAT));
      }
    } else if (warp == 8) {
      const CUtensorMap* tmW = m ? &p.tmW1 : &p.tmW0;
      const int gA = tau * 2 + m, gB = tau * 2 + 1 - m;
      auto wait_slot = [&](int k) {
        mbar_wait(BAR(B_EMPTY + slot_of(k)), (use_of(k) & 1) ^ 1);
        PT(64 + k);
      };
#pragma unroll 1
      for (int k = 4; k < 24; k++) {
        const int s = slot_of(k);
        const uint32_t sa = sb + s * ST_BYTES, sbb = sa + A_BYTES;
        const int kb = kblock(tau, k - 16);
        wait_slot(k);
        if (elect_one()) {
          mbar_expect_tx(BAR(B_FULL + s), k < 16 ? G1_BYTES : (k >> 1) == 9 ? B_BYTES : ST_BYTES);
          if (k < 16) {
            LOAD_STREAM(sa, tmD, BAR(B_FULL + s), k * 64, eps * 128);
            tma_load_2d(sbb, &p.tmX, BAR(B_FULL + s), k * 64, tau * 256);
          } else {
            LOAD_W(sbb, tmW, BAR(B_FULL + s), kb * 64, gA);
            LOAD_W(sbb + 16384, tmW, BAR(B_FULL + s), kb * 64, gB);
            if (k < 18) {
              tma_load_4d(sa, &p.tmXr, BAR(B_FULL + s), eps * 128, gA * 32 + s * 16);
              tma_load_4d(sa + 8192, &p.tmXr, BAR(B_FULL + s), eps * 128 + 64, gA * 32 + s * 16);
            }
          }
          if (k == PUB_K1) mbar_arrive(BAR(B_LATE));
          if (k >= WPF_K0 && k < WPF_K0 + WPF_N && (eps >> 1) == ((k - WPF_K0) & 3))
            tma_prefetch_4d(tmW, kblock(tau, k - WPF_K0) * 64, tau * 64 + (eps & 1) * 32);
          if (moe && k >= PF_K0 && k < PF_K0 + 2 * PF_N0 && !(k & 1)) tma_prefetch_2d(m ? &p.tmU : &p.tmG, f0, (k - PF_K0) * 64);
        }
      }
      uint32_t seen = 0;
#pragma unroll 1
      for (int k = 24; k < 48; k++) {
        const int s = slot_of(k);
        const uint32_t sa = sb + s * ST_BYTES, sbb = sa + A_BYTES;
        const int kb = kblock(tau, k - 16);
        const uint32_t need = (1u << kb) | ((kb & 3) == 3 ? 2u << (4 * tau) : 0u);
        wait_slot(k);
        side_first(k);
        if (elect_one()) {
          mbar_expect_tx(BAR(B_FULL + s), ST_BYTES);
          LOAD_W(sbb, tmW, BAR(B_FULL + s), kb * 64, gA);
          LOAD_W(sbb + 16384, tmW, BAR(B_FULL + s), kb * 64, gB);
        }
        uint32_t n = 0;
        while ((seen & need) != need && ++n < SPIN_LIMIT * 16) seen = *(volatile uint32_t*)&SM_(uint32_t, OFF_SEEN);
        if (elect_one()) tma_load_2d(sa, &p.tmAbL, BAR(B_FULL + s), kb * 64, abrow);
        side(k);
      }
      if (moe) {
        mbar_wait(BAR(B_EMPTY + 0), 1);
        if (elect_one()) { mbar_expect_tx(BAR(B_GU), (8 - NREG_H) * 16384); mbar_expect_tx(BAR(B_DN), 65536); }
#pragma unroll 1
        for (int i = 0; i < 10 - NREG_H; i++) {
          if (i == 3) mbar_wait(BAR(B_EMPTY + 1), 1);
          if (i == 4) {
            mbar_wait(BAR(B_EMPTY + 2), 1);
            mbar_wait(BAR(B_XCH), 0);
            PT(53);
          }
          const uint32_t dst = sb + late_off(i);
          if (elect_one()) {
            if (i < 6 - NREG_H) {
              LOAD_STREAM(dst, &p.tmG, BAR(B_GU), f0, (NREG_H + 2 + i) * 128);
              LOAD_STREAM(dst + 8192, &p.tmU, BAR(B_GU), f0, (NREG_H + 2 + i) * 128);
            } else {
#pragma unroll
              for (int b = 0; b < 4; b++) LOAD_STREAM(dst + b * 4096, &p.tmDn, BAR(B_DN), (4 * (i - 6 + NREG_H) + b) * 64, f0);
            }
          }
          const long long t0 = clock64();
          while (i < 9 - NREG_H && clock64() - t0 < MOE_PACE_CLK) {}
        }
      }
      const int lane = threadIdx.x & 31;
      mbar_wait(BAR(B_OUT), 0);
      const uint32_t km = SM_(uint32_t, OFF_WKEY + (lane & 7) * 8);
      const uint32_t bk = __reduce_max_sync(0xffffffffu, km);
      const int ww = __ffs(__ballot_sync(0xffffffffu, km == bk)) - 1;
#pragma unroll 1
      for (int i = 1; i <= 8; i++) {
        const int W = (ww + i) & 7;
        if (i == 8) {
          mbar_wait(BAR(B_XS), 0);
          if (SM_(uint32_t, OFF_KV) == bk) {
#pragma unroll 2
            for (int j = lane; j < 256; j += 32) {
              const int rho = j >> 4, row = row_of(gA * 128 + 32 * (W >> 1) + 8 * ((rho & 7) >> 1) + 4 * (W & 1) + 2 * (rho >> 3) + (rho & 1));
              const uint4 v = lds128_v(sb + OFF_OUT + (j & 8) * 2048 + (16 * W + rho) * 128 + (((j ^ rho) & 7) << 4));
              if (row != 0xFFFF - (int)(bk & 0xFFFFu))
                asm volatile("st.global.v4.b32 [%0], {%1, %2, %3, %4};" :: "l"(p.out + (size_t)row * 1024 + eps * 128 + (j & 15) * 8), "r"(v.x), "r"(v.y), "r"(v.z), "r"(v.w));
            }
            break;
          }
        }
        if (lane == 0) {
          tma_store_5d(&p.tmOut, sb + OFF_OUT + W * 2048, eps * 128, row_of(gA * 128 + 32 * (W >> 1) + 4 * (W & 1)));
          tma_store_5d(&p.tmOut, sb + OFF_OUT + 16384 + W * 2048, eps * 128 + 64, row_of(gA * 128 + 32 * (W >> 1) + 4 * (W & 1)));
        }
        const long long t0 = clock64();
        while (i < 7 && clock64() - t0 < OUT_PACE_CLK) {}
      }
      if (lane == 0) { bulk_commit(); bulk_wait_all(); }
      PT(22);
    } else {
      const int a = warp - 9;
      const int lane = threadIdx.x & 31;
      auto stage = [&](const bf16* src, int g) {
        if (elect_one()) {
          mbar_expect_tx(BAR(B_AUX + g), 16384);
          bulk_load(sb + OFF_XCH + g * 16384, src + g * 8192, 16384, BAR(B_AUX + g));
        }
      };
      uint32_t tag = 0;
#pragma unroll 1
      for (int i = 0; i < 3; i++) { i += keep_awake(); delay_clk<300>(); }
      mbar_wait(BAR(B_FULL + AUX_AFTER), 0);
      if (a == 0) PT(1);
      if (a == 1) mbar_wait(BAR(B_AUX + 0), 0);
      if (a < 2) stage(p.x + (size_t)cid * 16 * 1024, a);
#pragma unroll 1
      for (int it = 0; it < 4; it++) {
        const int g = it & 1;
        mbar_wait(BAR(B_AUX + g), it >> 1);
        if (a == 0) PT(2 + it);
        if (it == 2) tag = ld_relaxed32(&p.s->epoch) + 1;
        if (it == 2 && a == 2 && lane < 16) asm volatile("prefetch.global.L2 [%0];" :: "l"(p.wr + lane * 64));
        const uint32_t ad = sb + OFF_XCH + g * 16384 + (lane >> 2) * 2048;
        float s0 = 0.f, s1 = 0.f, q0 = 0.f, q1 = 0.f;
        auto row = [&](auto sq) {
#pragma unroll
          for (int i = 0; i < 11; i++) {
            if (i == 10 && a == 2) break;
            const uint4 v = lds128_v(ad + (((a * 44 + 4 * i + lane) & 127) << 4));
            const uint32_t ww[4] = {v.x, v.y, v.z, v.w};
#pragma unroll
            for (int z = 0; z < 4; z++) {
              const float d0 = bf_lo(ww[z]), d1 = bf_hi(ww[z]);
              s0 += d0; s1 += d1;
              if (decltype(sq)::value) { q0 = fmaf(d0, d0, q0); q1 = fmaf(d1, d1, q1); }
            }
          }
        };
        if (it < 2) row(IC<1>()); else row(IC<0>());
        s0 += s1; q0 += q1;
#pragma unroll
        for (int o = 1; o < 4; o <<= 1) { s0 += __shfl_xor_sync(0xffffffffu, s0, o); q0 += __shfl_xor_sync(0xffffffffu, q0, o); }
        if ((lane & 3) == 0) SM_(float2, OFF_PUB + a * 256 + it * 64 + (lane >> 2) * 8) = make_float2(s0, q0);
        if (it != 2) bar_sync(NB_AUX, 96);
        if (it < 2 && a == 2) stage(cid < 64 ? p.Dre + (size_t)cid * 16 * 1024 : p.Dim + (size_t)(cid - 64) * 16 * 1024, g);
      }
      if (a == 1) {
        const float2 v0 = SM_(float2, OFF_PUB + lane * 8), v1 = SM_(float2, OFF_PUB + 256 + lane * 8), v2 = SM_(float2, OFF_PUB + 512 + lane * 8);
        const float s = v0.x + v1.x + v2.x, mean = s * (1.f / 1024.f);
        const float rs = rcp_fast(ln_sd((v0.y + v1.y + v2.y) * (1.f / 1024.f) - mean * mean));
        pkt_st64((lane < 16 ? p.s->xstat : p.s->dsum) + cid * 16 + (lane & 15), lane < 16 ? pack_bf16(rs, mean) : __float_as_uint(s), tag);
        PT(6);
      }
      if (a == 2) {
        float s = 0.f;
#pragma unroll
        for (int q = 0; q < 4; q++) {
          const uint4 v = ldg_nc128(p.wr + (q * 32 + lane) * 8);
          s += ((bf_lo(v.x) + bf_hi(v.x)) + (bf_lo(v.y) + bf_hi(v.y))) + ((bf_lo(v.z) + bf_hi(v.z)) + (bf_lo(v.w) + bf_hi(v.w)));
          const int ch = q * 32 + lane - eps * 16;
          if (ch >= 0 && ch < 16) {
            SM_(uint32_t, OFF_WR + ch * 4) = v.x; SM_(uint32_t, OFF_WR + 80 + ch * 4) = v.y;
            SM_(uint32_t, OFF_WR + 160 + ch * 4) = v.z; SM_(uint32_t, OFF_WR + 240 + ch * 4) = v.w;
          }
        }
        s = warp_sum(s);
        if (lane == 0) { SM_(float, OFF_WSUM) = s; SM_(uint32_t, OFF_TAG) = tag; }
      }
      if (a < 2) __nanosleep(GATHER_NS);
      {
        const int i0 = a * 32 + lane;
        uint2 v[3], c0, c1; uint32_t n = 0;
        const uint2* dp = &p.s->dsum[abrow];
        while (true) {
#pragma unroll
          for (int q = 0; q < 3; q++) v[q] = pkt_ld64(&p.s->xstat[tau * 256 + min(i0 + 96 * q, 255)]);
          c0 = pkt_ld64(dp + i0); c1 = pkt_ld64(dp + min(i0 + 96, 127));
          if (__all_sync(0xffffffffu, v[0].y == tag && v[1].y == tag && v[2].y == tag && c0.y == tag && c1.y == tag) || ++n > SPIN_LIMIT) break;
          __nanosleep(200);
        }
#pragma unroll
        for (int q = 0; q < 3; q++) put_xstat(sb + OFF_RS, sb + OFF_EXB, min(i0 + 96 * q, 255), v[q].x, m);
        put_dsum(sb + OFF_EXA, i0, __uint_as_float(c0.x));
        put_dsum(sb + OFF_EXA, min(i0 + 96, 127), __uint_as_float(c1.x));
        fence_async_smem();
      }
      __syncwarp();
      if (lane == 0) mbar_arrive(BAR(B_STAT));
      if (a == 0) PT(7);
      if (a == 0) {
        const uint32_t* flg = reinterpret_cast<const uint32_t*>(&p.s->abflag[((eps * 2 + m) * 8 + (lane >> 2)) * 2]) + (lane & 3);
        if (NX < 256 && lane == 4 * tau + 1) flg = reinterpret_cast<const uint32_t*>(&p.s->hflag[(m * 8 + eps) * 2]);
        uint32_t seen = 0;
        auto fetch = [&](int s, uint32_t dst) {
          const int tile = sigma_of(tau, s);
          uint32_t n = 0;
          while (!((seen >> (4 * tile)) & 1) && ++n < SPIN_LIMIT) seen = __ballot_sync(0xffffffffu, ld_acquire32(flg) == tag);
          asm volatile("fence.proxy.async.global;" ::: "memory");
          PT(16 + s);
          if (elect_one()) tma_load_2d(dst, &p.tmAbL, BAR(B_FULL + s), tile * 256, abrow);
        };
        mbar_wait(BAR(B_EPI), 0);
#pragma unroll
        for (int s = 0; s < 4; s++) mbar_wait(BAR(B_FULL + s), 0);
        mbar_wait(BAR(B_STD + 0), 0);
        fetch(0, sb + OFF_XCH);
        fetch(1, sb + OFF_XCH + 16384);
        fetch(2, sb + 2 * ST_BYTES);
        if (elect_one()) mbar_arrive(BAR(B_PUB1));
        mbar_wait(BAR(B_STD + 1), 0);
        fetch(3, sb + 3 * ST_BYTES);
        uint32_t n = 0;
        while (true) {
          asm volatile("fence.proxy.async.global;" ::: "memory");
          *(volatile uint32_t*)&SM_(uint32_t, OFF_SEEN) = seen;
          if (seen == 0xFFFFFFFFu || ++n > SPIN_LIMIT) break;
          seen = __ballot_sync(0xffffffffu, ld_acquire32(flg) == tag);
          __nanosleep(100);
        }
      } else {
        uint32_t* flag = reinterpret_cast<uint32_t*>(&p.s->abflag[((eps * 2 + m) * 8 + tau) * 2]);
        if (a == 1) {
          mbar_wait(BAR(B_EPI), 0);
          PT(8);
          if (lane == 0) tma_store_2d(&p.tmAbS, sb + chunk_off(0, 0), tau * 256, abrow);
          mbar_wait(BAR(B_EPI0B), 0);
          if (lane == 0) {
            tma_store_2d(&p.tmAbS, sb + chunk_off(0, 1), tau * 256, abrow + 64);
            bulk_commit();
            bulk_wait_release();
            st_relaxed32(flag, tag);
            mbar_arrive(BAR(B_STD));
          }
          PT(12);
          mbar_wait(BAR(B_EPI + 1), 0);
          mbar_wait(BAR(B_LATE), 0);
          mbar_wait(BAR(B_PUB1), 0);
          PT(9);
          if (lane == 0) {
            tma_store_2d(&p.tmAbS, sb + chunk_off(1, 0), tau * 256 + 64, abrow);
            tma_store_2d(&p.tmAbS, sb + chunk_off(1, 1), tau * 256 + 64, abrow + 64);
            bulk_commit();
            bulk_wait_all();
            mbar_arrive(BAR(B_STD + 1));
            bulk_wait_release();
            st_relaxed32(flag + 1, tag);
          }
          PT(13);
        }
        auto copy_out = [&](int c) {
          mbar_wait(BAR(B_EPI + c), 0);
          PT(8 + c);
          bf16* dst = p.s->abT + (size_t)(abrow + (lane >> 3)) * 2048 + tau * 256 + c * 64 + (lane & 7) * 8;
          const uint32_t src = sb + chunk_off(c, 0) + (lane >> 3) * 128 + (((lane & 7) ^ (lane >> 3)) << 4);
          const uint32_t on = c * 64 + (lane & 7) * 8 < NX;
#pragma unroll 4
          for (int i = 0; i < 32; i++) {
            const uint4 v = lds128_v((src ^ ((i & 1) << 6)) + i * 512);
            asm volatile("{\n.reg .pred p;\nsetp.ne.b32 p, %5, 0;\n@p st.global.v4.b32 [%0], {%1, %2, %3, %4};\n}\n"
                         :: "l"(dst + i * 4 * 2048), "r"(v.x), "r"(v.y), "r"(v.z), "r"(v.w), "r"(on));
          }
          __syncwarp();
          if (lane == 0) mbar_arrive(BAR(B_STD + c));
        };
        if (a == 2) {
#pragma unroll 1
          for (int c = 2; c < 4; c++) copy_out(c);
          asm volatile("fence.acq_rel.gpu;" ::: "memory");
          __syncwarp();
          if (lane < 2) st_relaxed32(flag + 2 + lane, tag);
          PT(15);
        }
      }
      {
        mbar_wait(BAR(B_LATE), 1);
        const int grp = tau * 2 + m;
#pragma unroll 1
        for (int i = a; i < 14; i += 3) {
          uint4* dst = i < 8 ? &p.s->ypart[cid * 256 + i * 32 + lane] : i < 12 ? &p.s->hstat[(grp * 8 + eps) * 128 + (i - 8) * 32 + lane]
                     : i == 12 ? &p.s->cand[grp * 256 + eps * 32 + lane] : &p.s->key[(((lane >> 1) & 7) * 16 + grp) * 2 + (lane & 1)];
          if (i < 13 || eps == 0) pkt_st128(dst, 0, 0, 0, 0);
          __nanosleep(200);
        }
        __syncwarp();
        if (lane == 0) mbar_arrive(BAR(B_STAT));
      }
      {
        const uint4* kp = &p.s->key[(tau * 16 + (lane & 15)) * 2];
        const int i0 = a * 32 + lane;
        mbar_wait(BAR(B_KEY), 0);
        if (a == 0) PT(43);
        uint4 kq = pkt_ld128(kp), cv[3] = {};
        uint32_t n = 0, kv;
        int gspec = -1;
        while (true) {
          const bool ok = kq.y == tag && kq.w == tag;
          kv = __reduce_max_sync(0xffffffffu, ok ? kq.x : 0u);
          const int gs = group_of(0xFFFF - (int)(kv & 0xFFFFu));
          const bool cok = gs == gspec && cv[0].y == tag && cv[0].w == tag && cv[1].y == tag && cv[1].w == tag && cv[2].y == tag && cv[2].w == tag;
          if (__all_sync(0xffffffffu, ok && cok) || ++n > SPIN_LIMIT) break;
          if (!ok) kq = pkt_ld128(kp);
          n += keep_awake();
          const bool spec = __popc(__ballot_sync(0xffffffffu, ok)) >= 2 * SPEC_MIN;
          if (!cok && spec) {
#pragma unroll
            for (int i = 0; i < 3; i++) cv[i] = pkt_ld128(&p.s->cand[gs * 256 + min(i0 + 96 * i, 255)]);
          }
          if (spec) gspec = gs;
        }
        if (a == 0) PT(45);
        const uint32_t ms = __shfl_sync(0xffffffffu, kq.z, gspec);
        const uint32_t nm = ((ms & 0xFFFFu) ^ 0x8000u) * 0x10001u;
        const float is = rcp_fast(bf_hi(ms));
#pragma unroll
        for (int i = 0; i < 3; i++) {
          const int j = min(i0 + 96 * i, 255);
          SM_(uint2, OFF_XSEL + j * 8) = make_uint2(norm2(cv[i].x, nm, is), norm2(cv[i].z, nm, is));
        }
#pragma unroll
        for (int i = 0; i < 3; i++) SM_(uint2, OFF_HSEL + min(i0 + 96 * i, 255) * 8) = make_uint2(cv[i].x, cv[i].z);
        SM_(uint32_t, OFF_KV) = kv;
        __syncwarp();
        if (lane == 0) mbar_arrive(BAR(B_XS));
      }
    }
    asm volatile("barrier.cluster.wait.aligned;" ::: "memory");
  } else {
    reg_inc<REG_C>();
    const int tid = __shfl_sync(0xffffffffu, threadIdx.x, threadIdx.x & 31), lane = tid & 31;
    const int w = warp >> 2, wi = warp & 3, t = tid & 127;
    const int g = lane >> 2, q = lane & 3;
    const int turn_me = NB_TURN0 + w, turn_other = NB_TURN1 - w;
    auto release = [&](int s) { if (t == 0) mbar_arrive(BAR(B_EMPTY + s)); };
    if (MAP == 0 && helper) {
      asm volatile("barrier.cluster.arrive.relaxed.aligned;" ::: "memory");
      float s0[64], s1[64];
#pragma unroll
      for (int i = 0; i < 64; i++) { s0[i] = 0.f; s1[i] = 0.f; }
      if (w == 1) bar_arrive(NB_TURN0, 256);
      uint32_t o[32][2] = {};
      const int col = (eps - 2) * 8 + m * 4 + w;
      auto put = [&](auto tc, uint32_t buf) {
        constexpr int tl = decltype(tc)::value;
#pragma unroll
        for (int i = 0; i < 4; i++)
          smem_at<uint2>(buf + ((i >> 1) * 64 + wi * 16 + (i & 1) * 8 + g) * 32 + ((q * 8) ^ ((g & 4) << 2))) = make_uint2(o[8 * i + tl][0], o[8 * i + tl][1]);
      };
#pragma unroll 1
      for (int pass = 0; pass < 2; pass++) {
#pragma unroll 1
        for (int k = 16 * pass; k < 16 * pass + 16; k++) {
          const int s = slot_of(k);
          mbar_wait(BAR(B_FULL + s), use_of(k) & 1);
          bar_sync(turn_me, 256);
          const uint64_t da = make_desc(sb + s * ST_BYTES + A_BYTES + w * 16384), db = make_desc(sb + s * ST_BYTES);
          wgmma_fence();
#pragma unroll
          for (int kk = 0; kk < 4; kk++) {
            wgmma_n128(s0, da + kk * 2, db + kk * 2, kk > 0 || (k & 15));
            wgmma_n128(s1, da + 512 + kk * 2, db + kk * 2, kk > 0 || (k & 15));
          }
          wgmma_commit();
          if (k < 31 || w == 0) bar_arrive(turn_other, 256);
          if (pass && !(k & 1)) {
            const uint32_t buf = sb + OFF_XCH + 20480 + w * 4096;
            static_for<8>([&](auto ic) { if (k == 16 + 2 * decltype(ic)::value) put(ic, buf); });
            fence_async_smem();
            bar_sync(NB_WG0 + w, 128);
            if (t == 0) { tma_store_2d(&p.tmAbM, buf, (k - 16) * 128 + 240, col * 128); bulk_commit(); }
          }
          wgmma_wait0();
          release(s);
          if ((k & 1) && t == 0) asm volatile("cp.async.bulk.wait_group.read 0;" ::: "memory");
        }
        mbar_wait(BAR(B_STAT), 0);
        wgmma_fence();
        wgmma_n128(s0, make_desc_noswz(sb + OFF_XCH + pass * 8192 + w * 4096), make_desc_noswz(sb + OFF_XCH + 16384));
        wgmma_n128(s1, make_desc_noswz(sb + OFF_XCH + pass * 8192 + w * 4096 + 2048), make_desc_noswz(sb + OFF_XCH + 16384));
        wgmma_commit();
        uint4 rs[4];
#pragma unroll
        for (int i = 0; i < 4; i++) rs[i] = lds128_v(sb + OFF_RS + q * 144 + i * 16);
        wgmma_wait0();
        fence_acc(s0); fence_acc(s1);
#pragma unroll
        for (int i = 0; i < 32; i++) {
          const int tl = i & 7, hr = (i >> 3) & 1;
          const float* ac = (i >> 4) ? &s1[8 * tl + 2 * hr] : &s0[8 * tl + 2 * hr];
          o[i][0] = bmul2(pack_bf16(ac[0], ac[1]), (tl & 1) ? rs[tl >> 1].z : rs[tl >> 1].x);
          o[i][1] = bmul2(pack_bf16(ac[4], ac[5]), (tl & 1) ? rs[tl >> 1].w : rs[tl >> 1].y);
        }
      }
      static_for<8>([&](auto ic) { put(ic, sb + (w * 8 + decltype(ic)::value) * 4096); });
      fence_async_smem();
      bar_sync(NB_WG0 + w, 128);
      if (t == 0) {
#pragma unroll 1
        for (int i = 0; i < 8; i++) tma_store_2d(&p.tmAbM, sb + (w * 8 + i) * 4096, i * 256 + 240, (col + 2) * 128);
        bulk_commit();
        bulk_wait_release();
        st_relaxed32(&p.s->hflag[col * 2], SM_(uint32_t, OFF_TAG));
        st_relaxed32(&p.s->hflag[(col + 2) * 2], SM_(uint32_t, OFF_TAG));
      }
      asm volatile("barrier.cluster.wait.aligned;" ::: "memory");
      return;
    }
    float acc[128], a1[NX / 2];
#pragma unroll
    for (int i = 0; i < NX / 2; i++) a1[i] = 0.f;
    if (w == 1) bar_arrive(NB_TURN0, 256);
    auto kstep = [&](auto& d, int k, bool first, bool a_in_xch = false, bool mini = false) {
      const int s = slot_of(k);
      mbar_wait(BAR(B_FULL + s), use_of(k) & 1);
      CT(64 + k);
      bar_sync(turn_me, 256);
      const uint64_t da = make_desc(sb + (a_in_xch ? OFF_XCH + s * 16384 : s * ST_BYTES) + w * 8192), db = make_desc(sb + s * ST_BYTES + A_BYTES);
      wgmma_fence();
      wgmma_g1(d, da, db, !first);
#pragma unroll
      for (int kk = 1; kk < 4; kk++) wgmma_g1(d, da + kk * 2, db + kk * 2, 1);
      wgmma_commit();
      if (mini) {
        CT(29);
        mbar_wait(BAR(B_MINI), 0);
        CT(30);
        wgmma_fence();
        wgmma_g1(d, make_desc_32b(sb + OFF_MINI + w * 2048), make_desc_32b(sb + OFF_MINI + 4096), 1);
        wgmma_commit();
      }
      bar_arrive(turn_other, 256);
    };
    auto kdone = [&](int k) { wgmma_wait0(); release(slot_of(k)); };
    auto wgmma_wait1 = [&]() { asm volatile("wgmma.wait_group.sync.aligned 1;" ::: "memory"); };

#pragma unroll 1
    for (int k = 0; k < 14; k++) {
      kstep(a1, k, k == 0);
      if (k == 0) CT(0);
      if (k == 8 && warp == 2 && lane < 2) pkt_st128(&p.s->abflag[((eps * 2 + m) * 8 + tau) * 2 + lane], 0, 0, 0, 0);
      kdone(k);
    }
    uint32_t R[64];
    uint32_t tag;
    float p0[32], p1[NX / 2 - 32];
    auto pack = [&](auto cc) {
      constexpr int c = decltype(cc)::value;
#pragma unroll
      for (int j = 8 * c; j < min_c(8 * c + 8, NX / 8); j++) {
        const uint32_t rs = R[2 * j];
        const float* ac = c ? &p1[4 * j - 32] : &p0[4 * j];
        R[2 * j] = bmul2(pack_bf16(ac[0], ac[1]), rs);
        R[2 * j + 1] = bmul2(pack_bf16(ac[2], ac[3]), rs);
      }
    };
    auto put_chunk = [&](auto cc) {
      constexpr int c = decltype(cc)::value;
      const int rho = 16 * wi + (lane & 15);
#pragma unroll
      for (int j = 8 * c; j < min_c(8 * c + 8, NX / 8); j += 2) {
        const int chunk = (j & 7) + (lane >> 4);
        stsm_x4(sb + chunk_off(c, w) + rho * 128 + ((chunk ^ (lane & 7)) << 4), R[2 * j], R[2 * j + 1], R[2 * j + 2], R[2 * j + 3]);
      }
    };
    auto staged = [&](int bar) {
      fence_async_smem();
      __syncwarp();
      if (lane == 0) mbar_arrive(BAR(bar));
    };
    auto mma_rs = [&](auto cc, auto k0, auto k1) {
      constexpr int c = decltype(cc)::value;
      const uint64_t db = make_desc(sb + c * ST_BYTES + A_BYTES);
#pragma unroll
      for (int kk = decltype(k0)::value; kk < decltype(k1)::value; kk++)
        wgmma_n256_rs(acc, R[16 * c + 4 * kk], R[16 * c + 4 * kk + 1], R[16 * c + 4 * kk + 2], R[16 * c + 4 * kk + 3], db + kk * 2, c + kk > 0);
      wgmma_commit();
    };
    auto kdone_x = [&](int k, auto ic) {
      constexpr int i = decltype(ic)::value;
      uint32_t r[8];
#pragma unroll
      for (int z = 0; z < 2; z++) {
        const int tr = 32 * (i & 1) + 16 * z + 8 * (lane >> 4) + (lane & 7), chunk = 2 * wi + ((lane >> 3) & 1);
        ldsm_x4_t(sb + (i >> 1) * ST_BYTES + w * 8192 + tr * 128 + ((chunk ^ (lane & 7)) << 4), r[4 * z], r[4 * z + 1], r[4 * z + 2], r[4 * z + 3]);
      }
      float f[16];
#pragma unroll
      for (int z = 0; z < 8; z++) { f[2 * z] = bf_lo(r[z]); f[2 * z + 1] = bf_hi(r[z]); }
#pragma unroll
      for (int z = 0; z < 16; z++) asm volatile("" : "+f"(f[z]));
      kdone(k);
#pragma unroll
      for (int z = 0; z < 16; z++) asm volatile("add.f32 %0, %0, %1;" : "+f"(acc[16 * i + z]) : "f"(f[z]));
    };
    {
      const uint32_t rsa = sb + OFF_RS + q * 144;
      const uint64_t da2 = make_desc(sb + 2 * ST_BYTES + w * 8192), db2 = make_desc(sb + 2 * ST_BYTES + A_BYTES);
      const uint64_t da3 = make_desc(sb + 3 * ST_BYTES + w * 8192), db3 = make_desc(sb + 3 * ST_BYTES + A_BYTES);
      const uint64_t dax = make_desc_noswz(sb + OFF_EXA + w * 2048), dbx = make_desc_noswz(sb + OFF_EXB);
      auto load_rs = [&](int i) { const uint4 v = lds128_v(rsa + i * 16); R[8 * i] = v.x; R[8 * i + 2] = v.y; R[8 * i + 4] = v.z; R[8 * i + 6] = v.w; };
      fence_acc(a1);
#pragma unroll
      for (int i = 0; i < 32; i++) asm volatile("mov.b32 %0, %1;" : "=f"(p0[i]) : "f"(a1[i]));
#pragma unroll
      for (int i = 32; i < NX / 2; i++) asm volatile("mov.b32 %0, %1;" : "=f"(p1[i - 32]) : "f"(a1[i]));
      mbar_wait(BAR(B_FULL + 2), 1);
      CT(64 + 14);
      bar_sync(turn_me, 256);
      wgmma_fence();
#pragma unroll
      for (int kk = 0; kk < 4; kk++) wgmma_g1(p0, da2 + kk * 2, db2 + kk * 2, 1);
      wgmma_commit();
      mbar_wait(BAR(B_FULL + 3), 1);
      mbar_wait(BAR(B_STAT), 0);
      CT(64 + 15);
      wgmma_fence();
#pragma unroll
      for (int kk = 0; kk < 4; kk++) wgmma_g1(p0, da3 + kk * 2, db3 + kk * 2, 1);
      wgmma_g1(p0, dax, dbx, 1);
      wgmma_commit();
      bar_arrive(turn_other, 256);
      tag = SM_(uint32_t, OFF_TAG);
      load_rs(0); load_rs(1);
      wgmma_wait0();
      fence_acc(p0);
      pack(IC<0>());
      put_chunk(IC<0>());
      CT(20);
      if (w == 1) staged(B_EPI0B);
      bar_sync(turn_me, 256);
      wgmma_fence();
#pragma unroll
      for (int kk = 0; kk < 4; kk++) wgmma_g1(p1, da2 + kk * 2, db2 + 512 + kk * 2, 1);
      wgmma_commit();
      if (w == 0) staged(B_EPI);
      CT(21);
      wgmma_fence();
#pragma unroll
      for (int kk = 0; kk < 4; kk++) wgmma_g1(p1, da3 + kk * 2, db3 + 512 + kk * 2, 1);
      wgmma_g1(p1, dax, dbx + 128, 1);
      wgmma_commit();
      bar_arrive(turn_other, 256);
#pragma unroll
      for (int i = 2; i < 8; i++) load_rs(i);
      wgmma_wait1();
      release(2);
      kdone(15);
      mbar_wait(BAR(B_STAT), 0);
    }
    fence_acc(p1);
    CT(1);
    pack(IC<1>());
    pack(IC<2>());
    pack(IC<3>());
#pragma unroll
    for (int i = 16; i < NX / 4; i++) asm volatile("" : "+r"(R[i]));
#pragma unroll
    for (int i = 0; i < 128; i++) asm volatile("" : "=f"(acc[i]));
    mbar_wait(BAR(B_FULL + 0), 0);
    CT(2);
    CT(64 + 16);
    bar_sync(turn_me, 256);
    wgmma_fence();
    mma_rs(IC<0>(), IC<0>(), IC<4>());
    mbar_wait(BAR(B_FULL + 1), 0);
    CT(64 + 17);
    wgmma_fence();
    mma_rs(IC<1>(), IC<0>(), IC<2>());
    wgmma_wait1();
    release(0);
    mma_rs(IC<1>(), IC<2>(), IC<4>());
    bar_arrive(turn_other, 256);
    kdone_x(17, IC<0>());
    static_for<2>([&](auto ic) {
      constexpr int c = 2 + decltype(ic)::value;
      mbar_wait(BAR(B_FULL + c), 0);
      CT(64 + 16 + c);
      bar_sync(turn_me, 256);
      wgmma_fence();
      mma_rs(IC<c>(), IC<0>(), IC<min_c(4, NX / 16 - 4 * c)>());
      bar_arrive(turn_other, 256);
      if (c == 2) { put_chunk(IC<1>()); staged(B_EPI + 1); }
      kdone_x(16 + c, IC<c - 1>());
    });
#pragma unroll 1
    for (int k = 20; k < 23; k++) {
      kstep(acc, k, false, k < 22);
      if (k == 20) {
        kdone_x(k, IC<3>());
      } else {
        if (k == 21) put_chunk(IC<2>()); else put_chunk(IC<3>());
        __syncwarp();
        if (lane == 0) mbar_arrive(BAR(B_EPI + k - 19));
        kdone(k);
      }
    }
    uint32_t wf[32][4];
    auto load_wf = [&](auto hc) {
      constexpr int h = decltype(hc)::value;
      const int d = w * 64 + (lane >> 4) * 8 + (lane & 7);
      const uint32_t ad = sb + round_off(h) + (lane & 8) * 1024 + d * 64 + ((wi ^ ((lane >> 1) & 3)) << 4);
#pragma unroll
      for (int i = 0; i < 4; i++) ldsm_x4_t(ad + i * 1024, wf[4 * h + i][0], wf[4 * h + i][1], wf[4 * h + i][2], wf[4 * h + i][3]);
    };
    auto load_wf_rest = [&]() { static_for<8 - NREG_H>([&](auto ic) { load_wf(IC<NREG_H + decltype(ic)::value>()); }); };
#pragma unroll
    for (int i = 0; i < 4 * NREG_H; i++) { wf[i][0] = 0; wf[i][1] = 0; wf[i][2] = 0; wf[i][3] = 0; }
    const int grp = tau * 2 + m;
#pragma unroll 1
    for (int k = 23; k < 46; k++) {
      kstep(acc, k, false, false, NX < 256 && k == MINI_K);
      if (moe) {
        static_for<NREG_H>([&](auto hc) {
          constexpr int h = decltype(hc)::value;
          if (k == mr_k(h) + 1) { mbar_wait(BAR(B_MR + (h & 1)), (h >> 1) & 1); CT(32 + h); load_wf(hc); }
        });
      }
      if (k == RESET_K && tid == 0) mbar_arrive(BAR(B_LATE));
      kdone(k);
    }
    asm volatile("barrier.cluster.arrive.relaxed.aligned;" ::: "memory");
    mbar_wait(BAR(B_STAT), 1);
    uint32_t wa[16][2];
    uint32_t cd = code_of(tag);
    uint4* hp_pub = &p.s->hstat[(grp * 8 + eps) * 128 + warp * 16 + g];
    const uint4* hp_poll = &p.s->hstat[(grp * 8 + 2 * q) * 128 + warp * 16 + g];
    const uint32_t vec_off = (2 * wi) * 512 + q * 128 + ((g ^ (2 * q)) << 4);
    {
      float as[64], ak[64];
      fence_acc(acc);
#pragma unroll
      for (int i = 0; i < 64; i++) asm volatile("mov.b32 %0, %1;" : "=f"(as[i]) : "f"(acc[64 + i]));
#pragma unroll
      for (int i = 0; i < 64; i++) asm volatile("mov.b32 %0, %1;" : "=f"(ak[i]) : "f"(acc[i]));
      const uint64_t da1 = make_desc(sb + 2 * ST_BYTES + w * 8192), db1 = make_desc(sb + 2 * ST_BYTES + A_BYTES);
      const uint64_t da2 = make_desc(sb + 3 * ST_BYTES + w * 8192), db2 = make_desc(sb + 3 * ST_BYTES + A_BYTES);
      mbar_wait(BAR(B_FULL + 2), 1);
      CT(64 + 46);
      bar_sync(turn_me, 256);
      wgmma_fence();
#pragma unroll
      for (int kk = 0; kk < 4; kk++) wgmma_n128(as, da1 + kk * 2, db1 + 1024 + kk * 2);
      wgmma_commit();
      mbar_wait(BAR(B_FULL + 3), 1);
      CT(64 + 47);
      wgmma_fence();
#pragma unroll
      for (int kk = 0; kk < 4; kk++) wgmma_n128(as, da2 + kk * 2, db2 + 1024 + kk * 2);
      wgmma_commit();
      bar_arrive(turn_other, 256);
      const uint32_t rx = mapa(sb + OFF_PEER + w * 4096 + vec_off, 1 - m), rb = mapa(BAR(B_XCH), 1 - m);
      asm volatile("barrier.cluster.wait.aligned;" ::: "memory");
      CT(24);
      wgmma_wait0();
      fence_acc(as);
      CT(25);
      auto keep = [&]() {
        bar_sync(turn_me, 256);
        wgmma_fence();
#pragma unroll
        for (int kk = 0; kk < 4; kk++) wgmma_n128(ak, da1 + kk * 2, db1 + kk * 2);
        wgmma_commit();
#pragma unroll
        for (int kk = 0; kk < 4; kk++) wgmma_n128(ak, da2 + kk * 2, db2 + kk * 2);
        wgmma_commit();
        if (w == 0) bar_arrive(turn_other, 256);
      };
#pragma unroll
      for (int i = 0; i < 8; i++) {
        if (i == SEND_FIRST) keep();
        const float* ac = &as[16 * (i >> 1) + 2 * (i & 1)];
        st_async_v4(rx + (i >> 1) * 8192 + (i & 1) * 512, rb, pack_bf16(ac[0], ac[1]), pack_bf16(ac[4], ac[5]), pack_bf16(ac[8], ac[9]), pack_bf16(ac[12], ac[13]));
      }
      CT(26);
#pragma unroll
      for (int i = 0; i < 4; i++) {
        const uint4 v = lds128_v(sb + OFF_WR + q * 80 + i * 16);
        const uint32_t vv[4] = {v.x, v.y, v.z, v.w};
#pragma unroll
        for (int z = 0; z < 4; z++) {
          asm volatile("{\n.reg .pred p;\nsetp.ne.b32 p, %2, 0;\nselp.b32 %0, %1, 0x3F803F80, p;\n}" : "=r"(wa[4 * i + z][0]) : "r"(vv[z]), "r"(g & 1));
          asm volatile("{\n.reg .pred p;\nsetp.ne.b32 p, %2, 0;\nselp.b32 %0, %1, 0x3F803F80, p;\n}" : "=r"(wa[4 * i + z][1]) : "r"(vv[z]), "r"(g & 1));
        }
      }
      pin(cd); pin(hp_pub); pin(hp_poll);
      CT(27);
      wgmma_wait1();
      release(2);
      wgmma_wait0();
      fence_acc(ak);
      CT(3);
#pragma unroll
      for (int i = 0; i < 8; i++) {
        const float* ac = &ak[16 * (i >> 1) + 2 * (i & 1)];
        sts128(sb + (2 + (i >> 2)) * ST_BYTES + w * 8192 + ((i >> 1) & 1) * 4096 + (i & 1) * 512 + vec_off,
               pack_bf16(ac[0], ac[1]), pack_bf16(ac[4], ac[5]), pack_bf16(ac[8], ac[9]), pack_bf16(ac[12], ac[13]));
      }
    }
    uint32_t h[8][4];
    {
      const int qq = 2 * (warp & 1) + ((lane >> 3) & 1);
      const uint32_t lo = (lane >> 4) * 512 + qq * 128 + (((lane & 7) ^ (2 * qq)) << 4);
      bar_sync(NB_BOTH, 256);
#pragma unroll
      for (int ks = 0; ks < 8; ks++)
        ldsm_x4_t(sb + (2 + w) * ST_BYTES + (ks >> 2) * 8192 + (wi >> 1) * 4096 + (ks & 3) * 1024 + lo, h[ks][0], h[ks][1], h[ks][2], h[ks][3]);
      CT(28);
      mbar_wait_cluster(BAR(B_XCH), 0);
      CT(4);
      uint32_t r[8][4];
#pragma unroll
      for (int ks = 0; ks < 8; ks++) ldsm_x4_t(sb + OFF_PEER + (warp >> 1) * 8192 + ks * 1024 + lo, r[ks][0], r[ks][1], r[ks][2], r[ks][3]);
      float d[4][4] = {};
#pragma unroll
      for (int ks = 0; ks < 8; ks++) {
#pragma unroll
        for (int i = 0; i < 4; i++) {
          h[ks][i] = badd2(h[ks][i], r[ks][i]);
          mma1688(d[i], h[ks][i], wa[2 * ks + (i >> 1)][i & 1], h[ks][i]);
        }
      }
#pragma unroll
      for (int i = 0; i < 2; i++) {
        const float sq = (g & 1) ? d[i][1] + d[i + 2][1] : d[i][0] + d[i + 2][0];
        const float e0 = d[i][2] + d[i + 2][2], e1 = d[i][3] + d[i + 2][3];
        const float other = __shfl_xor_sync(0xffffffffu, (g & 1) ? e0 : e1, 4);
        if (q == (g >> 1)) pkt_st128(hp_pub + 8 * i, with_bit((g & 1) ? other : e0, cd), with_bit(sq, cd >> 1), __float_as_uint((g & 1) ? e1 : other), tag);
      }
    }
    CT(5);
    if (tid == 0) mbar_arrive(BAR(B_KEY));
    delay_clk<HOP1_DELAY>();
    float m_bf, sd, inv_sd, r_bf;
    uint4* key_pub = &p.s->key[((lane & 7) * 16 + grp) * 2];
    uint4* cand_pub = &p.s->cand[grp * 256 + eps * 32 + q];
    uint32_t trow_inv = 0xFFFFu - (uint32_t)row_of(grp * 128 + 32 * (warp >> 1) + 8 * (g >> 1) + 4 * (warp & 1) + (q & 2) + (g & 1));
    {
      uint4 u[4];
#pragma unroll
      for (int i = 0; i < 4; i++) u[i] = pkt_ld128(hp_poll + (i & 1) * 128 + (i >> 1) * 8);
      const float wsum = SM_(float, OFF_WSUM);
      pin(key_pub); pin(cand_pub); pin(trow_inv);
      uint32_t n = 0;
      while (true) {
        bool ok[4];
#pragma unroll
        for (int i = 0; i < 4; i++) ok[i] = u[i].w == tag && pair_code(u[i].x, u[i].y) == cd;
        const bool all = __all_sync(0xffffffffu, ok[0] && ok[1] && ok[2] && ok[3]);
        if (all || ++n > SPIN_LIMIT) break;
#pragma unroll
        for (int i = 0; i < 4; i++) pkt_ld128_if(u[i], hp_poll + (i & 1) * 128 + (i >> 1) * 8, !ok[i]);
      }
      CT(6);
      float a[3], b[3];
      a[0] = __uint_as_float(u[0].x & ~1u) + __uint_as_float(u[1].x & ~1u); b[0] = __uint_as_float(u[2].x & ~1u) + __uint_as_float(u[3].x & ~1u);
      a[1] = __uint_as_float(u[0].y & ~1u) + __uint_as_float(u[1].y & ~1u); b[1] = __uint_as_float(u[2].y & ~1u) + __uint_as_float(u[3].y & ~1u);
      a[2] = __uint_as_float(u[0].z) + __uint_as_float(u[1].z); b[2] = __uint_as_float(u[2].z) + __uint_as_float(u[3].z);
#pragma unroll
      for (int i = 0; i < 3; i++) {
        a[i] = ((q & 2) ? b[i] : a[i]) + __shfl_xor_sync(0xffffffffu, (q & 2) ? a[i] : b[i], 2);
        a[i] += __shfl_xor_sync(0xffffffffu, a[i], 1);
      }
      const float mu = a[0] * (1.f / 1024.f);
      m_bf = bf16r(mu);
      sd = ln_sd(a[1] * (1.f / 1024.f) - mu * mu);
      inv_sd = rcp_fast(sd);
      r_bf = bf16r((a[2] - m_bf * wsum) * inv_sd);
    }
    {
      const uint32_t u = __float_as_uint(r_bf);
      const uint32_t ord = (u & 0x80000000u) ? ~u : (u | 0x80000000u);
      const uint32_t key = (ord & 0xFFFF0000u) | trow_inv;
      const uint32_t wk = __reduce_max_sync(0xffffffffu, key);
      if (key == wk) SM_(uint2, OFF_WKEY + warp * 8) = make_uint2(wk, (__float_as_uint(m_bf) >> 16) | __float_as_uint(sd));
      const uint32_t wmask = __ballot_sync(0xffffffffu, key == wk);
      const bool hi = (wmask & 0xCCCCCCCCu) != 0;
      uint32_t c[16];
#pragma unroll
      for (int ks = 0; ks < 8; ks++) { c[2 * ks] = hi ? h[ks][1] : h[ks][0]; c[2 * ks + 1] = hi ? h[ks][3] : h[ks][2]; }
      bar_sync(NB_BOTH, 256);
      const uint2 km = SM_(uint2, OFF_WKEY + (lane & 7) * 8);
      const uint32_t bk = __reduce_max_sync(0xffffffffu, km.x);
      if (wk == bk) {
        if ((wmask >> (lane & 28)) & 15) {
#pragma unroll
          for (int ks = 0; ks < 8; ks++) pkt_st128(cand_pub + ks * 4, c[2 * ks], tag, c[2 * ks + 1], tag);
        }
      } else if (eps == 0) {
        const uint32_t kx = __shfl_sync(0xffffffffu, km.x, warp ^ 1), ms = __shfl_sync(0xffffffffu, km.y, warp ^ 1);
        if (kx == bk && lane < 8) pkt_st128(key_pub, bk, tag, ms, tag);
      }
      CT(7);
    }
    {
      const float ih = bf16r(inv_sd);
      const uint32_t nm = pack_bf16(-m_bf, -m_bf), iv = pack_bf16(ih, inv_sd - ih);
      const uint32_t nm_o = __shfl_xor_sync(0xffffffffu, nm, 2), iv_o = __shfl_xor_sync(0xffffffffu, iv, 2);
      const uint32_t nm2[2] = {(q & 2) ? nm_o : nm, (q & 2) ? nm : nm_o}, iv2[2] = {(q & 2) ? iv_o : iv, (q & 2) ? iv : iv_o};
      const uint32_t hi2[2] = {__byte_perm(iv2[0], 0, 0x1010), __byte_perm(iv2[1], 0, 0x1010)}, lo2[2] = {__byte_perm(iv2[0], 0, 0x3232), __byte_perm(iv2[1], 0, 0x3232)};
      const uint32_t oa = sb + OFF_OUT + (warp * 16 + (lane & 15)) * 128;
#pragma unroll
      for (int ks = 0; ks < 8; ks++) {
        uint32_t o[4];
#pragma unroll
        for (int i = 0; i < 4; i++) {
          const uint32_t dd = badd2(h[ks][i], nm2[i & 1]);
          o[i] = badd2(h[ks][i], bfma2(dd, hi2[i & 1], bmul2(dd, lo2[i & 1])));
        }
        stsm_x4(oa + (ks >> 2) * 16384 + (((2 * (ks & 3) + (lane >> 4)) ^ (lane & 7)) << 4), o[0], o[1], o[2], o[3]);
      }
      staged(B_OUT);
    }
    CT(8);
    uint32_t df[16][4];
    auto load_df = [&]() {
      const int frow = (lane & 7) + ((lane >> 4) << 3), hi = (lane >> 3) & 1;
      const uint32_t base = sb + down_off(warp >> 1) + (warp & 1) * 8192 + frow * 128;
#pragma unroll
      for (int mt = 0; mt < 8; mt++) {
#pragma unroll
        for (int ks = 0; ks < 2; ks++)
          ldsm_x4_t(base + (mt >> 2) * 4096 + ks * 2048 + (((2 * (mt & 3) + hi) ^ (lane & 7)) << 4),
                    df[2 * mt + ks][0], df[2 * mt + ks][1], df[2 * mt + ks][2], df[2 * mt + ks][3]);
      }
    };
    if (moe) {
      mbar_wait(BAR(B_GU), 0);
      load_wf_rest();
      mbar_wait(BAR(B_DN), 0);
      load_df();
    }
    uint4* y_pub = &p.s->ypart[cid * 256 + tid];
    uint32_t xs_ad = sb + OFF_XSEL + (8 * (g >> 2) + 4 * w + (g & 3)) * 32 + q * 8, gp_ad = sb + OFF_GP + (wi * 8 + g) * 16 + w * 8 + (q >> 1) * 4;
    pin(y_pub); pin(xs_ad); pin(gp_ad);
    mbar_wait(BAR(B_XS), 0);
    CT(9);
    if (moe) {
      float gd[8][4] = {};
      uint2 bx[4];
#pragma unroll
      for (int r = 0; r < 4; r++) bx[r] = smem_at<uint2>(xs_ad + r * 512);
#pragma unroll
      for (int r = 0; r < 4; r++) {
#pragma unroll
        for (int i = 0; i < 8; i++) mma16816(gd[i], wf[8 * r + i][0], wf[8 * r + i][1], wf[8 * r + i][2], wf[8 * r + i][3], bx[r].x, bx[r].y);
      }
      const float gs = sel4(q, gd[0][0] + gd[1][1], gd[2][0] + gd[3][1], gd[4][0] + gd[5][1], gd[6][0] + gd[7][1]);
      const float us = sel4(q, gd[0][2] + gd[1][3], gd[2][2] + gd[3][3], gd[4][2] + gd[5][3], gd[6][2] + gd[7][3]);
      float v = ((q & 2) ? us : gs) + __shfl_xor_sync(0xffffffffu, (q & 2) ? gs : us, 2);
      v += __shfl_xor_sync(0xffffffffu, v, 1);
      smem_at<float>(gp_ad) = v;
      CT(10);
      bar_sync(NB_BOTH, 256);
      uint32_t bq[4];
      {
        const float4 p0 = SM_(float4, OFF_GP + lane * 16);
        const float gt = bf16r(p0.x + p0.z), up = bf16r(p0.y + p0.w);
        const float act = bf16r(gt * sigmoid_fast(gt)) * up;
        const uint32_t pr = pack_bf16(act, __shfl_down_sync(0xffffffffu, act, 1));
#pragma unroll
        for (int i = 0; i < 4; i++) bq[i] = __shfl_sync(0xffffffffu, pr, 8 * i + 2 * q);
      }
      CT(11);
      float yd[8][4] = {};
#pragma unroll
      for (int ks = 0; ks < 2; ks++) {
#pragma unroll
        for (int mt = 0; mt < 8; mt++) mma16816(yd[mt], df[2 * mt + ks][0], df[2 * mt + ks][1], df[2 * mt + ks][2], df[2 * mt + ks][3], bq[2 * ks], bq[2 * ks + 1]);
      }
      pkt_st128(y_pub, with_bit(sel4(q, yd[0][0], yd[2][0], yd[4][0], yd[6][0]), cd), with_bit(sel4(q, yd[0][2], yd[2][2], yd[4][2], yd[6][2]), cd >> 1),
                with_bit(sel4(q, yd[1][0], yd[3][0], yd[5][0], yd[7][0]), cd), with_bit(sel4(q, yd[1][2], yd[3][2], yd[5][2], yd[7][2]), cd >> 1));
    } else {
      const long long tw = clock64();
      while (clock64() - tw < IDLE_WAIT_CLK) __nanosleep(100);
    }
    CT(12);
    const uint32_t kv = SM_(uint32_t, OFF_KV);
    const int tsel = (int)(~kv & 2047u);
    const float r_sel = __uint_as_float((kv & 0x80000000u) ? (kv & 0x7FFF0000u) : (~kv & 0xFFFF0000u));
    const float sig = bf16r(sigmoid_fast(r_sel));
    const int pfin = 2 * cid + (tid & 1);
    const int col_fin = (pfin >> 5) * 128 + (pfin & 3) * 32 + ((pfin & 31) >> 2) + 8 * ((tid >> 1) & 3);
    const int sel_off = (col_fin >> 4) * 32 + ((col_fin & 7) >> 1) * 8 + ((col_fin >> 3) & 1) * 4 + (col_fin & 1) * 2;
    const float hn_fin = __uint_as_float((uint32_t)SM_(uint16_t, OFF_XSEL + sel_off) << 16), h_fin = __uint_as_float((uint32_t)SM_(uint16_t, OFF_HSEL + sel_off) << 16);
    bf16* out_fin = p.out + (size_t)tsel * 1024 + col_fin;
    {
      const uint4* src = &p.s->ypart[(16 + (tid >> 1)) * 256 + pfin];
      pin(src); pin(out_fin);
      uint4 v = make_uint4(0, 0, 0, 0);
      if (warp < 7) {
        delay_clk<HOP3_DELAY>();
        uint32_t n = 0;
        bool ok = false;
        do {
          pkt_ld128_if(v, src, !ok);
          ok = pair_code(v.x, v.y) == cd && pair_code(v.z, v.w) == cd;
        } while (!__all_sync(0xffffffffu, ok) && ++n < SPIN_LIMIT);
      }
      CT(13);
      const float y0 = __uint_as_float(v.x & ~1u), y1 = __uint_as_float(v.y & ~1u), y2 = __uint_as_float(v.z & ~1u), y3 = __uint_as_float(v.w & ~1u);
      const float a0 = ((lane & 2) ? y1 : y0) + __shfl_xor_sync(0xffffffffu, (lane & 2) ? y0 : y1, 2);
      const float a1 = ((lane & 2) ? y3 : y2) + __shfl_xor_sync(0xffffffffu, (lane & 2) ? y2 : y3, 2);
      float b = ((lane & 4) ? a1 : a0) + __shfl_xor_sync(0xffffffffu, (lane & 4) ? a0 : a1, 4);
      b += __shfl_xor_sync(0xffffffffu, b, 8);
      b += __shfl_xor_sync(0xffffffffu, b, 16);
      if (lane < 8) SM_(float, OFF_FIN + lane * 32 + warp * 4) = b;
    }
    bar_sync(NB_BOTH, 256);
    if (tid < 8) {
      const float4 y0 = SM_(float4, OFF_FIN + tid * 32), y1 = SM_(float4, OFF_FIN + tid * 32 + 16);
      const float y = ((y0.x + y0.y) + (y0.z + y0.w)) + ((y1.x + y1.y) + y1.z);
      *out_fin = __float2bfloat16_rn(h_fin + bf16r(hn_fin + bf16r(bf16r(y) * sig)));
      if (cid == 0 && tid == 0) st_relaxed32(&p.s->epoch, tag);
    }
    CT(14);
  }
}

__global__ void __launch_bounds__(384, 1) occupancy_probe_kernel() {}

typedef CUresult (*EncodeFn)(CUtensorMap*, CUtensorMapDataType, cuuint32_t, void*, const cuuint64_t*, const cuuint64_t*, const cuuint32_t*, const cuuint32_t*,
                             CUtensorMapInterleave, CUtensorMapSwizzle, CUtensorMapL2promotion, CUtensorMapFloatOOBfill);

static void make_tm(EncodeFn enc, CUtensorMap* tm, const void* ptr, uint64_t rows, uint64_t cols, uint32_t brows, uint32_t bcols, CUtensorMapSwizzle sw,
                    CUtensorMapL2promotion promo = CU_TENSOR_MAP_L2_PROMOTION_L2_128B) {
  cuuint64_t dims[2] = {cols, rows};
  cuuint64_t strides[1] = {cols * 2};
  cuuint32_t box[2] = {bcols, brows};
  cuuint32_t es[2] = {1, 1};
  enc(tm, CU_TENSOR_MAP_DATA_TYPE_BFLOAT16, 2, const_cast<void*>(ptr), dims, strides, box, es, CU_TENSOR_MAP_INTERLEAVE_NONE, sw,
      promo, CU_TENSOR_MAP_FLOAT_OOB_FILL_NONE);
}

static void make_tm_rows(EncodeFn enc, CUtensorMap* tm, const void* ptr, uint64_t cols, uint32_t brows, uint32_t bcols, CUtensorMapSwizzle sw,
                         CUtensorMapL2promotion promo = CU_TENSOR_MAP_L2_PROMOTION_L2_128B) {
  cuuint64_t dims[4] = {cols, 2, 2, 512};
  cuuint64_t strides[3] = {row_of(1) * cols * 2, row_of(2) * cols * 2, row_of(4) * cols * 2};
  cuuint32_t box[4] = {bcols, 2, 2, brows / 4};
  cuuint32_t es[4] = {1, 1, 1, 1};
  enc(tm, CU_TENSOR_MAP_DATA_TYPE_BFLOAT16, 4, const_cast<void*>(ptr), dims, strides, box, es, CU_TENSOR_MAP_INTERLEAVE_NONE, sw, promo,
      CU_TENSOR_MAP_FLOAT_OOB_FILL_NONE);
}

extern "C" void kernel_launch(void* const* d_in, const int* in_sizes, int n_in, void* d_out, int out_size) {
  (void)in_sizes; (void)n_in; (void)out_size;
  static EncodeFn enc = nullptr;
  static void* abT = nullptr;
  static int map = 0;
  if (!enc) {
    void* fn = nullptr; cudaDriverEntryPointQueryResult st;
    cudaGetDriverEntryPoint("cuTensorMapEncodeTiled", &fn, cudaEnableDefault, &st);
    enc = (EncodeFn)fn;
    cudaGetSymbolAddress(&abT, g_scratch);
    cudaFuncSetAttribute(fnet_moe_kernel<0>, cudaFuncAttributeMaxDynamicSharedMemorySize, SMEM_TOTAL);
    cudaFuncSetAttribute(fnet_moe_kernel<1>, cudaFuncAttributeMaxDynamicSharedMemorySize, SMEM_TOTAL);
    cudaFuncSetAttribute(occupancy_probe_kernel, cudaFuncAttributeMaxDynamicSharedMemorySize, SMEM_TOTAL);
    cudaFuncSetAttribute(occupancy_probe_kernel, cudaFuncAttributeNonPortableClusterSizeAllowed, 1);
    auto max_clusters = [&](int size) {
      cudaLaunchConfig_t cfg = {};
      cfg.gridDim = dim3(128); cfg.blockDim = dim3(384); cfg.dynamicSmemBytes = SMEM_TOTAL;
      cudaLaunchAttribute at[1];
      at[0].id = cudaLaunchAttributeClusterDimension; at[0].val.clusterDim.x = size; at[0].val.clusterDim.y = 1; at[0].val.clusterDim.z = 1;
      cfg.attrs = at; cfg.numAttrs = 1;
      int ncl = 0;
      return cudaOccupancyMaxActiveClusters(&ncl, occupancy_probe_kernel, &cfg) == cudaSuccess ? ncl : 0;
    };
    int dev = 0, sms = 0;
    cudaGetDevice(&dev);
    cudaDeviceGetAttribute(&sms, cudaDevAttrMultiProcessorCount, dev);
    map = (sms == 132 && max_clusters(2) == 66 && max_clusters(16) == 7) ? 0 : 1;
    (void)cudaGetLastError();
  }
  Params p;
  const bf16* x = (const bf16*)d_in[0];
  make_tm(enc, &p.tmD0, d_in[3], 1024, 1024, 128, 64, CU_TENSOR_MAP_SWIZZLE_128B);
  make_tm(enc, &p.tmD1, d_in[4], 1024, 1024, 128, 64, CU_TENSOR_MAP_SWIZZLE_128B);
  make_tm(enc, &p.tmX, x, 2048, 1024, map == 0 ? NX0 : 256, 64, CU_TENSOR_MAP_SWIZZLE_128B);
  make_tm_rows(enc, &p.tmXr, x, 1024, 64, 64, CU_TENSOR_MAP_SWIZZLE_128B);
  make_tm(enc, &p.tmAbS, abT, 2048, 2048, 64, 64, CU_TENSOR_MAP_SWIZZLE_128B);
  make_tm(enc, &p.tmAbL, abT, 2048, 2048, 128, 64, CU_TENSOR_MAP_SWIZZLE_128B);
  make_tm_rows(enc, &p.tmW0, d_in[1], 2048, 128, 64, CU_TENSOR_MAP_SWIZZLE_128B);
  make_tm_rows(enc, &p.tmW1, d_in[2], 2048, 128, 64, CU_TENSOR_MAP_SWIZZLE_128B);
  {
    cuuint64_t dims[5] = {1024, 2, 4, 2, 2048};
    cuuint64_t strides[4] = {row_of(1) * 2048, row_of(8) * 2048, row_of(2) * 2048, 2048};
    cuuint32_t box[5] = {64, 2, 4, 2, 1};
    cuuint32_t es[5] = {1, 1, 1, 1, 1};
    enc(&p.tmOut, CU_TENSOR_MAP_DATA_TYPE_BFLOAT16, 5, d_out, dims, strides, box, es, CU_TENSOR_MAP_INTERLEAVE_NONE, CU_TENSOR_MAP_SWIZZLE_128B,
        CU_TENSOR_MAP_L2_PROMOTION_NONE, CU_TENSOR_MAP_FLOAT_OOB_FILL_NONE);
  }
  {
    cuuint64_t dims[5] = {1024, 2, 4, 2, 8};
    cuuint64_t strides[4] = {2048, 4 * 2048, 2 * 2048, 256 * 2048};
    cuuint32_t box[5] = {64, 2, 4, 2, 8};
    cuuint32_t es[5] = {1, 1, 1, 1, 1};
    enc(&p.tmXh, CU_TENSOR_MAP_DATA_TYPE_BFLOAT16, 5, const_cast<bf16*>(x) + 240 * 1024, dims, strides, box, es, CU_TENSOR_MAP_INTERLEAVE_NONE,
        CU_TENSOR_MAP_SWIZZLE_128B, CU_TENSOR_MAP_L2_PROMOTION_L2_128B, CU_TENSOR_MAP_FLOAT_OOB_FILL_NONE);
  }
  make_tm(enc, &p.tmAbM, abT, 2048, 2048, 128, 16, CU_TENSOR_MAP_SWIZZLE_32B, CU_TENSOR_MAP_L2_PROMOTION_NONE);
  make_tm_rows(enc, &p.tmWM0, d_in[1], 2048, 128, 16, CU_TENSOR_MAP_SWIZZLE_32B);
  make_tm_rows(enc, &p.tmWM1, d_in[2], 2048, 128, 16, CU_TENSOR_MAP_SWIZZLE_32B);
  make_tm(enc, &p.tmG, d_in[7], 1024, 3584, 128, 32, CU_TENSOR_MAP_SWIZZLE_64B);
  make_tm(enc, &p.tmU, d_in[8], 1024, 3584, 128, 32, CU_TENSOR_MAP_SWIZZLE_64B);
  make_tm(enc, &p.tmDn, d_in[9], 3584, 1024, 32, 64, CU_TENSOR_MAP_SWIZZLE_128B);
  p.x = x; p.Dre = (const bf16*)d_in[3]; p.Dim = (const bf16*)d_in[4];
  p.wr = (const bf16*)d_in[6]; p.wdown = (const bf16*)d_in[9]; p.wgate = (const bf16*)d_in[7]; p.wup = (const bf16*)d_in[8];
  p.out = (bf16*)d_out; p.s = (Scratch*)abT;
  if (map == 1) fnet_moe_kernel<1><<<128, 384, SMEM_TOTAL>>>(p);
  else fnet_moe_kernel<0><<<132, 384, SMEM_TOTAL>>>(p);
}
```

```cpp
#include <cuda.h>
#include <cuda_runtime.h>
#include <cuda_bf16.h>
#include <stdint.h>
#include <type_traits>

typedef __nv_bfloat16 bf16;

constexpr int NX0 = 240;
constexpr int REG_C = 232, REG_P = 40;
__host__ __device__ constexpr int row_of(int p) { return (p & 1) * 1024 + ((p >> 1) & 1) * 512 + (p >> 2); }
__host__ __device__ constexpr int group_of(int row) { return (row & 511) >> 5; }
__device__ __forceinline__ int sigma_of(int tau, int r) { return r + (r >= tau); }
__device__ __forceinline__ int kblock(int tau, int j) {
  const int i = j - 4, c = (i * 37) >> 8;
  return j < 4 ? tau * 4 + j : sigma_of(tau, i - 7 * c) * 4 + c;
}
constexpr int HL_N = 2;
constexpr int AUX_DELAY = 250;
constexpr int PF_K0 = 8, PF_N0 = 2, PF_K1 = 24;
constexpr int WPF_K0 = 12, WPF_N = 10;
constexpr int WPF2_K = 44, WPF2_N = 4;
constexpr int GU_K = 46;
constexpr int PUB_K1 = 22;
constexpr int NREG_H = 5;
constexpr int MR_K0 = 29, MR_P = 6;
constexpr int MINI_PF_K = 35, MINI_LOAD_K = 43, MINI_K = 42;
constexpr int RESET_K = 37;
constexpr int SEND_FIRST = 2;
constexpr int GATHER_NS = 400;
constexpr int MOE_PACE_CLK = 300;
constexpr int OUT_PACE_CLK = 70;
constexpr int HOP1_DELAY = 150, HOP3_DELAY = 450;
constexpr int SPEC_MIN = 10;
constexpr int IDLE_WAIT_CLK = 1200;
__host__ __device__ constexpr int mr_k(int h) { return MR_K0 + MR_P * (h >> 1) + 2 * (h & 1); }
constexpr int A_BYTES = 128 * 64 * 2;
constexpr int B_BYTES = 256 * 64 * 2;
constexpr int ST_BYTES = A_BYTES + B_BYTES;
constexpr int OFF_XCH = 4 * ST_BYTES;
constexpr int OFF_BAR = OFF_XCH + 32768;
constexpr int OFF_WR = OFF_BAR + 384;
constexpr int OFF_RS = OFF_WR + 384;
constexpr int OFF_PUB = OFF_RS + 640;
constexpr int OFF_MISC = OFF_PUB + 768;
constexpr int SMEM_TOTAL = OFF_MISC + 256;
constexpr int OFF_WSUM = OFF_MISC, OFF_TAG = OFF_MISC + 4;
constexpr int OFF_SEEN = OFF_MISC + 8;
constexpr int OFF_KV = OFF_MISC + 12;
constexpr int OFF_WKEY = OFF_MISC + 32;
constexpr int OFF_MINI = OFF_XCH + 16384;
constexpr int OFF_EXA = OFF_XCH;
constexpr int OFF_EXB = OFF_XCH + 4096;
__host__ __device__ constexpr int chunk_off(int c, int w) { return (c == 1 ? 3 * ST_BYTES : c == 2 ? OFF_XCH : OFF_XCH + 16384) + w * 8192; }
__host__ __device__ constexpr int late_off(int i) { return i < 4 ? i * 16384 : 2 * ST_BYTES + A_BYTES + (i - 4) * 16384; }
__host__ __device__ constexpr int round_off(int h) { return h < NREG_H + 2 ? OFF_XCH + (h & 1) * 16384 : late_off(h - NREG_H - 2); }
__host__ __device__ constexpr int down_off(int i) { return late_off(6 - NREG_H + i); }
constexpr int OFF_PEER = ST_BYTES + A_BYTES;
constexpr int OFF_OUT = 3 * ST_BYTES + A_BYTES;
constexpr int OFF_XSEL = OFF_PEER;
constexpr int OFF_HSEL = OFF_PEER + 4096;
constexpr int OFF_GP = OFF_PEER + 8192;
constexpr int OFF_FIN = OFF_PEER + 9216;
__device__ __forceinline__ int slot_of(int k) { return k & 3; }
__device__ __forceinline__ int use_of(int k) { return k >> 2; }
enum { B_FULL = 0, B_EMPTY = 4, B_EPI = 8, B_STD = 12, B_EPI0B = 16, B_LATE = 17, B_STAT = 18, B_XCH = 19, B_MR = 20  , B_GU = 22,
       B_DN = 23, B_AUX = 24  , B_OUT = 26, B_KEY = 27, B_XS = 28, B_MINI = 29, B_PUB1 = 30, B_COUNT = 31 };
enum { NB_TURN0 = 1, NB_TURN1 = 2, NB_WG0 = 3, NB_BOTH = 5, NB_AUX = 6 };

struct Scratch {
  bf16 abT[2048 * 2048];
  uint2 xstat[2048];
  uint2 dsum[2048];
  uint4 abflag[16 * 8 * 2];
  uint4 hflag[16 * 2];
  uint4 hstat[16 * 8 * 128];
  uint4 cand[16 * 256];
  uint4 key[8 * 16 * 2];
  uint4 ypart[128 * 256];
  uint32_t epoch;
};
__device__ __align__(1024) Scratch g_scratch;

struct Params {
  Scratch* s; bf16* out;
  const bf16* x; const bf16* Dre; const bf16* Dim; const bf16* wr; const bf16* wdown; const bf16* wgate; const bf16* wup;
  CUtensorMap tmX, tmD0, tmD1, tmXr, tmAbS, tmAbL, tmW0, tmW1, tmOut, tmG, tmU, tmDn, tmXh, tmAbM, tmWM0, tmWM1;
};

#define SPIN_LIMIT (1u << 14)
#define MBAR_LIMIT (1u << 10)
__device__ __forceinline__ uint32_t smem_u32(const void* p) { return (uint32_t)__cvta_generic_to_shared(p); }
__device__ __forceinline__ void mbar_init(uint32_t bar, uint32_t cnt) { asm volatile("mbarrier.init.shared::cta.b64 [%0], %1;" :: "r"(bar), "r"(cnt) : "memory"); }
__device__ __forceinline__ void mbar_expect_tx(uint32_t bar, uint32_t bytes) { asm volatile("mbarrier.arrive.expect_tx.shared::cta.b64 _, [%0], %1;" :: "r"(bar), "r"(bytes) : "memory"); }
__device__ __forceinline__ void mbar_arrive(uint32_t bar) { asm volatile("mbarrier.arrive.shared::cta.b64 _, [%0];" :: "r"(bar) : "memory"); }
__device__ __forceinline__ void mbar_wait(uint32_t bar, uint32_t parity) {
  uint32_t ok, n = 0;
  do {
    asm volatile("{\n.reg .pred p;\nmbarrier.try_wait.parity.shared::cta.b64 p, [%1], %2;\nselp.u32 %0, 1, 0, p;\n}\n" : "=r"(ok) : "r"(bar), "r"(parity) : "memory");
  } while (!ok && ++n < MBAR_LIMIT);
}
__device__ __forceinline__ void mbar_wait_cluster(uint32_t bar, uint32_t parity) {
  uint32_t ok, n = 0;
  do {
    asm volatile("{\n.reg .pred p;\nmbarrier.try_wait.parity.acquire.cluster.shared::cta.b64 p, [%1], %2;\nselp.u32 %0, 1, 0, p;\n}\n" : "=r"(ok) : "r"(bar), "r"(parity) : "memory");
  } while (!ok && ++n < MBAR_LIMIT);
}
__device__ __forceinline__ void tma_load_2d(uint32_t dst, const CUtensorMap* tm, uint32_t bar, int c0, int c1) {
  asm volatile("cp.async.bulk.tensor.2d.shared::cluster.global.mbarrier::complete_tx::bytes [%0], [%1, {%3, %4}], [%2];"
    :: "r"(dst), "l"(tm), "r"(bar), "r"(c0), "r"(c1) : "memory");
}
__device__ __forceinline__ void tma_load_2d_hint(uint32_t dst, const CUtensorMap* tm, uint32_t bar, int c0, int c1, uint64_t pol) {
  asm volatile("cp.async.bulk.tensor.2d.shared::cluster.global.mbarrier::complete_tx::bytes.L2::cache_hint [%0], [%1, {%3, %4}], [%2], %5;"
    :: "r"(dst), "l"(tm), "r"(bar), "r"(c0), "r"(c1), "l"(pol) : "memory");
}
__device__ __forceinline__ uint64_t policy_evict_first() { uint64_t p; asm volatile("createpolicy.fractional.L2::evict_first.b64 %0, 1.0;" : "=l"(p)); return p; }
__device__ __forceinline__ void tma_store_2d(const CUtensorMap* tm, uint32_t src, int c0, int c1) {
  asm volatile("cp.async.bulk.tensor.2d.global.shared::cta.bulk_group [%0, {%2, %3}], [%1];" :: "l"(tm), "r"(src), "r"(c0), "r"(c1) : "memory");
}
__device__ __forceinline__ void tma_prefetch_2d(const CUtensorMap* tm, int c0, int c1) {
  asm volatile("cp.async.bulk.prefetch.tensor.2d.L2.global.tile [%0, {%1, %2}];" :: "l"(tm), "r"(c0), "r"(c1) : "memory");
}
__device__ __forceinline__ void bulk_load(uint32_t dst, const void* src, uint32_t bytes, uint32_t bar) {
  asm volatile("cp.async.bulk.shared::cluster.global.mbarrier::complete_tx::bytes [%0], [%1], %2, [%3];" :: "r"(dst), "l"(src), "r"(bytes), "r"(bar) : "memory");
}
__device__ __forceinline__ void bulk_commit() { asm volatile("cp.async.bulk.commit_group;" ::: "memory"); }
__device__ __forceinline__ void bulk_wait_all() { asm volatile("cp.async.bulk.wait_group 0;" ::: "memory"); }
__device__ __forceinline__ void bulk_wait_release() {
  bulk_wait_all();
  asm volatile("fence.proxy.async.global;" ::: "memory");
  asm volatile("fence.acq_rel.gpu;" ::: "memory");
}
__device__ __forceinline__ void fence_async_smem() { asm volatile("fence.proxy.async.shared::cta;" ::: "memory"); }
__device__ __forceinline__ void wgmma_fence() { asm volatile("wgmma.fence.sync.aligned;" ::: "memory"); }
__device__ __forceinline__ void wgmma_commit() { asm volatile("wgmma.commit_group.sync.aligned;" ::: "memory"); }
__device__ __forceinline__ void wgmma_wait0() { asm volatile("wgmma.wait_group.sync.aligned 0;" ::: "memory"); }
__device__ __forceinline__ void bar_sync(int id, int n) { asm volatile("bar.sync %0, %1;" :: "r"(id), "r"(n) : "memory"); }
__device__ __forceinline__ void bar_arrive(int id, int n) { asm volatile("bar.arrive %0, %1;" :: "r"(id), "r"(n) : "memory"); }
template<int R> __device__ __forceinline__ void reg_inc() { asm volatile("setmaxnreg.inc.sync.aligned.u32 %0;" :: "n"(R)); }
template<int R> __device__ __forceinline__ void reg_dec() { asm volatile("setmaxnreg.dec.sync.aligned.u32 %0;" :: "n"(R)); }
__device__ __forceinline__ bool elect_one() {
  uint32_t p;
  asm volatile("{\n.reg .pred q;\nelect.sync _|q, 0xffffffff;\nselp.u32 %0, 1, 0, q;\n}\n" : "=r"(p));
  return p != 0;
}
__device__ __forceinline__ uint32_t mapa(uint32_t addr, uint32_t cta) { uint32_t r; asm volatile("mapa.shared::cluster.u32 %0, %1, %2;" : "=r"(r) : "r"(addr), "r"(cta)); return r; }
__device__ __forceinline__ void st_async_v4(uint32_t addr, uint32_t bar, uint32_t a, uint32_t b, uint32_t c, uint32_t d) {
  asm volatile("st.async.weak.shared::cluster.mbarrier::complete_tx::bytes.v4.b32 [%0], {%2, %3, %4, %5}, [%1];" :: "r"(addr), "r"(bar), "r"(a), "r"(b), "r"(c), "r"(d) : "memory");
}
__device__ __forceinline__ void stsm_x4(uint32_t addr, uint32_t a, uint32_t b, uint32_t c, uint32_t d) {
  asm volatile("stmatrix.sync.aligned.m8n8.x4.shared.b16 [%0], {%1, %2, %3, %4};" :: "r"(addr), "r"(a), "r"(b), "r"(c), "r"(d));
}
__device__ __forceinline__ uint4 lds128_v(uint32_t addr) { uint4 v; asm volatile("ld.shared.v4.b32 {%0, %1, %2, %3}, [%4];" : "=r"(v.x), "=r"(v.y), "=r"(v.z), "=r"(v.w) : "r"(addr)); return v; }
extern __shared__ __align__(1024) uint8_t smem_raw[];
template<class T> __device__ __forceinline__ T& smem_at(uint32_t addr) { return *reinterpret_cast<T*>(__cvta_shared_to_generic(addr)); }
#define SM_(T, off) smem_at<T>(sb + (off))
__device__ __forceinline__ uint4 ldg_nc128(const void* p) { uint4 v; asm volatile("ld.global.nc.v4.b32 {%0, %1, %2, %3}, [%4];" : "=r"(v.x), "=r"(v.y), "=r"(v.z), "=r"(v.w) : "l"(p)); return v; }
__device__ __forceinline__ void pkt_st128(void* p, uint32_t a, uint32_t b, uint32_t c, uint32_t d) {
  asm volatile("{\n.reg .b128 v;\n.reg .b64 lo, hi;\nmov.b64 lo, {%1, %2};\nmov.b64 hi, {%3, %4};\nmov.b128 v, {lo, hi};\nst.relaxed.gpu.global.b128 [%0], v;\n}\n"
    :: "l"(p), "r"(a), "r"(b), "r"(c), "r"(d) : "memory");
}
__device__ __forceinline__ uint4 pkt_ld128(const void* p) {
  uint4 r;
  asm volatile("{\n.reg .b128 v;\n.reg .b64 lo, hi;\nld.relaxed.gpu.global.b128 v, [%4];\nmov.b128 {lo, hi}, v;\nmov.b64 {%0, %1}, lo;\nmov.b64 {%2, %3}, hi;\n}\n"
    : "=r"(r.x), "=r"(r.y), "=r"(r.z), "=r"(r.w) : "l"(p) : "memory");
  return r;
}
__device__ __forceinline__ void pkt_ld128_if(uint4& r, const void* p, bool cond) {
  asm volatile("{\n.reg .pred q;\n.reg .b64 lo, hi;\nsetp.ne.b32 q, %5, 0;\nmov.b64 lo, {%0, %1};\nmov.b64 hi, {%2, %3};\n"
               "@q ld.relaxed.gpu.global.v2.b64 {lo, hi}, [%4];\nmov.b64 {%0, %1}, lo;\nmov.b64 {%2, %3}, hi;\n}\n"
    : "+r"(r.x), "+r"(r.y), "+r"(r.z), "+r"(r.w) : "l"(p), "r"((uint32_t)cond) : "memory");
}
__device__ __forceinline__ void pkt_st64(void* p, uint32_t a, uint32_t b) {
  asm volatile("{\n.reg .b64 v;\nmov.b64 v, {%1, %2};\nst.relaxed.gpu.global.b64 [%0], v;\n}\n" :: "l"(p), "r"(a), "r"(b) : "memory");
}
__device__ __forceinline__ uint2 pkt_ld64(const void* p) {
  uint2 r;
  asm volatile("{\n.reg .b64 v;\nld.relaxed.gpu.global.b64 v, [%2];\nmov.b64 {%0, %1}, v;\n}\n" : "=r"(r.x), "=r"(r.y) : "l"(p) : "memory");
  return r;
}
__device__ __forceinline__ uint32_t ld_relaxed32(const void* p) { uint32_t v; asm volatile("ld.relaxed.gpu.global.b32 %0, [%1];" : "=r"(v) : "l"(p) : "memory"); return v; }
__device__ __forceinline__ uint32_t ld_acquire32(const void* p) { uint32_t v; asm volatile("ld.acquire.gpu.global.b32 %0, [%1];" : "=r"(v) : "l"(p) : "memory"); return v; }
__device__ __forceinline__ void st_relaxed32(void* p, uint32_t v) { asm volatile("st.relaxed.gpu.global.b32 [%0], %1;" :: "l"(p), "r"(v) : "memory"); }
__device__ __forceinline__ uint32_t code_of(uint32_t tag) { return tag % 3u + 1u; }
__device__ __forceinline__ uint32_t with_bit(float v, uint32_t bit) { return (__float_as_uint(v) & ~1u) | (bit & 1u); }
__device__ __forceinline__ uint32_t pair_code(uint32_t a, uint32_t b) { return (a & 1u) | ((b & 1u) << 1); }
__device__ __forceinline__ uint32_t pack_bf16(float lo, float hi) { uint32_t r; asm("cvt.rn.bf16x2.f32 %0, %1, %2;" : "=r"(r) : "f"(hi), "f"(lo)); return r; }
__device__ __forceinline__ float bf_lo(uint32_t v) { return __uint_as_float(v << 16); }
__device__ __forceinline__ float bf_hi(uint32_t v) { return __uint_as_float(v & 0xFFFF0000u); }
__device__ __forceinline__ float bf16r(float x) { return __uint_as_float(pack_bf16(0.f, x)); }
__device__ __forceinline__ uint32_t badd2(uint32_t a, uint32_t b) { uint32_t r; asm("add.rn.bf16x2 %0, %1, %2;" : "=r"(r) : "r"(a), "r"(b)); return r; }
__device__ __forceinline__ uint32_t bmul2(uint32_t a, uint32_t b) { uint32_t r; asm("mul.rn.bf16x2 %0, %1, %2;" : "=r"(r) : "r"(a), "r"(b)); return r; }
__device__ __forceinline__ float warp_sum(float v) {
#pragma unroll
  for (int o = 16; o > 0; o >>= 1) v += __shfl_xor_sync(0xffffffffu, v, o);
  return v;
}
__device__ __forceinline__ uint64_t make_desc(uint32_t addr) {
  return (uint64_t)((addr & 0x3FFFF) >> 4) | ((uint64_t)1 << 16) | ((uint64_t)64 << 32) | ((uint64_t)1 << 62);
}
__device__ __forceinline__ uint64_t make_desc_noswz(uint32_t addr) {
  return (uint64_t)((addr & 0x3FFFF) >> 4) | ((uint64_t)8 << 16) | ((uint64_t)16 << 32);
}
__device__ __forceinline__ uint64_t make_desc_32b(uint32_t addr) {
  return (uint64_t)((addr & 0x3FFFF) >> 4) | ((uint64_t)1 << 16) | ((uint64_t)16 << 32) | ((uint64_t)3 << 62);
}
__device__ __forceinline__ void wgmma_n256(float (&d)[128], uint64_t da, uint64_t db, int scale_d) {
  asm volatile("{\n.reg .pred p;\nsetp.ne.b32 p, %130, 0;\n"
    "wgmma.mma_async.sync.aligned.m64n256k16.f32.bf16.bf16 "
    "{%0, %1, %2, %3, %4, %5, %6, %7, %8, %9, %10, %11, %12, %13, %14, %15, %16, %17, %18, %19, %20, %21, %22, %23, %24, %25, %26, %27, %28, %29, %30, %31, "
    "%32, %33, %34, %35, %36, %37, %38, %39, %40, %41, %42, %43, %44, %45, %46, %47, %48, %49, %50, %51, %52, %53, %54, %55, %56, %57, %58, %59, %60, %61, %62, %63, "
    "%64, %65, %66, %67, %68, %69, %70, %71, %72, %73, %74, %75, %76, %77, %78, %79, %80, %81, %82, %83, %84, %85, %86, %87, %88, %89, %90, %91, %92, %93, %94, %95, "
    "%96, %97, %98, %99, %100, %101, %102, %103, %104, %105, %106, %107, %108, %109, %110, %111, %112, %113, %114, %115, %116, %117, %118, %119, %120, %121, %122, %123, %124, %125, %126, %127}, "
    "%128, %129, p, 1, 1, 0, 0;\n}\n"
    : "+f"(d[0]), "+f"(d[1]), "+f"(d[2]), "+f"(d[3]), "+f"(d[4]), "+f"(d[5]), "+f"(d[6]), "+f"(d[7]),
      "+f"(d[8]), "+f"(d[9]), "+f"(d[10]), "+f"(d[11]), "+f"(d[12]), "+f"(d[13]), "+f"(d[14]), "+f"(d[15]),
      "+f"(d[16]), "+f"(d[17]), "+f"(d[18]), "+f"(d[19]), "+f"(d[20]), "+f"(d[21]), "+f"(d[22]), "+f"(d[23]),
      "+f"(d[24]), "+f"(d[25]), "+f"(d[26]), "+f"(d[27]), "+f"(d[28]), "+f"(d[29]), "+f"(d[30]), "+f"(d[31]),
      "+f"(d[32]), "+f"(d[33]), "+f"(d[34]), "+f"(d[35]), "+f"(d[36]), "+f"(d[37]), "+f"(d[38]), "+f"(d[39]),
      "+f"(d[40]), "+f"(d[41]), "+f"(d[42]), "+f"(d[43]), "+f"(d[44]), "+f"(d[45]), "+f"(d[46]), "+f"(d[47]),
      "+f"(d[48]), "+f"(d[49]), "+f"(d[50]), "+f"(d[51]), "+f"(d[52]), "+f"(d[53]), "+f"(d[54]), "+f"(d[55]),
      "+f"(d[56]), "+f"(d[57]), "+f"(d[58]), "+f"(d[59]), "+f"(d[60]), "+f"(d[61]), "+f"(d[62]), "+f"(d[63]),
      "+f"(d[64]), "+f"(d[65]), "+f"(d[66]), "+f"(d[67]), "+f"(d[68]), "+f"(d[69]), "+f"(d[70]), "+f"(d[71]),
      "+f"(d[72]), "+f"(d[73]), "+f"(d[74]), "+f"(d[75]), "+f"(d[76]), "+f"(d[77]), "+f"(d[78]), "+f"(d[79]),
      "+f"(d[80]), "+f"(d[81]), "+f"(d[82]), "+f"(d[83]), "+f"(d[84]), "+f"(d[85]), "+f"(d[86]), "+f"(d[87]),
      "+f"(d[88]), "+f"(d[89]), "+f"(d[90]), "+f"(d[91]), "+f"(d[92]), "+f"(d[93]), "+f"(d[94]), "+f"(d[95]),
      "+f"(d[96]), "+f"(d[97]), "+f"(d[98]), "+f"(d[99]), "+f"(d[100]), "+f"(d[101]), "+f"(d[102]), "+f"(d[103]),
      "+f"(d[104]), "+f"(d[105]), "+f"(d[106]), "+f"(d[107]), "+f"(d[108]), "+f"(d[109]), "+f"(d[110]), "+f"(d[111]),
      "+f"(d[112]), "+f"(d[113]), "+f"(d[114]), "+f"(d[115]), "+f"(d[116]), "+f"(d[117]), "+f"(d[118]), "+f"(d[119]),
      "+f"(d[120]), "+f"(d[121]), "+f"(d[122]), "+f"(d[123]), "+f"(d[124]), "+f"(d[125]), "+f"(d[126]), "+f"(d[127])
    : "l"(da), "l"(db), "r"(scale_d));
}
__device__ __forceinline__ void wgmma_g1(float (&d)[128], uint64_t da, uint64_t db, int scale_d) { wgmma_n256(d, da, db, scale_d); }
__device__ __forceinline__ void wgmma_g1(float (&d)[120], uint64_t da, uint64_t db, int scale_d) {
  asm volatile("{\n.reg .pred p;\nsetp.ne.b32 p, %122, 0;\n"
    "wgmma.mma_async.sync.aligned.m64n240k16.f32.bf16.bf16 "
    "{%0, %1, %2, %3, %4, %5, %6, %7, %8, %9, %10, %11, %12, %13, %14, %15, %16, %17, %18, %19, %20, %21, %22, %23, %24, %25, %26, %27, %28, %29, %30, %31, %32, %33, %34, %35, %36, %37, %38, %39, %40, %41, %42, %43, %44, %45, %46, %47, %48, %49, %50, %51, %52, %53, %54, %55, %56, %57, %58, %59, %60, %61, %62, %63, %64, %65, %66, %67, %68, %69, %70, %71, %72, %73, %74, %75, %76, %77, %78, %79, %80, %81, %82, %83, %84, %85, %86, %87, %88, %89, %90, %91, %92, %93, %94, %95, %96, %97, %98, %99, %100, %101, %102, %103, %104, %105, %106, %107, %108, %109, %110, %111, %112, %113, %114, %115, %116, %117, %118, %119}, "
    "%120, %121, p, 1, 1, 0, 0;\n}\n"
    : "+f"(d[0]), "+f"(d[1]), "+f"(d[2]), "+f"(d[3]), "+f"(d[4]), "+f"(d[5]), "+f"(d[6]), "+f"(d[7]), "+f"(d[8]), "+f"(d[9]), "+f"(d[10]), "+f"(d[11]), "+f"(d[12]), "+f"(d[13]), "+f"(d[14]), "+f"(d[15]), "+f"(d[16]), "+f"(d[17]), "+f"(d[18]), "+f"(d[19]), "+f"(d[20]), "+f"(d[21]), "+f"(d[22]), "+f"(d[23]), "+f"(d[24]), "+f"(d[25]), "+f"(d[26]), "+f"(d[27]), "+f"(d[28]), "+f"(d[29]), "+f"(d[30]), "+f"(d[31]), "+f"(d[32]), "+f"(d[33]), "+f"(d[34]), "+f"(d[35]), "+f"(d[36]), "+f"(d[37]), "+f"(d[38]), "+f"(d[39]), "+f"(d[40]), "+f"(d[41]), "+f"(d[42]), "+f"(d[43]), "+f"(d[44]), "+f"(d[45]), "+f"(d[46]), "+f"(d[47]), "+f"(d[48]), "+f"(d[49]), "+f"(d[50]), "+f"(d[51]), "+f"(d[52]), "+f"(d[53]), "+f"(d[54]), "+f"(d[55]), "+f"(d[56]), "+f"(d[57]), "+f"(d[58]), "+f"(d[59]), "+f"(d[60]), "+f"(d[61]), "+f"(d[62]), "+f"(d[63]), "+f"(d[64]), "+f"(d[65]), "+f"(d[66]), "+f"(d[67]), "+f"(d[68]), "+f"(d[69]), "+f"(d[70]), "+f"(d[71]), "+f"(d[72]), "+f"(d[73]), "+f"(d[74]), "+f"(d[75]), "+f"(d[76]), "+f"(d[77]), "+f"(d[78]), "+f"(d[79]), "+f"(d[80]), "+f"(d[81]), "+f"(d[82]), "+f"(d[83]), "+f"(d[84]), "+f"(d[85]), "+f"(d[86]), "+f"(d[87]), "+f"(d[88]), "+f"(d[89]), "+f"(d[90]), "+f"(d[91]), "+f"(d[92]), "+f"(d[93]), "+f"(d[94]), "+f"(d[95]), "+f"(d[96]), "+f"(d[97]), "+f"(d[98]), "+f"(d[99]), "+f"(d[100]), "+f"(d[101]), "+f"(d[102]), "+f"(d[103]), "+f"(d[104]), "+f"(d[105]), "+f"(d[106]), "+f"(d[107]), "+f"(d[108]), "+f"(d[109]), "+f"(d[110]), "+f"(d[111]), "+f"(d[112]), "+f"(d[113]), "+f"(d[114]), "+f"(d[115]), "+f"(d[116]), "+f"(d[117]), "+f"(d[118]), "+f"(d[119])
    : "l"(da), "l"(db), "r"(scale_d));
}
__device__ __forceinline__ void wgmma_g1(float (&d)[32], uint64_t da, uint64_t db, int scale_d) {
  asm volatile("{\n.reg .pred p;\nsetp.ne.b32 p, %34, 0;\n"
    "wgmma.mma_async.sync.aligned.m64n64k16.f32.bf16.bf16 "
    "{%0, %1, %2, %3, %4, %5, %6, %7, %8, %9, %10, %11, %12, %13, %14, %15, %16, %17, %18, %19, %20, %21, %22, %23, %24, %25, %26, %27, %28, %29, %30, %31}, "
    "%32, %33, p, 1, 1, 0, 0;\n}\n"
    : "+f"(d[0]), "+f"(d[1]), "+f"(d[2]), "+f"(d[3]), "+f"(d[4]), "+f"(d[5]), "+f"(d[6]), "+f"(d[7]), "+f"(d[8]), "+f"(d[9]), "+f"(d[10]), "+f"(d[11]), "+f"(d[12]), "+f"(d[13]), "+f"(d[14]), "+f"(d[15]), "+f"(d[16]), "+f"(d[17]), "+f"(d[18]), "+f"(d[19]), "+f"(d[20]), "+f"(d[21]), "+f"(d[22]), "+f"(d[23]), "+f"(d[24]), "+f"(d[25]), "+f"(d[26]), "+f"(d[27]), "+f"(d[28]), "+f"(d[29]), "+f"(d[30]), "+f"(d[31])
    : "l"(da), "l"(db), "r"(scale_d));
}
__device__ __forceinline__ void wgmma_g1(float (&d)[88], uint64_t da, uint64_t db, int scale_d) {
  asm volatile("{\n.reg .pred p;\nsetp.ne.b32 p, %90, 0;\n"
    "wgmma.mma_async.sync.aligned.m64n176k16.f32.bf16.bf16 "
    "{%0, %1, %2, %3, %4, %5, %6, %7, %8, %9, %10, %11, %12, %13, %14, %15, %16, %17, %18, %19, %20, %21, %22, %23, %24, %25, %26, %27, %28, %29, %30, %31, %32, %33, %34, %35, %36, %37, %38, %39, %40, %41, %42, %43, %44, %45, %46, %47, %48, %49, %50, %51, %52, %53, %54, %55, %56, %57, %58, %59, %60, %61, %62, %63, %64, %65, %66, %67, %68, %69, %70, %71, %72, %73, %74, %75, %76, %77, %78, %79, %80, %81, %82, %83, %84, %85, %86, %87}, "
    "%88, %89, p, 1, 1, 0, 0;\n}\n"
    : "+f"(d[0]), "+f"(d[1]), "+f"(d[2]), "+f"(d[3]), "+f"(d[4]), "+f"(d[5]), "+f"(d[6]), "+f"(d[7]), "+f"(d[8]), "+f"(d[9]), "+f"(d[10]), "+f"(d[11]), "+f"(d[12]), "+f"(d[13]), "+f"(d[14]), "+f"(d[15]), "+f"(d[16]), "+f"(d[17]), "+f"(d[18]), "+f"(d[19]), "+f"(d[20]), "+f"(d[21]), "+f"(d[22]), "+f"(d[23]), "+f"(d[24]), "+f"(d[25]), "+f"(d[26]), "+f"(d[27]), "+f"(d[28]), "+f"(d[29]), "+f"(d[30]), "+f"(d[31]), "+f"(d[32]), "+f"(d[33]), "+f"(d[34]), "+f"(d[35]), "+f"(d[36]), "+f"(d[37]), "+f"(d[38]), "+f"(d[39]), "+f"(d[40]), "+f"(d[41]), "+f"(d[42]), "+f"(d[43]), "+f"(d[44]), "+f"(d[45]), "+f"(d[46]), "+f"(d[47]), "+f"(d[48]), "+f"(d[49]), "+f"(d[50]), "+f"(d[51]), "+f"(d[52]), "+f"(d[53]), "+f"(d[54]), "+f"(d[55]), "+f"(d[56]), "+f"(d[57]), "+f"(d[58]), "+f"(d[59]), "+f"(d[60]), "+f"(d[61]), "+f"(d[62]), "+f"(d[63]), "+f"(d[64]), "+f"(d[65]), "+f"(d[66]), "+f"(d[67]), "+f"(d[68]), "+f"(d[69]), "+f"(d[70]), "+f"(d[71]), "+f"(d[72]), "+f"(d[73]), "+f"(d[74]), "+f"(d[75]), "+f"(d[76]), "+f"(d[77]), "+f"(d[78]), "+f"(d[79]), "+f"(d[80]), "+f"(d[81]), "+f"(d[82]), "+f"(d[83]), "+f"(d[84]), "+f"(d[85]), "+f"(d[86]), "+f"(d[87])
    : "l"(da), "l"(db), "r"(scale_d));
}
__device__ __forceinline__ void wgmma_g1(float (&d)[96], uint64_t da, uint64_t db, int scale_d) {
  asm volatile("{\n.reg .pred p;\nsetp.ne.b32 p, %98, 0;\n"
    "wgmma.mma_async.sync.aligned.m64n192k16.f32.bf16.bf16 "
    "{%0, %1, %2, %3, %4, %5, %6, %7, %8, %9, %10, %11, %12, %13, %14, %15, %16, %17, %18, %19, %20, %21, %22, %23, %24, %25, %26, %27, %28, %29, %30, %31, %32, %33, %34, %35, %36, %37, %38, %39, %40, %41, %42, %43, %44, %45, %46, %47, %48, %49, %50, %51, %52, %53, %54, %55, %56, %57, %58, %59, %60, %61, %62, %63, %64, %65, %66, %67, %68, %69, %70, %71, %72, %73, %74, %75, %76, %77, %78, %79, %80, %81, %82, %83, %84, %85, %86, %87, %88, %89, %90, %91, %92, %93, %94, %95}, "
    "%96, %97, p, 1, 1, 0, 0;\n}\n"
    : "+f"(d[0]), "+f"(d[1]), "+f"(d[2]), "+f"(d[3]), "+f"(d[4]), "+f"(d[5]), "+f"(d[6]), "+f"(d[7]), "+f"(d[8]), "+f"(d[9]), "+f"(d[10]), "+f"(d[11]), "+f"(d[12]), "+f"(d[13]), "+f"(d[14]), "+f"(d[15]), "+f"(d[16]), "+f"(d[17]), "+f"(d[18]), "+f"(d[19]), "+f"(d[20]), "+f"(d[21]), "+f"(d[22]), "+f"(d[23]), "+f"(d[24]), "+f"(d[25]), "+f"(d[26]), "+f"(d[27]), "+f"(d[28]), "+f"(d[29]), "+f"(d[30]), "+f"(d[31]), "+f"(d[32]), "+f"(d[33]), "+f"(d[34]), "+f"(d[35]), "+f"(d[36]), "+f"(d[37]), "+f"(d[38]), "+f"(d[39]), "+f"(d[40]), "+f"(d[41]), "+f"(d[42]), "+f"(d[43]), "+f"(d[44]), "+f"(d[45]), "+f"(d[46]), "+f"(d[47]), "+f"(d[48]), "+f"(d[49]), "+f"(d[50]), "+f"(d[51]), "+f"(d[52]), "+f"(d[53]), "+f"(d[54]), "+f"(d[55]), "+f"(d[56]), "+f"(d[57]), "+f"(d[58]), "+f"(d[59]), "+f"(d[60]), "+f"(d[61]), "+f"(d[62]), "+f"(d[63]), "+f"(d[64]), "+f"(d[65]), "+f"(d[66]), "+f"(d[67]), "+f"(d[68]), "+f"(d[69]), "+f"(d[70]), "+f"(d[71]), "+f"(d[72]), "+f"(d[73]), "+f"(d[74]), "+f"(d[75]), "+f"(d[76]), "+f"(d[77]), "+f"(d[78]), "+f"(d[79]), "+f"(d[80]), "+f"(d[81]), "+f"(d[82]), "+f"(d[83]), "+f"(d[84]), "+f"(d[85]), "+f"(d[86]), "+f"(d[87]), "+f"(d[88]), "+f"(d[89]), "+f"(d[90]), "+f"(d[91]), "+f"(d[92]), "+f"(d[93]), "+f"(d[94]), "+f"(d[95])
    : "l"(da), "l"(db), "r"(scale_d));
}
__device__ __forceinline__ void wgmma_n256_rs(float (&d)[128], uint32_t a0, uint32_t a1, uint32_t a2, uint32_t a3, uint64_t db, int scale_d) {
  asm volatile("{\n.reg .pred p;\nsetp.ne.b32 p, %133, 0;\n"
    "wgmma.mma_async.sync.aligned.m64n256k16.f32.bf16.bf16 "
    "{%0, %1, %2, %3, %4, %5, %6, %7, %8, %9, %10, %11, %12, %13, %14, %15, %16, %17, %18, %19, %20, %21, %22, %23, %24, %25, %26, %27, %28, %29, %30, %31, "
    "%32, %33, %34, %35, %36, %37, %38, %39, %40, %41, %42, %43, %44, %45, %46, %47, %48, %49, %50, %51, %52, %53, %54, %55, %56, %57, %58, %59, %60, %61, %62, %63, "
    "%64, %65, %66, %67, %68, %69, %70, %71, %72, %73, %74, %75, %76, %77, %78, %79, %80, %81, %82, %83, %84, %85, %86, %87, %88, %89, %90, %91, %92, %93, %94, %95, "
    "%96, %97, %98, %99, %100, %101, %102, %103, %104, %105, %106, %107, %108, %109, %110, %111, %112, %113, %114, %115, %116, %117, %118, %119, %120, %121, %122, %123, %124, %125, %126, %127}, "
    "{%128, %129, %130, %131}, %132, p, 1, 1, 0;\n}\n"
    : "+f"(d[0]), "+f"(d[1]), "+f"(d[2]), "+f"(d[3]), "+f"(d[4]), "+f"(d[5]), "+f"(d[6]), "+f"(d[7]),
      "+f"(d[8]), "+f"(d[9]), "+f"(d[10]), "+f"(d[11]), "+f"(d[12]), "+f"(d[13]), "+f"(d[14]), "+f"(d[15]),
      "+f"(d[16]), "+f"(d[17]), "+f"(d[18]), "+f"(d[19]), "+f"(d[20]), "+f"(d[21]), "+f"(d[22]), "+f"(d[23]),
      "+f"(d[24]), "+f"(d[25]), "+f"(d[26]), "+f"(d[27]), "+f"(d[28]), "+f"(d[29]), "+f"(d[30]), "+f"(d[31]),
      "+f"(d[32]), "+f"(d[33]), "+f"(d[34]), "+f"(d[35]), "+f"(d[36]), "+f"(d[37]), "+f"(d[38]), "+f"(d[39]),
      "+f"(d[40]), "+f"(d[41]), "+f"(d[42]), "+f"(d[43]), "+f"(d[44]), "+f"(d[45]), "+f"(d[46]), "+f"(d[47]),
      "+f"(d[48]), "+f"(d[49]), "+f"(d[50]), "+f"(d[51]), "+f"(d[52]), "+f"(d[53]), "+f"(d[54]), "+f"(d[55]),
      "+f"(d[56]), "+f"(d[57]), "+f"(d[58]), "+f"(d[59]), "+f"(d[60]), "+f"(d[61]), "+f"(d[62]), "+f"(d[63]),
      "+f"(d[64]), "+f"(d[65]), "+f"(d[66]), "+f"(d[67]), "+f"(d[68]), "+f"(d[69]), "+f"(d[70]), "+f"(d[71]),
      "+f"(d[72]), "+f"(d[73]), "+f"(d[74]), "+f"(d[75]), "+f"(d[76]), "+f"(d[77]), "+f"(d[78]), "+f"(d[79]),
      "+f"(d[80]), "+f"(d[81]), "+f"(d[82]), "+f"(d[83]), "+f"(d[84]), "+f"(d[85]), "+f"(d[86]), "+f"(d[87]),
      "+f"(d[88]), "+f"(d[89]), "+f"(d[90]), "+f"(d[91]), "+f"(d[92]), "+f"(d[93]), "+f"(d[94]), "+f"(d[95]),
      "+f"(d[96]), "+f"(d[97]), "+f"(d[98]), "+f"(d[99]), "+f"(d[100]), "+f"(d[101]), "+f"(d[102]), "+f"(d[103]),
      "+f"(d[104]), "+f"(d[105]), "+f"(d[106]), "+f"(d[107]), "+f"(d[108]), "+f"(d[109]), "+f"(d[110]), "+f"(d[111]),
      "+f"(d[112]), "+f"(d[113]), "+f"(d[114]), "+f"(d[115]), "+f"(d[116]), "+f"(d[117]), "+f"(d[118]), "+f"(d[119]),
      "+f"(d[120]), "+f"(d[121]), "+f"(d[122]), "+f"(d[123]), "+f"(d[124]), "+f"(d[125]), "+f"(d[126]), "+f"(d[127])
    : "r"(a0), "r"(a1), "r"(a2), "r"(a3), "l"(db), "r"(scale_d));
}
__device__ __forceinline__ void wgmma_n128(float (&d)[64], uint64_t da, uint64_t db, int scale_d = 1) {
  asm volatile("{\n.reg .pred p;\nsetp.ne.b32 p, %66, 0;\n"
    "wgmma.mma_async.sync.aligned.m64n128k16.f32.bf16.bf16 "
    "{%0, %1, %2, %3, %4, %5, %6, %7, %8, %9, %10, %11, %12, %13, %14, %15, %16, %17, %18, %19, %20, %21, %22, %23, %24, %25, %26, %27, %28, %29, %30, %31, %32, %33, %34, %35, %36, %37, %38, %39, %40, %41, %42, %43, %44, %45, %46, %47, %48, %49, %50, %51, %52, %53, %54, %55, %56, %57, %58, %59, %60, %61, %62, %63}, "
    "%64, %65, p, 1, 1, 0, 0;\n}\n"
    : "+f"(d[0]), "+f"(d[1]), "+f"(d[2]), "+f"(d[3]), "+f"(d[4]), "+f"(d[5]), "+f"(d[6]), "+f"(d[7]), "+f"(d[8]), "+f"(d[9]), "+f"(d[10]), "+f"(d[11]), "+f"(d[12]), "+f"(d[13]), "+f"(d[14]), "+f"(d[15]), "+f"(d[16]), "+f"(d[17]), "+f"(d[18]), "+f"(d[19]), "+f"(d[20]), "+f"(d[21]), "+f"(d[22]), "+f"(d[23]), "+f"(d[24]), "+f"(d[25]), "+f"(d[26]), "+f"(d[27]), "+f"(d[28]), "+f"(d[29]), "+f"(d[30]), "+f"(d[31]), "+f"(d[32]), "+f"(d[33]), "+f"(d[34]), "+f"(d[35]), "+f"(d[36]), "+f"(d[37]), "+f"(d[38]), "+f"(d[39]), "+f"(d[40]), "+f"(d[41]), "+f"(d[42]), "+f"(d[43]), "+f"(d[44]), "+f"(d[45]), "+f"(d[46]), "+f"(d[47]), "+f"(d[48]), "+f"(d[49]), "+f"(d[50]), "+f"(d[51]), "+f"(d[52]), "+f"(d[53]), "+f"(d[54]), "+f"(d[55]), "+f"(d[56]), "+f"(d[57]), "+f"(d[58]), "+f"(d[59]), "+f"(d[60]), "+f"(d[61]), "+f"(d[62]), "+f"(d[63])
    : "l"(da), "l"(db), "r"(scale_d));
}
template<int N> __device__ __forceinline__ void fence_acc(float (&d)[N]) {
#pragma unroll
  for (int i = 0; i < N; i++) asm volatile("" : "+f"(d[i]) :: "memory");
}

template<int N, int I = 0, class F> __device__ __forceinline__ void static_for(F&& f) {
  if constexpr (I < N) { f(std::integral_constant<int, I>()); static_for<N, I + 1>(f); }
}

__device__ __forceinline__ void ldsm_x4_t(uint32_t addr, uint32_t& a, uint32_t& b, uint32_t& c, uint32_t& d) {
  asm volatile("ldmatrix.sync.aligned.m8n8.x4.trans.shared.b16 {%0, %1, %2, %3}, [%4];" : "=r"(a), "=r"(b), "=r"(c), "=r"(d) : "r"(addr));
}
__device__ __forceinline__ void sts128(uint32_t addr, uint32_t a, uint32_t b, uint32_t c, uint32_t d) {
  asm volatile("st.shared.v4.b32 [%0], {%1, %2, %3, %4};" :: "r"(addr), "r"(a), "r"(b), "r"(c), "r"(d));
}
__device__ __forceinline__ void mma16816(float (&c)[4], uint32_t a0, uint32_t a1, uint32_t a2, uint32_t a3, uint32_t b0, uint32_t b1) {
  asm volatile("mma.sync.aligned.m16n8k16.row.col.f32.bf16.bf16.f32 {%0, %1, %2, %3}, {%4, %5, %6, %7}, {%8, %9}, {%0, %1, %2, %3};"
      : "+f"(c[0]), "+f"(c[1]), "+f"(c[2]), "+f"(c[3]) : "r"(a0), "r"(a1), "r"(a2), "r"(a3), "r"(b0), "r"(b1));
}
__device__ __forceinline__ void mma1688(float (&c)[4], uint32_t a0, uint32_t a1, uint32_t b0) {
  asm volatile("mma.sync.aligned.m16n8k8.row.col.f32.bf16.bf16.f32 {%0, %1, %2, %3}, {%4, %5}, {%6}, {%0, %1, %2, %3};"
      : "+f"(c[0]), "+f"(c[1]), "+f"(c[2]), "+f"(c[3]) : "r"(a0), "r"(a1), "r"(b0));
}
__device__ __forceinline__ uint32_t keep_awake() {
  float c0;
  asm volatile("{\n.reg .f32 c1, c2, c3, z;\n.reg .b32 a;\nmov.b32 a, 0;\nmov.f32 z, 0f00000000;\n"
               "mma.sync.aligned.m16n8k8.row.col.f32.bf16.bf16.f32 {%0, c1, c2, c3}, {a, a}, {a}, {z, z, z, z};\n}\n" : "=f"(c0));
  return __float_as_uint(c0);
}
__device__ __forceinline__ void pin(uint32_t& v) { asm volatile("shfl.sync.bfly.b32 %0, %0, 0, 0x1f, 0xffffffff;" : "+r"(v)); }
template<class T> __device__ __forceinline__ void pin(T*& v) {
  uint32_t lo = (uint32_t)(uint64_t)v, hi = (uint32_t)((uint64_t)v >> 32);
  pin(lo); pin(hi);
  v = (T*)(((uint64_t)hi << 32) | lo);
}
__device__ __forceinline__ float sel4(int q, float a, float b, float c, float d) {
  float r;
  asm("{\n.reg .pred p, o;\n.reg .f32 x, y;\n.reg .b32 t;\nand.b32 t, %1, 1;\nsetp.ne.b32 p, t, 0;\nsetp.gt.s32 o, %1, 1;\n"
      "selp.f32 x, %3, %2, p;\nselp.f32 y, %5, %4, p;\nselp.f32 %0, y, x, o;\n}\n" : "=f"(r) : "r"(q), "f"(a), "f"(b), "f"(c), "f"(d));
  return r;
}
__device__ __forceinline__ uint32_t bfma2(uint32_t a, uint32_t b, uint32_t c) { uint32_t r; asm("fma.rn.bf16x2 %0, %1, %2, %3;" : "=r"(r) : "r"(a), "r"(b), "r"(c)); return r; }
__device__ __forceinline__ void tma_load_5d(uint32_t dst, const CUtensorMap* tm, uint32_t bar, int c0, int c4) {
  asm volatile("cp.async.bulk.tensor.5d.shared::cluster.global.mbarrier::complete_tx::bytes [%0], [%1, {%3, %4, %4, %4, %5}], [%2];"
    :: "r"(dst), "l"(tm), "r"(bar), "r"(c0), "r"(0), "r"(c4) : "memory");
}
__device__ __forceinline__ void tma_load_4d(uint32_t dst, const CUtensorMap* tm, uint32_t bar, int c0, int c3) {
  asm volatile("cp.async.bulk.tensor.4d.shared::cluster.global.mbarrier::complete_tx::bytes [%0], [%1, {%3, %4, %4, %5}], [%2];"
    :: "r"(dst), "l"(tm), "r"(bar), "r"(c0), "r"(0), "r"(c3) : "memory");
}
__device__ __forceinline__ void tma_load_4d_hint(uint32_t dst, const CUtensorMap* tm, uint32_t bar, int c0, int c3, uint64_t pol) {
  asm volatile("cp.async.bulk.tensor.4d.shared::cluster.global.mbarrier::complete_tx::bytes.L2::cache_hint [%0], [%1, {%3, %4, %4, %5}], [%2], %6;"
    :: "r"(dst), "l"(tm), "r"(bar), "r"(c0), "r"(0), "r"(c3), "l"(pol) : "memory");
}
__device__ __forceinline__ void tma_prefetch_4d(const CUtensorMap* tm, int c0, int c3) {
  asm volatile("cp.async.bulk.prefetch.tensor.4d.L2.global.tile [%0, {%1, %2, %2, %3}];" :: "l"(tm), "r"(c0), "r"(0), "r"(c3) : "memory");
}
__device__ __forceinline__ void tma_store_5d(const CUtensorMap* tm, uint32_t src, int c0, int c4) {
  asm volatile("cp.async.bulk.tensor.5d.global.shared::cta.bulk_group [%0, {%2, %3, %3, %3, %4}], [%1];" :: "l"(tm), "r"(src), "r"(c0), "r"(0), "r"(c4) : "memory");
}
__device__ __forceinline__ float rcp_fast(float x) { float r; asm("rcp.approx.ftz.f32 %0, %1;" : "=f"(r) : "f"(x)); return r; }
__device__ __forceinline__ float sigmoid_fast(float x) { float e; asm("ex2.approx.ftz.f32 %0, %1;" : "=f"(e) : "f"(x * -1.4426950408889634f)); return rcp_fast(1.f + e); }
__device__ __forceinline__ float sqrt_fast(float x) { float r; asm("sqrt.approx.ftz.f32 %0, %1;" : "=f"(r) : "f"(x)); return r; }
__device__ __forceinline__ float ln_sd(float var) { return bf16r(sqrt_fast(bf16r(bf16r(fmaxf(var, 0.f)) + 1e-5f))); }
__device__ __forceinline__ uint32_t norm2(uint32_t h, uint32_t neg_mean2, float inv_sd) {
  const uint32_t d = badd2(h, neg_mean2);
  return pack_bf16(bf_lo(d) * inv_sd, bf_hi(d) * inv_sd);
}
template<int N> __device__ __forceinline__ void delay_clk() {
  if constexpr (N > 0) { const uint32_t t0 = clock(); while ((uint32_t)clock() - t0 < N) {} }
}
__device__ __forceinline__ void put_xstat(uint32_t rs, uint32_t exb, int col, uint32_t mean_rstd, int m) {
  smem_at<uint16_t>(rs + ((col & 7) >> 1) * 144 + (col >> 3) * 4 + (col & 1) * 2) = (uint16_t)(mean_rstd ^ (m << 15));
  const uint32_t nm = (mean_rstd >> 16) ^ 0x8000u;
  smem_at<uint4>(exb + (col >> 3) * 256 + (col & 7) * 16) = make_uint4(nm | (nm << 16), nm, 0, 0);
  smem_at<uint4>(exb + (col >> 3) * 256 + 128 + (col & 7) * 16) = make_uint4(0, 0, 0, 0);
}
__device__ __forceinline__ void put_dsum(uint32_t exa, int e, float c) {
  const float hi = bf16r(c), mid = bf16r(c - hi), lo = bf16r((c - hi) - mid);
  smem_at<uint4>(exa + (e >> 3) * 256 + (e & 7) * 16) = make_uint4((__float_as_uint(hi) >> 16) | (__float_as_uint(mid) & 0xFFFF0000u), __float_as_uint(lo) >> 16, 0, 0);
  smem_at<uint4>(exa + (e >> 3) * 256 + 128 + (e & 7) * 16) = make_uint4(0, 0, 0, 0);
}
__host__ __device__ constexpr int min_c(int a, int b) { return a < b ? a : b; }
template<int V> using IC = std::integral_constant<int, V>;

#define CT(slot) do {} while (0)
#define PT(slot) do {} while (0)

template<int MAP>
__global__ void __cluster_dims__(2, 1, 1) __launch_bounds__(384, 1)
fnet_moe_kernel(const __grid_constant__ Params p) {
  constexpr int NX = MAP == 0 ? NX0 : 256;
  constexpr int G1_BYTES = A_BYTES + NX * 128;
  uint32_t sb;
  asm volatile("mov.u32 %0, %1;" : "=r"(sb) : "r"(smem_u32(smem_raw)));
  const int m = blockIdx.x & 1;
  int tau, eps;
  bool helper = false;
  if (MAP == 0) {
    uint32_t smid;
    asm volatile("mov.u32 %0, %%smid;" : "=r"(smid));
    const int c = smid >> 1, e7 = ((c - 32) * 37) >> 8;
    helper = c == 60 || c == 61;
    tau = c < 32 ? (c & 7) : (c < 60 ? c - 31 - 7 * e7 : 0);
    eps = c < 32 ? (c >> 3) : (c < 60 ? 4 + e7 : c - 58);
  } else {
    tau = (blockIdx.x >> 1) & 7; eps = blockIdx.x >> 4;
  }
  const int cid = tau * 16 + eps * 2 + m;
  const bool moe = tau > 0;
  auto BAR = [&](int i) { return sb + OFF_BAR + 8 * i; };
  const CUtensorMap* tmD = m ? &p.tmD1 : &p.tmD0;
  const uint64_t pol_ef = policy_evict_first();
#define LOAD_STREAM(d, tm, bar, c0, c1) tma_load_2d_hint(d, tm, bar, c0, c1, pol_ef)
#define LOAD_W(d, tm, bar, c0, grp) tma_load_4d_hint(d, tm, bar, c0, (grp) * 32, pol_ef)
  auto helper_load = [&](int k) {
    const uint32_t sa = sb + slot_of(k) * ST_BYTES, bar = BAR(B_FULL + slot_of(k));
    const CUtensorMap* tm = eps == 3 ? &p.tmD1 : &p.tmD0;
    tma_load_5d(sa, &p.tmXh, bar, (k & 15) * 64, 0);
    tma_load_2d(sa + A_BYTES, tm, bar, (k & 15) * 64, m * 512 + (k >> 4) * 256);
    tma_load_2d(sa + A_BYTES + 16384, tm, bar, (k & 15) * 64, m * 512 + (k >> 4) * 256 + 128);
  };
  if (threadIdx.x < 32 && elect_one()) {
    mbar_init(BAR(B_FULL), 1);
    asm volatile("fence.mbarrier_init.release.cluster;" ::: "memory");
    if (!helper) {
      tma_load_2d(sb + A_BYTES, &p.tmX, BAR(B_FULL), 0, tau * 256);
      tma_load_2d(sb, tmD, BAR(B_FULL), 0, eps * 128);
    }
    PT(52);
#pragma unroll
    for (int k = 1; k < 4; k++) mbar_init(BAR(B_FULL + k), 1);
    asm volatile("fence.mbarrier_init.release.cluster;" ::: "memory");
#pragma unroll
    for (int k = 0; k < 4; k++) mbar_expect_tx(BAR(B_FULL + k), helper ? ST_BYTES : G1_BYTES);
    if (!helper) {
#pragma unroll
      for (int k = 1; k < 4; k++) {
        tma_load_2d(sb + k * ST_BYTES + A_BYTES, &p.tmX, BAR(B_FULL + k), k * 64, tau * 256);
        LOAD_STREAM(sb + k * ST_BYTES, tmD, BAR(B_FULL + k), k * 64, eps * 128);
      }
    } else {
#pragma unroll 1
      for (int k = 0; k < 4; k++) helper_load(k);
    }
    PT(0);
  }
  __syncwarp();
  const int warp = __shfl_sync(0xffffffffu, threadIdx.x >> 5, 0);
  if (warp == 8) {
    if (elect_one()) {
#pragma unroll
      for (int b = B_EMPTY; b < B_COUNT; b++)
        mbar_init(BAR(b), b < B_EPI ? 2 : (b == B_EPI || b == B_EPI0B) ? 4 : (b < B_STD || b == B_OUT) ? 8 : (b == B_STAT || b == B_XS) ? 3 : 1);
      asm volatile("fence.mbarrier_init.release.cluster;" ::: "memory");
      mbar_expect_tx(BAR(B_XCH), 32768);
      SM_(uint32_t, OFF_SEEN) = 0;
    }
  }
  __syncthreads();

  if (warp >= 8) {
    reg_dec<REG_P>();
    asm volatile("barrier.cluster.arrive.relaxed.aligned;" ::: "memory");
    const int abrow = m * 1024 + eps * 128;
    const int f0 = (cid - 16) * 32;
    const CUtensorMap* tmWM = m ? &p.tmWM1 : &p.tmWM0;
    auto side_first = [&](int k) {
      if (NX < 256 && k == MINI_LOAD_K) {
        static_assert(NX == 256 || (mr_k(NREG_H) == MINI_LOAD_K && (NREG_H & 1) == 1), "second half of the staging buffer must be free");
        mbar_wait(BAR(B_STD + 3), 0);
        uint32_t n = 0;
        while (!((*(volatile uint32_t*)&SM_(uint32_t, OFF_SEEN) >> (4 * tau + 1)) & 1) && ++n < SPIN_LIMIT * 16) {}
        if (elect_one()) {
          mbar_expect_tx(BAR(B_MINI), 12288);
          tma_load_2d(sb + OFF_MINI, &p.tmAbM, BAR(B_MINI), tau * 256 + 240, abrow);
          LOAD_W(sb + OFF_MINI + 4096, tmWM, BAR(B_MINI), tau * 256 + 240, tau * 2 + m);
          LOAD_W(sb + OFF_MINI + 8192, tmWM, BAR(B_MINI), tau * 256 + 240, tau * 2 + 1 - m);
        }
      }
    };
    auto side = [&](int k) {
      if (NX < 256 && k == MINI_PF_K && elect_one()) tma_prefetch_4d(tmWM, tau * 256 + 240, tau * 64 + (eps & 1) * 32);
      if (k == WPF2_K && eps < WPF2_N && elect_one()) tma_prefetch_4d(m ? &p.tmW1 : &p.tmW0, kblock(tau, 31 - (eps >> 1)) * 64, tau * 64 + (eps & 1) * 32);
      if (!moe) return;
      const int i = k - MR_K0, r6 = i / MR_P, u = i - MR_P * r6, h = 2 * r6 + (u >> 1);
      if (i >= 0 && u < 4 && h < NREG_H) {
        if (h < 2) mbar_wait(BAR(B_STD + 2 + h), 0);
        if (elect_one()) {
          if (!(u & 1)) mbar_expect_tx(BAR(B_MR + (h & 1)), 16384);
          LOAD_STREAM(sb + OFF_XCH + u * 8192, (u & 1) ? &p.tmU : &p.tmG, BAR(B_MR + (h & 1)), f0, h * 128);
        }
      }
      if (k >= GU_K && k < GU_K + 2 && elect_one()) {
        static_assert(mr_k(NREG_H + 1) <= GU_K + 1 && MINI_K + 4 <= GU_K && GU_K < 47, "staging buffer must be free");
        LOAD_STREAM(sb + round_off(NREG_H + k - GU_K), &p.tmG, BAR(B_GU), f0, (NREG_H + k - GU_K) * 128);
        LOAD_STREAM(sb + round_off(NREG_H + k - GU_K) + 8192, &p.tmU, BAR(B_GU), f0, (NREG_H + k - GU_K) * 128);
      }
      if (k >= PF_K1 && !(k & 1) && elect_one()) {
        const int j = PF_N0 + ((k - PF_K1) >> 1);
        if (j < 8) tma_prefetch_2d(m ? &p.tmU : &p.tmG, f0, j * 128);
        else if (j < 12) asm volatile("cp.async.bulk.prefetch.L2.global [%0], %1;" :: "l"(p.wdown + (size_t)f0 * 1024 + (j - 8) * 8192), "r"(16384) : "memory");
      }
    };
    if (MAP == 0 && helper) {
      if (warp == 8) {
#pragma unroll 1
        for (int k = 4; k < 32; k++) {
          mbar_wait(BAR(B_EMPTY + slot_of(k)), (use_of(k) & 1) ^ 1);
          if (elect_one()) {
            mbar_expect_tx(BAR(B_FULL + slot_of(k)), ST_BYTES);
            helper_load(k);
            if (k == 12) mbar_arrive(BAR(B_LATE));
          }
        }
      } else {
        const int i0 = threadIdx.x - 288, lane = threadIdx.x & 31, col0 = (eps - 2) * 8 + m * 4;
        mbar_wait(BAR(B_LATE), 0);
        const uint32_t tag = ld_relaxed32(&p.s->epoch) + 1;
        if (i0 < 8) pkt_st128(&p.s->hflag[col0 * 2 + i0], 0, 0, 0, 0);
        SM_(uint32_t, OFF_TAG) = tag;
#pragma unroll 1
        for (int j0 = i0; j0 < 768; j0 += 384) {
          uint2 v[4]; uint32_t n = 0;
          while (true) {
#pragma unroll
            for (int z = 0; z < 4; z++) {
              const int j = j0 + 96 * z;
              v[z] = pkt_ld64(p.s->xstat + (j < 128 ? 256 * (j >> 4) + 240 + 2 * (j & 6) + ((j >> 2) & 2) + (j & 1)
                                          : j < 640 ? 2048 + col0 * 128 + j - 128 : (j - 640) * 16));
            }
            if (__all_sync(0xffffffffu, v[0].y == tag && v[1].y == tag && v[2].y == tag && v[3].y == tag) || ++n > SPIN_LIMIT) break;
            __nanosleep(300);
          }
#pragma unroll
          for (int z = 0; z < 4; z++) {
            const int j = j0 + 96 * z;
            if (j < 128) put_xstat(sb + OFF_RS, sb + OFF_XCH + 16384, j, v[z].x, eps - 2);
            else if (j < 640) put_dsum(sb + OFF_XCH, j - 128, __uint_as_float(v[z].x));
          }
        }
        fence_async_smem();
        __syncwarp();
        if (lane == 0) mbar_arrive(BAR(B_STAT));
      }
    } else if (warp == 8) {
      const CUtensorMap* tmW = m ? &p.tmW1 : &p.tmW0;
      const int gA = tau * 2 + m, gB = tau * 2 + 1 - m;
      auto wait_slot = [&](int k) {
        mbar_wait(BAR(B_EMPTY + slot_of(k)), (use_of(k) & 1) ^ 1);
        PT(64 + k);
      };
#pragma unroll 1
      for (int k = 4; k < 24; k++) {
        const int s = slot_of(k);
        const uint32_t sa = sb + s * ST_BYTES, sbb = sa + A_BYTES;
        const int kb = kblock(tau, k - 16);
        wait_slot(k);
        if (elect_one()) {
          mbar_expect_tx(BAR(B_FULL + s), k < 16 ? G1_BYTES : (k >> 1) == 9 ? B_BYTES : ST_BYTES);
          if (k < 16) {
            LOAD_STREAM(sa, tmD, BAR(B_FULL + s), k * 64, eps * 128);
            tma_load_2d(sbb, &p.tmX, BAR(B_FULL + s), k * 64, tau * 256);
          } else {
            LOAD_W(sbb, tmW, BAR(B_FULL + s), kb * 64, gA);
            LOAD_W(sbb + 16384, tmW, BAR(B_FULL + s), kb * 64, gB);
            if (k < 18) {
              tma_load_4d(sa, &p.tmXr, BAR(B_FULL + s), eps * 128, gA * 32 + s * 16);
              tma_load_4d(sa + 8192, &p.tmXr, BAR(B_FULL + s), eps * 128 + 64, gA * 32 + s * 16);
            }
          }
          if (k == PUB_K1) mbar_arrive(BAR(B_LATE));
          if (k >= WPF_K0 && k < WPF_K0 + WPF_N && (eps >> 1) == ((k - WPF_K0) & 3))
            tma_prefetch_4d(tmW, kblock(tau, k - WPF_K0) * 64, tau * 64 + (eps & 1) * 32);
          if (moe && k >= PF_K0 && k < PF_K0 + 2 * PF_N0 && !(k & 1)) tma_prefetch_2d(m ? &p.tmU : &p.tmG, f0, (k - PF_K0) * 64);
        }
      }
      uint32_t seen = 0;
#pragma unroll 1
      for (int k = 24; k < 48; k++) {
        const int s = slot_of(k);
        const uint32_t sa = sb + s * ST_BYTES, sbb = sa + A_BYTES;
        const int kb = kblock(tau, k - 16);
        const uint32_t need = (1u << kb) | ((kb & 3) == 3 ? 2u << (4 * tau) : 0u);
        wait_slot(k);
        side_first(k);
        if (elect_one()) {
          mbar_expect_tx(BAR(B_FULL + s), ST_BYTES);
          LOAD_W(sbb, tmW, BAR(B_FULL + s), kb * 64, gA);
          LOAD_W(sbb + 16384, tmW, BAR(B_FULL + s), kb * 64, gB);
        }
        uint32_t n = 0;
        while ((seen & need) != need && ++n < SPIN_LIMIT * 16) seen = *(volatile uint32_t*)&SM_(uint32_t, OFF_SEEN);
        if (elect_one()) tma_load_2d(sa, &p.tmAbL, BAR(B_FULL + s), kb * 64, abrow);
        side(k);
      }
      if (moe) {
        mbar_wait(BAR(B_EMPTY + 0), 1);
        if (elect_one()) { mbar_expect_tx(BAR(B_GU), (8 - NREG_H) * 16384); mbar_expect_tx(BAR(B_DN), 65536); }
#pragma unroll 1
        for (int i = 0; i < 10 - NREG_H; i++) {
          if (i == 3) mbar_wait(BAR(B_EMPTY + 1), 1);
          if (i == 4) {
            mbar_wait(BAR(B_EMPTY + 2), 1);
            mbar_wait(BAR(B_XCH), 0);
            PT(53);
          }
          const uint32_t dst = sb + late_off(i);
          if (elect_one()) {
            if (i < 6 - NREG_H) {
              LOAD_STREAM(dst, &p.tmG, BAR(B_GU), f0, (NREG_H + 2 + i) * 128);
              LOAD_STREAM(dst + 8192, &p.tmU, BAR(B_GU), f0, (NREG_H + 2 + i) * 128);
            } else {
#pragma unroll
              for (int b = 0; b < 4; b++) LOAD_STREAM(dst + b * 4096, &p.tmDn, BAR(B_DN), (4 * (i - 6 + NREG_H) + b) * 64, f0);
            }
          }
          const long long t0 = clock64();
          while (i < 9 - NREG_H && clock64() - t0 < MOE_PACE_CLK) {}
        }
      }
      const int lane = threadIdx.x & 31;
      mbar_wait(BAR(B_OUT), 0);
      const uint32_t km = SM_(uint32_t, OFF_WKEY + (lane & 7) * 8);
      const uint32_t bk = __reduce_max_sync(0xffffffffu, km);
      const int ww = __ffs(__ballot_sync(0xffffffffu, km == bk)) - 1;
#pragma unroll 1
      for (int i = 1; i <= 8; i++) {
        const int W = (ww + i) & 7;
        if (i == 8) {
          mbar_wait(BAR(B_XS), 0);
          if (SM_(uint32_t, OFF_KV) == bk) {
#pragma unroll 2
            for (int j = lane; j < 256; j += 32) {
              const int rho = j >> 4, row = row_of(gA * 128 + 32 * (W >> 1) + 8 * ((rho & 7) >> 1) + 4 * (W & 1) + 2 * (rho >> 3) + (rho & 1));
              const uint4 v = lds128_v(sb + OFF_OUT + (j & 8) * 2048 + (16 * W + rho) * 128 + (((j ^ rho) & 7) << 4));
              if (row != 0xFFFF - (int)(bk & 0xFFFFu))
                asm volatile("st.global.v4.b32 [%0], {%1, %2, %3, %4};" :: "l"(p.out + (size_t)row * 1024 + eps * 128 + (j & 15) * 8), "r"(v.x), "r"(v.y), "r"(v.z), "r"(v.w));
            }
            break;
          }
        }
        if (lane == 0) {
          tma_store_5d(&p.tmOut, sb + OFF_OUT + W * 2048, eps * 128, row_of(gA * 128 + 32 * (W >> 1) + 4 * (W & 1)));
          tma_store_5d(&p.tmOut, sb + OFF_OUT + 16384 + W * 2048, eps * 128 + 64, row_of(gA * 128 + 32 * (W >> 1) + 4 * (W & 1)));
        }
        const long long t0 = clock64();
        while (i < 7 && clock64() - t0 < OUT_PACE_CLK) {}
      }
      if (lane == 0) { bulk_commit(); bulk_wait_all(); }
      PT(22);
    } else {
      const int a = warp - 9;
      const int lane = threadIdx.x & 31;
      auto stage = [&](const bf16* src, int g) {
        if (elect_one()) {
          mbar_expect_tx(BAR(B_AUX + g), 16384);
          bulk_load(sb + OFF_XCH + g * 16384, src + g * 8192, 16384, BAR(B_AUX + g));
        }
      };
      uint32_t tag = 0;
#pragma unroll 1
      for (int i = 0; i < 3; i++) { i += keep_awake(); delay_clk<300>(); }
      mbar_wait(BAR(B_FULL + 0), 0);
      delay_clk<AUX_DELAY>();
      if (a == 0) PT(1);
      if (a == 1) mbar_wait(BAR(B_AUX + 0), 0);
      if (a < 2) stage(p.x + (size_t)cid * 16 * 1024, a);
#pragma unroll 1
      for (int it = 0; it < 4; it++) {
        const int g = it & 1;
        mbar_wait(BAR(B_AUX + g), it >> 1);
        if (a == 0) PT(2 + it);
        if (it == 2) tag = ld_relaxed32(&p.s->epoch) + 1;
        if (it == 2 && a == 2 && lane < 16) asm volatile("prefetch.global.L2 [%0];" :: "l"(p.wr + lane * 64));
        const uint32_t ad = sb + OFF_XCH + g * 16384 + (lane >> 2) * 2048;
        float s0 = 0.f, s1 = 0.f, q0 = 0.f, q1 = 0.f;
        auto row = [&](auto sq) {
#pragma unroll
          for (int i = 0; i < 11; i++) {
            if (i == 10 && a == 2) break;
            const uint4 v = lds128_v(ad + (((a * 44 + 4 * i + lane) & 127) << 4));
            const uint32_t ww[4] = {v.x, v.y, v.z, v.w};
#pragma unroll
            for (int z = 0; z < 4; z++) {
              const float d0 = bf_lo(ww[z]), d1 = bf_hi(ww[z]);
              s0 += d0; s1 += d1;
              if (decltype(sq)::value) { q0 = fmaf(d0, d0, q0); q1 = fmaf(d1, d1, q1); }
            }
          }
        };
        if (it < 2) row(IC<1>()); else row(IC<0>());
        s0 += s1; q0 += q1;
#pragma unroll
        for (int o = 1; o < 4; o <<= 1) { s0 += __shfl_xor_sync(0xffffffffu, s0, o); q0 += __shfl_xor_sync(0xffffffffu, q0, o); }
        if ((lane & 3) == 0) SM_(float2, OFF_PUB + a * 256 + it * 64 + (lane >> 2) * 8) = make_float2(s0, q0);
        if (it != 2) bar_sync(NB_AUX, 96);
        if (it < 2 && a == 2) stage(cid < 64 ? p.Dre + (size_t)cid * 16 * 1024 : p.Dim + (size_t)(cid - 64) * 16 * 1024, g);
      }
      if (a == 1) {
        const float2 v0 = SM_(float2, OFF_PUB + lane * 8), v1 = SM_(float2, OFF_PUB + 256 + lane * 8), v2 = SM_(float2, OFF_PUB + 512 + lane * 8);
        const float s = v0.x + v1.x + v2.x, mean = s * (1.f / 1024.f);
        const float rs = rcp_fast(ln_sd((v0.y + v1.y + v2.y) * (1.f / 1024.f) - mean * mean));
        pkt_st64((lane < 16 ? p.s->xstat : p.s->dsum) + cid * 16 + (lane & 15), lane < 16 ? pack_bf16(rs, mean) : __float_as_uint(s), tag);
        PT(6);
      }
      if (a == 2) {
        float s = 0.f;
#pragma unroll
        for (int q = 0; q < 4; q++) {
          const uint4 v = ldg_nc128(p.wr + (q * 32 + lane) * 8);
          s += ((bf_lo(v.x) + bf_hi(v.x)) + (bf_lo(v.y) + bf_hi(v.y))) + ((bf_lo(v.z) + bf_hi(v.z)) + (bf_lo(v.w) + bf_hi(v.w)));
          const int ch = q * 32 + lane - eps * 16;
          if (ch >= 0 && ch < 16) {
            SM_(uint32_t, OFF_WR + ch * 4) = v.x; SM_(uint32_t, OFF_WR + 80 + ch * 4) = v.y;
            SM_(uint32_t, OFF_WR + 160 + ch * 4) = v.z; SM_(uint32_t, OFF_WR + 240 + ch * 4) = v.w;
          }
        }
        s = warp_sum(s);
        if (lane == 0) { SM_(float, OFF_WSUM) = s; SM_(uint32_t, OFF_TAG) = tag; }
      }
      if (a < 2) __nanosleep(GATHER_NS);
      {
        const int i0 = a * 32 + lane;
        uint2 v[3], c0, c1; uint32_t n = 0;
        const uint2* dp = &p.s->dsum[abrow];
        while (true) {
#pragma unroll
          for (int q = 0; q < 3; q++) v[q] = pkt_ld64(&p.s->xstat[tau * 256 + min(i0 + 96 * q, 255)]);
          c0 = pkt_ld64(dp + i0); c1 = pkt_ld64(dp + min(i0 + 96, 127));
          if (__all_sync(0xffffffffu, v[0].y == tag && v[1].y == tag && v[2].y == tag && c0.y == tag && c1.y == tag) || ++n > SPIN_LIMIT) break;
          __nanosleep(200);
        }
#pragma unroll
        for (int q = 0; q < 3; q++) put_xstat(sb + OFF_RS, sb + OFF_EXB, min(i0 + 96 * q, 255), v[q].x, m);
        put_dsum(sb + OFF_EXA, i0, __uint_as_float(c0.x));
        put_dsum(sb + OFF_EXA, min(i0 + 96, 127), __uint_as_float(c1.x));
        fence_async_smem();
      }
      __syncwarp();
      if (lane == 0) mbar_arrive(BAR(B_STAT));
      if (a == 0) PT(7);
      if (a == 0) {
        const uint32_t* flg = reinterpret_cast<const uint32_t*>(&p.s->abflag[((eps * 2 + m) * 8 + (lane >> 2)) * 2]) + (lane & 3);
        if (NX < 256 && lane == 4 * tau + 1) flg = reinterpret_cast<const uint32_t*>(&p.s->hflag[(m * 8 + eps) * 2]);
        uint32_t seen = 0;
        auto fetch = [&](int s, uint32_t dst) {
          const int tile = sigma_of(tau, s);
          uint32_t n = 0;
          while (!((seen >> (4 * tile)) & 1) && ++n < SPIN_LIMIT) seen = __ballot_sync(0xffffffffu, ld_acquire32(flg) == tag);
          asm volatile("fence.proxy.async.global;" ::: "memory");
          PT(16 + s);
          if (elect_one()) tma_load_2d(dst, &p.tmAbL, BAR(B_FULL + s), tile * 256, abrow);
        };
        mbar_wait(BAR(B_EPI), 0);
#pragma unroll
        for (int s = 0; s < 4; s++) mbar_wait(BAR(B_FULL + s), 0);
        fetch(0, sb + OFF_XCH);
        mbar_wait(BAR(B_STD + 0), 0);
        fetch(1, sb + OFF_XCH + 16384);
        fetch(2, sb + 2 * ST_BYTES);
        if (elect_one()) mbar_arrive(BAR(B_PUB1));
        mbar_wait(BAR(B_STD + 1), 0);
        fetch(3, sb + 3 * ST_BYTES);
        uint32_t n = 0, told = 0;
        while (true) {
          if (seen != told) {
            asm volatile("fence.proxy.async.global;" ::: "memory");
            *(volatile uint32_t*)&SM_(uint32_t, OFF_SEEN) = seen;
            told = seen;
          }
          if (seen == 0xFFFFFFFFu || ++n > SPIN_LIMIT) break;
          __nanosleep(100);
          seen = __ballot_sync(0xffffffffu, ld_acquire32(flg) == tag);
        }
        PT(58);
      } else {
        uint32_t* flag = reinterpret_cast<uint32_t*>(&p.s->abflag[((eps * 2 + m) * 8 + tau) * 2]);
        if (a == 1) {
          mbar_wait(BAR(B_EPI), 0);
          PT(8);
          if (lane == 0) tma_store_2d(&p.tmAbS, sb + chunk_off(0, 0), tau * 256, abrow);
          mbar_wait(BAR(B_EPI0B), 0);
          if (lane == 0) {
            tma_store_2d(&p.tmAbS, sb + chunk_off(0, 1), tau * 256, abrow + 64);
            bulk_commit();
            bulk_wait_all();
            mbar_arrive(BAR(B_STD));
            bulk_wait_release();
            st_relaxed32(flag, tag);
          }
          PT(12);
          mbar_wait(BAR(B_EPI + 1), 0);
          mbar_wait(BAR(B_LATE), 0);
          mbar_wait(BAR(B_PUB1), 0);
          PT(9);
          if (lane == 0) {
            tma_store_2d(&p.tmAbS, sb + chunk_off(1, 0), tau * 256 + 64, abrow);
            tma_store_2d(&p.tmAbS, sb + chunk_off(1, 1), tau * 256 + 64, abrow + 64);
            bulk_commit();
            bulk_wait_all();
            mbar_arrive(BAR(B_STD + 1));
            bulk_wait_release();
            st_relaxed32(flag + 1, tag);
          }
          PT(13);
        }
        auto copy_out = [&](int c) {
          mbar_wait(BAR(B_EPI + c), 0);
          PT(8 + c);
          bf16* dst = p.s->abT + (size_t)(abrow + (lane >> 3)) * 2048 + tau * 256 + c * 64 + (lane & 7) * 8;
          const uint32_t src = sb + chunk_off(c, 0) + (lane >> 3) * 128 + (((lane & 7) ^ (lane >> 3)) << 4);
          const uint32_t on = c * 64 + (lane & 7) * 8 < NX;
#pragma unroll 4
          for (int i = 0; i < 32; i++) {
            const uint4 v = lds128_v((src ^ ((i & 1) << 6)) + i * 512);
            asm volatile("{\n.reg .pred p;\nsetp.ne.b32 p, %5, 0;\n@p st.global.v4.b32 [%0], {%1, %2, %3, %4};\n}\n"
                         :: "l"(dst + i * 4 * 2048), "r"(v.x), "r"(v.y), "r"(v.z), "r"(v.w), "r"(on));
          }
          __syncwarp();
          if (lane == 0) mbar_arrive(BAR(B_STD + c));
        };
        if (a == 2) {
#pragma unroll 1
          for (int c = 2; c < 4; c++) copy_out(c);
          asm volatile("fence.acq_rel.gpu;" ::: "memory");
          __syncwarp();
          if (lane < 2) st_relaxed32(flag + 2 + lane, tag);
          PT(15);
        }
      }
      {
        mbar_wait(BAR(B_LATE), 1);
        const int grp = tau * 2 + m;
#pragma unroll 1
        for (int i = a; i < 14; i += 3) {
          uint4* dst = i < 8 ? &p.s->ypart[cid * 256 + i * 32 + lane] : i < 12 ? &p.s->hstat[(grp * 8 + eps) * 128 + (i - 8) * 32 + lane]
                     : i == 12 ? &p.s->cand[grp * 256 + eps * 32 + lane] : &p.s->key[(((lane >> 1) & 7) * 16 + grp) * 2 + (lane & 1)];
          if (i < 13 || eps == 0) pkt_st128(dst, 0, 0, 0, 0);
          __nanosleep(200);
        }
        __syncwarp();
        if (lane == 0) mbar_arrive(BAR(B_STAT));
      }
      {
        const uint4* kp = &p.s->key[(tau * 16 + (lane & 15)) * 2];
        const int i0 = a * 32 + lane;
        mbar_wait(BAR(B_KEY), 0);
        if (a == 0) PT(43);
        uint4 kq = pkt_ld128(kp), cv[3] = {};
        uint32_t n = 0, kv;
        int gspec = -1;
        while (true) {
          const bool ok = kq.y == tag && kq.w == tag;
          kv = __reduce_max_sync(0xffffffffu, ok ? kq.x : 0u);
          const int gs = group_of(0xFFFF - (int)(kv & 0xFFFFu));
          const bool cok = gs == gspec && cv[0].y == tag && cv[0].w == tag && cv[1].y == tag && cv[1].w == tag && cv[2].y == tag && cv[2].w == tag;
          if (__all_sync(0xffffffffu, ok && cok) || ++n > SPIN_LIMIT) break;
          if (!ok) kq = pkt_ld128(kp);
          n += keep_awake();
          const bool spec = __popc(__ballot_sync(0xffffffffu, ok)) >= 2 * SPEC_MIN;
          if (!cok && spec) {
#pragma unroll
            for (int i = 0; i < 3; i++) cv[i] = pkt_ld128(&p.s->cand[gs * 256 + min(i0 + 96 * i, 255)]);
          }
          if (spec) gspec = gs;
        }
        if (a == 0) PT(45);
        const uint32_t ms = __shfl_sync(0xffffffffu, kq.z, gspec);
        const uint32_t nm = ((ms & 0xFFFFu) ^ 0x8000u) * 0x10001u;
        const float is = rcp_fast(bf_hi(ms));
#pragma unroll
        for (int i = 0; i < 3; i++) {
          const int j = min(i0 + 96 * i, 255);
          SM_(uint2, OFF_XSEL + j * 8) = make_uint2(norm2(cv[i].x, nm, is), norm2(cv[i].z, nm, is));
        }
#pragma unroll
        for (int i = 0; i < 3; i++) SM_(uint2, OFF_HSEL + min(i0 + 96 * i, 255) * 8) = make_uint2(cv[i].x, cv[i].z);
        SM_(uint32_t, OFF_KV) = kv;
        __syncwarp();
        if (lane == 0) mbar_arrive(BAR(B_XS));
      }
    }
    asm volatile("barrier.cluster.wait.aligned;" ::: "memory");
  } else {
    reg_inc<REG_C>();
    const int tid = __shfl_sync(0xffffffffu, threadIdx.x, threadIdx.x & 31), lane = tid & 31;
    const int w = warp >> 2, wi = warp & 3, t = tid & 127;
    const int g = lane >> 2, q = lane & 3;
    const int turn_me = NB_TURN0 + w, turn_other = NB_TURN1 - w;
    auto release = [&](int s) { if (t == 0) mbar_arrive(BAR(B_EMPTY + s)); };
    if (MAP == 0 && helper) {
      asm volatile("barrier.cluster.arrive.relaxed.aligned;" ::: "memory");
      float s0[64], s1[64];
#pragma unroll
      for (int i = 0; i < 64; i++) { s0[i] = 0.f; s1[i] = 0.f; }
      if (w == 1) bar_arrive(NB_TURN0, 256);
      uint32_t o[32][2] = {};
      const int col = (eps - 2) * 8 + m * 4 + w;
      auto put = [&](auto tc, uint32_t buf) {
        constexpr int tl = decltype(tc)::value;
#pragma unroll
        for (int i = 0; i < 4; i++)
          smem_at<uint2>(buf + ((i >> 1) * 64 + wi * 16 + (i & 1) * 8 + g) * 32 + ((q * 8) ^ ((g & 4) << 2))) = make_uint2(o[8 * i + tl][0], o[8 * i + tl][1]);
      };
      auto mma_step = [&](int k) {
        const int s = slot_of(k);
        const uint64_t da = make_desc(sb + s * ST_BYTES + A_BYTES + w * 16384), db = make_desc(sb + s * ST_BYTES);
        wgmma_fence();
#pragma unroll
        for (int kk = 0; kk < 4; kk++) {
          wgmma_n128(s0, da + kk * 2, db + kk * 2, kk > 0 || (k & 15));
          wgmma_n128(s1, da + 512 + kk * 2, db + kk * 2, kk > 0 || (k & 15));
        }
        wgmma_commit();
      };
#pragma unroll 1
      for (int pass = 0; pass < 2; pass++) {
#pragma unroll 1
        for (int k = 16 * pass; k < (pass ? 32 - HL_N : 16); k++) {
          mbar_wait(BAR(B_FULL + slot_of(k)), use_of(k) & 1);
          bar_sync(turn_me, 256);
          mma_step(k);
          bar_arrive(turn_other, 256);
          if (pass && k < 24) {
            const uint32_t buf = sb + OFF_XCH + ((k & 1) ? 0 : 20480) + w * 4096;
            static_for<8>([&](auto ic) { if (k == 16 + decltype(ic)::value) put(ic, buf); });
            fence_async_smem();
            bar_sync(NB_WG0 + w, 128);
            if (t == 0) { tma_store_2d(&p.tmAbM, buf, (k - 16) * 256 + 240, col * 128); bulk_commit(); }
          }
          wgmma_wait0();
          release(slot_of(k));
          if (t == 0) asm volatile("cp.async.bulk.wait_group.read 1;" ::: "memory");
        }
        if (pass) {
          bar_sync(turn_me, 256);
#pragma unroll
          for (int k = 32 - HL_N; k < 32; k++) {
            mbar_wait(BAR(B_FULL + slot_of(k)), 1);
            mma_step(k);
          }
        }
        mbar_wait(BAR(B_STAT), 0);
        wgmma_fence();
        wgmma_n128(s0, make_desc_noswz(sb + OFF_XCH + pass * 8192 + w * 4096), make_desc_noswz(sb + OFF_XCH + 16384));
        wgmma_n128(s1, make_desc_noswz(sb + OFF_XCH + pass * 8192 + w * 4096 + 2048), make_desc_noswz(sb + OFF_XCH + 16384));
        wgmma_commit();
        if (pass && w == 0) bar_arrive(turn_other, 256);
        uint4 rs[4];
#pragma unroll
        for (int i = 0; i < 4; i++) rs[i] = lds128_v(sb + OFF_RS + q * 144 + i * 16);
        wgmma_wait0();
        fence_acc(s0); fence_acc(s1);
#pragma unroll
        for (int i = 0; i < 32; i++) {
          const int tl = i & 7, hr = (i >> 3) & 1;
          const float* ac = (i >> 4) ? &s1[8 * tl + 2 * hr] : &s0[8 * tl + 2 * hr];
          o[i][0] = bmul2(pack_bf16(ac[0], ac[1]), (tl & 1) ? rs[tl >> 1].z : rs[tl >> 1].x);
          o[i][1] = bmul2(pack_bf16(ac[4], ac[5]), (tl & 1) ? rs[tl >> 1].w : rs[tl >> 1].y);
        }
      }
      static_for<8>([&](auto ic) { put(ic, sb + (w * 8 + decltype(ic)::value) * 4096); });
      fence_async_smem();
      bar_sync(NB_WG0 + w, 128);
      if (t == 0) {
#pragma unroll 1
        for (int i = 0; i < 8; i++) tma_store_2d(&p.tmAbM, sb + (w * 8 + i) * 4096, i * 256 + 240, (col + 2) * 128);
        bulk_commit();
        bulk_wait_release();
        st_relaxed32(&p.s->hflag[col * 2], SM_(uint32_t, OFF_TAG));
        st_relaxed32(&p.s->hflag[(col + 2) * 2], SM_(uint32_t, OFF_TAG));
      }
      asm volatile("barrier.cluster.wait.aligned;" ::: "memory");
      return;
    }
    float acc[128], a1[NX / 2];
#pragma unroll
    for (int i = 0; i < NX / 2; i++) a1[i] = 0.f;
    if (w == 1) bar_arrive(NB_TURN0, 256);
    auto kstep = [&](auto& d, int k, bool first, bool a_in_xch = false, bool mini = false) {
      const int s = slot_of(k);
      mbar_wait(BAR(B_FULL + s), use_of(k) & 1);
      CT(64 + k);
      bar_sync(turn_me, 256);
      const uint64_t da = make_desc(sb + (a_in_xch ? OFF_XCH + s * 16384 : s * ST_BYTES) + w * 8192), db = make_desc(sb + s * ST_BYTES + A_BYTES);
      wgmma_fence();
      wgmma_g1(d, da, db, !first);
#pragma unroll
      for (int kk = 1; kk < 4; kk++) wgmma_g1(d, da + kk * 2, db + kk * 2, 1);
      wgmma_commit();
      if (mini) {
        CT(29);
        mbar_wait(BAR(B_MINI), 0);
        CT(30);
        wgmma_fence();
        wgmma_g1(d, make_desc_32b(sb + OFF_MINI + w * 2048), make_desc_32b(sb + OFF_MINI + 4096), 1);
        wgmma_commit();
      }
      bar_arrive(turn_other, 256);
    };
    auto kdone = [&](int k) { wgmma_wait0(); release(slot_of(k)); };
    auto wgmma_wait1 = [&]() { asm volatile("wgmma.wait_group.sync.aligned 1;" ::: "memory"); };

#pragma unroll 1
    for (int k = 0; k < 13; k++) {
      kstep(a1, k, k == 0);
      if (k == 0) CT(0);
      if (k == 8 && warp == 2 && lane < 2) pkt_st128(&p.s->abflag[((eps * 2 + m) * 8 + tau) * 2 + lane], 0, 0, 0, 0);
      kdone(k);
    }
    uint32_t R[64];
    kstep(a1, 13, false);
    mbar_wait(BAR(B_STAT), 0);
    const uint32_t tag = SM_(uint32_t, OFF_TAG);
#pragma unroll
    for (int i = 0; i < 8; i++) { const uint4 v = lds128_v(sb + OFF_RS + q * 144 + i * 16); R[8 * i] = v.x; R[8 * i + 2] = v.y; R[8 * i + 4] = v.z; R[8 * i + 6] = v.w; }
    kdone(13);
    float p0[32], p1[NX / 2 - 32];
    auto pack = [&](auto cc) {
      constexpr int c = decltype(cc)::value;
#pragma unroll
      for (int j = 8 * c; j < min_c(8 * c + 8, NX / 8); j++) {
        const uint32_t rs = R[2 * j];
        const float* ac = c ? &p1[4 * j - 32] : &p0[4 * j];
        R[2 * j] = bmul2(pack_bf16(ac[0], ac[1]), rs);
        R[2 * j + 1] = bmul2(pack_bf16(ac[2], ac[3]), rs);
      }
    };
    auto put_chunk = [&](auto cc) {
      constexpr int c = decltype(cc)::value;
      const int rho = 16 * wi + (lane & 15);
#pragma unroll
      for (int j = 8 * c; j < min_c(8 * c + 8, NX / 8); j += 2) {
        const int chunk = (j & 7) + (lane >> 4);
        stsm_x4(sb + chunk_off(c, w) + rho * 128 + ((chunk ^ (lane & 7)) << 4), R[2 * j], R[2 * j + 1], R[2 * j + 2], R[2 * j + 3]);
      }
    };
    auto staged = [&](int bar) {
      fence_async_smem();
      __syncwarp();
      if (lane == 0) mbar_arrive(BAR(bar));
    };
    auto mma_rs = [&](auto cc, auto k0, auto k1) {
      constexpr int c = decltype(cc)::value;
      const uint64_t db = make_desc(sb + c * ST_BYTES + A_BYTES);
#pragma unroll
      for (int kk = decltype(k0)::value; kk < decltype(k1)::value; kk++)
        wgmma_n256_rs(acc, R[16 * c + 4 * kk], R[16 * c + 4 * kk + 1], R[16 * c + 4 * kk + 2], R[16 * c + 4 * kk + 3], db + kk * 2, c + kk > 0);
      wgmma_commit();
    };
    auto kdone_x = [&](int k, auto ic) {
      constexpr int i = decltype(ic)::value;
      uint32_t r[8];
#pragma unroll
      for (int z = 0; z < 2; z++) {
        const int tr = 32 * (i & 1) + 16 * z + 8 * (lane >> 4) + (lane & 7), chunk = 2 * wi + ((lane >> 3) & 1);
        ldsm_x4_t(sb + (i >> 1) * ST_BYTES + w * 8192 + tr * 128 + ((chunk ^ (lane & 7)) << 4), r[4 * z], r[4 * z + 1], r[4 * z + 2], r[4 * z + 3]);
      }
      float f[16];
#pragma unroll
      for (int z = 0; z < 8; z++) { f[2 * z] = bf_lo(r[z]); f[2 * z + 1] = bf_hi(r[z]); }
#pragma unroll
      for (int z = 0; z < 16; z++) asm volatile("" : "+f"(f[z]));
      kdone(k);
#pragma unroll
      for (int z = 0; z < 16; z++) asm volatile("add.f32 %0, %0, %1;" : "+f"(acc[16 * i + z]) : "f"(f[z]));
    };
    {
      const uint64_t da2 = make_desc(sb + 2 * ST_BYTES + w * 8192), db2 = make_desc(sb + 2 * ST_BYTES + A_BYTES);
      const uint64_t da3 = make_desc(sb + 3 * ST_BYTES + w * 8192), db3 = make_desc(sb + 3 * ST_BYTES + A_BYTES);
      const uint64_t dax = make_desc_noswz(sb + OFF_EXA + w * 2048), dbx = make_desc_noswz(sb + OFF_EXB);
      fence_acc(a1);
#pragma unroll
      for (int i = 0; i < 32; i++) asm volatile("mov.b32 %0, %1;" : "=f"(p0[i]) : "f"(a1[i]));
#pragma unroll
      for (int i = 32; i < NX / 2; i++) asm volatile("mov.b32 %0, %1;" : "=f"(p1[i - 32]) : "f"(a1[i]));
      mbar_wait(BAR(B_FULL + 2), 1);
      CT(64 + 14);
      bar_sync(turn_me, 256);
      wgmma_fence();
#pragma unroll
      for (int kk = 0; kk < 4; kk++) wgmma_g1(p0, da2 + kk * 2, db2 + kk * 2, 1);
      wgmma_commit();
      mbar_wait(BAR(B_FULL + 3), 1);
      CT(64 + 15);
      wgmma_fence();
#pragma unroll
      for (int kk = 0; kk < 4; kk++) wgmma_g1(p0, da3 + kk * 2, db3 + kk * 2, 1);
      wgmma_g1(p0, dax, dbx, 1);
      wgmma_commit();
      bar_arrive(turn_other, 256);
      wgmma_wait0();
      fence_acc(p0);
      pack(IC<0>());
      put_chunk(IC<0>());
      CT(20);
      bar_sync(turn_me, 256);
      wgmma_fence();
#pragma unroll
      for (int kk = 0; kk < 4; kk++) wgmma_g1(p1, da2 + kk * 2, db2 + 512 + kk * 2, 1);
      wgmma_commit();
      staged(w ? B_EPI0B : B_EPI);
      CT(21);
      wgmma_fence();
#pragma unroll
      for (int kk = 0; kk < 4; kk++) wgmma_g1(p1, da3 + kk * 2, db3 + 512 + kk * 2, 1);
      wgmma_g1(p1, dax, dbx + 128, 1);
      wgmma_commit();
      bar_arrive(turn_other, 256);
      wgmma_wait1();
      release(2);
      kdone(15);
      mbar_wait(BAR(B_STAT), 0);
    }
    fence_acc(p1);
    CT(1);
    pack(IC<1>());
    pack(IC<2>());
    pack(IC<3>());
#pragma unroll
    for (int i = 16; i < NX / 4; i++) asm volatile("" : "+r"(R[i]));
#pragma unroll
    for (int i = 0; i < 128; i++) asm volatile("" : "=f"(acc[i]));
    mbar_wait(BAR(B_FULL + 0), 0);
    CT(2);
    static_for<4>([&](auto ic) {
      constexpr int c = decltype(ic)::value;
      if (c) mbar_wait(BAR(B_FULL + c), 0);
      CT(64 + 16 + c);
      bar_sync(turn_me, 256);
      wgmma_fence();
      mma_rs(IC<c>(), IC<0>(), IC<min_c(4, NX / 16 - 4 * c)>());
      bar_arrive(turn_other, 256);
      if constexpr (c == 0) { put_chunk(IC<1>()); staged(B_EPI + 1); kdone(16); } else kdone_x(16 + c, IC<c - 1>());
    });
#pragma unroll 1
    for (int k = 20; k < 23; k++) {
      kstep(acc, k, false, k < 22);
      if (k == 20) {
        kdone_x(k, IC<3>());
      } else {
        if (k == 21) put_chunk(IC<2>()); else put_chunk(IC<3>());
        __syncwarp();
        if (lane == 0) mbar_arrive(BAR(B_EPI + k - 19));
        kdone(k);
      }
    }
    uint32_t wf[32][4];
    auto load_wf = [&](auto hc) {
      constexpr int h = decltype(hc)::value;
      const int d = w * 64 + (lane >> 4) * 8 + (lane & 7);
      const uint32_t ad = sb + round_off(h) + (lane & 8) * 1024 + d * 64 + ((wi ^ ((lane >> 1) & 3)) << 4);
#pragma unroll
      for (int i = 0; i < 4; i++) ldsm_x4_t(ad + i * 1024, wf[4 * h + i][0], wf[4 * h + i][1], wf[4 * h + i][2], wf[4 * h + i][3]);
    };
    auto load_wf_rest = [&]() { static_for<8 - NREG_H>([&](auto ic) { load_wf(IC<NREG_H + decltype(ic)::value>()); }); };
#pragma unroll
    for (int i = 0; i < 4 * NREG_H; i++) { wf[i][0] = 0; wf[i][1] = 0; wf[i][2] = 0; wf[i][3] = 0; }
    const int grp = tau * 2 + m;
#pragma unroll 1
    for (int k = 23; k < 46; k++) {
      kstep(acc, k, false, false, NX < 256 && k == MINI_K);
      if (moe) {
        static_for<NREG_H>([&](auto hc) {
          constexpr int h = decltype(hc)::value;
          if (k == mr_k(h) + 1) { mbar_wait(BAR(B_MR + (h & 1)), (h >> 1) & 1); CT(32 + h); load_wf(hc); }
        });
      }
      if (k == RESET_K && tid == 0) mbar_arrive(BAR(B_LATE));
      kdone(k);
    }
    asm volatile("barrier.cluster.arrive.relaxed.aligned;" ::: "memory");
    mbar_wait(BAR(B_STAT), 1);
    uint32_t wa[16][2];
    uint32_t cd = code_of(tag);
    uint4* hp_pub = &p.s->hstat[(grp * 8 + eps) * 128 + warp * 16 + g];
    const uint4* hp_poll = &p.s->hstat[(grp * 8 + 2 * q) * 128 + warp * 16 + g];
    const uint32_t vec_off = (2 * wi) * 512 + q * 128 + ((g ^ (2 * q)) << 4);
    {
      float as[64], ak[64];
      fence_acc(acc);
#pragma unroll
      for (int i = 0; i < 64; i++) asm volatile("mov.b32 %0, %1;" : "=f"(as[i]) : "f"(acc[64 + i]));
#pragma unroll
      for (int i = 0; i < 64; i++) asm volatile("mov.b32 %0, %1;" : "=f"(ak[i]) : "f"(acc[i]));
      const uint64_t da1 = make_desc(sb + 2 * ST_BYTES + w * 8192), db1 = make_desc(sb + 2 * ST_BYTES + A_BYTES);
      const uint64_t da2 = make_desc(sb + 3 * ST_BYTES + w * 8192), db2 = make_desc(sb + 3 * ST_BYTES + A_BYTES);
      mbar_wait(BAR(B_FULL + 2), 1);
      CT(64 + 46);
      bar_sync(turn_me, 256);
      wgmma_fence();
#pragma unroll
      for (int kk = 0; kk < 4; kk++) wgmma_n128(as, da1 + kk * 2, db1 + 1024 + kk * 2);
      wgmma_commit();
      mbar_wait(BAR(B_FULL + 3), 1);
      CT(64 + 47);
      wgmma_fence();
#pragma unroll
      for (int kk = 0; kk < 4; kk++) wgmma_n128(as, da2 + kk * 2, db2 + 1024 + kk * 2);
      wgmma_commit();
      bar_arrive(turn_other, 256);
      const uint32_t rx = mapa(sb + OFF_PEER + w * 4096 + vec_off, 1 - m), rb = mapa(BAR(B_XCH), 1 - m);
      asm volatile("barrier.cluster.wait.aligned;" ::: "memory");
      CT(24);
      wgmma_wait0();
      fence_acc(as);
      CT(25);
      auto keep = [&]() {
        bar_sync(turn_me, 256);
        wgmma_fence();
#pragma unroll
        for (int kk = 0; kk < 4; kk++) wgmma_n128(ak, da1 + kk * 2, db1 + kk * 2);
        wgmma_commit();
#pragma unroll
        for (int kk = 0; kk < 4; kk++) wgmma_n128(ak, da2 + kk * 2, db2 + kk * 2);
        wgmma_commit();
        if (w == 0) bar_arrive(turn_other, 256);
      };
#pragma unroll
      for (int i = 0; i < 8; i++) {
        if (i == SEND_FIRST) keep();
        const float* ac = &as[16 * (i >> 1) + 2 * (i & 1)];
        st_async_v4(rx + (i >> 1) * 8192 + (i & 1) * 512, rb, pack_bf16(ac[0], ac[1]), pack_bf16(ac[4], ac[5]), pack_bf16(ac[8], ac[9]), pack_bf16(ac[12], ac[13]));
      }
      CT(26);
#pragma unroll
      for (int i = 0; i < 4; i++) {
        const uint4 v = lds128_v(sb + OFF_WR + q * 80 + i * 16);
        const uint32_t vv[4] = {v.x, v.y, v.z, v.w};
#pragma unroll
        for (int z = 0; z < 4; z++) {
          asm volatile("{\n.reg .pred p;\nsetp.ne.b32 p, %2, 0;\nselp.b32 %0, %1, 0x3F803F80, p;\n}" : "=r"(wa[4 * i + z][0]) : "r"(vv[z]), "r"(g & 1));
          asm volatile("{\n.reg .pred p;\nsetp.ne.b32 p, %2, 0;\nselp.b32 %0, %1, 0x3F803F80, p;\n}" : "=r"(wa[4 * i + z][1]) : "r"(vv[z]), "r"(g & 1));
        }
      }
      pin(cd); pin(hp_pub); pin(hp_poll);
      CT(27);
      wgmma_wait1();
      release(2);
      wgmma_wait0();
      fence_acc(ak);
      CT(3);
#pragma unroll
      for (int i = 0; i < 8; i++) {
        const float* ac = &ak[16 * (i >> 1) + 2 * (i & 1)];
        sts128(sb + (2 + (i >> 2)) * ST_BYTES + w * 8192 + ((i >> 1) & 1) * 4096 + (i & 1) * 512 + vec_off,
               pack_bf16(ac[0], ac[1]), pack_bf16(ac[4], ac[5]), pack_bf16(ac[8], ac[9]), pack_bf16(ac[12], ac[13]));
      }
    }
    uint32_t h[8][4];
    {
      const int qq = 2 * (warp & 1) + ((lane >> 3) & 1);
      const uint32_t lo = (lane >> 4) * 512 + qq * 128 + (((lane & 7) ^ (2 * qq)) << 4);
      bar_sync(NB_BOTH, 256);
#pragma unroll
      for (int ks = 0; ks < 8; ks++)
        ldsm_x4_t(sb + (2 + w) * ST_BYTES + (ks >> 2) * 8192 + (wi >> 1) * 4096 + (ks & 3) * 1024 + lo, h[ks][0], h[ks][1], h[ks][2], h[ks][3]);
      CT(28);
      mbar_wait_cluster(BAR(B_XCH), 0);
      CT(4);
      uint32_t r[8][4];
#pragma unroll
      for (int ks = 0; ks < 8; ks++) ldsm_x4_t(sb + OFF_PEER + (warp >> 1) * 8192 + ks * 1024 + lo, r[ks][0], r[ks][1], r[ks][2], r[ks][3]);
      float d[4][4] = {};
#pragma unroll
      for (int ks = 0; ks < 8; ks++) {
#pragma unroll
        for (int i = 0; i < 4; i++) {
          h[ks][i] = badd2(h[ks][i], r[ks][i]);
          mma1688(d[i], h[ks][i], wa[2 * ks + (i >> 1)][i & 1], h[ks][i]);
        }
      }
#pragma unroll
      for (int i = 0; i < 2; i++) {
        const float sq = (g & 1) ? d[i][1] + d[i + 2][1] : d[i][0] + d[i + 2][0];
        const float e0 = d[i][2] + d[i + 2][2], e1 = d[i][3] + d[i + 2][3];
        const float other = __shfl_xor_sync(0xffffffffu, (g & 1) ? e0 : e1, 4);
        if (q == (g >> 1)) pkt_st128(hp_pub + 8 * i, with_bit((g & 1) ? other : e0, cd), with_bit(sq, cd >> 1), __float_as_uint((g & 1) ? e1 : other), tag);
      }
    }
    CT(5);
    if (tid == 0) mbar_arrive(BAR(B_KEY));
    delay_clk<HOP1_DELAY>();
    float m_bf, sd, inv_sd, r_bf;
    uint4* key_pub = &p.s->key[((lane & 7) * 16 + grp) * 2];
    uint4* cand_pub = &p.s->cand[grp * 256 + eps * 32 + q];
    uint32_t trow_inv = 0xFFFFu - (uint32_t)row_of(grp * 128 + 32 * (warp >> 1) + 8 * (g >> 1) + 4 * (warp & 1) + (q & 2) + (g & 1));
    {
      uint4 u[4];
#pragma unroll
      for (int i = 0; i < 4; i++) u[i] = pkt_ld128(hp_poll + (i & 1) * 128 + (i >> 1) * 8);
      const float wsum = SM_(float, OFF_WSUM);
      pin(key_pub); pin(cand_pub); pin(trow_inv);
      uint32_t n = 0;
      while (true) {
        bool ok[4];
#pragma unroll
        for (int i = 0; i < 4; i++) ok[i] = u[i].w == tag && pair_code(u[i].x, u[i].y) == cd;
        const bool all = __all_sync(0xffffffffu, ok[0] && ok[1] && ok[2] && ok[3]);
        if (all || ++n > SPIN_LIMIT) break;
#pragma unroll
        for (int i = 0; i < 4; i++) pkt_ld128_if(u[i], hp_poll + (i & 1) * 128 + (i >> 1) * 8, !ok[i]);
      }
      CT(6);
      float a[3], b[3];
      a[0] = __uint_as_float(u[0].x & ~1u) + __uint_as_float(u[1].x & ~1u); b[0] = __uint_as_float(u[2].x & ~1u) + __uint_as_float(u[3].x & ~1u);
      a[1] = __uint_as_float(u[0].y & ~1u) + __uint_as_float(u[1].y & ~1u); b[1] = __uint_as_float(u[2].y & ~1u) + __uint_as_float(u[3].y & ~1u);
      a[2] = __uint_as_float(u[0].z) + __uint_as_float(u[1].z); b[2] = __uint_as_float(u[2].z) + __uint_as_float(u[3].z);
#pragma unroll
      for (int i = 0; i < 3; i++) {
        a[i] = ((q & 2) ? b[i] : a[i]) + __shfl_xor_sync(0xffffffffu, (q & 2) ? a[i] : b[i], 2);
        a[i] += __shfl_xor_sync(0xffffffffu, a[i], 1);
      }
      const float mu = a[0] * (1.f / 1024.f);
      m_bf = bf16r(mu);
      sd = ln_sd(a[1] * (1.f / 1024.f) - mu * mu);
      inv_sd = rcp_fast(sd);
      r_bf = bf16r((a[2] - m_bf * wsum) * inv_sd);
    }
    {
      const uint32_t u = __float_as_uint(r_bf);
      const uint32_t ord = (u & 0x80000000u) ? ~u : (u | 0x80000000u);
      const uint32_t key = (ord & 0xFFFF0000u) | trow_inv;
      const uint32_t wk = __reduce_max_sync(0xffffffffu, key);
      if (key == wk) SM_(uint2, OFF_WKEY + warp * 8) = make_uint2(wk, (__float_as_uint(m_bf) >> 16) | __float_as_uint(sd));
      const uint32_t wmask = __ballot_sync(0xffffffffu, key == wk);
      const bool hi = (wmask & 0xCCCCCCCCu) != 0;
      uint32_t c[16];
#pragma unroll
      for (int ks = 0; ks < 8; ks++) { c[2 * ks] = hi ? h[ks][1] : h[ks][0]; c[2 * ks + 1] = hi ? h[ks][3] : h[ks][2]; }
      bar_sync(NB_BOTH, 256);
      const uint2 km = SM_(uint2, OFF_WKEY + (lane & 7) * 8);
      const uint32_t bk = __reduce_max_sync(0xffffffffu, km.x);
      if (wk == bk) {
        if ((wmask >> (lane & 28)) & 15) {
#pragma unroll
          for (int ks = 0; ks < 8; ks++) pkt_st128(cand_pub + ks * 4, c[2 * ks], tag, c[2 * ks + 1], tag);
        }
      } else if (eps == 0) {
        const uint32_t kx = __shfl_sync(0xffffffffu, km.x, warp ^ 1), ms = __shfl_sync(0xffffffffu, km.y, warp ^ 1);
        if (kx == bk && lane < 8) pkt_st128(key_pub, bk, tag, ms, tag);
      }
      CT(7);
    }
    {
      const float ih = bf16r(inv_sd);
      const uint32_t nm = pack_bf16(-m_bf, -m_bf), iv = pack_bf16(ih, inv_sd - ih);
      const uint32_t nm_o = __shfl_xor_sync(0xffffffffu, nm, 2), iv_o = __shfl_xor_sync(0xffffffffu, iv, 2);
      const uint32_t nm2[2] = {(q & 2) ? nm_o : nm, (q & 2) ? nm : nm_o}, iv2[2] = {(q & 2) ? iv_o : iv, (q & 2) ? iv : iv_o};
      const uint32_t hi2[2] = {__byte_perm(iv2[0], 0, 0x1010), __byte_perm(iv2[1], 0, 0x1010)}, lo2[2] = {__byte_perm(iv2[0], 0, 0x3232), __byte_perm(iv2[1], 0, 0x3232)};
      const uint32_t oa = sb + OFF_OUT + (warp * 16 + (lane & 15)) * 128;
#pragma unroll
      for (int ks = 0; ks < 8; ks++) {
        uint32_t o[4];
#pragma unroll
        for (int i = 0; i < 4; i++) {
          const uint32_t dd = badd2(h[ks][i], nm2[i & 1]);
          o[i] = badd2(h[ks][i], bfma2(dd, hi2[i & 1], bmul2(dd, lo2[i & 1])));
        }
        stsm_x4(oa + (ks >> 2) * 16384 + (((2 * (ks & 3) + (lane >> 4)) ^ (lane & 7)) << 4), o[0], o[1], o[2], o[3]);
      }
      staged(B_OUT);
    }
    CT(8);
    uint32_t df[16][4];
    auto load_df = [&]() {
      const int frow = (lane & 7) + ((lane >> 4) << 3), hi = (lane >> 3) & 1;
      const uint32_t base = sb + down_off(warp >> 1) + (warp & 1) * 8192 + frow * 128;
#pragma unroll
      for (int mt = 0; mt < 8; mt++) {
#pragma unroll
        for (int ks = 0; ks < 2; ks++)
          ldsm_x4_t(base + (mt >> 2) * 4096 + ks * 2048 + (((2 * (mt & 3) + hi) ^ (lane & 7)) << 4),
                    df[2 * mt + ks][0], df[2 * mt + ks][1], df[2 * mt + ks][2], df[2 * mt + ks][3]);
      }
    };
    if (moe) {
      mbar_wait(BAR(B_GU), 0);
      load_wf_rest();
      mbar_wait(BAR(B_DN), 0);
      load_df();
    }
    uint4* y_pub = &p.s->ypart[cid * 256 + tid];
    uint32_t xs_ad = sb + OFF_XSEL + (8 * (g >> 2) + 4 * w + (g & 3)) * 32 + q * 8, gp_ad = sb + OFF_GP + (wi * 8 + g) * 16 + w * 8 + (q >> 1) * 4;
    pin(y_pub); pin(xs_ad); pin(gp_ad);
    mbar_wait(BAR(B_XS), 0);
    CT(9);
    if (moe) {
      float gd[8][4] = {};
      uint2 bx[4];
#pragma unroll
      for (int r = 0; r < 4; r++) bx[r] = smem_at<uint2>(xs_ad + r * 512);
#pragma unroll
      for (int r = 0; r < 4; r++) {
#pragma unroll
        for (int i = 0; i < 8; i++) mma16816(gd[i], wf[8 * r + i][0], wf[8 * r + i][1], wf[8 * r + i][2], wf[8 * r + i][3], bx[r].x, bx[r].y);
      }
      const float gs = sel4(q, gd[0][0] + gd[1][1], gd[2][0] + gd[3][1], gd[4][0] + gd[5][1], gd[6][0] + gd[7][1]);
      const float us = sel4(q, gd[0][2] + gd[1][3], gd[2][2] + gd[3][3], gd[4][2] + gd[5][3], gd[6][2] + gd[7][3]);
      float v = ((q & 2) ? us : gs) + __shfl_xor_sync(0xffffffffu, (q & 2) ? gs : us, 2);
      v += __shfl_xor_sync(0xffffffffu, v, 1);
      smem_at<float>(gp_ad) = v;
      CT(10);
      bar_sync(NB_BOTH, 256);
      uint32_t bq[4];
      {
        const float4 p0 = SM_(float4, OFF_GP + lane * 16);
        const float gt = bf16r(p0.x + p0.z), up = bf16r(p0.y + p0.w);
        const float act = bf16r(gt * sigmoid_fast(gt)) * up;
        const uint32_t pr = pack_bf16(act, __shfl_down_sync(0xffffffffu, act, 1));
#pragma unroll
        for (int i = 0; i < 4; i++) bq[i] = __shfl_sync(0xffffffffu, pr, 8 * i + 2 * q);
      }
      CT(11);
      float yd[8][4] = {};
#pragma unroll
      for (int ks = 0; ks < 2; ks++) {
#pragma unroll
        for (int mt = 0; mt < 8; mt++) mma16816(yd[mt], df[2 * mt + ks][0], df[2 * mt + ks][1], df[2 * mt + ks][2], df[2 * mt + ks][3], bq[2 * ks], bq[2 * ks + 1]);
      }
      pkt_st128(y_pub, with_bit(sel4(q, yd[0][0], yd[2][0], yd[4][0], yd[6][0]), cd), with_bit(sel4(q, yd[0][2], yd[2][2], yd[4][2], yd[6][2]), cd >> 1),
                with_bit(sel4(q, yd[1][0], yd[3][0], yd[5][0], yd[7][0]), cd), with_bit(sel4(q, yd[1][2], yd[3][2], yd[5][2], yd[7][2]), cd >> 1));
    } else {
      const long long tw = clock64();
      while (clock64() - tw < IDLE_WAIT_CLK) __nanosleep(100);
    }
    CT(12);
    const uint32_t kv = SM_(uint32_t, OFF_KV);
    const int tsel = (int)(~kv & 2047u);
    const float r_sel = __uint_as_float((kv & 0x80000000u) ? (kv & 0x7FFF0000u) : (~kv & 0xFFFF0000u));
    const float sig = bf16r(sigmoid_fast(r_sel));
    const int pfin = 2 * cid + (tid & 1);
    const int col_fin = (pfin >> 5) * 128 + (pfin & 3) * 32 + ((pfin & 31) >> 2) + 8 * ((tid >> 1) & 3);
    const int sel_off = (col_fin >> 4) * 32 + ((col_fin & 7) >> 1) * 8 + ((col_fin >> 3) & 1) * 4 + (col_fin & 1) * 2;
    const float hn_fin = __uint_as_float((uint32_t)SM_(uint16_t, OFF_XSEL + sel_off) << 16), h_fin = __uint_as_float((uint32_t)SM_(uint16_t, OFF_HSEL + sel_off) << 16);
    bf16* out_fin = p.out + (size_t)tsel * 1024 + col_fin;
    {
      const uint4* src = &p.s->ypart[(16 + (tid >> 1)) * 256 + pfin];
      pin(src); pin(out_fin);
      uint4 v = make_uint4(0, 0, 0, 0);
      if (warp < 7) {
        delay_clk<HOP3_DELAY>();
        uint32_t n = 0;
        bool ok = false;
        do {
          pkt_ld128_if(v, src, !ok);
          ok = pair_code(v.x, v.y) == cd && pair_code(v.z, v.w) == cd;
        } while (!__all_sync(0xffffffffu, ok) && ++n < SPIN_LIMIT);
      }
      CT(13);
      const float y0 = __uint_as_float(v.x & ~1u), y1 = __uint_as_float(v.y & ~1u), y2 = __uint_as_float(v.z & ~1u), y3 = __uint_as_float(v.w & ~1u);
      const float a0 = ((lane & 2) ? y1 : y0) + __shfl_xor_sync(0xffffffffu, (lane & 2) ? y0 : y1, 2);
      const float a1 = ((lane & 2) ? y3 : y2) + __shfl_xor_sync(0xffffffffu, (lane & 2) ? y2 : y3, 2);
      float b = ((lane & 4) ? a1 : a0) + __shfl_xor_sync(0xffffffffu, (lane & 4) ? a0 : a1, 4);
      b += __shfl_xor_sync(0xffffffffu, b, 8);
      b += __shfl_xor_sync(0xffffffffu, b, 16);
      if (lane < 8) SM_(float, OFF_FIN + lane * 32 + warp * 4) = b;
    }
    bar_sync(NB_BOTH, 256);
    if (tid < 8) {
      const float4 y0 = SM_(float4, OFF_FIN + tid * 32), y1 = SM_(float4, OFF_FIN + tid * 32 + 16);
      const float y = ((y0.x + y0.y) + (y0.z + y0.w)) + ((y1.x + y1.y) + y1.z);
      *out_fin = __float2bfloat16_rn(h_fin + bf16r(hn_fin + bf16r(bf16r(y) * sig)));
      if (cid == 0 && tid == 0) st_relaxed32(&p.s->epoch, tag);
    }
    CT(14);
  }
}

__global__ void __launch_bounds__(384, 1) occupancy_probe_kernel() {}

typedef CUresult (*EncodeFn)(CUtensorMap*, CUtensorMapDataType, cuuint32_t, void*, const cuuint64_t*, const cuuint64_t*, const cuuint32_t*, const cuuint32_t*,
                             CUtensorMapInterleave, CUtensorMapSwizzle, CUtensorMapL2promotion, CUtensorMapFloatOOBfill);

static void make_tm(EncodeFn enc, CUtensorMap* tm, const void* ptr, uint64_t rows, uint64_t cols, uint32_t brows, uint32_t bcols, CUtensorMapSwizzle sw,
                    CUtensorMapL2promotion promo = CU_TENSOR_MAP_L2_PROMOTION_L2_128B) {
  cuuint64_t dims[2] = {cols, rows};
  cuuint64_t strides[1] = {cols * 2};
  cuuint32_t box[2] = {bcols, brows};
  cuuint32_t es[2] = {1, 1};
  enc(tm, CU_TENSOR_MAP_DATA_TYPE_BFLOAT16, 2, const_cast<void*>(ptr), dims, strides, box, es, CU_TENSOR_MAP_INTERLEAVE_NONE, sw,
      promo, CU_TENSOR_MAP_FLOAT_OOB_FILL_NONE);
}

static void make_tm_rows(EncodeFn enc, CUtensorMap* tm, const void* ptr, uint64_t cols, uint32_t brows, uint32_t bcols, CUtensorMapSwizzle sw,
                         CUtensorMapL2promotion promo = CU_TENSOR_MAP_L2_PROMOTION_L2_128B) {
  cuuint64_t dims[4] = {cols, 2, 2, 512};
  cuuint64_t strides[3] = {row_of(1) * cols * 2, row_of(2) * cols * 2, row_of(4) * cols * 2};
  cuuint32_t box[4] = {bcols, 2, 2, brows / 4};
  cuuint32_t es[4] = {1, 1, 1, 1};
  enc(tm, CU_TENSOR_MAP_DATA_TYPE_BFLOAT16, 4, const_cast<void*>(ptr), dims, strides, box, es, CU_TENSOR_MAP_INTERLEAVE_NONE, sw, promo,
      CU_TENSOR_MAP_FLOAT_OOB_FILL_NONE);
}

extern "C" void kernel_launch(void* const* d_in, const int* in_sizes, int n_in, void* d_out, int out_size) {
  (void)in_sizes; (void)n_in; (void)out_size;
  static EncodeFn enc = nullptr;
  static void* abT = nullptr;
  static int map = 0;
  if (!enc) {
    void* fn = nullptr; cudaDriverEntryPointQueryResult st;
    cudaGetDriverEntryPoint("cuTensorMapEncodeTiled", &fn, cudaEnableDefault, &st);
    enc = (EncodeFn)fn;
    cudaGetSymbolAddress(&abT, g_scratch);
    cudaFuncSetAttribute(fnet_moe_kernel<0>, cudaFuncAttributeMaxDynamicSharedMemorySize, SMEM_TOTAL);
    cudaFuncSetAttribute(fnet_moe_kernel<1>, cudaFuncAttributeMaxDynamicSharedMemorySize, SMEM_TOTAL);
    cudaFuncSetAttribute(occupancy_probe_kernel, cudaFuncAttributeMaxDynamicSharedMemorySize, SMEM_TOTAL);
    cudaFuncSetAttribute(occupancy_probe_kernel, cudaFuncAttributeNonPortableClusterSizeAllowed, 1);
    auto max_clusters = [&](int size) {
      cudaLaunchConfig_t cfg = {};
      cfg.gridDim = dim3(128); cfg.blockDim = dim3(384); cfg.dynamicSmemBytes = SMEM_TOTAL;
      cudaLaunchAttribute at[1];
      at[0].id = cudaLaunchAttributeClusterDimension; at[0].val.clusterDim.x = size; at[0].val.clusterDim.y = 1; at[0].val.clusterDim.z = 1;
      cfg.attrs = at; cfg.numAttrs = 1;
      int ncl = 0;
      return cudaOccupancyMaxActiveClusters(&ncl, occupancy_probe_kernel, &cfg) == cudaSuccess ? ncl : 0;
    };
    int dev = 0, sms = 0;
    cudaGetDevice(&dev);
    cudaDeviceGetAttribute(&sms, cudaDevAttrMultiProcessorCount, dev);
    map = (sms == 132 && max_clusters(2) == 66 && max_clusters(16) == 7) ? 0 : 1;
    (void)cudaGetLastError();
  }
  Params p;
  const bf16* x = (const bf16*)d_in[0];
  make_tm(enc, &p.tmD0, d_in[3], 1024, 1024, 128, 64, CU_TENSOR_MAP_SWIZZLE_128B);
  make_tm(enc, &p.tmD1, d_in[4], 1024, 1024, 128, 64, CU_TENSOR_MAP_SWIZZLE_128B);
  make_tm(enc, &p.tmX, x, 2048, 1024, map == 0 ? NX0 : 256, 64, CU_TENSOR_MAP_SWIZZLE_128B);
  make_tm_rows(enc, &p.tmXr, x, 1024, 64, 64, CU_TENSOR_MAP_SWIZZLE_128B);
  make_tm(enc, &p.tmAbS, abT, 2048, 2048, 64, 64, CU_TENSOR_MAP_SWIZZLE_128B);
  make_tm(enc, &p.tmAbL, abT, 2048, 2048, 128, 64, CU_TENSOR_MAP_SWIZZLE_128B);
  make_tm_rows(enc, &p.tmW0, d_in[1], 2048, 128, 64, CU_TENSOR_MAP_SWIZZLE_128B);
  make_tm_rows(enc, &p.tmW1, d_in[2], 2048, 128, 64, CU_TENSOR_MAP_SWIZZLE_128B);
  {
    cuuint64_t dims[5] = {1024, 2, 4, 2, 2048};
    cuuint64_t strides[4] = {row_of(1) * 2048, row_of(8) * 2048, row_of(2) * 2048, 2048};
    cuuint32_t box[5] = {64, 2, 4, 2, 1};
    cuuint32_t es[5] = {1, 1, 1, 1, 1};
    enc(&p.tmOut, CU_TENSOR_MAP_DATA_TYPE_BFLOAT16, 5, d_out, dims, strides, box, es, CU_TENSOR_MAP_INTERLEAVE_NONE, CU_TENSOR_MAP_SWIZZLE_128B,
        CU_TENSOR_MAP_L2_PROMOTION_NONE, CU_TENSOR_MAP_FLOAT_OOB_FILL_NONE);
  }
  {
    cuuint64_t dims[5] = {1024, 2, 4, 2, 8};
    cuuint64_t strides[4] = {2048, 4 * 2048, 2 * 2048, 256 * 2048};
    cuuint32_t box[5] = {64, 2, 4, 2, 8};
    cuuint32_t es[5] = {1, 1, 1, 1, 1};
    enc(&p.tmXh, CU_TENSOR_MAP_DATA_TYPE_BFLOAT16, 5, const_cast<bf16*>(x) + 240 * 1024, dims, strides, box, es, CU_TENSOR_MAP_INTERLEAVE_NONE,
        CU_TENSOR_MAP_SWIZZLE_128B, CU_TENSOR_MAP_L2_PROMOTION_L2_128B, CU_TENSOR_MAP_FLOAT_OOB_FILL_NONE);
  }
  make_tm(enc, &p.tmAbM, abT, 2048, 2048, 128, 16, CU_TENSOR_MAP_SWIZZLE_32B, CU_TENSOR_MAP_L2_PROMOTION_NONE);
  make_tm_rows(enc, &p.tmWM0, d_in[1], 2048, 128, 16, CU_TENSOR_MAP_SWIZZLE_32B);
  make_tm_rows(enc, &p.tmWM1, d_in[2], 2048, 128, 16, CU_TENSOR_MAP_SWIZZLE_32B);
  make_tm(enc, &p.tmG, d_in[7], 1024, 3584, 128, 32, CU_TENSOR_MAP_SWIZZLE_64B);
  make_tm(enc, &p.tmU, d_in[8], 1024, 3584, 128, 32, CU_TENSOR_MAP_SWIZZLE_64B);
  make_tm(enc, &p.tmDn, d_in[9], 3584, 1024, 32, 64, CU_TENSOR_MAP_SWIZZLE_128B);
  p.x = x; p.Dre = (const bf16*)d_in[3]; p.Dim = (const bf16*)d_in[4];
  p.wr = (const bf16*)d_in[6]; p.wdown = (const bf16*)d_in[9]; p.wgate = (const bf16*)d_in[7]; p.wup = (const bf16*)d_in[8];
  p.out = (bf16*)d_out; p.s = (Scratch*)abT;
  if (map == 1) fnet_moe_kernel<1><<<128, 384, SMEM_TOTAL>>>(p);
  else fnet_moe_kernel<0><<<132, 384, SMEM_TOTAL>>>(p);
}
```

```cpp
#include <cuda.h>
#include <cuda_runtime.h>
#include <cuda_bf16.h>
#include <stdint.h>
#include <type_traits>

typedef __nv_bfloat16 bf16;

constexpr int NX0 = 240;
constexpr int REG_C = 232, REG_P = 40;
__host__ __device__ constexpr int row_of(int p) { return (p & 1) * 1024 + ((p >> 1) & 1) * 512 + (p >> 2); }
__host__ __device__ constexpr int group_of(int row) { return (row & 511) >> 5; }
__device__ __forceinline__ int sigma_of(int tau, int r) { return r + (r >= tau); }
__device__ __forceinline__ int kblock(int tau, int j) {
  const int i = j - 4, c = (i * 37) >> 8;
  return j < 4 ? tau * 4 + j : sigma_of(tau, i - 7 * c) * 4 + c;
}
constexpr int GAP1 = 300, GAP2 = 600;
constexpr int HL_N = 2;
constexpr int AUX_DELAY = 250;
constexpr int PF_K0 = 8, PF_N0 = 2, PF_K1 = 24;
constexpr int WPF_K0 = 12, WPF_N = 10;
constexpr int WPF2_K = 44, WPF2_N = 4;
constexpr int GU_K = 46;
constexpr int PUB_K1 = 21;
constexpr int NREG_H = 5;
constexpr int MR_K0 = 29, MR_P = 6;
constexpr int MINI_PF_K = 35, MINI_LOAD_K = 43, MINI_K = 42;
constexpr int RESET_K = 37;
constexpr int SEND_FIRST = 2;
constexpr int GATHER_NS = 400;
constexpr int MOE_PACE_CLK = 300;
constexpr int OUT_PACE_CLK = 70;
constexpr int HOP1_DELAY = 150, HOP3_DELAY = 450;
constexpr int SPEC_MIN = 10;
constexpr int IDLE_WAIT_CLK = 1200;
__host__ __device__ constexpr int mr_k(int h) { return MR_K0 + MR_P * (h >> 1) + 2 * (h & 1); }
constexpr int A_BYTES = 128 * 64 * 2;
constexpr int B_BYTES = 256 * 64 * 2;
constexpr int ST_BYTES = A_BYTES + B_BYTES;
constexpr int OFF_XCH = 4 * ST_BYTES;
constexpr int OFF_BAR = OFF_XCH + 32768;
constexpr int OFF_WR = OFF_BAR + 384;
constexpr int OFF_RS = OFF_WR + 384;
constexpr int OFF_PUB = OFF_RS + 640;
constexpr int OFF_MISC = OFF_PUB + 768;
constexpr int SMEM_TOTAL = OFF_MISC + 256;
constexpr int OFF_WSUM = OFF_MISC, OFF_TAG = OFF_MISC + 4;
constexpr int OFF_SEEN = OFF_MISC + 8;
constexpr int OFF_KV = OFF_MISC + 12;
constexpr int OFF_WKEY = OFF_MISC + 32;
constexpr int OFF_MINI = OFF_XCH + 16384;
constexpr int OFF_EXA = OFF_XCH;
constexpr int OFF_EXB = OFF_XCH + 4096;
__host__ __device__ constexpr int chunk_off(int c, int w) { return (c == 1 ? 3 * ST_BYTES : c == 2 ? OFF_XCH : OFF_XCH + 16384) + w * 8192; }
__host__ __device__ constexpr int late_off(int i) { return i < 4 ? i * 16384 : 2 * ST_BYTES + A_BYTES + (i - 4) * 16384; }
__host__ __device__ constexpr int round_off(int h) { return h < NREG_H + 2 ? OFF_XCH + (h & 1) * 16384 : late_off(h - NREG_H - 2); }
__host__ __device__ constexpr int down_off(int i) { return late_off(6 - NREG_H + i); }
constexpr int OFF_PEER = ST_BYTES + A_BYTES;
constexpr int OFF_OUT = 3 * ST_BYTES + A_BYTES;
constexpr int OFF_XSEL = OFF_PEER;
constexpr int OFF_HSEL = OFF_PEER + 4096;
constexpr int OFF_GP = OFF_PEER + 8192;
constexpr int OFF_FIN = OFF_PEER + 9216;
__device__ __forceinline__ int slot_of(int k) { return k & 3; }
__device__ __forceinline__ int use_of(int k) { return k >> 2; }
enum { B_FULL = 0, B_EMPTY = 4, B_EPI = 8, B_STD = 12, B_EPI0B = 16, B_LATE = 17, B_STAT = 18, B_XCH = 19, B_MR = 20  , B_GU = 22,
       B_DN = 23, B_AUX = 24  , B_OUT = 26, B_KEY = 27, B_XS = 28, B_MINI = 29, B_PUB1 = 30, B_COUNT = 31 };
enum { NB_TURN0 = 1, NB_TURN1 = 2, NB_WG0 = 3, NB_BOTH = 5, NB_AUX = 6 };

struct Scratch {
  bf16 abT[2048 * 2048];
  uint2 xstat[2048];
  uint2 dsum[2048];
  uint4 abflag[16 * 8 * 2];
  uint4 hflag[16 * 2];
  uint4 hstat[16 * 8 * 128];
  uint4 cand[16 * 256];
  uint4 key[8 * 16 * 2];
  uint4 ypart[128 * 256];
  uint32_t epoch;
};
__device__ __align__(1024) Scratch g_scratch;

struct Params {
  Scratch* s; bf16* out;
  const bf16* x; const bf16* Dre; const bf16* Dim; const bf16* wr; const bf16* wdown; const bf16* wgate; const bf16* wup;
  CUtensorMap tmX, tmD0, tmD1, tmXr, tmAbS, tmAbL, tmW0, tmW1, tmOut, tmG, tmU, tmDn, tmXh, tmAbM, tmWM0, tmWM1;
};

#define SPIN_LIMIT (1u << 14)
#define MBAR_LIMIT (1u << 10)
__device__ __forceinline__ uint32_t smem_u32(const void* p) { return (uint32_t)__cvta_generic_to_shared(p); }
__device__ __forceinline__ void mbar_init(uint32_t bar, uint32_t cnt) { asm volatile("mbarrier.init.shared::cta.b64 [%0], %1;" :: "r"(bar), "r"(cnt) : "memory"); }
__device__ __forceinline__ void mbar_expect_tx(uint32_t bar, uint32_t bytes) { asm volatile("mbarrier.arrive.expect_tx.shared::cta.b64 _, [%0], %1;" :: "r"(bar), "r"(bytes) : "memory"); }
__device__ __forceinline__ void mbar_arrive(uint32_t bar) { asm volatile("mbarrier.arrive.shared::cta.b64 _, [%0];" :: "r"(bar) : "memory"); }
__device__ __forceinline__ void mbar_wait(uint32_t bar, uint32_t parity) {
  uint32_t ok, n = 0;
  do {
    asm volatile("{\n.reg .pred p;\nmbarrier.try_wait.parity.shared::cta.b64 p, [%1], %2;\nselp.u32 %0, 1, 0, p;\n}\n" : "=r"(ok) : "r"(bar), "r"(parity) : "memory");
  } while (!ok && ++n < MBAR_LIMIT);
}
__device__ __forceinline__ void mbar_wait_cluster(uint32_t bar, uint32_t parity) {
  uint32_t ok, n = 0;
  do {
    asm volatile("{\n.reg .pred p;\nmbarrier.try_wait.parity.acquire.cluster.shared::cta.b64 p, [%1], %2;\nselp.u32 %0, 1, 0, p;\n}\n" : "=r"(ok) : "r"(bar), "r"(parity) : "memory");
  } while (!ok && ++n < MBAR_LIMIT);
}
__device__ __forceinline__ void tma_load_2d(uint32_t dst, const CUtensorMap* tm, uint32_t bar, int c0, int c1) {
  asm volatile("cp.async.bulk.tensor.2d.shared::cluster.global.mbarrier::complete_tx::bytes [%0], [%1, {%3, %4}], [%2];"
    :: "r"(dst), "l"(tm), "r"(bar), "r"(c0), "r"(c1) : "memory");
}
__device__ __forceinline__ void tma_load_2d_hint(uint32_t dst, const CUtensorMap* tm, uint32_t bar, int c0, int c1, uint64_t pol) {
  asm volatile("cp.async.bulk.tensor.2d.shared::cluster.global.mbarrier::complete_tx::bytes.L2::cache_hint [%0], [%1, {%3, %4}], [%2], %5;"
    :: "r"(dst), "l"(tm), "r"(bar), "r"(c0), "r"(c1), "l"(pol) : "memory");
}
__device__ __forceinline__ uint64_t policy_evict_first() { uint64_t p; asm volatile("createpolicy.fractional.L2::evict_first.b64 %0, 1.0;" : "=l"(p)); return p; }
__device__ __forceinline__ void tma_store_2d(const CUtensorMap* tm, uint32_t src, int c0, int c1) {
  asm volatile("cp.async.bulk.tensor.2d.global.shared::cta.bulk_group [%0, {%2, %3}], [%1];" :: "l"(tm), "r"(src), "r"(c0), "r"(c1) : "memory");
}
__device__ __forceinline__ void tma_prefetch_2d(const CUtensorMap* tm, int c0, int c1) {
  asm volatile("cp.async.bulk.prefetch.tensor.2d.L2.global.tile [%0, {%1, %2}];" :: "l"(tm), "r"(c0), "r"(c1) : "memory");
}
__device__ __forceinline__ void bulk_load(uint32_t dst, const void* src, uint32_t bytes, uint32_t bar) {
  asm volatile("cp.async.bulk.shared::cluster.global.mbarrier::complete_tx::bytes [%0], [%1], %2, [%3];" :: "r"(dst), "l"(src), "r"(bytes), "r"(bar) : "memory");
}
__device__ __forceinline__ void bulk_commit() { asm volatile("cp.async.bulk.commit_group;" ::: "memory"); }
__device__ __forceinline__ void bulk_wait_all() { asm volatile("cp.async.bulk.wait_group 0;" ::: "memory"); }
__device__ __forceinline__ void bulk_wait_release() {
  bulk_wait_all();
  asm volatile("fence.proxy.async.global;" ::: "memory");
  asm volatile("fence.acq_rel.gpu;" ::: "memory");
}
__device__ __forceinline__ void fence_async_smem() { asm volatile("fence.proxy.async.shared::cta;" ::: "memory"); }
__device__ __forceinline__ void wgmma_fence() { asm volatile("wgmma.fence.sync.aligned;" ::: "memory"); }
__device__ __forceinline__ void wgmma_commit() { asm volatile("wgmma.commit_group.sync.aligned;" ::: "memory"); }
__device__ __forceinline__ void wgmma_wait0() { asm volatile("wgmma.wait_group.sync.aligned 0;" ::: "memory"); }
__device__ __forceinline__ void bar_sync(int id, int n) { asm volatile("bar.sync %0, %1;" :: "r"(id), "r"(n) : "memory"); }
__device__ __forceinline__ void bar_arrive(int id, int n) { asm volatile("bar.arrive %0, %1;" :: "r"(id), "r"(n) : "memory"); }
template<int R> __device__ __forceinline__ void reg_inc() { asm volatile("setmaxnreg.inc.sync.aligned.u32 %0;" :: "n"(R)); }
template<int R> __device__ __forceinline__ void reg_dec() { asm volatile("setmaxnreg.dec.sync.aligned.u32 %0;" :: "n"(R)); }
__device__ __forceinline__ bool elect_one() {
  uint32_t p;
  asm volatile("{\n.reg .pred q;\nelect.sync _|q, 0xffffffff;\nselp.u32 %0, 1, 0, q;\n}\n" : "=r"(p));
  return p != 0;
}
__device__ __forceinline__ uint32_t mapa(uint32_t addr, uint32_t cta) { uint32_t r; asm volatile("mapa.shared::cluster.u32 %0, %1, %2;" : "=r"(r) : "r"(addr), "r"(cta)); return r; }
__device__ __forceinline__ void st_async_v4(uint32_t addr, uint32_t bar, uint32_t a, uint32_t b, uint32_t c, uint32_t d) {
  asm volatile("st.async.weak.shared::cluster.mbarrier::complete_tx::bytes.v4.b32 [%0], {%2, %3, %4, %5}, [%1];" :: "r"(addr), "r"(bar), "r"(a), "r"(b), "r"(c), "r"(d) : "memory");
}
__device__ __forceinline__ void stsm_x4(uint32_t addr, uint32_t a, uint32_t b, uint32_t c, uint32_t d) {
  asm volatile("stmatrix.sync.aligned.m8n8.x4.shared.b16 [%0], {%1, %2, %3, %4};" :: "r"(addr), "r"(a), "r"(b), "r"(c), "r"(d));
}
__device__ __forceinline__ uint4 lds128_v(uint32_t addr) { uint4 v; asm volatile("ld.shared.v4.b32 {%0, %1, %2, %3}, [%4];" : "=r"(v.x), "=r"(v.y), "=r"(v.z), "=r"(v.w) : "r"(addr)); return v; }
extern __shared__ __align__(1024) uint8_t smem_raw[];
template<class T> __device__ __forceinline__ T& smem_at(uint32_t addr) { return *reinterpret_cast<T*>(__cvta_shared_to_generic(addr)); }
#define SM_(T, off) smem_at<T>(sb + (off))
__device__ __forceinline__ uint4 ldg_nc128(const void* p) { uint4 v; asm volatile("ld.global.nc.v4.b32 {%0, %1, %2, %3}, [%4];" : "=r"(v.x), "=r"(v.y), "=r"(v.z), "=r"(v.w) : "l"(p)); return v; }
__device__ __forceinline__ void pkt_st128(void* p, uint32_t a, uint32_t b, uint32_t c, uint32_t d) {
  asm volatile("{\n.reg .b128 v;\n.reg .b64 lo, hi;\nmov.b64 lo, {%1, %2};\nmov.b64 hi, {%3, %4};\nmov.b128 v, {lo, hi};\nst.relaxed.gpu.global.b128 [%0], v;\n}\n"
    :: "l"(p), "r"(a), "r"(b), "r"(c), "r"(d) : "memory");
}
__device__ __forceinline__ uint4 pkt_ld128(const void* p) {
  uint4 r;
  asm volatile("{\n.reg .b128 v;\n.reg .b64 lo, hi;\nld.relaxed.gpu.global.b128 v, [%4];\nmov.b128 {lo, hi}, v;\nmov.b64 {%0, %1}, lo;\nmov.b64 {%2, %3}, hi;\n}\n"
    : "=r"(r.x), "=r"(r.y), "=r"(r.z), "=r"(r.w) : "l"(p) : "memory");
  return r;
}
__device__ __forceinline__ void pkt_ld128_if(uint4& r, const void* p, bool cond) {
  asm volatile("{\n.reg .pred q;\n.reg .b64 lo, hi;\nsetp.ne.b32 q, %5, 0;\nmov.b64 lo, {%0, %1};\nmov.b64 hi, {%2, %3};\n"
               "@q ld.relaxed.gpu.global.v2.b64 {lo, hi}, [%4];\nmov.b64 {%0, %1}, lo;\nmov.b64 {%2, %3}, hi;\n}\n"
    : "+r"(r.x), "+r"(r.y), "+r"(r.z), "+r"(r.w) : "l"(p), "r"((uint32_t)cond) : "memory");
}
__device__ __forceinline__ void pkt_st64(void* p, uint32_t a, uint32_t b) {
  asm volatile("{\n.reg .b64 v;\nmov.b64 v, {%1, %2};\nst.relaxed.gpu.global.b64 [%0], v;\n}\n" :: "l"(p), "r"(a), "r"(b) : "memory");
}
__device__ __forceinline__ uint2 pkt_ld64(const void* p) {
  uint2 r;
  asm volatile("{\n.reg .b64 v;\nld.relaxed.gpu.global.b64 v, [%2];\nmov.b64 {%0, %1}, v;\n}\n" : "=r"(r.x), "=r"(r.y) : "l"(p) : "memory");
  return r;
}
__device__ __forceinline__ uint32_t ld_relaxed32(const void* p) { uint32_t v; asm volatile("ld.relaxed.gpu.global.b32 %0, [%1];" : "=r"(v) : "l"(p) : "memory"); return v; }
__device__ __forceinline__ uint32_t ld_acquire32(const void* p) { uint32_t v; asm volatile("ld.acquire.gpu.global.b32 %0, [%1];" : "=r"(v) : "l"(p) : "memory"); return v; }
__device__ __forceinline__ void st_relaxed32(void* p, uint32_t v) { asm volatile("st.relaxed.gpu.global.b32 [%0], %1;" :: "l"(p), "r"(v) : "memory"); }
__device__ __forceinline__ uint32_t code_of(uint32_t tag) { return tag % 3u + 1u; }
__device__ __forceinline__ uint32_t with_bit(float v, uint32_t bit) { return (__float_as_uint(v) & ~1u) | (bit & 1u); }
__device__ __forceinline__ uint32_t pair_code(uint32_t a, uint32_t b) { return (a & 1u) | ((b & 1u) << 1); }
__device__ __forceinline__ uint32_t pack_bf16(float lo, float hi) { uint32_t r; asm("cvt.rn.bf16x2.f32 %0, %1, %2;" : "=r"(r) : "f"(hi), "f"(lo)); return r; }
__device__ __forceinline__ float bf_lo(uint32_t v) { return __uint_as_float(v << 16); }
__device__ __forceinline__ float bf_hi(uint32_t v) { return __uint_as_float(v & 0xFFFF0000u); }
__device__ __forceinline__ float bf16r(float x) { return __uint_as_float(pack_bf16(0.f, x)); }
__device__ __forceinline__ uint32_t badd2(uint32_t a, uint32_t b) { uint32_t r; asm("add.rn.bf16x2 %0, %1, %2;" : "=r"(r) : "r"(a), "r"(b)); return r; }
__device__ __forceinline__ uint32_t bmul2(uint32_t a, uint32_t b) { uint32_t r; asm("mul.rn.bf16x2 %0, %1, %2;" : "=r"(r) : "r"(a), "r"(b)); return r; }
__device__ __forceinline__ float warp_sum(float v) {
#pragma unroll
  for (int o = 16; o > 0; o >>= 1) v += __shfl_xor_sync(0xffffffffu, v, o);
  return v;
}
__device__ __forceinline__ uint64_t make_desc(uint32_t addr) {
  return (uint64_t)((addr & 0x3FFFF) >> 4) | ((uint64_t)1 << 16) | ((uint64_t)64 << 32) | ((uint64_t)1 << 62);
}
__device__ __forceinline__ uint64_t make_desc_noswz(uint32_t addr) {
  return (uint64_t)((addr & 0x3FFFF) >> 4) | ((uint64_t)8 << 16) | ((uint64_t)16 << 32);
}
__device__ __forceinline__ uint64_t make_desc_32b(uint32_t addr) {
  return (uint64_t)((addr & 0x3FFFF) >> 4) | ((uint64_t)1 << 16) | ((uint64_t)16 << 32) | ((uint64_t)3 << 62);
}
__device__ __forceinline__ void wgmma_n256(float (&d)[128], uint64_t da, uint64_t db, int scale_d) {
  asm volatile("{\n.reg .pred p;\nsetp.ne.b32 p, %130, 0;\n"
    "wgmma.mma_async.sync.aligned.m64n256k16.f32.bf16.bf16 "
    "{%0, %1, %2, %3, %4, %5, %6, %7, %8, %9, %10, %11, %12, %13, %14, %15, %16, %17, %18, %19, %20, %21, %22, %23, %24, %25, %26, %27, %28, %29, %30, %31, "
    "%32, %33, %34, %35, %36, %37, %38, %39, %40, %41, %42, %43, %44, %45, %46, %47, %48, %49, %50, %51, %52, %53, %54, %55, %56, %57, %58, %59, %60, %61, %62, %63, "
    "%64, %65, %66, %67, %68, %69, %70, %71, %72, %73, %74, %75, %76, %77, %78, %79, %80, %81, %82, %83, %84, %85, %86, %87, %88, %89, %90, %91, %92, %93, %94, %95, "
    "%96, %97, %98, %99, %100, %101, %102, %103, %104, %105, %106, %107, %108, %109, %110, %111, %112, %113, %114, %115, %116, %117, %118, %119, %120, %121, %122, %123, %124, %125, %126, %127}, "
    "%128, %129, p, 1, 1, 0, 0;\n}\n"
    : "+f"(d[0]), "+f"(d[1]), "+f"(d[2]), "+f"(d[3]), "+f"(d[4]), "+f"(d[5]), "+f"(d[6]), "+f"(d[7]),
      "+f"(d[8]), "+f"(d[9]), "+f"(d[10]), "+f"(d[11]), "+f"(d[12]), "+f"(d[13]), "+f"(d[14]), "+f"(d[15]),
      "+f"(d[16]), "+f"(d[17]), "+f"(d[18]), "+f"(d[19]), "+f"(d[20]), "+f"(d[21]), "+f"(d[22]), "+f"(d[23]),
      "+f"(d[24]), "+f"(d[25]), "+f"(d[26]), "+f"(d[27]), "+f"(d[28]), "+f"(d[29]), "+f"(d[30]), "+f"(d[31]),
      "+f"(d[32]), "+f"(d[33]), "+f"(d[34]), "+f"(d[35]), "+f"(d[36]), "+f"(d[37]), "+f"(d[38]), "+f"(d[39]),
      "+f"(d[40]), "+f"(d[41]), "+f"(d[42]), "+f"(d[43]), "+f"(d[44]), "+f"(d[45]), "+f"(d[46]), "+f"(d[47]),
      "+f"(d[48]), "+f"(d[49]), "+f"(d[50]), "+f"(d[51]), "+f"(d[52]), "+f"(d[53]), "+f"(d[54]), "+f"(d[55]),
      "+f"(d[56]), "+f"(d[57]), "+f"(d[58]), "+f"(d[59]), "+f"(d[60]), "+f"(d[61]), "+f"(d[62]), "+f"(d[63]),
      "+f"(d[64]), "+f"(d[65]), "+f"(d[66]), "+f"(d[67]), "+f"(d[68]), "+f"(d[69]), "+f"(d[70]), "+f"(d[71]),
      "+f"(d[72]), "+f"(d[73]), "+f"(d[74]), "+f"(d[75]), "+f"(d[76]), "+f"(d[77]), "+f"(d[78]), "+f"(d[79]),
      "+f"(d[80]), "+f"(d[81]), "+f"(d[82]), "+f"(d[83]), "+f"(d[84]), "+f"(d[85]), "+f"(d[86]), "+f"(d[87]),
      "+f"(d[88]), "+f"(d[89]), "+f"(d[90]), "+f"(d[91]), "+f"(d[92]), "+f"(d[93]), "+f"(d[94]), "+f"(d[95]),
      "+f"(d[96]), "+f"(d[97]), "+f"(d[98]), "+f"(d[99]), "+f"(d[100]), "+f"(d[101]), "+f"(d[102]), "+f"(d[103]),
      "+f"(d[104]), "+f"(d[105]), "+f"(d[106]), "+f"(d[107]), "+f"(d[108]), "+f"(d[109]), "+f"(d[110]), "+f"(d[111]),
      "+f"(d[112]), "+f"(d[113]), "+f"(d[114]), "+f"(d[115]), "+f"(d[116]), "+f"(d[117]), "+f"(d[118]), "+f"(d[119]),
      "+f"(d[120]), "+f"(d[121]), "+f"(d[122]), "+f"(d[123]), "+f"(d[124]), "+f"(d[125]), "+f"(d[126]), "+f"(d[127])
    : "l"(da), "l"(db), "r"(scale_d));
}
__device__ __forceinline__ void wgmma_g1(float (&d)[128], uint64_t da, uint64_t db, int scale_d) { wgmma_n256(d, da, db, scale_d); }
__device__ __forceinline__ void wgmma_g1(float (&d)[120], uint64_t da, uint64_t db, int scale_d) {
  asm volatile("{\n.reg .pred p;\nsetp.ne.b32 p, %122, 0;\n"
    "wgmma.mma_async.sync.aligned.m64n240k16.f32.bf16.bf16 "
    "{%0, %1, %2, %3, %4, %5, %6, %7, %8, %9, %10, %11, %12, %13, %14, %15, %16, %17, %18, %19, %20, %21, %22, %23, %24, %25, %26, %27, %28, %29, %30, %31, %32, %33, %34, %35, %36, %37, %38, %39, %40, %41, %42, %43, %44, %45, %46, %47, %48, %49, %50, %51, %52, %53, %54, %55, %56, %57, %58, %59, %60, %61, %62, %63, %64, %65, %66, %67, %68, %69, %70, %71, %72, %73, %74, %75, %76, %77, %78, %79, %80, %81, %82, %83, %84, %85, %86, %87, %88, %89, %90, %91, %92, %93, %94, %95, %96, %97, %98, %99, %100, %101, %102, %103, %104, %105, %106, %107, %108, %109, %110, %111, %112, %113, %114, %115, %116, %117, %118, %119}, "
    "%120, %121, p, 1, 1, 0, 0;\n}\n"
    : "+f"(d[0]), "+f"(d[1]), "+f"(d[2]), "+f"(d[3]), "+f"(d[4]), "+f"(d[5]), "+f"(d[6]), "+f"(d[7]), "+f"(d[8]), "+f"(d[9]), "+f"(d[10]), "+f"(d[11]), "+f"(d[12]), "+f"(d[13]), "+f"(d[14]), "+f"(d[15]), "+f"(d[16]), "+f"(d[17]), "+f"(d[18]), "+f"(d[19]), "+f"(d[20]), "+f"(d[21]), "+f"(d[22]), "+f"(d[23]), "+f"(d[24]), "+f"(d[25]), "+f"(d[26]), "+f"(d[27]), "+f"(d[28]), "+f"(d[29]), "+f"(d[30]), "+f"(d[31]), "+f"(d[32]), "+f"(d[33]), "+f"(d[34]), "+f"(d[35]), "+f"(d[36]), "+f"(d[37]), "+f"(d[38]), "+f"(d[39]), "+f"(d[40]), "+f"(d[41]), "+f"(d[42]), "+f"(d[43]), "+f"(d[44]), "+f"(d[45]), "+f"(d[46]), "+f"(d[47]), "+f"(d[48]), "+f"(d[49]), "+f"(d[50]), "+f"(d[51]), "+f"(d[52]), "+f"(d[53]), "+f"(d[54]), "+f"(d[55]), "+f"(d[56]), "+f"(d[57]), "+f"(d[58]), "+f"(d[59]), "+f"(d[60]), "+f"(d[61]), "+f"(d[62]), "+f"(d[63]), "+f"(d[64]), "+f"(d[65]), "+f"(d[66]), "+f"(d[67]), "+f"(d[68]), "+f"(d[69]), "+f"(d[70]), "+f"(d[71]), "+f"(d[72]), "+f"(d[73]), "+f"(d[74]), "+f"(d[75]), "+f"(d[76]), "+f"(d[77]), "+f"(d[78]), "+f"(d[79]), "+f"(d[80]), "+f"(d[81]), "+f"(d[82]), "+f"(d[83]), "+f"(d[84]), "+f"(d[85]), "+f"(d[86]), "+f"(d[87]), "+f"(d[88]), "+f"(d[89]), "+f"(d[90]), "+f"(d[91]), "+f"(d[92]), "+f"(d[93]), "+f"(d[94]), "+f"(d[95]), "+f"(d[96]), "+f"(d[97]), "+f"(d[98]), "+f"(d[99]), "+f"(d[100]), "+f"(d[101]), "+f"(d[102]), "+f"(d[103]), "+f"(d[104]), "+f"(d[105]), "+f"(d[106]), "+f"(d[107]), "+f"(d[108]), "+f"(d[109]), "+f"(d[110]), "+f"(d[111]), "+f"(d[112]), "+f"(d[113]), "+f"(d[114]), "+f"(d[115]), "+f"(d[116]), "+f"(d[117]), "+f"(d[118]), "+f"(d[119])
    : "l"(da), "l"(db), "r"(scale_d));
}
__device__ __forceinline__ void wgmma_g1(float (&d)[32], uint64_t da, uint64_t db, int scale_d) {
  asm volatile("{\n.reg .pred p;\nsetp.ne.b32 p, %34, 0;\n"
    "wgmma.mma_async.sync.aligned.m64n64k16.f32.bf16.bf16 "
    "{%0, %1, %2, %3, %4, %5, %6, %7, %8, %9, %10, %11, %12, %13, %14, %15, %16, %17, %18, %19, %20, %21, %22, %23, %24, %25, %26, %27, %28, %29, %30, %31}, "
    "%32, %33, p, 1, 1, 0, 0;\n}\n"
    : "+f"(d[0]), "+f"(d[1]), "+f"(d[2]), "+f"(d[3]), "+f"(d[4]), "+f"(d[5]), "+f"(d[6]), "+f"(d[7]), "+f"(d[8]), "+f"(d[9]), "+f"(d[10]), "+f"(d[11]), "+f"(d[12]), "+f"(d[13]), "+f"(d[14]), "+f"(d[15]), "+f"(d[16]), "+f"(d[17]), "+f"(d[18]), "+f"(d[19]), "+f"(d[20]), "+f"(d[21]), "+f"(d[22]), "+f"(d[23]), "+f"(d[24]), "+f"(d[25]), "+f"(d[26]), "+f"(d[27]), "+f"(d[28]), "+f"(d[29]), "+f"(d[30]), "+f"(d[31])
    : "l"(da), "l"(db), "r"(scale_d));
}
__device__ __forceinline__ void wgmma_g1(float (&d)[88], uint64_t da, uint64_t db, int scale_d) {
  asm volatile("{\n.reg .pred p;\nsetp.ne.b32 p, %90, 0;\n"
    "wgmma.mma_async.sync.aligned.m64n176k16.f32.bf16.bf16 "
    "{%0, %1, %2, %3, %4, %5, %6, %7, %8, %9, %10, %11, %12, %13, %14, %15, %16, %17, %18, %19, %20, %21, %22, %23, %24, %25, %26, %27, %28, %29, %30, %31, %32, %33, %34, %35, %36, %37, %38, %39, %40, %41, %42, %43, %44, %45, %46, %47, %48, %49, %50, %51, %52, %53, %54, %55, %56, %57, %58, %59, %60, %61, %62, %63, %64, %65, %66, %67, %68, %69, %70, %71, %72, %73, %74, %75, %76, %77, %78, %79, %80, %81, %82, %83, %84, %85, %86, %87}, "
    "%88, %89, p, 1, 1, 0, 0;\n}\n"
    : "+f"(d[0]), "+f"(d[1]), "+f"(d[2]), "+f"(d[3]), "+f"(d[4]), "+f"(d[5]), "+f"(d[6]), "+f"(d[7]), "+f"(d[8]), "+f"(d[9]), "+f"(d[10]), "+f"(d[11]), "+f"(d[12]), "+f"(d[13]), "+f"(d[14]), "+f"(d[15]), "+f"(d[16]), "+f"(d[17]), "+f"(d[18]), "+f"(d[19]), "+f"(d[20]), "+f"(d[21]), "+f"(d[22]), "+f"(d[23]), "+f"(d[24]), "+f"(d[25]), "+f"(d[26]), "+f"(d[27]), "+f"(d[28]), "+f"(d[29]), "+f"(d[30]), "+f"(d[31]), "+f"(d[32]), "+f"(d[33]), "+f"(d[34]), "+f"(d[35]), "+f"(d[36]), "+f"(d[37]), "+f"(d[38]), "+f"(d[39]), "+f"(d[40]), "+f"(d[41]), "+f"(d[42]), "+f"(d[43]), "+f"(d[44]), "+f"(d[45]), "+f"(d[46]), "+f"(d[47]), "+f"(d[48]), "+f"(d[49]), "+f"(d[50]), "+f"(d[51]), "+f"(d[52]), "+f"(d[53]), "+f"(d[54]), "+f"(d[55]), "+f"(d[56]), "+f"(d[57]), "+f"(d[58]), "+f"(d[59]), "+f"(d[60]), "+f"(d[61]), "+f"(d[62]), "+f"(d[63]), "+f"(d[64]), "+f"(d[65]), "+f"(d[66]), "+f"(d[67]), "+f"(d[68]), "+f"(d[69]), "+f"(d[70]), "+f"(d[71]), "+f"(d[72]), "+f"(d[73]), "+f"(d[74]), "+f"(d[75]), "+f"(d[76]), "+f"(d[77]), "+f"(d[78]), "+f"(d[79]), "+f"(d[80]), "+f"(d[81]), "+f"(d[82]), "+f"(d[83]), "+f"(d[84]), "+f"(d[85]), "+f"(d[86]), "+f"(d[87])
    : "l"(da), "l"(db), "r"(scale_d));
}
__device__ __forceinline__ void wgmma_g1(float (&d)[96], uint64_t da, uint64_t db, int scale_d) {
  asm volatile("{\n.reg .pred p;\nsetp.ne.b32 p, %98, 0;\n"
    "wgmma.mma_async.sync.aligned.m64n192k16.f32.bf16.bf16 "
    "{%0, %1, %2, %3, %4, %5, %6, %7, %8, %9, %10, %11, %12, %13, %14, %15, %16, %17, %18, %19, %20, %21, %22, %23, %24, %25, %26, %27, %28, %29, %30, %31, %32, %33, %34, %35, %36, %37, %38, %39, %40, %41, %42, %43, %44, %45, %46, %47, %48, %49, %50, %51, %52, %53, %54, %55, %56, %57, %58, %59, %60, %61, %62, %63, %64, %65, %66, %67, %68, %69, %70, %71, %72, %73, %74, %75, %76, %77, %78, %79, %80, %81, %82, %83, %84, %85, %86, %87, %88, %89, %90, %91, %92, %93, %94, %95}, "
    "%96, %97, p, 1, 1, 0, 0;\n}\n"
    : "+f"(d[0]), "+f"(d[1]), "+f"(d[2]), "+f"(d[3]), "+f"(d[4]), "+f"(d[5]), "+f"(d[6]), "+f"(d[7]), "+f"(d[8]), "+f"(d[9]), "+f"(d[10]), "+f"(d[11]), "+f"(d[12]), "+f"(d[13]), "+f"(d[14]), "+f"(d[15]), "+f"(d[16]), "+f"(d[17]), "+f"(d[18]), "+f"(d[19]), "+f"(d[20]), "+f"(d[21]), "+f"(d[22]), "+f"(d[23]), "+f"(d[24]), "+f"(d[25]), "+f"(d[26]), "+f"(d[27]), "+f"(d[28]), "+f"(d[29]), "+f"(d[30]), "+f"(d[31]), "+f"(d[32]), "+f"(d[33]), "+f"(d[34]), "+f"(d[35]), "+f"(d[36]), "+f"(d[37]), "+f"(d[38]), "+f"(d[39]), "+f"(d[40]), "+f"(d[41]), "+f"(d[42]), "+f"(d[43]), "+f"(d[44]), "+f"(d[45]), "+f"(d[46]), "+f"(d[47]), "+f"(d[48]), "+f"(d[49]), "+f"(d[50]), "+f"(d[51]), "+f"(d[52]), "+f"(d[53]), "+f"(d[54]), "+f"(d[55]), "+f"(d[56]), "+f"(d[57]), "+f"(d[58]), "+f"(d[59]), "+f"(d[60]), "+f"(d[61]), "+f"(d[62]), "+f"(d[63]), "+f"(d[64]), "+f"(d[65]), "+f"(d[66]), "+f"(d[67]), "+f"(d[68]), "+f"(d[69]), "+f"(d[70]), "+f"(d[71]), "+f"(d[72]), "+f"(d[73]), "+f"(d[74]), "+f"(d[75]), "+f"(d[76]), "+f"(d[77]), "+f"(d[78]), "+f"(d[79]), "+f"(d[80]), "+f"(d[81]), "+f"(d[82]), "+f"(d[83]), "+f"(d[84]), "+f"(d[85]), "+f"(d[86]), "+f"(d[87]), "+f"(d[88]), "+f"(d[89]), "+f"(d[90]), "+f"(d[91]), "+f"(d[92]), "+f"(d[93]), "+f"(d[94]), "+f"(d[95])
    : "l"(da), "l"(db), "r"(scale_d));
}
__device__ __forceinline__ void wgmma_n256_rs(float (&d)[128], uint32_t a0, uint32_t a1, uint32_t a2, uint32_t a3, uint64_t db, int scale_d) {
  asm volatile("{\n.reg .pred p;\nsetp.ne.b32 p, %133, 0;\n"
    "wgmma.mma_async.sync.aligned.m64n256k16.f32.bf16.bf16 "
    "{%0, %1, %2, %3, %4, %5, %6, %7, %8, %9, %10, %11, %12, %13, %14, %15, %16, %17, %18, %19, %20, %21, %22, %23, %24, %25, %26, %27, %28, %29, %30, %31, "
    "%32, %33, %34, %35, %36, %37, %38, %39, %40, %41, %42, %43, %44, %45, %46, %47, %48, %49, %50, %51, %52, %53, %54, %55, %56, %57, %58, %59, %60, %61, %62, %63, "
    "%64, %65, %66, %67, %68, %69, %70, %71, %72, %73, %74, %75, %76, %77, %78, %79, %80, %81, %82, %83, %84, %85, %86, %87, %88, %89, %90, %91, %92, %93, %94, %95, "
    "%96, %97, %98, %99, %100, %101, %102, %103, %104, %105, %106, %107, %108, %109, %110, %111, %112, %113, %114, %115, %116, %117, %118, %119, %120, %121, %122, %123, %124, %125, %126, %127}, "
    "{%128, %129, %130, %131}, %132, p, 1, 1, 0;\n}\n"
    : "+f"(d[0]), "+f"(d[1]), "+f"(d[2]), "+f"(d[3]), "+f"(d[4]), "+f"(d[5]), "+f"(d[6]), "+f"(d[7]),
      "+f"(d[8]), "+f"(d[9]), "+f"(d[10]), "+f"(d[11]), "+f"(d[12]), "+f"(d[13]), "+f"(d[14]), "+f"(d[15]),
      "+f"(d[16]), "+f"(d[17]), "+f"(d[18]), "+f"(d[19]), "+f"(d[20]), "+f"(d[21]), "+f"(d[22]), "+f"(d[23]),
      "+f"(d[24]), "+f"(d[25]), "+f"(d[26]), "+f"(d[27]), "+f"(d[28]), "+f"(d[29]), "+f"(d[30]), "+f"(d[31]),
      "+f"(d[32]), "+f"(d[33]), "+f"(d[34]), "+f"(d[35]), "+f"(d[36]), "+f"(d[37]), "+f"(d[38]), "+f"(d[39]),
      "+f"(d[40]), "+f"(d[41]), "+f"(d[42]), "+f"(d[43]), "+f"(d[44]), "+f"(d[45]), "+f"(d[46]), "+f"(d[47]),
      "+f"(d[48]), "+f"(d[49]), "+f"(d[50]), "+f"(d[51]), "+f"(d[52]), "+f"(d[53]), "+f"(d[54]), "+f"(d[55]),
      "+f"(d[56]), "+f"(d[57]), "+f"(d[58]), "+f"(d[59]), "+f"(d[60]), "+f"(d[61]), "+f"(d[62]), "+f"(d[63]),
      "+f"(d[64]), "+f"(d[65]), "+f"(d[66]), "+f"(d[67]), "+f"(d[68]), "+f"(d[69]), "+f"(d[70]), "+f"(d[71]),
      "+f"(d[72]), "+f"(d[73]), "+f"(d[74]), "+f"(d[75]), "+f"(d[76]), "+f"(d[77]), "+f"(d[78]), "+f"(d[79]),
      "+f"(d[80]), "+f"(d[81]), "+f"(d[82]), "+f"(d[83]), "+f"(d[84]), "+f"(d[85]), "+f"(d[86]), "+f"(d[87]),
      "+f"(d[88]), "+f"(d[89]), "+f"(d[90]), "+f"(d[91]), "+f"(d[92]), "+f"(d[93]), "+f"(d[94]), "+f"(d[95]),
      "+f"(d[96]), "+f"(d[97]), "+f"(d[98]), "+f"(d[99]), "+f"(d[100]), "+f"(d[101]), "+f"(d[102]), "+f"(d[103]),
      "+f"(d[104]), "+f"(d[105]), "+f"(d[106]), "+f"(d[107]), "+f"(d[108]), "+f"(d[109]), "+f"(d[110]), "+f"(d[111]),
      "+f"(d[112]), "+f"(d[113]), "+f"(d[114]), "+f"(d[115]), "+f"(d[116]), "+f"(d[117]), "+f"(d[118]), "+f"(d[119]),
      "+f"(d[120]), "+f"(d[121]), "+f"(d[122]), "+f"(d[123]), "+f"(d[124]), "+f"(d[125]), "+f"(d[126]), "+f"(d[127])
    : "r"(a0), "r"(a1), "r"(a2), "r"(a3), "l"(db), "r"(scale_d));
}
__device__ __forceinline__ void wgmma_n128(float (&d)[64], uint64_t da, uint64_t db, int scale_d = 1) {
  asm volatile("{\n.reg .pred p;\nsetp.ne.b32 p, %66, 0;\n"
    "wgmma.mma_async.sync.aligned.m64n128k16.f32.bf16.bf16 "
    "{%0, %1, %2, %3, %4, %5, %6, %7, %8, %9, %10, %11, %12, %13, %14, %15, %16, %17, %18, %19, %20, %21, %22, %23, %24, %25, %26, %27, %28, %29, %30, %31, %32, %33, %34, %35, %36, %37, %38, %39, %40, %41, %42, %43, %44, %45, %46, %47, %48, %49, %50, %51, %52, %53, %54, %55, %56, %57, %58, %59, %60, %61, %62, %63}, "
    "%64, %65, p, 1, 1, 0, 0;\n}\n"
    : "+f"(d[0]), "+f"(d[1]), "+f"(d[2]), "+f"(d[3]), "+f"(d[4]), "+f"(d[5]), "+f"(d[6]), "+f"(d[7]), "+f"(d[8]), "+f"(d[9]), "+f"(d[10]), "+f"(d[11]), "+f"(d[12]), "+f"(d[13]), "+f"(d[14]), "+f"(d[15]), "+f"(d[16]), "+f"(d[17]), "+f"(d[18]), "+f"(d[19]), "+f"(d[20]), "+f"(d[21]), "+f"(d[22]), "+f"(d[23]), "+f"(d[24]), "+f"(d[25]), "+f"(d[26]), "+f"(d[27]), "+f"(d[28]), "+f"(d[29]), "+f"(d[30]), "+f"(d[31]), "+f"(d[32]), "+f"(d[33]), "+f"(d[34]), "+f"(d[35]), "+f"(d[36]), "+f"(d[37]), "+f"(d[38]), "+f"(d[39]), "+f"(d[40]), "+f"(d[41]), "+f"(d[42]), "+f"(d[43]), "+f"(d[44]), "+f"(d[45]), "+f"(d[46]), "+f"(d[47]), "+f"(d[48]), "+f"(d[49]), "+f"(d[50]), "+f"(d[51]), "+f"(d[52]), "+f"(d[53]), "+f"(d[54]), "+f"(d[55]), "+f"(d[56]), "+f"(d[57]), "+f"(d[58]), "+f"(d[59]), "+f"(d[60]), "+f"(d[61]), "+f"(d[62]), "+f"(d[63])
    : "l"(da), "l"(db), "r"(scale_d));
}
template<int N> __device__ __forceinline__ void fence_acc(float (&d)[N]) {
#pragma unroll
  for (int i = 0; i < N; i++) asm volatile("" : "+f"(d[i]) :: "memory");
}

template<int N, int I = 0, class F> __device__ __forceinline__ void static_for(F&& f) {
  if constexpr (I < N) { f(std::integral_constant<int, I>()); static_for<N, I + 1>(f); }
}

__device__ __forceinline__ void ldsm_x4_t(uint32_t addr, uint32_t& a, uint32_t& b, uint32_t& c, uint32_t& d) {
  asm volatile("ldmatrix.sync.aligned.m8n8.x4.trans.shared.b16 {%0, %1, %2, %3}, [%4];" : "=r"(a), "=r"(b), "=r"(c), "=r"(d) : "r"(addr));
}
__device__ __forceinline__ void sts128(uint32_t addr, uint32_t a, uint32_t b, uint32_t c, uint32_t d) {
  asm volatile("st.shared.v4.b32 [%0], {%1, %2, %3, %4};" :: "r"(addr), "r"(a), "r"(b), "r"(c), "r"(d));
}
__device__ __forceinline__ void mma16816(float (&c)[4], uint32_t a0, uint32_t a1, uint32_t a2, uint32_t a3, uint32_t b0, uint32_t b1) {
  asm volatile("mma.sync.aligned.m16n8k16.row.col.f32.bf16.bf16.f32 {%0, %1, %2, %3}, {%4, %5, %6, %7}, {%8, %9}, {%0, %1, %2, %3};"
      : "+f"(c[0]), "+f"(c[1]), "+f"(c[2]), "+f"(c[3]) : "r"(a0), "r"(a1), "r"(a2), "r"(a3), "r"(b0), "r"(b1));
}
__device__ __forceinline__ void mma1688(float (&c)[4], uint32_t a0, uint32_t a1, uint32_t b0) {
  asm volatile("mma.sync.aligned.m16n8k8.row.col.f32.bf16.bf16.f32 {%0, %1, %2, %3}, {%4, %5}, {%6}, {%0, %1, %2, %3};"
      : "+f"(c[0]), "+f"(c[1]), "+f"(c[2]), "+f"(c[3]) : "r"(a0), "r"(a1), "r"(b0));
}
__device__ __forceinline__ uint32_t keep_awake() {
  float c0;
  asm volatile("{\n.reg .f32 c1, c2, c3, z;\n.reg .b32 a;\nmov.b32 a, 0;\nmov.f32 z, 0f00000000;\n"
               "mma.sync.aligned.m16n8k8.row.col.f32.bf16.bf16.f32 {%0, c1, c2, c3}, {a, a}, {a}, {z, z, z, z};\n}\n" : "=f"(c0));
  return __float_as_uint(c0);
}
__device__ __forceinline__ void pin(uint32_t& v) { asm volatile("shfl.sync.bfly.b32 %0, %0, 0, 0x1f, 0xffffffff;" : "+r"(v)); }
template<class T> __device__ __forceinline__ void pin(T*& v) {
  uint32_t lo = (uint32_t)(uint64_t)v, hi = (uint32_t)((uint64_t)v >> 32);
  pin(lo); pin(hi);
  v = (T*)(((uint64_t)hi << 32) | lo);
}
__device__ __forceinline__ float sel4(int q, float a, float b, float c, float d) {
  float r;
  asm("{\n.reg .pred p, o;\n.reg .f32 x, y;\n.reg .b32 t;\nand.b32 t, %1, 1;\nsetp.ne.b32 p, t, 0;\nsetp.gt.s32 o, %1, 1;\n"
      "selp.f32 x, %3, %2, p;\nselp.f32 y, %5, %4, p;\nselp.f32 %0, y, x, o;\n}\n" : "=f"(r) : "r"(q), "f"(a), "f"(b), "f"(c), "f"(d));
  return r;
}
__device__ __forceinline__ uint32_t bfma2(uint32_t a, uint32_t b, uint32_t c) { uint32_t r; asm("fma.rn.bf16x2 %0, %1, %2, %3;" : "=r"(r) : "r"(a), "r"(b), "r"(c)); return r; }
__device__ __forceinline__ void tma_load_5d(uint32_t dst, const CUtensorMap* tm, uint32_t bar, int c0, int c4) {
  asm volatile("cp.async.bulk.tensor.5d.shared::cluster.global.mbarrier::complete_tx::bytes [%0], [%1, {%3, %4, %4, %4, %5}], [%2];"
    :: "r"(dst), "l"(tm), "r"(bar), "r"(c0), "r"(0), "r"(c4) : "memory");
}
__device__ __forceinline__ void tma_load_4d(uint32_t dst, const CUtensorMap* tm, uint32_t bar, int c0, int c3) {
  asm volatile("cp.async.bulk.tensor.4d.shared::cluster.global.mbarrier::complete_tx::bytes [%0], [%1, {%3, %4, %4, %5}], [%2];"
    :: "r"(dst), "l"(tm), "r"(bar), "r"(c0), "r"(0), "r"(c3) : "memory");
}
__device__ __forceinline__ void tma_load_4d_hint(uint32_t dst, const CUtensorMap* tm, uint32_t bar, int c0, int c3, uint64_t pol) {
  asm volatile("cp.async.bulk.tensor.4d.shared::cluster.global.mbarrier::complete_tx::bytes.L2::cache_hint [%0], [%1, {%3, %4, %4, %5}], [%2], %6;"
    :: "r"(dst), "l"(tm), "r"(bar), "r"(c0), "r"(0), "r"(c3), "l"(pol) : "memory");
}
__device__ __forceinline__ void tma_prefetch_4d(const CUtensorMap* tm, int c0, int c3) {
  asm volatile("cp.async.bulk.prefetch.tensor.4d.L2.global.tile [%0, {%1, %2, %2, %3}];" :: "l"(tm), "r"(c0), "r"(0), "r"(c3) : "memory");
}
__device__ __forceinline__ void tma_store_5d(const CUtensorMap* tm, uint32_t src, int c0, int c4) {
  asm volatile("cp.async.bulk.tensor.5d.global.shared::cta.bulk_group [%0, {%2, %3, %3, %3, %4}], [%1];" :: "l"(tm), "r"(src), "r"(c0), "r"(0), "r"(c4) : "memory");
}
__device__ __forceinline__ float rcp_fast(float x) { float r; asm("rcp.approx.ftz.f32 %0, %1;" : "=f"(r) : "f"(x)); return r; }
__device__ __forceinline__ float sigmoid_fast(float x) { float e; asm("ex2.approx.ftz.f32 %0, %1;" : "=f"(e) : "f"(x * -1.4426950408889634f)); return rcp_fast(1.f + e); }
__device__ __forceinline__ float sqrt_fast(float x) { float r; asm("sqrt.approx.ftz.f32 %0, %1;" : "=f"(r) : "f"(x)); return r; }
__device__ __forceinline__ float ln_sd(float var) { return bf16r(sqrt_fast(bf16r(bf16r(fmaxf(var, 0.f)) + 1e-5f))); }
__device__ __forceinline__ uint32_t norm2(uint32_t h, uint32_t neg_mean2, float inv_sd) {
  const uint32_t d = badd2(h, neg_mean2);
  return pack_bf16(bf_lo(d) * inv_sd, bf_hi(d) * inv_sd);
}
template<int N> __device__ __forceinline__ void delay_clk() {
  if constexpr (N > 0) { const uint32_t t0 = clock(); while ((uint32_t)clock() - t0 < N) {} }
}
__device__ __forceinline__ void put_xstat(uint32_t rs, uint32_t exb, int col, uint32_t mean_rstd, int m) {
  smem_at<uint16_t>(rs + ((col & 7) >> 1) * 144 + (col >> 3) * 4 + (col & 1) * 2) = (uint16_t)(mean_rstd ^ (m << 15));
  const uint32_t nm = (mean_rstd >> 16) ^ 0x8000u;
  smem_at<uint4>(exb + (col >> 3) * 256 + (col & 7) * 16) = make_uint4(nm | (nm << 16), nm, 0, 0);
  smem_at<uint4>(exb + (col >> 3) * 256 + 128 + (col & 7) * 16) = make_uint4(0, 0, 0, 0);
}
__device__ __forceinline__ void put_dsum(uint32_t exa, int e, float c) {
  const float hi = bf16r(c), mid = bf16r(c - hi), lo = bf16r((c - hi) - mid);
  smem_at<uint4>(exa + (e >> 3) * 256 + (e & 7) * 16) = make_uint4((__float_as_uint(hi) >> 16) | (__float_as_uint(mid) & 0xFFFF0000u), __float_as_uint(lo) >> 16, 0, 0);
  smem_at<uint4>(exa + (e >> 3) * 256 + 128 + (e & 7) * 16) = make_uint4(0, 0, 0, 0);
}
__host__ __device__ constexpr int min_c(int a, int b) { return a < b ? a : b; }
template<int V> using IC = std::integral_constant<int, V>;

#define CT(slot) do {} while (0)
#define PT(slot) do {} while (0)

template<int MAP>
__global__ void __cluster_dims__(2, 1, 1) __launch_bounds__(384, 1)
fnet_moe_kernel(const __grid_constant__ Params p) {
  constexpr int NX = MAP == 0 ? NX0 : 256;
  constexpr int G1_BYTES = A_BYTES + NX * 128;
  uint32_t sb;
  asm volatile("mov.u32 %0, %1;" : "=r"(sb) : "r"(smem_u32(smem_raw)));
  const int m = blockIdx.x & 1;
  int tau, eps;
  bool helper = false;
  if (MAP == 0) {
    uint32_t smid;
    asm volatile("mov.u32 %0, %%smid;" : "=r"(smid));
    const int c = smid >> 1, e7 = ((c - 32) * 37) >> 8;
    helper = c == 60 || c == 61;
    tau = c < 32 ? (c & 7) : (c < 60 ? c - 31 - 7 * e7 : 0);
    eps = c < 32 ? (c >> 3) : (c < 60 ? 4 + e7 : c - 58);
  } else {
    tau = (blockIdx.x >> 1) & 7; eps = blockIdx.x >> 4;
  }
  const int cid = tau * 16 + eps * 2 + m;
  const bool moe = tau > 0;
  auto BAR = [&](int i) { return sb + OFF_BAR + 8 * i; };
  const CUtensorMap* tmD = m ? &p.tmD1 : &p.tmD0;
  const uint64_t pol_ef = policy_evict_first();
#define LOAD_STREAM(d, tm, bar, c0, c1) tma_load_2d_hint(d, tm, bar, c0, c1, pol_ef)
#define LOAD_W(d, tm, bar, c0, grp) tma_load_4d_hint(d, tm, bar, c0, (grp) * 32, pol_ef)
  auto helper_load = [&](int k) {
    const uint32_t sa = sb + slot_of(k) * ST_BYTES, bar = BAR(B_FULL + slot_of(k));
    const CUtensorMap* tm = eps == 3 ? &p.tmD1 : &p.tmD0;
    tma_load_5d(sa, &p.tmXh, bar, (k & 15) * 64, 0);
    tma_load_2d(sa + A_BYTES, tm, bar, (k & 15) * 64, m * 512 + (k >> 4) * 256);
    tma_load_2d(sa + A_BYTES + 16384, tm, bar, (k & 15) * 64, m * 512 + (k >> 4) * 256 + 128);
  };
  if (threadIdx.x < 32 && elect_one()) {
    mbar_init(BAR(B_FULL), 1);
    asm volatile("fence.mbarrier_init.release.cluster;" ::: "memory");
    if (!helper) {
      tma_load_2d(sb + A_BYTES, &p.tmX, BAR(B_FULL), 0, tau * 256);
      tma_load_2d(sb, tmD, BAR(B_FULL), 0, eps * 128);
    }
    PT(52);
#pragma unroll
    for (int k = 1; k < 4; k++) mbar_init(BAR(B_FULL + k), 1);
    asm volatile("fence.mbarrier_init.release.cluster;" ::: "memory");
#pragma unroll
    for (int k = 0; k < 4; k++) mbar_expect_tx(BAR(B_FULL + k), helper ? ST_BYTES : G1_BYTES);
    if (!helper) {
#pragma unroll
      for (int k = 1; k < 4; k++) {
        tma_load_2d(sb + k * ST_BYTES + A_BYTES, &p.tmX, BAR(B_FULL + k), k * 64, tau * 256);
        LOAD_STREAM(sb + k * ST_BYTES, tmD, BAR(B_FULL + k), k * 64, eps * 128);
      }
    } else {
#pragma unroll 1
      for (int k = 0; k < 4; k++) helper_load(k);
    }
    PT(0);
  }
  __syncwarp();
  const int warp = __shfl_sync(0xffffffffu, threadIdx.x >> 5, 0);
  if (warp == 8) {
    if (elect_one()) {
#pragma unroll
      for (int b = B_EMPTY; b < B_COUNT; b++)
        mbar_init(BAR(b), b < B_EPI ? 2 : (b == B_EPI || b == B_EPI0B) ? 4 : (b < B_STD || b == B_OUT) ? 8 : (b == B_STAT || b == B_XS) ? 3 : 1);
      asm volatile("fence.mbarrier_init.release.cluster;" ::: "memory");
      mbar_expect_tx(BAR(B_XCH), 32768);
      SM_(uint32_t, OFF_SEEN) = 0;
    }
  }
  __syncthreads();

  if (warp >= 8) {
    reg_dec<REG_P>();
    asm volatile("barrier.cluster.arrive.relaxed.aligned;" ::: "memory");
    const int abrow = m * 1024 + eps * 128;
    const int f0 = (cid - 16) * 32;
    const CUtensorMap* tmWM = m ? &p.tmWM1 : &p.tmWM0;
    auto side_first = [&](int k) {
      if (NX < 256 && k == MINI_LOAD_K) {
        static_assert(NX == 256 || (mr_k(NREG_H) == MINI_LOAD_K && (NREG_H & 1) == 1), "second half of the staging buffer must be free");
        mbar_wait(BAR(B_STD + 3), 0);
        uint32_t n = 0;
        while (!((*(volatile uint32_t*)&SM_(uint32_t, OFF_SEEN) >> (4 * tau + 1)) & 1) && ++n < SPIN_LIMIT * 16) {}
        if (elect_one()) {
          mbar_expect_tx(BAR(B_MINI), 12288);
          tma_load_2d(sb + OFF_MINI, &p.tmAbM, BAR(B_MINI), tau * 256 + 240, abrow);
          LOAD_W(sb + OFF_MINI + 4096, tmWM, BAR(B_MINI), tau * 256 + 240, tau * 2 + m);
          LOAD_W(sb + OFF_MINI + 8192, tmWM, BAR(B_MINI), tau * 256 + 240, tau * 2 + 1 - m);
        }
      }
    };
    auto side = [&](int k) {
      if (NX < 256 && k == MINI_PF_K && elect_one()) tma_prefetch_4d(tmWM, tau * 256 + 240, tau * 64 + (eps & 1) * 32);
      if (k == WPF2_K && eps < WPF2_N && elect_one()) tma_prefetch_4d(m ? &p.tmW1 : &p.tmW0, kblock(tau, 31 - (eps >> 1)) * 64, tau * 64 + (eps & 1) * 32);
      if (!moe) return;
      const int i = k - MR_K0, r6 = i / MR_P, u = i - MR_P * r6, h = 2 * r6 + (u >> 1);
      if (i >= 0 && u < 4 && h < NREG_H) {
        if (h < 2) mbar_wait(BAR(B_STD + 2 + h), 0);
        if (elect_one()) {
          if (!(u & 1)) mbar_expect_tx(BAR(B_MR + (h & 1)), 16384);
          LOAD_STREAM(sb + OFF_XCH + u * 8192, (u & 1) ? &p.tmU : &p.tmG, BAR(B_MR + (h & 1)), f0, h * 128);
        }
      }
      if (k >= GU_K && k < GU_K + 2 && elect_one()) {
        static_assert(mr_k(NREG_H + 1) <= GU_K + 1 && MINI_K + 4 <= GU_K && GU_K < 47, "staging buffer must be free");
        LOAD_STREAM(sb + round_off(NREG_H + k - GU_K), &p.tmG, BAR(B_GU), f0, (NREG_H + k - GU_K) * 128);
        LOAD_STREAM(sb + round_off(NREG_H + k - GU_K) + 8192, &p.tmU, BAR(B_GU), f0, (NREG_H + k - GU_K) * 128);
      }
      if (k >= PF_K1 && !(k & 1) && elect_one()) {
        const int j = PF_N0 + ((k - PF_K1) >> 1);
        if (j < 8) tma_prefetch_2d(m ? &p.tmU : &p.tmG, f0, j * 128);
        else if (j < 12) asm volatile("cp.async.bulk.prefetch.L2.global [%0], %1;" :: "l"(p.wdown + (size_t)f0 * 1024 + (j - 8) * 8192), "r"(16384) : "memory");
      }
    };
    if (MAP == 0 && helper) {
      if (warp == 8) {
#pragma unroll 1
        for (int k = 4; k < 32; k++) {
          mbar_wait(BAR(B_EMPTY + slot_of(k)), (use_of(k) & 1) ^ 1);
          if (elect_one()) {
            mbar_expect_tx(BAR(B_FULL + slot_of(k)), ST_BYTES);
            helper_load(k);
            if (k == 12) mbar_arrive(BAR(B_LATE));
          }
        }
      } else {
        const int i0 = threadIdx.x - 288, lane = threadIdx.x & 31, col0 = (eps - 2) * 8 + m * 4;
        mbar_wait(BAR(B_LATE), 0);
        const uint32_t tag = ld_relaxed32(&p.s->epoch) + 1;
        if (i0 < 8) pkt_st128(&p.s->hflag[col0 * 2 + i0], 0, 0, 0, 0);
        SM_(uint32_t, OFF_TAG) = tag;
#pragma unroll 1
        for (int j0 = i0; j0 < 768; j0 += 384) {
          uint2 v[4]; uint32_t n = 0;
          while (true) {
#pragma unroll
            for (int z = 0; z < 4; z++) {
              const int j = j0 + 96 * z;
              v[z] = pkt_ld64(p.s->xstat + (j < 128 ? 256 * (j >> 4) + 240 + 2 * (j & 6) + ((j >> 2) & 2) + (j & 1)
                                          : j < 640 ? 2048 + col0 * 128 + j - 128 : (j - 640) * 16));
            }
            if (__all_sync(0xffffffffu, v[0].y == tag && v[1].y == tag && v[2].y == tag && v[3].y == tag) || ++n > SPIN_LIMIT) break;
            __nanosleep(300);
          }
#pragma unroll
          for (int z = 0; z < 4; z++) {
            const int j = j0 + 96 * z;
            if (j < 128) put_xstat(sb + OFF_RS, sb + OFF_XCH + 16384, j, v[z].x, eps - 2);
            else if (j < 640) put_dsum(sb + OFF_XCH, j - 128, __uint_as_float(v[z].x));
          }
        }
        fence_async_smem();
        __syncwarp();
        if (lane == 0) mbar_arrive(BAR(B_STAT));
      }
    } else if (warp == 8) {
      const CUtensorMap* tmW = m ? &p.tmW1 : &p.tmW0;
      const int gA = tau * 2 + m, gB = tau * 2 + 1 - m;
      auto wait_slot = [&](int k) {
        mbar_wait(BAR(B_EMPTY + slot_of(k)), (use_of(k) & 1) ^ 1);
        PT(64 + k);
      };
#pragma unroll 1
      for (int k = 4; k < 24; k++) {
        const int s = slot_of(k);
        const uint32_t sa = sb + s * ST_BYTES, sbb = sa + A_BYTES;
        const int kb = kblock(tau, k - 16);
        wait_slot(k);
        if (elect_one()) {
          mbar_expect_tx(BAR(B_FULL + s), k < 16 ? G1_BYTES : (k >> 1) == 9 ? B_BYTES : ST_BYTES);
          if (k < 16) {
            LOAD_STREAM(sa, tmD, BAR(B_FULL + s), k * 64, eps * 128);
            tma_load_2d(sbb, &p.tmX, BAR(B_FULL + s), k * 64, tau * 256);
          } else {
            LOAD_W(sbb, tmW, BAR(B_FULL + s), kb * 64, gA);
            LOAD_W(sbb + 16384, tmW, BAR(B_FULL + s), kb * 64, gB);
            if (k < 18) {
              tma_load_4d(sa, &p.tmXr, BAR(B_FULL + s), eps * 128, gA * 32 + s * 16);
              tma_load_4d(sa + 8192, &p.tmXr, BAR(B_FULL + s), eps * 128 + 64, gA * 32 + s * 16);
            }
          }
          if (k == PUB_K1) mbar_arrive(BAR(B_LATE));
          if (k >= WPF_K0 && k < WPF_K0 + WPF_N && (eps >> 1) == ((k - WPF_K0) & 3))
            tma_prefetch_4d(tmW, kblock(tau, k - WPF_K0) * 64, tau * 64 + (eps & 1) * 32);
          if (moe && k >= PF_K0 && k < PF_K0 + 2 * PF_N0 && !(k & 1)) tma_prefetch_2d(m ? &p.tmU : &p.tmG, f0, (k - PF_K0) * 64);
        }
      }
      uint32_t seen = 0;
#pragma unroll 1
      for (int k = 24; k < 48; k++) {
        const int s = slot_of(k);
        const uint32_t sa = sb + s * ST_BYTES, sbb = sa + A_BYTES;
        const int kb = kblock(tau, k - 16);
        const uint32_t need = (1u << kb) | ((kb & 3) == 3 ? 2u << (4 * tau) : 0u);
        wait_slot(k);
        side_first(k);
        if (elect_one()) {
          mbar_expect_tx(BAR(B_FULL + s), ST_BYTES);
          LOAD_W(sbb, tmW, BAR(B_FULL + s), kb * 64, gA);
          LOAD_W(sbb + 16384, tmW, BAR(B_FULL + s), kb * 64, gB);
        }
        uint32_t n = 0;
        while ((seen & need) != need && ++n < SPIN_LIMIT * 16) seen = *(volatile uint32_t*)&SM_(uint32_t, OFF_SEEN);
        if (elect_one()) tma_load_2d(sa, &p.tmAbL, BAR(B_FULL + s), kb * 64, abrow);
        side(k);
      }
      if (moe) {
        mbar_wait(BAR(B_EMPTY + 0), 1);
        if (elect_one()) { mbar_expect_tx(BAR(B_GU), (8 - NREG_H) * 16384); mbar_expect_tx(BAR(B_DN), 65536); }
#pragma unroll 1
        for (int i = 0; i < 10 - NREG_H; i++) {
          if (i == 3) mbar_wait(BAR(B_EMPTY + 1), 1);
          if (i == 4) {
            mbar_wait(BAR(B_EMPTY + 2), 1);
            mbar_wait(BAR(B_XCH), 0);
            PT(53);
          }
          const uint32_t dst = sb + late_off(i);
          if (elect_one()) {
            if (i < 6 - NREG_H) {
              LOAD_STREAM(dst, &p.tmG, BAR(B_GU), f0, (NREG_H + 2 + i) * 128);
              LOAD_STREAM(dst + 8192, &p.tmU, BAR(B_GU), f0, (NREG_H + 2 + i) * 128);
            } else {
#pragma unroll
              for (int b = 0; b < 4; b++) LOAD_STREAM(dst + b * 4096, &p.tmDn, BAR(B_DN), (4 * (i - 6 + NREG_H) + b) * 64, f0);
            }
          }
          const long long t0 = clock64();
          while (i < 9 - NREG_H && clock64() - t0 < MOE_PACE_CLK) {}
        }
      }
      const int lane = threadIdx.x & 31;
      mbar_wait(BAR(B_OUT), 0);
      const uint32_t km = SM_(uint32_t, OFF_WKEY + (lane & 7) * 8);
      const uint32_t bk = __reduce_max_sync(0xffffffffu, km);
      const int ww = __ffs(__ballot_sync(0xffffffffu, km == bk)) - 1;
#pragma unroll 1
      for (int i = 1; i <= 8; i++) {
        const int W = (ww + i) & 7;
        if (i == 8) {
          mbar_wait(BAR(B_XS), 0);
          if (SM_(uint32_t, OFF_KV) == bk) {
#pragma unroll 2
            for (int j = lane; j < 256; j += 32) {
              const int rho = j >> 4, row = row_of(gA * 128 + 32 * (W >> 1) + 8 * ((rho & 7) >> 1) + 4 * (W & 1) + 2 * (rho >> 3) + (rho & 1));
              const uint4 v = lds128_v(sb + OFF_OUT + (j & 8) * 2048 + (16 * W + rho) * 128 + (((j ^ rho) & 7) << 4));
              if (row != 0xFFFF - (int)(bk & 0xFFFFu))
                asm volatile("st.global.v4.b32 [%0], {%1, %2, %3, %4};" :: "l"(p.out + (size_t)row * 1024 + eps * 128 + (j & 15) * 8), "r"(v.x), "r"(v.y), "r"(v.z), "r"(v.w));
            }
            break;
          }
        }
        if (lane == 0) {
          tma_store_5d(&p.tmOut, sb + OFF_OUT + W * 2048, eps * 128, row_of(gA * 128 + 32 * (W >> 1) + 4 * (W & 1)));
          tma_store_5d(&p.tmOut, sb + OFF_OUT + 16384 + W * 2048, eps * 128 + 64, row_of(gA * 128 + 32 * (W >> 1) + 4 * (W & 1)));
        }
        const long long t0 = clock64();
        while (i < 7 && clock64() - t0 < OUT_PACE_CLK) {}
      }
      if (lane == 0) { bulk_commit(); bulk_wait_all(); }
      PT(22);
    } else {
      const int a = warp - 9;
      const int lane = threadIdx.x & 31;
      auto stage = [&](const bf16* src, int g) {
        if (elect_one()) {
          mbar_expect_tx(BAR(B_AUX + g), 16384);
          bulk_load(sb + OFF_XCH + g * 16384, src + g * 8192, 16384, BAR(B_AUX + g));
        }
      };
      uint32_t tag = 0;
#pragma unroll 1
      for (int i = 0; i < 3; i++) { i += keep_awake(); delay_clk<300>(); }
      mbar_wait(BAR(B_FULL + 0), 0);
      delay_clk<AUX_DELAY>();
      if (a == 0) PT(1);
      if (a == 1) mbar_wait(BAR(B_AUX + 0), 0);
      if (a < 2) stage(p.x + (size_t)cid * 16 * 1024, a);
#pragma unroll 1
      for (int it = 0; it < 4; it++) {
        const int g = it & 1;
        mbar_wait(BAR(B_AUX + g), it >> 1);
        if (a == 0) PT(2 + it);
        if (it == 2) tag = ld_relaxed32(&p.s->epoch) + 1;
        if (it == 2 && a == 2 && lane < 16) asm volatile("prefetch.global.L2 [%0];" :: "l"(p.wr + lane * 64));
        const uint32_t ad = sb + OFF_XCH + g * 16384 + (lane >> 2) * 2048;
        float s0 = 0.f, s1 = 0.f, q0 = 0.f, q1 = 0.f;
        auto row = [&](auto sq) {
#pragma unroll
          for (int i = 0; i < 11; i++) {
            if (i == 10 && a == 2) break;
            const uint4 v = lds128_v(ad + (((a * 44 + 4 * i + lane) & 127) << 4));
            const uint32_t ww[4] = {v.x, v.y, v.z, v.w};
#pragma unroll
            for (int z = 0; z < 4; z++) {
              const float d0 = bf_lo(ww[z]), d1 = bf_hi(ww[z]);
              s0 += d0; s1 += d1;
              if (decltype(sq)::value) { q0 = fmaf(d0, d0, q0); q1 = fmaf(d1, d1, q1); }
            }
          }
        };
        if (it < 2) row(IC<1>()); else row(IC<0>());
        s0 += s1; q0 += q1;
#pragma unroll
        for (int o = 1; o < 4; o <<= 1) { s0 += __shfl_xor_sync(0xffffffffu, s0, o); q0 += __shfl_xor_sync(0xffffffffu, q0, o); }
        if ((lane & 3) == 0) SM_(float2, OFF_PUB + a * 256 + it * 64 + (lane >> 2) * 8) = make_float2(s0, q0);
        if (it != 2) bar_sync(NB_AUX, 96);
        if (it < 2 && a == 2) stage(cid < 64 ? p.Dre + (size_t)cid * 16 * 1024 : p.Dim + (size_t)(cid - 64) * 16 * 1024, g);
      }
      if (a == 1) {
        const float2 v0 = SM_(float2, OFF_PUB + lane * 8), v1 = SM_(float2, OFF_PUB + 256 + lane * 8), v2 = SM_(float2, OFF_PUB + 512 + lane * 8);
        const float s = v0.x + v1.x + v2.x, mean = s * (1.f / 1024.f);
        const float rs = rcp_fast(ln_sd((v0.y + v1.y + v2.y) * (1.f / 1024.f) - mean * mean));
        pkt_st64((lane < 16 ? p.s->xstat : p.s->dsum) + cid * 16 + (lane & 15), lane < 16 ? pack_bf16(rs, mean) : __float_as_uint(s), tag);
        PT(6);
      }
      if (a == 2) {
        float s = 0.f;
#pragma unroll
        for (int q = 0; q < 4; q++) {
          const uint4 v = ldg_nc128(p.wr + (q * 32 + lane) * 8);
          s += ((bf_lo(v.x) + bf_hi(v.x)) + (bf_lo(v.y) + bf_hi(v.y))) + ((bf_lo(v.z) + bf_hi(v.z)) + (bf_lo(v.w) + bf_hi(v.w)));
          const int ch = q * 32 + lane - eps * 16;
          if (ch >= 0 && ch < 16) {
            SM_(uint32_t, OFF_WR + ch * 4) = v.x; SM_(uint32_t, OFF_WR + 80 + ch * 4) = v.y;
            SM_(uint32_t, OFF_WR + 160 + ch * 4) = v.z; SM_(uint32_t, OFF_WR + 240 + ch * 4) = v.w;
          }
        }
        s = warp_sum(s);
        if (lane == 0) { SM_(float, OFF_WSUM) = s; SM_(uint32_t, OFF_TAG) = tag; }
      }
      if (a < 2) __nanosleep(GATHER_NS);
      {
        const int i0 = a * 32 + lane;
        uint2 v[3], c0, c1; uint32_t n = 0;
        const uint2* dp = &p.s->dsum[abrow];
        while (true) {
#pragma unroll
          for (int q = 0; q < 3; q++) v[q] = pkt_ld64(&p.s->xstat[tau * 256 + min(i0 + 96 * q, 255)]);
          c0 = pkt_ld64(dp + i0); c1 = pkt_ld64(dp + min(i0 + 96, 127));
          if (__all_sync(0xffffffffu, v[0].y == tag && v[1].y == tag && v[2].y == tag && c0.y == tag && c1.y == tag) || ++n > SPIN_LIMIT) break;
          __nanosleep(200);
        }
#pragma unroll
        for (int q = 0; q < 3; q++) put_xstat(sb + OFF_RS, sb + OFF_EXB, min(i0 + 96 * q, 255), v[q].x, m);
        put_dsum(sb + OFF_EXA, i0, __uint_as_float(c0.x));
        put_dsum(sb + OFF_EXA, min(i0 + 96, 127), __uint_as_float(c1.x));
        fence_async_smem();
      }
      __syncwarp();
      if (lane == 0) mbar_arrive(BAR(B_STAT));
      if (a == 0) PT(7);
      if (a == 0) {
        const uint32_t* flg = reinterpret_cast<const uint32_t*>(&p.s->abflag[((eps * 2 + m) * 8 + (lane >> 2)) * 2]) + (lane & 3);
        if (NX < 256 && lane == 4 * tau + 1) flg = reinterpret_cast<const uint32_t*>(&p.s->hflag[(m * 8 + eps) * 2]);
        uint32_t seen = 0;
        auto fetch = [&](int s, uint32_t dst) {
          const int tile = sigma_of(tau, s);
          uint32_t n = 0;
          while (!((seen >> (4 * tile)) & 1) && ++n < SPIN_LIMIT) seen = __ballot_sync(0xffffffffu, ld_acquire32(flg) == tag);
          asm volatile("fence.proxy.async.global;" ::: "memory");
          PT(16 + s);
          if (elect_one()) tma_load_2d(dst, &p.tmAbL, BAR(B_FULL + s), tile * 256, abrow);
        };
        mbar_wait(BAR(B_EPI), 0);
#pragma unroll
        for (int s = 0; s < 4; s++) mbar_wait(BAR(B_FULL + s), 0);
        fetch(0, sb + OFF_XCH);
        mbar_wait(BAR(B_STD + 0), 0);
        delay_clk<GAP1>();
        fetch(1, sb + OFF_XCH + 16384);
        if (elect_one()) mbar_arrive(BAR(B_PUB1));
        delay_clk<GAP2>();
        fetch(2, sb + 2 * ST_BYTES);
        mbar_wait(BAR(B_STD + 1), 0);
        fetch(3, sb + 3 * ST_BYTES);
        uint32_t n = 0, told = 0;
        while (true) {
          if (seen != told) {
            asm volatile("fence.proxy.async.global;" ::: "memory");
            *(volatile uint32_t*)&SM_(uint32_t, OFF_SEEN) = seen;
            told = seen;
          }
          if (seen == 0xFFFFFFFFu || ++n > SPIN_LIMIT) break;
          __nanosleep(100);
          seen = __ballot_sync(0xffffffffu, ld_acquire32(flg) == tag);
        }
        PT(58);
      } else {
        uint32_t* flag = reinterpret_cast<uint32_t*>(&p.s->abflag[((eps * 2 + m) * 8 + tau) * 2]);
        if (a == 1) {
          mbar_wait(BAR(B_EPI), 0);
          PT(8);
          if (lane == 0) tma_store_2d(&p.tmAbS, sb + chunk_off(0, 0), tau * 256, abrow);
          mbar_wait(BAR(B_EPI0B), 0);
          if (lane == 0) {
            tma_store_2d(&p.tmAbS, sb + chunk_off(0, 1), tau * 256, abrow + 64);
            bulk_commit();
            bulk_wait_all();
            mbar_arrive(BAR(B_STD));
            bulk_wait_release();
            st_relaxed32(flag, tag);
          }
          PT(12);
          mbar_wait(BAR(B_EPI + 1), 0);
          mbar_wait(BAR(B_LATE), 0);
          mbar_wait(BAR(B_PUB1), 0);
          PT(9);
          if (lane == 0) {
            tma_store_2d(&p.tmAbS, sb + chunk_off(1, 0), tau * 256 + 64, abrow);
            tma_store_2d(&p.tmAbS, sb + chunk_off(1, 1), tau * 256 + 64, abrow + 64);
            bulk_commit();
            bulk_wait_all();
            mbar_arrive(BAR(B_STD + 1));
            bulk_wait_release();
            st_relaxed32(flag + 1, tag);
          }
          PT(13);
        }
        auto copy_out = [&](int c) {
          mbar_wait(BAR(B_EPI + c), 0);
          PT(8 + c);
          bf16* dst = p.s->abT + (size_t)(abrow + (lane >> 3)) * 2048 + tau * 256 + c * 64 + (lane & 7) * 8;
          const uint32_t src = sb + chunk_off(c, 0) + (lane >> 3) * 128 + (((lane & 7) ^ (lane >> 3)) << 4);
          const uint32_t on = c * 64 + (lane & 7) * 8 < NX;
#pragma unroll 4
          for (int i = 0; i < 32; i++) {
            const uint4 v = lds128_v((src ^ ((i & 1) << 6)) + i * 512);
            asm volatile("{\n.reg .pred p;\nsetp.ne.b32 p, %5, 0;\n@p st.global.v4.b32 [%0], {%1, %2, %3, %4};\n}\n"
                         :: "l"(dst + i * 4 * 2048), "r"(v.x), "r"(v.y), "r"(v.z), "r"(v.w), "r"(on));
          }
          __syncwarp();
          if (lane == 0) mbar_arrive(BAR(B_STD + c));
        };
        if (a == 2) {
#pragma unroll 1
          for (int c = 2; c < 4; c++) copy_out(c);
          asm volatile("fence.acq_rel.gpu;" ::: "memory");
          __syncwarp();
          if (lane < 2) st_relaxed32(flag + 2 + lane, tag);
          PT(15);
        }
      }
      {
        mbar_wait(BAR(B_LATE), 1);
        const int grp = tau * 2 + m;
#pragma unroll 1
        for (int i = a; i < 14; i += 3) {
          uint4* dst = i < 8 ? &p.s->ypart[cid * 256 + i * 32 + lane] : i < 12 ? &p.s->hstat[(grp * 8 + eps) * 128 + (i - 8) * 32 + lane]
                     : i == 12 ? &p.s->cand[grp * 256 + eps * 32 + lane] : &p.s->key[(((lane >> 1) & 7) * 16 + grp) * 2 + (lane & 1)];
          if (i < 13 || eps == 0) pkt_st128(dst, 0, 0, 0, 0);
          __nanosleep(200);
        }
        __syncwarp();
        if (lane == 0) mbar_arrive(BAR(B_STAT));
      }
      {
        const uint4* kp = &p.s->key[(tau * 16 + (lane & 15)) * 2];
        const int i0 = a * 32 + lane;
        mbar_wait(BAR(B_KEY), 0);
        if (a == 0) PT(43);
        uint4 kq = pkt_ld128(kp), cv[3] = {};
        uint32_t n = 0, kv;
        int gspec = -1;
        while (true) {
          const bool ok = kq.y == tag && kq.w == tag;
          kv = __reduce_max_sync(0xffffffffu, ok ? kq.x : 0u);
          const int gs = group_of(0xFFFF - (int)(kv & 0xFFFFu));
          const bool cok = gs == gspec && cv[0].y == tag && cv[0].w == tag && cv[1].y == tag && cv[1].w == tag && cv[2].y == tag && cv[2].w == tag;
          if (__all_sync(0xffffffffu, ok && cok) || ++n > SPIN_LIMIT) break;
          if (!ok) kq = pkt_ld128(kp);
          n += keep_awake();
          const bool spec = __popc(__ballot_sync(0xffffffffu, ok)) >= 2 * SPEC_MIN;
          if (!cok && spec) {
#pragma unroll
            for (int i = 0; i < 3; i++) cv[i] = pkt_ld128(&p.s->cand[gs * 256 + min(i0 + 96 * i, 255)]);
          }
          if (spec) gspec = gs;
        }
        if (a == 0) PT(45);
        const uint32_t ms = __shfl_sync(0xffffffffu, kq.z, gspec);
        const uint32_t nm = ((ms & 0xFFFFu) ^ 0x8000u) * 0x10001u;
        const float is = rcp_fast(bf_hi(ms));
#pragma unroll
        for (int i = 0; i < 3; i++) {
          const int j = min(i0 + 96 * i, 255);
          SM_(uint2, OFF_XSEL + j * 8) = make_uint2(norm2(cv[i].x, nm, is), norm2(cv[i].z, nm, is));
        }
#pragma unroll
        for (int i = 0; i < 3; i++) SM_(uint2, OFF_HSEL + min(i0 + 96 * i, 255) * 8) = make_uint2(cv[i].x, cv[i].z);
        SM_(uint32_t, OFF_KV) = kv;
        __syncwarp();
        if (lane == 0) mbar_arrive(BAR(B_XS));
      }
    }
    asm volatile("barrier.cluster.wait.aligned;" ::: "memory");
  } else {
    reg_inc<REG_C>();
    const int tid = __shfl_sync(0xffffffffu, threadIdx.x, threadIdx.x & 31), lane = tid & 31;
    const int w = warp >> 2, wi = warp & 3, t = tid & 127;
    const int g = lane >> 2, q = lane & 3;
    const int turn_me = NB_TURN0 + w, turn_other = NB_TURN1 - w;
    auto release = [&](int s) { if (t == 0) mbar_arrive(BAR(B_EMPTY + s)); };
    if (MAP == 0 && helper) {
      asm volatile("barrier.cluster.arrive.relaxed.aligned;" ::: "memory");
      float s0[64], s1[64];
#pragma unroll
      for (int i = 0; i < 64; i++) { s0[i] = 0.f; s1[i] = 0.f; }
      if (w == 1) bar_arrive(NB_TURN0, 256);
      uint32_t o[32][2] = {};
      const int col = (eps - 2) * 8 + m * 4 + w;
      auto put = [&](auto tc, uint32_t buf) {
        constexpr int tl = decltype(tc)::value;
#pragma unroll
        for (int i = 0; i < 4; i++)
          smem_at<uint2>(buf + ((i >> 1) * 64 + wi * 16 + (i & 1) * 8 + g) * 32 + ((q * 8) ^ ((g & 4) << 2))) = make_uint2(o[8 * i + tl][0], o[8 * i + tl][1]);
      };
      auto mma_step = [&](int k) {
        const int s = slot_of(k);
        const uint64_t da = make_desc(sb + s * ST_BYTES + A_BYTES + w * 16384), db = make_desc(sb + s * ST_BYTES);
        wgmma_fence();
#pragma unroll
        for (int kk = 0; kk < 4; kk++) {
          wgmma_n128(s0, da + kk * 2, db + kk * 2, kk > 0 || (k & 15));
          wgmma_n128(s1, da + 512 + kk * 2, db + kk * 2, kk > 0 || (k & 15));
        }
        wgmma_commit();
      };
#pragma unroll 1
      for (int pass = 0; pass < 2; pass++) {
#pragma unroll 1
        for (int k = 16 * pass; k < (pass ? 32 - HL_N : 16); k++) {
          mbar_wait(BAR(B_FULL + slot_of(k)), use_of(k) & 1);
          bar_sync(turn_me, 256);
          mma_step(k);
          bar_arrive(turn_other, 256);
          if (pass && k < 24) {
            const uint32_t buf = sb + OFF_XCH + ((k & 1) ? 0 : 20480) + w * 4096;
            static_for<8>([&](auto ic) { if (k == 16 + decltype(ic)::value) put(ic, buf); });
            fence_async_smem();
            bar_sync(NB_WG0 + w, 128);
            if (t == 0) { tma_store_2d(&p.tmAbM, buf, (k - 16) * 256 + 240, col * 128); bulk_commit(); }
          }
          wgmma_wait0();
          release(slot_of(k));
          if (t == 0) asm volatile("cp.async.bulk.wait_group.read 1;" ::: "memory");
        }
        if (pass) {
          bar_sync(turn_me, 256);
#pragma unroll
          for (int k = 32 - HL_N; k < 32; k++) {
            mbar_wait(BAR(B_FULL + slot_of(k)), 1);
            mma_step(k);
          }
        }
        mbar_wait(BAR(B_STAT), 0);
        wgmma_fence();
        wgmma_n128(s0, make_desc_noswz(sb + OFF_XCH + pass * 8192 + w * 4096), make_desc_noswz(sb + OFF_XCH + 16384));
        wgmma_n128(s1, make_desc_noswz(sb + OFF_XCH + pass * 8192 + w * 4096 + 2048), make_desc_noswz(sb + OFF_XCH + 16384));
        wgmma_commit();
        if (pass && w == 0) bar_arrive(turn_other, 256);
        uint4 rs[4];
#pragma unroll
        for (int i = 0; i < 4; i++) rs[i] = lds128_v(sb + OFF_RS + q * 144 + i * 16);
        wgmma_wait0();
        fence_acc(s0); fence_acc(s1);
#pragma unroll
        for (int i = 0; i < 32; i++) {
          const int tl = i & 7, hr = (i >> 3) & 1;
          const float* ac = (i >> 4) ? &s1[8 * tl + 2 * hr] : &s0[8 * tl + 2 * hr];
          o[i][0] = bmul2(pack_bf16(ac[0], ac[1]), (tl & 1) ? rs[tl >> 1].z : rs[tl >> 1].x);
          o[i][1] = bmul2(pack_bf16(ac[4], ac[5]), (tl & 1) ? rs[tl >> 1].w : rs[tl >> 1].y);
        }
      }
      static_for<8>([&](auto ic) { put(ic, sb + (w * 8 + decltype(ic)::value) * 4096); });
      fence_async_smem();
      bar_sync(NB_WG0 + w, 128);
      if (t == 0) {
#pragma unroll 1
        for (int i = 0; i < 8; i++) tma_store_2d(&p.tmAbM, sb + (w * 8 + i) * 4096, i * 256 + 240, (col + 2) * 128);
        bulk_commit();
        bulk_wait_release();
        st_relaxed32(&p.s->hflag[col * 2], SM_(uint32_t, OFF_TAG));
        st_relaxed32(&p.s->hflag[(col + 2) * 2], SM_(uint32_t, OFF_TAG));
      }
      asm volatile("barrier.cluster.wait.aligned;" ::: "memory");
      return;
    }
    float acc[128], a1[NX / 2];
#pragma unroll
    for (int i = 0; i < NX / 2; i++) a1[i] = 0.f;
    if (w == 1) bar_arrive(NB_TURN0, 256);
    auto kstep = [&](auto& d, int k, bool first, bool a_in_xch = false, bool mini = false) {
      const int s = slot_of(k);
      mbar_wait(BAR(B_FULL + s), use_of(k) & 1);
      CT(64 + k);
      bar_sync(turn_me, 256);
      const uint64_t da = make_desc(sb + (a_in_xch ? OFF_XCH + s * 16384 : s * ST_BYTES) + w * 8192), db = make_desc(sb + s * ST_BYTES + A_BYTES);
      wgmma_fence();
      wgmma_g1(d, da, db, !first);
#pragma unroll
      for (int kk = 1; kk < 4; kk++) wgmma_g1(d, da + kk * 2, db + kk * 2, 1);
      wgmma_commit();
      if (mini) {
        CT(29);
        mbar_wait(BAR(B_MINI), 0);
        CT(30);
        wgmma_fence();
        wgmma_g1(d, make_desc_32b(sb + OFF_MINI + w * 2048), make_desc_32b(sb + OFF_MINI + 4096), 1);
        wgmma_commit();
      }
      bar_arrive(turn_other, 256);
    };
    auto kdone = [&](int k) { wgmma_wait0(); release(slot_of(k)); };
    auto wgmma_wait1 = [&]() { asm volatile("wgmma.wait_group.sync.aligned 1;" ::: "memory"); };

#pragma unroll 1
    for (int k = 0; k < 13; k++) {
      kstep(a1, k, k == 0);
      if (k == 0) CT(0);
      if (k == 8 && warp == 2 && lane < 2) pkt_st128(&p.s->abflag[((eps * 2 + m) * 8 + tau) * 2 + lane], 0, 0, 0, 0);
      kdone(k);
    }
    uint32_t R[64];
    kstep(a1, 13, false);
    mbar_wait(BAR(B_STAT), 0);
    const uint32_t tag = SM_(uint32_t, OFF_TAG);
#pragma unroll
    for (int i = 0; i < 8; i++) { const uint4 v = lds128_v(sb + OFF_RS + q * 144 + i * 16); R[8 * i] = v.x; R[8 * i + 2] = v.y; R[8 * i + 4] = v.z; R[8 * i + 6] = v.w; }
    kdone(13);
    float p0[32], p1[NX / 2 - 32];
    auto pack = [&](auto cc) {
      constexpr int c = decltype(cc)::value;
#pragma unroll
      for (int j = 8 * c; j < min_c(8 * c + 8, NX / 8); j++) {
        const uint32_t rs = R[2 * j];
        const float* ac = c ? &p1[4 * j - 32] : &p0[4 * j];
        R[2 * j] = bmul2(pack_bf16(ac[0], ac[1]), rs);
        R[2 * j + 1] = bmul2(pack_bf16(ac[2], ac[3]), rs);
      }
    };
    auto put_chunk = [&](auto cc) {
      constexpr int c = decltype(cc)::value;
      const int rho = 16 * wi + (lane & 15);
#pragma unroll
      for (int j = 8 * c; j < min_c(8 * c + 8, NX / 8); j += 2) {
        const int chunk = (j & 7) + (lane >> 4);
        stsm_x4(sb + chunk_off(c, w) + rho * 128 + ((chunk ^ (lane & 7)) << 4), R[2 * j], R[2 * j + 1], R[2 * j + 2], R[2 * j + 3]);
      }
    };
    auto staged = [&](int bar) {
      fence_async_smem();
      __syncwarp();
      if (lane == 0) mbar_arrive(BAR(bar));
    };
    auto mma_rs = [&](auto cc, auto k0, auto k1) {
      constexpr int c = decltype(cc)::value;
      const uint64_t db = make_desc(sb + c * ST_BYTES + A_BYTES);
#pragma unroll
      for (int kk = decltype(k0)::value; kk < decltype(k1)::value; kk++)
        wgmma_n256_rs(acc, R[16 * c + 4 * kk], R[16 * c + 4 * kk + 1], R[16 * c + 4 * kk + 2], R[16 * c + 4 * kk + 3], db + kk * 2, c + kk > 0);
      wgmma_commit();
    };
    auto kdone_x = [&](int k, auto ic) {
      constexpr int i = decltype(ic)::value;
      uint32_t r[8];
#pragma unroll
      for (int z = 0; z < 2; z++) {
        const int tr = 32 * (i & 1) + 16 * z + 8 * (lane >> 4) + (lane & 7), chunk = 2 * wi + ((lane >> 3) & 1);
        ldsm_x4_t(sb + (i >> 1) * ST_BYTES + w * 8192 + tr * 128 + ((chunk ^ (lane & 7)) << 4), r[4 * z], r[4 * z + 1], r[4 * z + 2], r[4 * z + 3]);
      }
      float f[16];
#pragma unroll
      for (int z = 0; z < 8; z++) { f[2 * z] = bf_lo(r[z]); f[2 * z + 1] = bf_hi(r[z]); }
#pragma unroll
      for (int z = 0; z < 16; z++) asm volatile("" : "+f"(f[z]));
      kdone(k);
#pragma unroll
      for (int z = 0; z < 16; z++) asm volatile("add.f32 %0, %0, %1;" : "+f"(acc[16 * i + z]) : "f"(f[z]));
    };
    {
      const uint64_t da2 = make_desc(sb + 2 * ST_BYTES + w * 8192), db2 = make_desc(sb + 2 * ST_BYTES + A_BYTES);
      const uint64_t da3 = make_desc(sb + 3 * ST_BYTES + w * 8192), db3 = make_desc(sb + 3 * ST_BYTES + A_BYTES);
      const uint64_t dax = make_desc_noswz(sb + OFF_EXA + w * 2048), dbx = make_desc_noswz(sb + OFF_EXB);
      fence_acc(a1);
#pragma unroll
      for (int i = 0; i < 32; i++) asm volatile("mov.b32 %0, %1;" : "=f"(p0[i]) : "f"(a1[i]));
#pragma unroll
      for (int i = 32; i < NX / 2; i++) asm volatile("mov.b32 %0, %1;" : "=f"(p1[i - 32]) : "f"(a1[i]));
      mbar_wait(BAR(B_FULL + 2), 1);
      CT(64 + 14);
      bar_sync(turn_me, 256);
      wgmma_fence();
#pragma unroll
      for (int kk = 0; kk < 4; kk++) wgmma_g1(p0, da2 + kk * 2, db2 + kk * 2, 1);
      wgmma_commit();
      mbar_wait(BAR(B_FULL + 3), 1);
      CT(64 + 15);
      wgmma_fence();
#pragma unroll
      for (int kk = 0; kk < 4; kk++) wgmma_g1(p0, da3 + kk * 2, db3 + kk * 2, 1);
      wgmma_g1(p0, dax, dbx, 1);
      wgmma_commit();
      bar_arrive(turn_other, 256);
      wgmma_wait0();
      fence_acc(p0);
      pack(IC<0>());
      put_chunk(IC<0>());
      CT(20);
      bar_sync(turn_me, 256);
      wgmma_fence();
#pragma unroll
      for (int kk = 0; kk < 4; kk++) wgmma_g1(p1, da2 + kk * 2, db2 + 512 + kk * 2, 1);
      wgmma_commit();
      staged(w ? B_EPI0B : B_EPI);
      CT(21);
      wgmma_fence();
#pragma unroll
      for (int kk = 0; kk < 4; kk++) wgmma_g1(p1, da3 + kk * 2, db3 + 512 + kk * 2, 1);
      wgmma_g1(p1, dax, dbx + 128, 1);
      wgmma_commit();
      bar_arrive(turn_other, 256);
      wgmma_wait1();
      release(2);
      kdone(15);
      mbar_wait(BAR(B_STAT), 0);
    }
    fence_acc(p1);
    CT(1);
    pack(IC<1>());
    pack(IC<2>());
    pack(IC<3>());
#pragma unroll
    for (int i = 16; i < NX / 4; i++) asm volatile("" : "+r"(R[i]));
#pragma unroll
    for (int i = 0; i < 128; i++) asm volatile("" : "=f"(acc[i]));
    mbar_wait(BAR(B_FULL + 0), 0);
    CT(2);
    static_for<4>([&](auto ic) {
      constexpr int c = decltype(ic)::value;
      if (c) mbar_wait(BAR(B_FULL + c), 0);
      CT(64 + 16 + c);
      bar_sync(turn_me, 256);
      wgmma_fence();
      mma_rs(IC<c>(), IC<0>(), IC<min_c(4, NX / 16 - 4 * c)>());
      bar_arrive(turn_other, 256);
      if constexpr (c == 0) { put_chunk(IC<1>()); staged(B_EPI + 1); kdone(16); } else kdone_x(16 + c, IC<c - 1>());
    });
#pragma unroll 1
    for (int k = 20; k < 23; k++) {
      kstep(acc, k, false, k < 22);
      if (k == 20) {
        kdone_x(k, IC<3>());
      } else {
        if (k == 21) put_chunk(IC<2>()); else put_chunk(IC<3>());
        __syncwarp();
        if (lane == 0) mbar_arrive(BAR(B_EPI + k - 19));
        kdone(k);
      }
    }
    uint32_t wf[32][4];
    auto load_wf = [&](auto hc) {
      constexpr int h = decltype(hc)::value;
      const int d = w * 64 + (lane >> 4) * 8 + (lane & 7);
      const uint32_t ad = sb + round_off(h) + (lane & 8) * 1024 + d * 64 + ((wi ^ ((lane >> 1) & 3)) << 4);
#pragma unroll
      for (int i = 0; i < 4; i++) ldsm_x4_t(ad + i * 1024, wf[4 * h + i][0], wf[4 * h + i][1], wf[4 * h + i][2], wf[4 * h + i][3]);
    };
    auto load_wf_rest = [&]() { static_for<8 - NREG_H>([&](auto ic) { load_wf(IC<NREG_H + decltype(ic)::value>()); }); };
#pragma unroll
    for (int i = 0; i < 4 * NREG_H; i++) { wf[i][0] = 0; wf[i][1] = 0; wf[i][2] = 0; wf[i][3] = 0; }
    const int grp = tau * 2 + m;
#pragma unroll 1
    for (int k = 23; k < 46; k++) {
      kstep(acc, k, false, false, NX < 256 && k == MINI_K);
      if (moe) {
        static_for<NREG_H>([&](auto hc) {
          constexpr int h = decltype(hc)::value;
          if (k == mr_k(h) + 1) { mbar_wait(BAR(B_MR + (h & 1)), (h >> 1) & 1); CT(32 + h); load_wf(hc); }
        });
      }
      if (k == RESET_K && tid == 0) mbar_arrive(BAR(B_LATE));
      kdone(k);
    }
    asm volatile("barrier.cluster.arrive.relaxed.aligned;" ::: "memory");
    mbar_wait(BAR(B_STAT), 1);
    uint32_t wa[16][2];
    uint32_t cd = code_of(tag);
    uint4* hp_pub = &p.s->hstat[(grp * 8 + eps) * 128 + warp * 16 + g];
    const uint4* hp_poll = &p.s->hstat[(grp * 8 + 2 * q) * 128 + warp * 16 + g];
    const uint32_t vec_off = (2 * wi) * 512 + q * 128 + ((g ^ (2 * q)) << 4);
    {
      float as[64], ak[64];
      fence_acc(acc);
#pragma unroll
      for (int i = 0; i < 64; i++) asm volatile("mov.b32 %0, %1;" : "=f"(as[i]) : "f"(acc[64 + i]));
#pragma unroll
      for (int i = 0; i < 64; i++) asm volatile("mov.b32 %0, %1;" : "=f"(ak[i]) : "f"(acc[i]));
      const uint64_t da1 = make_desc(sb + 2 * ST_BYTES + w * 8192), db1 = make_desc(sb + 2 * ST_BYTES + A_BYTES);
      const uint64_t da2 = make_desc(sb + 3 * ST_BYTES + w * 8192), db2 = make_desc(sb + 3 * ST_BYTES + A_BYTES);
      mbar_wait(BAR(B_FULL + 2), 1);
      CT(64 + 46);
      bar_sync(turn_me, 256);
      wgmma_fence();
#pragma unroll
      for (int kk = 0; kk < 4; kk++) wgmma_n128(as, da1 + kk * 2, db1 + 1024 + kk * 2);
      wgmma_commit();
      mbar_wait(BAR(B_FULL + 3), 1);
      CT(64 + 47);
      wgmma_fence();
#pragma unroll
      for (int kk = 0; kk < 4; kk++) wgmma_n128(as, da2 + kk * 2, db2 + 1024 + kk * 2);
      wgmma_commit();
      bar_arrive(turn_other, 256);
      const uint32_t rx = mapa(sb + OFF_PEER + w * 4096 + vec_off, 1 - m), rb = mapa(BAR(B_XCH), 1 - m);
      asm volatile("barrier.cluster.wait.aligned;" ::: "memory");
      CT(24);
      wgmma_wait0();
      fence_acc(as);
      CT(25);
      auto keep = [&]() {
        bar_sync(turn_me, 256);
        wgmma_fence();
#pragma unroll
        for (int kk = 0; kk < 4; kk++) wgmma_n128(ak, da1 + kk * 2, db1 + kk * 2);
        wgmma_commit();
#pragma unroll
        for (int kk = 0; kk < 4; kk++) wgmma_n128(ak, da2 + kk * 2, db2 + kk * 2);
        wgmma_commit();
        if (w == 0) bar_arrive(turn_other, 256);
      };
#pragma unroll
      for (int i = 0; i < 8; i++) {
        if (i == SEND_FIRST) keep();
        const float* ac = &as[16 * (i >> 1) + 2 * (i & 1)];
        st_async_v4(rx + (i >> 1) * 8192 + (i & 1) * 512, rb, pack_bf16(ac[0], ac[1]), pack_bf16(ac[4], ac[5]), pack_bf16(ac[8], ac[9]), pack_bf16(ac[12], ac[13]));
      }
      CT(26);
#pragma unroll
      for (int i = 0; i < 4; i++) {
        const uint4 v = lds128_v(sb + OFF_WR + q * 80 + i * 16);
        const uint32_t vv[4] = {v.x, v.y, v.z, v.w};
#pragma unroll
        for (int z = 0; z < 4; z++) {
          asm volatile("{\n.reg .pred p;\nsetp.ne.b32 p, %2, 0;\nselp.b32 %0, %1, 0x3F803F80, p;\n}" : "=r"(wa[4 * i + z][0]) : "r"(vv[z]), "r"(g & 1));
          asm volatile("{\n.reg .pred p;\nsetp.ne.b32 p, %2, 0;\nselp.b32 %0, %1, 0x3F803F80, p;\n}" : "=r"(wa[4 * i + z][1]) : "r"(vv[z]), "r"(g & 1));
        }
      }
      pin(cd); pin(hp_pub); pin(hp_poll);
      CT(27);
      wgmma_wait1();
      release(2);
      wgmma_wait0();
      fence_acc(ak);
      CT(3);
#pragma unroll
      for (int i = 0; i < 8; i++) {
        const float* ac = &ak[16 * (i >> 1) + 2 * (i & 1)];
        sts128(sb + (2 + (i >> 2)) * ST_BYTES + w * 8192 + ((i >> 1) & 1) * 4096 + (i & 1) * 512 + vec_off,
               pack_bf16(ac[0], ac[1]), pack_bf16(ac[4], ac[5]), pack_bf16(ac[8], ac[9]), pack_bf16(ac[12], ac[13]));
      }
    }
    uint32_t h[8][4];
    {
      const int qq = 2 * (warp & 1) + ((lane >> 3) & 1);
      const uint32_t lo = (lane >> 4) * 512 + qq * 128 + (((lane & 7) ^ (2 * qq)) << 4);
      bar_sync(NB_BOTH, 256);
#pragma unroll
      for (int ks = 0; ks < 8; ks++)
        ldsm_x4_t(sb + (2 + w) * ST_BYTES + (ks >> 2) * 8192 + (wi >> 1) * 4096 + (ks & 3) * 1024 + lo, h[ks][0], h[ks][1], h[ks][2], h[ks][3]);
      CT(28);
      mbar_wait_cluster(BAR(B_XCH), 0);
      CT(4);
      uint32_t r[8][4];
#pragma unroll
      for (int ks = 0; ks < 8; ks++) ldsm_x4_t(sb + OFF_PEER + (warp >> 1) * 8192 + ks * 1024 + lo, r[ks][0], r[ks][1], r[ks][2], r[ks][3]);
      float d[4][4] = {};
#pragma unroll
      for (int ks = 0; ks < 8; ks++) {
#pragma unroll
        for (int i = 0; i < 4; i++) {
          h[ks][i] = badd2(h[ks][i], r[ks][i]);
          mma1688(d[i], h[ks][i], wa[2 * ks + (i >> 1)][i & 1], h[ks][i]);
        }
      }
#pragma unroll
      for (int i = 0; i < 2; i++) {
        const float sq = (g & 1) ? d[i][1] + d[i + 2][1] : d[i][0] + d[i + 2][0];
        const float e0 = d[i][2] + d[i + 2][2], e1 = d[i][3] + d[i + 2][3];
        const float other = __shfl_xor_sync(0xffffffffu, (g & 1) ? e0 : e1, 4);
        if (q == (g >> 1)) pkt_st128(hp_pub + 8 * i, with_bit((g & 1) ? other : e0, cd), with_bit(sq, cd >> 1), __float_as_uint((g & 1) ? e1 : other), tag);
      }
    }
    CT(5);
    if (tid == 0) mbar_arrive(BAR(B_KEY));
    delay_clk<HOP1_DELAY>();
    float m_bf, sd, inv_sd, r_bf;
    uint4* key_pub = &p.s->key[((lane & 7) * 16 + grp) * 2];
    uint4* cand_pub = &p.s->cand[grp * 256 + eps * 32 + q];
    uint32_t trow_inv = 0xFFFFu - (uint32_t)row_of(grp * 128 + 32 * (warp >> 1) + 8 * (g >> 1) + 4 * (warp & 1) + (q & 2) + (g & 1));
    {
      uint4 u[4];
#pragma unroll
      for (int i = 0; i < 4; i++) u[i] = pkt_ld128(hp_poll + (i & 1) * 128 + (i >> 1) * 8);
      const float wsum = SM_(float, OFF_WSUM);
      pin(key_pub); pin(cand_pub); pin(trow_inv);
      uint32_t n = 0;
      while (true) {
        bool ok[4];
#pragma unroll
        for (int i = 0; i < 4; i++) ok[i] = u[i].w == tag && pair_code(u[i].x, u[i].y) == cd;
        const bool all = __all_sync(0xffffffffu, ok[0] && ok[1] && ok[2] && ok[3]);
        if (all || ++n > SPIN_LIMIT) break;
#pragma unroll
        for (int i = 0; i < 4; i++) pkt_ld128_if(u[i], hp_poll + (i & 1) * 128 + (i >> 1) * 8, !ok[i]);
      }
      CT(6);
      float a[3], b[3];
      a[0] = __uint_as_float(u[0].x & ~1u) + __uint_as_float(u[1].x & ~1u); b[0] = __uint_as_float(u[2].x & ~1u) + __uint_as_float(u[3].x & ~1u);
      a[1] = __uint_as_float(u[0].y & ~1u) + __uint_as_float(u[1].y & ~1u); b[1] = __uint_as_float(u[2].y & ~1u) + __uint_as_float(u[3].y & ~1u);
      a[2] = __uint_as_float(u[0].z) + __uint_as_float(u[1].z); b[2] = __uint_as_float(u[2].z) + __uint_as_float(u[3].z);
#pragma unroll
      for (int i = 0; i < 3; i++) {
        a[i] = ((q & 2) ? b[i] : a[i]) + __shfl_xor_sync(0xffffffffu, (q & 2) ? a[i] : b[i], 2);
        a[i] += __shfl_xor_sync(0xffffffffu, a[i], 1);
      }
      const float mu = a[0] * (1.f / 1024.f);
      m_bf = bf16r(mu);
      sd = ln_sd(a[1] * (1.f / 1024.f) - mu * mu);
      inv_sd = rcp_fast(sd);
      r_bf = bf16r((a[2] - m_bf * wsum) * inv_sd);
    }
    {
      const uint32_t u = __float_as_uint(r_bf);
      const uint32_t ord = (u & 0x80000000u) ? ~u : (u | 0x80000000u);
      const uint32_t key = (ord & 0xFFFF0000u) | trow_inv;
      const uint32_t wk = __reduce_max_sync(0xffffffffu, key);
      if (key == wk) SM_(uint2, OFF_WKEY + warp * 8) = make_uint2(wk, (__float_as_uint(m_bf) >> 16) | __float_as_uint(sd));
      const uint32_t wmask = __ballot_sync(0xffffffffu, key == wk);
      const bool hi = (wmask & 0xCCCCCCCCu) != 0;
      uint32_t c[16];
#pragma unroll
      for (int ks = 0; ks < 8; ks++) { c[2 * ks] = hi ? h[ks][1] : h[ks][0]; c[2 * ks + 1] = hi ? h[ks][3] : h[ks][2]; }
      bar_sync(NB_BOTH, 256);
      const uint2 km = SM_(uint2, OFF_WKEY + (lane & 7) * 8);
      const uint32_t bk = __reduce_max_sync(0xffffffffu, km.x);
      if (wk == bk) {
        if ((wmask >> (lane & 28)) & 15) {
#pragma unroll
          for (int ks = 0; ks < 8; ks++) pkt_st128(cand_pub + ks * 4, c[2 * ks], tag, c[2 * ks + 1], tag);
        }
      } else if (eps == 0) {
        const uint32_t kx = __shfl_sync(0xffffffffu, km.x, warp ^ 1), ms = __shfl_sync(0xffffffffu, km.y, warp ^ 1);
        if (kx == bk && lane < 8) pkt_st128(key_pub, bk, tag, ms, tag);
      }
      CT(7);
    }
    {
      const float ih = bf16r(inv_sd);
      const uint32_t nm = pack_bf16(-m_bf, -m_bf), iv = pack_bf16(ih, inv_sd - ih);
      const uint32_t nm_o = __shfl_xor_sync(0xffffffffu, nm, 2), iv_o = __shfl_xor_sync(0xffffffffu, iv, 2);
      const uint32_t nm2[2] = {(q & 2) ? nm_o : nm, (q & 2) ? nm : nm_o}, iv2[2] = {(q & 2) ? iv_o : iv, (q & 2) ? iv : iv_o};
      const uint32_t hi2[2] = {__byte_perm(iv2[0], 0, 0x1010), __byte_perm(iv2[1], 0, 0x1010)}, lo2[2] = {__byte_perm(iv2[0], 0, 0x3232), __byte_perm(iv2[1], 0, 0x3232)};
      const uint32_t oa = sb + OFF_OUT + (warp * 16 + (lane & 15)) * 128;
#pragma unroll
      for (int ks = 0; ks < 8; ks++) {
        uint32_t o[4];
#pragma unroll
        for (int i = 0; i < 4; i++) {
          const uint32_t dd = badd2(h[ks][i], nm2[i & 1]);
          o[i] = badd2(h[ks][i], bfma2(dd, hi2[i & 1], bmul2(dd, lo2[i & 1])));
        }
        stsm_x4(oa + (ks >> 2) * 16384 + (((2 * (ks & 3) + (lane >> 4)) ^ (lane & 7)) << 4), o[0], o[1], o[2], o[3]);
      }
      staged(B_OUT);
    }
    CT(8);
    uint32_t df[16][4];
    auto load_df = [&]() {
      const int frow = (lane & 7) + ((lane >> 4) << 3), hi = (lane >> 3) & 1;
      const uint32_t base = sb + down_off(warp >> 1) + (warp & 1) * 8192 + frow * 128;
#pragma unroll
      for (int mt = 0; mt < 8; mt++) {
#pragma unroll
        for (int ks = 0; ks < 2; ks++)
          ldsm_x4_t(base + (mt >> 2) * 4096 + ks * 2048 + (((2 * (mt & 3) + hi) ^ (lane & 7)) << 4),
                    df[2 * mt + ks][0], df[2 * mt + ks][1], df[2 * mt + ks][2], df[2 * mt + ks][3]);
      }
    };
    if (moe) {
      mbar_wait(BAR(B_GU), 0);
      load_wf_rest();
      mbar_wait(BAR(B_DN), 0);
      load_df();
    }
    uint4* y_pub = &p.s->ypart[cid * 256 + tid];
    uint32_t xs_ad = sb + OFF_XSEL + (8 * (g >> 2) + 4 * w + (g & 3)) * 32 + q * 8, gp_ad = sb + OFF_GP + (wi * 8 + g) * 16 + w * 8 + (q >> 1) * 4;
    pin(y_pub); pin(xs_ad); pin(gp_ad);
    mbar_wait(BAR(B_XS), 0);
    CT(9);
    if (moe) {
      float gd[8][4] = {};
      uint2 bx[4];
#pragma unroll
      for (int r = 0; r < 4; r++) bx[r] = smem_at<uint2>(xs_ad + r * 512);
#pragma unroll
      for (int r = 0; r < 4; r++) {
#pragma unroll
        for (int i = 0; i < 8; i++) mma16816(gd[i], wf[8 * r + i][0], wf[8 * r + i][1], wf[8 * r + i][2], wf[8 * r + i][3], bx[r].x, bx[r].y);
      }
      const float gs = sel4(q, gd[0][0] + gd[1][1], gd[2][0] + gd[3][1], gd[4][0] + gd[5][1], gd[6][0] + gd[7][1]);
      const float us = sel4(q, gd[0][2] + gd[1][3], gd[2][2] + gd[3][3], gd[4][2] + gd[5][3], gd[6][2] + gd[7][3]);
      float v = ((q & 2) ? us : gs) + __shfl_xor_sync(0xffffffffu, (q & 2) ? gs : us, 2);
      v += __shfl_xor_sync(0xffffffffu, v, 1);
      smem_at<float>(gp_ad) = v;
      CT(10);
      bar_sync(NB_BOTH, 256);
      uint32_t bq[4];
      {
        const float4 p0 = SM_(float4, OFF_GP + lane * 16);
        const float gt = bf16r(p0.x + p0.z), up = bf16r(p0.y + p0.w);
        const float act = bf16r(gt * sigmoid_fast(gt)) * up;
        const uint32_t pr = pack_bf16(act, __shfl_down_sync(0xffffffffu, act, 1));
#pragma unroll
        for (int i = 0; i < 4; i++) bq[i] = __shfl_sync(0xffffffffu, pr, 8 * i + 2 * q);
      }
      CT(11);
      float yd[8][4] = {};
#pragma unroll
      for (int ks = 0; ks < 2; ks++) {
#pragma unroll
        for (int mt = 0; mt < 8; mt++) mma16816(yd[mt], df[2 * mt + ks][0], df[2 * mt + ks][1], df[2 * mt + ks][2], df[2 * mt + ks][3], bq[2 * ks], bq[2 * ks + 1]);
      }
      pkt_st128(y_pub, with_bit(sel4(q, yd[0][0], yd[2][0], yd[4][0], yd[6][0]), cd), with_bit(sel4(q, yd[0][2], yd[2][2], yd[4][2], yd[6][2]), cd >> 1),
                with_bit(sel4(q, yd[1][0], yd[3][0], yd[5][0], yd[7][0]), cd), with_bit(sel4(q, yd[1][2], yd[3][2], yd[5][2], yd[7][2]), cd >> 1));
    } else {
      const long long tw = clock64();
      while (clock64() - tw < IDLE_WAIT_CLK) __nanosleep(100);
    }
    CT(12);
    const uint32_t kv = SM_(uint32_t, OFF_KV);
    const int tsel = (int)(~kv & 2047u);
    const float r_sel = __uint_as_float((kv & 0x80000000u) ? (kv & 0x7FFF0000u) : (~kv & 0xFFFF0000u));
    const float sig = bf16r(sigmoid_fast(r_sel));
    const int pfin = 2 * cid + (tid & 1);
    const int col_fin = (pfin >> 5) * 128 + (pfin & 3) * 32 + ((pfin & 31) >> 2) + 8 * ((tid >> 1) & 3);
    const int sel_off = (col_fin >> 4) * 32 + ((col_fin & 7) >> 1) * 8 + ((col_fin >> 3) & 1) * 4 + (col_fin & 1) * 2;
    const float hn_fin = __uint_as_float((uint32_t)SM_(uint16_t, OFF_XSEL + sel_off) << 16), h_fin = __uint_as_float((uint32_t)SM_(uint16_t, OFF_HSEL + sel_off) << 16);
    bf16* out_fin = p.out + (size_t)tsel * 1024 + col_fin;
    {
      const uint4* src = &p.s->ypart[(16 + (tid >> 1)) * 256 + pfin];
      pin(src); pin(out_fin);
      uint4 v = make_uint4(0, 0, 0, 0);
      if (warp < 7) {
        delay_clk<HOP3_DELAY>();
        uint32_t n = 0;
        bool ok = false;
        do {
          pkt_ld128_if(v, src, !ok);
          ok = pair_code(v.x, v.y) == cd && pair_code(v.z, v.w) == cd;
        } while (!__all_sync(0xffffffffu, ok) && ++n < SPIN_LIMIT);
      }
      CT(13);
      const float y0 = __uint_as_float(v.x & ~1u), y1 = __uint_as_float(v.y & ~1u), y2 = __uint_as_float(v.z & ~1u), y3 = __uint_as_float(v.w & ~1u);
      const float a0 = ((lane & 2) ? y1 : y0) + __shfl_xor_sync(0xffffffffu, (lane & 2) ? y0 : y1, 2);
      const float a1 = ((lane & 2) ? y3 : y2) + __shfl_xor_sync(0xffffffffu, (lane & 2) ? y2 : y3, 2);
      float b = ((lane & 4) ? a1 : a0) + __shfl_xor_sync(0xffffffffu, (lane & 4) ? a0 : a1, 4);
      b += __shfl_xor_sync(0xffffffffu, b, 8);
      b += __shfl_xor_sync(0xffffffffu, b, 16);
      if (lane < 8) SM_(float, OFF_FIN + lane * 32 + warp * 4) = b;
    }
    bar_sync(NB_BOTH, 256);
    if (tid < 8) {
      const float4 y0 = SM_(float4, OFF_FIN + tid * 32), y1 = SM_(float4, OFF_FIN + tid * 32 + 16);
      const float y = ((y0.x + y0.y) + (y0.z + y0.w)) + ((y1.x + y1.y) + y1.z);
      *out_fin = __float2bfloat16_rn(h_fin + bf16r(hn_fin + bf16r(bf16r(y) * sig)));
      if (cid == 0 && tid == 0) st_relaxed32(&p.s->epoch, tag);
    }
    CT(14);
  }
}

__global__ void __launch_bounds__(384, 1) occupancy_probe_kernel() {}

typedef CUresult (*EncodeFn)(CUtensorMap*, CUtensorMapDataType, cuuint32_t, void*, const cuuint64_t*, const cuuint64_t*, const cuuint32_t*, const cuuint32_t*,
                             CUtensorMapInterleave, CUtensorMapSwizzle, CUtensorMapL2promotion, CUtensorMapFloatOOBfill);

static void make_tm(EncodeFn enc, CUtensorMap* tm, const void* ptr, uint64_t rows, uint64_t cols, uint32_t brows, uint32_t bcols, CUtensorMapSwizzle sw,
                    CUtensorMapL2promotion promo = CU_TENSOR_MAP_L2_PROMOTION_L2_128B) {
  cuuint64_t dims[2] = {cols, rows};
  cuuint64_t strides[1] = {cols * 2};
  cuuint32_t box[2] = {bcols, brows};
  cuuint32_t es[2] = {1, 1};
  enc(tm, CU_TENSOR_MAP_DATA_TYPE_BFLOAT16, 2, const_cast<void*>(ptr), dims, strides, box, es, CU_TENSOR_MAP_INTERLEAVE_NONE, sw,
      promo, CU_TENSOR_MAP_FLOAT_OOB_FILL_NONE);
}

static void make_tm_rows(EncodeFn enc, CUtensorMap* tm, const void* ptr, uint64_t cols, uint32_t brows, uint32_t bcols, CUtensorMapSwizzle sw,
                         CUtensorMapL2promotion promo = CU_TENSOR_MAP_L2_PROMOTION_L2_128B) {
  cuuint64_t dims[4] = {cols, 2, 2, 512};
  cuuint64_t strides[3] = {row_of(1) * cols * 2, row_of(2) * cols * 2, row_of(4) * cols * 2};
  cuuint32_t box[4] = {bcols, 2, 2, brows / 4};
  cuuint32_t es[4] = {1, 1, 1, 1};
  enc(tm, CU_TENSOR_MAP_DATA_TYPE_BFLOAT16, 4, const_cast<void*>(ptr), dims, strides, box, es, CU_TENSOR_MAP_INTERLEAVE_NONE, sw, promo,
      CU_TENSOR_MAP_FLOAT_OOB_FILL_NONE);
}

extern "C" void kernel_launch(void* const* d_in, const int* in_sizes, int n_in, void* d_out, int out_size) {
  (void)in_sizes; (void)n_in; (void)out_size;
  static EncodeFn enc = nullptr;
  static void* abT = nullptr;
  static int map = 0;
  if (!enc) {
    void* fn = nullptr; cudaDriverEntryPointQueryResult st;
    cudaGetDriverEntryPoint("cuTensorMapEncodeTiled", &fn, cudaEnableDefault, &st);
    enc = (EncodeFn)fn;
    cudaGetSymbolAddress(&abT, g_scratch);
    cudaFuncSetAttribute(fnet_moe_kernel<0>, cudaFuncAttributeMaxDynamicSharedMemorySize, SMEM_TOTAL);
    cudaFuncSetAttribute(fnet_moe_kernel<1>, cudaFuncAttributeMaxDynamicSharedMemorySize, SMEM_TOTAL);
    cudaFuncSetAttribute(occupancy_probe_kernel, cudaFuncAttributeMaxDynamicSharedMemorySize, SMEM_TOTAL);
    cudaFuncSetAttribute(occupancy_probe_kernel, cudaFuncAttributeNonPortableClusterSizeAllowed, 1);
    auto max_clusters = [&](int size) {
      cudaLaunchConfig_t cfg = {};
      cfg.gridDim = dim3(128); cfg.blockDim = dim3(384); cfg.dynamicSmemBytes = SMEM_TOTAL;
      cudaLaunchAttribute at[1];
      at[0].id = cudaLaunchAttributeClusterDimension; at[0].val.clusterDim.x = size; at[0].val.clusterDim.y = 1; at[0].val.clusterDim.z = 1;
      cfg.attrs = at; cfg.numAttrs = 1;
      int ncl = 0;
      return cudaOccupancyMaxActiveClusters(&ncl, occupancy_probe_kernel, &cfg) == cudaSuccess ? ncl : 0;
    };
    int dev = 0, sms = 0;
    cudaGetDevice(&dev);
    cudaDeviceGetAttribute(&sms, cudaDevAttrMultiProcessorCount, dev);
    map = (sms == 132 && max_clusters(2) == 66 && max_clusters(16) == 7) ? 0 : 1;
    (void)cudaGetLastError();
  }
  Params p;
  const bf16* x = (const bf16*)d_in[0];
  make_tm(enc, &p.tmD0, d_in[3], 1024, 1024, 128, 64, CU_TENSOR_MAP_SWIZZLE_128B);
  make_tm(enc, &p.tmD1, d_in[4], 1024, 1024, 128, 64, CU_TENSOR_MAP_SWIZZLE_128B);
  make_tm(enc, &p.tmX, x, 2048, 1024, map == 0 ? NX0 : 256, 64, CU_TENSOR_MAP_SWIZZLE_128B);
  make_tm_rows(enc, &p.tmXr, x, 1024, 64, 64, CU_TENSOR_MAP_SWIZZLE_128B);
  make_tm(enc, &p.tmAbS, abT, 2048, 2048, 64, 64, CU_TENSOR_MAP_SWIZZLE_128B);
  make_tm(enc, &p.tmAbL, abT, 2048, 2048, 128, 64, CU_TENSOR_MAP_SWIZZLE_128B);
  make_tm_rows(enc, &p.tmW0, d_in[1], 2048, 128, 64, CU_TENSOR_MAP_SWIZZLE_128B);
  make_tm_rows(enc, &p.tmW1, d_in[2], 2048, 128, 64, CU_TENSOR_MAP_SWIZZLE_128B);
  {
    cuuint64_t dims[5] = {1024, 2, 4, 2, 2048};
    cuuint64_t strides[4] = {row_of(1) * 2048, row_of(8) * 2048, row_of(2) * 2048, 2048};
    cuuint32_t box[5] = {64, 2, 4, 2, 1};
    cuuint32_t es[5] = {1, 1, 1, 1, 1};
    enc(&p.tmOut, CU_TENSOR_MAP_DATA_TYPE_BFLOAT16, 5, d_out, dims, strides, box, es, CU_TENSOR_MAP_INTERLEAVE_NONE, CU_TENSOR_MAP_SWIZZLE_128B,
        CU_TENSOR_MAP_L2_PROMOTION_NONE, CU_TENSOR_MAP_FLOAT_OOB_FILL_NONE);
  }
  {
    cuuint64_t dims[5] = {1024, 2, 4, 2, 8};
    cuuint64_t strides[4] = {2048, 4 * 2048, 2 * 2048, 256 * 2048};
    cuuint32_t box[5] = {64, 2, 4, 2, 8};
    cuuint32_t es[5] = {1, 1, 1, 1, 1};
    enc(&p.tmXh, CU_TENSOR_MAP_DATA_TYPE_BFLOAT16, 5, const_cast<bf16*>(x) + 240 * 1024, dims, strides, box, es, CU_TENSOR_MAP_INTERLEAVE_NONE,
        CU_TENSOR_MAP_SWIZZLE_128B, CU_TENSOR_MAP_L2_PROMOTION_L2_128B, CU_TENSOR_MAP_FLOAT_OOB_FILL_NONE);
  }
  make_tm(enc, &p.tmAbM, abT, 2048, 2048, 128, 16, CU_TENSOR_MAP_SWIZZLE_32B, CU_TENSOR_MAP_L2_PROMOTION_NONE);
  make_tm_rows(enc, &p.tmWM0, d_in[1], 2048, 128, 16, CU_TENSOR_MAP_SWIZZLE_32B);
  make_tm_rows(enc, &p.tmWM1, d_in[2], 2048, 128, 16, CU_TENSOR_MAP_SWIZZLE_32B);
  make_tm(enc, &p.tmG, d_in[7], 1024, 3584, 128, 32, CU_TENSOR_MAP_SWIZZLE_64B);
  make_tm(enc, &p.tmU, d_in[8], 1024, 3584, 128, 32, CU_TENSOR_MAP_SWIZZLE_64B);
  make_tm(enc, &p.tmDn, d_in[9], 3584, 1024, 32, 64, CU_TENSOR_MAP_SWIZZLE_128B);
  p.x = x; p.Dre = (const bf16*)d_in[3]; p.Dim = (const bf16*)d_in[4];
  p.wr = (const bf16*)d_in[6]; p.wdown = (const bf16*)d_in[9]; p.wgate = (const bf16*)d_in[7]; p.wup = (const bf16*)d_in[8];
  p.out = (bf16*)d_out; p.s = (Scratch*)abT;
  if (map == 1) fnet_moe_kernel<1><<<128, 384, SMEM_TOTAL>>>(p);
  else fnet_moe_kernel<0><<<132, 384, SMEM_TOTAL>>>(p);
}
```

```cpp
#include <cuda.h>
#include <cuda_runtime.h>
#include <cuda_bf16.h>
#include <stdint.h>
#include <type_traits>

typedef __nv_bfloat16 bf16;

constexpr int NX0 = 240;
constexpr int REG_C = 232, REG_P = 40;
__host__ __device__ constexpr int row_of(int p) { return (p & 1) * 1024 + ((p >> 1) & 1) * 512 + (p >> 2); }
__host__ __device__ constexpr int group_of(int row) { return (row & 511) >> 5; }
__device__ __forceinline__ int sigma_of(int tau, int r) { return r + (r >= tau); }
__device__ __forceinline__ int kblock(int tau, int j) {
  const int i = j - 4, c = (i * 37) >> 8;
  return j < 4 ? tau * 4 + j : sigma_of(tau, i - 7 * c) * 4 + c;
}
constexpr int GAP1 = 300, GAP2 = 600;
constexpr int HL_N = 2;
constexpr int AUX_DELAY = 250;
constexpr int PF_K0 = 8, PF_N0 = 2, PF_K1 = 24;
constexpr int WPF_K0 = 12, WPF_N = 10;
constexpr int WPF2_K = 44, WPF2_N = 4;
constexpr int PUB_K1 = 21;
constexpr int NREG_H = 5;
constexpr int MR_K0 = 29, MR_LAG = 0;
constexpr int MINI_PF_K = 35, MINI_LOAD_K = 43, MINI_K = 42;
constexpr int RESET_K = 37;
constexpr int SEND_FIRST = 2;
constexpr int GATHER_NS = 400;
constexpr int MOE_PACE_CLK = 300;
constexpr int OUT_PACE_CLK = 70;
constexpr int HOP1_DELAY = 150, HOP3_DELAY = 450;
constexpr int SPEC_MIN = 10;
constexpr int IDLE_WAIT_CLK = 1200;
__host__ __device__ constexpr int mr_k(int h) { return MR_K0 + 2 * h + MR_LAG * (h >> 1); }
constexpr int A_BYTES = 128 * 64 * 2;
constexpr int B_BYTES = 256 * 64 * 2;
constexpr int ST_BYTES = A_BYTES + B_BYTES;
constexpr int OFF_XCH = 4 * ST_BYTES;
constexpr int OFF_BAR = OFF_XCH + 32768;
constexpr int OFF_WR = OFF_BAR + 384;
constexpr int OFF_RS = OFF_WR + 384;
constexpr int OFF_PUB = OFF_RS + 640;
constexpr int OFF_MISC = OFF_PUB + 768;
constexpr int SMEM_TOTAL = OFF_MISC + 256;
constexpr int OFF_WSUM = OFF_MISC, OFF_TAG = OFF_MISC + 4;
constexpr int OFF_SEEN = OFF_MISC + 8;
constexpr int OFF_KV = OFF_MISC + 12;
constexpr int OFF_WKEY = OFF_MISC + 32;
constexpr int OFF_MINI = OFF_XCH;
constexpr int OFF_EXA = OFF_XCH;
constexpr int OFF_EXB = OFF_XCH + 4096;
__host__ __device__ constexpr int chunk_off(int c, int w) { return (c == 1 ? 3 * ST_BYTES : c == 2 ? OFF_XCH : OFF_XCH + 16384) + w * 8192; }
__host__ __device__ constexpr int late_off(int i) { return i < 4 ? i * 16384 : 2 * ST_BYTES + A_BYTES + (i - 4) * 16384; }
__host__ __device__ constexpr int round_off(int h) { return h < NREG_H + 2 ? OFF_XCH + (h & 1) * 16384 : late_off(h - NREG_H - 2); }
__host__ __device__ constexpr int down_off(int i) { return late_off(6 - NREG_H + i); }
constexpr int OFF_PEER = ST_BYTES + A_BYTES;
constexpr int OFF_OUT = 3 * ST_BYTES + A_BYTES;
constexpr int OFF_XSEL = OFF_PEER;
constexpr int OFF_HSEL = OFF_PEER + 4096;
constexpr int OFF_GP = OFF_PEER + 8192;
constexpr int OFF_FIN = OFF_PEER + 9216;
__device__ __forceinline__ int slot_of(int k) { return k & 3; }
__device__ __forceinline__ int use_of(int k) { return k >> 2; }
enum { B_FULL = 0, B_EMPTY = 4, B_EPI = 8, B_STD = 12, B_EPI0B = 16, B_LATE = 17, B_STAT = 18, B_XCH = 19, B_MR = 20  , B_GU = 22,
       B_DN = 23, B_AUX = 24  , B_OUT = 26, B_KEY = 27, B_XS = 28, B_MINI = 29, B_PUB1 = 30, B_COUNT = 31 };
enum { NB_TURN0 = 1, NB_TURN1 = 2, NB_WG0 = 3, NB_BOTH = 5, NB_AUX = 6 };

struct Scratch {
  bf16 abT[2048 * 2048];
  uint2 xstat[2048];
  uint2 dsum[2048];
  uint4 abflag[16 * 8 * 2];
  uint4 hflag[16 * 2];
  uint4 hstat[16 * 8 * 128];
  uint4 cand[16 * 256];
  uint4 key[8 * 16 * 2];
  uint4 ypart[128 * 256];
  uint32_t epoch;
};
__device__ __align__(1024) Scratch g_scratch;

struct Params {
  Scratch* s; bf16* out;
  const bf16* x; const bf16* Dre; const bf16* Dim; const bf16* wr; const bf16* wdown; const bf16* wgate; const bf16* wup;
  CUtensorMap tmX, tmD0, tmD1, tmXr, tmAbS, tmAbL, tmW0, tmW1, tmOut, tmG, tmU, tmDn, tmXh, tmAbM, tmWM0, tmWM1;
};

#define SPIN_LIMIT (1u << 14)
#define MBAR_LIMIT (1u << 10)
__device__ __forceinline__ uint32_t smem_u32(const void* p) { return (uint32_t)__cvta_generic_to_shared(p); }
__device__ __forceinline__ void mbar_init(uint32_t bar, uint32_t cnt) { asm volatile("mbarrier.init.shared::cta.b64 [%0], %1;" :: "r"(bar), "r"(cnt) : "memory"); }
__device__ __forceinline__ void mbar_expect_tx(uint32_t bar, uint32_t bytes) { asm volatile("mbarrier.arrive.expect_tx.shared::cta.b64 _, [%0], %1;" :: "r"(bar), "r"(bytes) : "memory"); }
__device__ __forceinline__ void mbar_arrive(uint32_t bar) { asm volatile("mbarrier.arrive.shared::cta.b64 _, [%0];" :: "r"(bar) : "memory"); }
__device__ __forceinline__ void mbar_wait(uint32_t bar, uint32_t parity) {
  uint32_t ok, n = 0;
  do {
    asm volatile("{\n.reg .pred p;\nmbarrier.try_wait.parity.shared::cta.b64 p, [%1], %2;\nselp.u32 %0, 1, 0, p;\n}\n" : "=r"(ok) : "r"(bar), "r"(parity) : "memory");
  } while (!ok && ++n < MBAR_LIMIT);
}
__device__ __forceinline__ void mbar_wait_cluster(uint32_t bar, uint32_t parity) {
  uint32_t ok, n = 0;
  do {
    asm volatile("{\n.reg .pred p;\nmbarrier.try_wait.parity.acquire.cluster.shared::cta.b64 p, [%1], %2;\nselp.u32 %0, 1, 0, p;\n}\n" : "=r"(ok) : "r"(bar), "r"(parity) : "memory");
  } while (!ok && ++n < MBAR_LIMIT);
}
__device__ __forceinline__ void tma_load_2d(uint32_t dst, const CUtensorMap* tm, uint32_t bar, int c0, int c1) {
  asm volatile("cp.async.bulk.tensor.2d.shared::cluster.global.mbarrier::complete_tx::bytes [%0], [%1, {%3, %4}], [%2];"
    :: "r"(dst), "l"(tm), "r"(bar), "r"(c0), "r"(c1) : "memory");
}
__device__ __forceinline__ void tma_load_2d_hint(uint32_t dst, const CUtensorMap* tm, uint32_t bar, int c0, int c1, uint64_t pol) {
  asm volatile("cp.async.bulk.tensor.2d.shared::cluster.global.mbarrier::complete_tx::bytes.L2::cache_hint [%0], [%1, {%3, %4}], [%2], %5;"
    :: "r"(dst), "l"(tm), "r"(bar), "r"(c0), "r"(c1), "l"(pol) : "memory");
}
__device__ __forceinline__ uint64_t policy_evict_first() { uint64_t p; asm volatile("createpolicy.fractional.L2::evict_first.b64 %0, 1.0;" : "=l"(p)); return p; }
__device__ __forceinline__ void tma_store_2d(const CUtensorMap* tm, uint32_t src, int c0, int c1) {
  asm volatile("cp.async.bulk.tensor.2d.global.shared::cta.bulk_group [%0, {%2, %3}], [%1];" :: "l"(tm), "r"(src), "r"(c0), "r"(c1) : "memory");
}
__device__ __forceinline__ void tma_prefetch_2d(const CUtensorMap* tm, int c0, int c1) {
  asm volatile("cp.async.bulk.prefetch.tensor.2d.L2.global.tile [%0, {%1, %2}];" :: "l"(tm), "r"(c0), "r"(c1) : "memory");
}
__device__ __forceinline__ void bulk_load(uint32_t dst, const void* src, uint32_t bytes, uint32_t bar) {
  asm volatile("cp.async.bulk.shared::cluster.global.mbarrier::complete_tx::bytes [%0], [%1], %2, [%3];" :: "r"(dst), "l"(src), "r"(bytes), "r"(bar) : "memory");
}
__device__ __forceinline__ void bulk_commit() { asm volatile("cp.async.bulk.commit_group;" ::: "memory"); }
__device__ __forceinline__ void bulk_wait_all() { asm volatile("cp.async.bulk.wait_group 0;" ::: "memory"); }
__device__ __forceinline__ void bulk_wait_release() {
  bulk_wait_all();
  asm volatile("fence.proxy.async.global;" ::: "memory");
  asm volatile("fence.acq_rel.gpu;" ::: "memory");
}
__device__ __forceinline__ void fence_async_smem() { asm volatile("fence.proxy.async.shared::cta;" ::: "memory"); }
__device__ __forceinline__ void wgmma_fence() { asm volatile("wgmma.fence.sync.aligned;" ::: "memory"); }
__device__ __forceinline__ void wgmma_commit() { asm volatile("wgmma.commit_group.sync.aligned;" ::: "memory"); }
__device__ __forceinline__ void wgmma_wait0() { asm volatile("wgmma.wait_group.sync.aligned 0;" ::: "memory"); }
__device__ __forceinline__ void bar_sync(int id, int n) { asm volatile("bar.sync %0, %1;" :: "r"(id), "r"(n) : "memory"); }
__device__ __forceinline__ void bar_arrive(int id, int n) { asm volatile("bar.arrive %0, %1;" :: "r"(id), "r"(n) : "memory"); }
template<int R> __device__ __forceinline__ void reg_inc() { asm volatile("setmaxnreg.inc.sync.aligned.u32 %0;" :: "n"(R)); }
template<int R> __device__ __forceinline__ void reg_dec() { asm volatile("setmaxnreg.dec.sync.aligned.u32 %0;" :: "n"(R)); }
__device__ __forceinline__ bool elect_one() {
  uint32_t p;
  asm volatile("{\n.reg .pred q;\nelect.sync _|q, 0xffffffff;\nselp.u32 %0, 1, 0, q;\n}\n" : "=r"(p));
  return p != 0;
}
__device__ __forceinline__ uint32_t mapa(uint32_t addr, uint32_t cta) { uint32_t r; asm volatile("mapa.shared::cluster.u32 %0, %1, %2;" : "=r"(r) : "r"(addr), "r"(cta)); return r; }
__device__ __forceinline__ void st_async_v4(uint32_t addr, uint32_t bar, uint32_t a, uint32_t b, uint32_t c, uint32_t d) {
  asm volatile("st.async.weak.shared::cluster.mbarrier::complete_tx::bytes.v4.b32 [%0], {%2, %3, %4, %5}, [%1];" :: "r"(addr), "r"(bar), "r"(a), "r"(b), "r"(c), "r"(d) : "memory");
}
__device__ __forceinline__ void stsm_x4(uint32_t addr, uint32_t a, uint32_t b, uint32_t c, uint32_t d) {
  asm volatile("stmatrix.sync.aligned.m8n8.x4.shared.b16 [%0], {%1, %2, %3, %4};" :: "r"(addr), "r"(a), "r"(b), "r"(c), "r"(d));
}
__device__ __forceinline__ uint4 lds128_v(uint32_t addr) { uint4 v; asm volatile("ld.shared.v4.b32 {%0, %1, %2, %3}, [%4];" : "=r"(v.x), "=r"(v.y), "=r"(v.z), "=r"(v.w) : "r"(addr)); return v; }
extern __shared__ __align__(1024) uint8_t smem_raw[];
template<class T> __device__ __forceinline__ T& smem_at(uint32_t addr) { return *reinterpret_cast<T*>(__cvta_shared_to_generic(addr)); }
#define SM_(T, off) smem_at<T>(sb + (off))
__device__ __forceinline__ uint4 ldg_nc128(const void* p) { uint4 v; asm volatile("ld.global.nc.v4.b32 {%0, %1, %2, %3}, [%4];" : "=r"(v.x), "=r"(v.y), "=r"(v.z), "=r"(v.w) : "l"(p)); return v; }
__device__ __forceinline__ void pkt_st128(void* p, uint32_t a, uint32_t b, uint32_t c, uint32_t d) {
  asm volatile("{\n.reg .b128 v;\n.reg .b64 lo, hi;\nmov.b64 lo, {%1, %2};\nmov.b64 hi, {%3, %4};\nmov.b128 v, {lo, hi};\nst.relaxed.gpu.global.b128 [%0], v;\n}\n"
    :: "l"(p), "r"(a), "r"(b), "r"(c), "r"(d) : "memory");
}
__device__ __forceinline__ uint4 pkt_ld128(const void* p) {
  uint4 r;
  asm volatile("{\n.reg .b128 v;\n.reg .b64 lo, hi;\nld.relaxed.gpu.global.b128 v, [%4];\nmov.b128 {lo, hi}, v;\nmov.b64 {%0, %1}, lo;\nmov.b64 {%2, %3}, hi;\n}\n"
    : "=r"(r.x), "=r"(r.y), "=r"(r.z), "=r"(r.w) : "l"(p) : "memory");
  return r;
}
__device__ __forceinline__ void pkt_ld128_if(uint4& r, const void* p, bool cond) {
  asm volatile("{\n.reg .pred q;\n.reg .b64 lo, hi;\nsetp.ne.b32 q, %5, 0;\nmov.b64 lo, {%0, %1};\nmov.b64 hi, {%2, %3};\n"
               "@q ld.relaxed.gpu.global.v2.b64 {lo, hi}, [%4];\nmov.b64 {%0, %1}, lo;\nmov.b64 {%2, %3}, hi;\n}\n"
    : "+r"(r.x), "+r"(r.y), "+r"(r.z), "+r"(r.w) : "l"(p), "r"((uint32_t)cond) : "memory");
}
__device__ __forceinline__ void pkt_st64(void* p, uint32_t a, uint32_t b) {
  asm volatile("{\n.reg .b64 v;\nmov.b64 v, {%1, %2};\nst.relaxed.gpu.global.b64 [%0], v;\n}\n" :: "l"(p), "r"(a), "r"(b) : "memory");
}
__device__ __forceinline__ uint2 pkt_ld64(const void* p) {
  uint2 r;
  asm volatile("{\n.reg .b64 v;\nld.relaxed.gpu.global.b64 v, [%2];\nmov.b64 {%0, %1}, v;\n}\n" : "=r"(r.x), "=r"(r.y) : "l"(p) : "memory");
  return r;
}
__device__ __forceinline__ uint32_t ld_relaxed32(const void* p) { uint32_t v; asm volatile("ld.relaxed.gpu.global.b32 %0, [%1];" : "=r"(v) : "l"(p) : "memory"); return v; }
__device__ __forceinline__ uint32_t ld_acquire32(const void* p) { uint32_t v; asm volatile("ld.acquire.gpu.global.b32 %0, [%1];" : "=r"(v) : "l"(p) : "memory"); return v; }
__device__ __forceinline__ void st_relaxed32(void* p, uint32_t v) { asm volatile("st.relaxed.gpu.global.b32 [%0], %1;" :: "l"(p), "r"(v) : "memory"); }
__device__ __forceinline__ uint32_t code_of(uint32_t tag) { return tag % 3u + 1u; }
__device__ __forceinline__ uint32_t with_bit(float v, uint32_t bit) { return (__float_as_uint(v) & ~1u) | (bit & 1u); }
__device__ __forceinline__ uint32_t pair_code(uint32_t a, uint32_t b) { return (a & 1u) | ((b & 1u) << 1); }
__device__ __forceinline__ uint32_t pack_bf16(float lo, float hi) { uint32_t r; asm("cvt.rn.bf16x2.f32 %0, %1, %2;" : "=r"(r) : "f"(hi), "f"(lo)); return r; }
__device__ __forceinline__ float bf_lo(uint32_t v) { return __uint_as_float(v << 16); }
__device__ __forceinline__ float bf_hi(uint32_t v) { return __uint_as_float(v & 0xFFFF0000u); }
__device__ __forceinline__ float bf16r(float x) { return __uint_as_float(pack_bf16(0.f, x)); }
__device__ __forceinline__ uint32_t badd2(uint32_t a, uint32_t b) { uint32_t r; asm("add.rn.bf16x2 %0, %1, %2;" : "=r"(r) : "r"(a), "r"(b)); return r; }
__device__ __forceinline__ uint32_t bmul2(uint32_t a, uint32_t b) { uint32_t r; asm("mul.rn.bf16x2 %0, %1, %2;" : "=r"(r) : "r"(a), "r"(b)); return r; }
__device__ __forceinline__ float warp_sum(float v) {
#pragma unroll
  for (int o = 16; o > 0; o >>= 1) v += __shfl_xor_sync(0xffffffffu, v, o);
  return v;
}
__device__ __forceinline__ uint64_t make_desc(uint32_t addr) {
  return (uint64_t)((addr & 0x3FFFF) >> 4) | ((uint64_t)1 << 16) | ((uint64_t)64 << 32) | ((uint64_t)1 << 62);
}
__device__ __forceinline__ uint64_t make_desc_noswz(uint32_t addr) {
  return (uint64_t)((addr & 0x3FFFF) >> 4) | ((uint64_t)8 << 16) | ((uint64_t)16 << 32);
}
__device__ __forceinline__ uint64_t make_desc_32b(uint32_t addr) {
  return (uint64_t)((addr & 0x3FFFF) >> 4) | ((uint64_t)1 << 16) | ((uint64_t)16 << 32) | ((uint64_t)3 << 62);
}
__device__ __forceinline__ void wgmma_n256(float (&d)[128], uint64_t da, uint64_t db, int scale_d) {
  asm volatile("{\n.reg .pred p;\nsetp.ne.b32 p, %130, 0;\n"
    "wgmma.mma_async.sync.aligned.m64n256k16.f32.bf16.bf16 "
    "{%0, %1, %2, %3, %4, %5, %6, %7, %8, %9, %10, %11, %12, %13, %14, %15, %16, %17, %18, %19, %20, %21, %22, %23, %24, %25, %26, %27, %28, %29, %30, %31, "
    "%32, %33, %34, %35, %36, %37, %38, %39, %40, %41, %42, %43, %44, %45, %46, %47, %48, %49, %50, %51, %52, %53, %54, %55, %56, %57, %58, %59, %60, %61, %62, %63, "
    "%64, %65, %66, %67, %68, %69, %70, %71, %72, %73, %74, %75, %76, %77, %78, %79, %80, %81, %82, %83, %84, %85, %86, %87, %88, %89, %90, %91, %92, %93, %94, %95, "
    "%96, %97, %98, %99, %100, %101, %102, %103, %104, %105, %106, %107, %108, %109, %110, %111, %112, %113, %114, %115, %116, %117, %118, %119, %120, %121, %122, %123, %124, %125, %126, %127}, "
    "%128, %129, p, 1, 1, 0, 0;\n}\n"
    : "+f"(d[0]), "+f"(d[1]), "+f"(d[2]), "+f"(d[3]), "+f"(d[4]), "+f"(d[5]), "+f"(d[6]), "+f"(d[7]),
      "+f"(d[8]), "+f"(d[9]), "+f"(d[10]), "+f"(d[11]), "+f"(d[12]), "+f"(d[13]), "+f"(d[14]), "+f"(d[15]),
      "+f"(d[16]), "+f"(d[17]), "+f"(d[18]), "+f"(d[19]), "+f"(d[20]), "+f"(d[21]), "+f"(d[22]), "+f"(d[23]),
      "+f"(d[24]), "+f"(d[25]), "+f"(d[26]), "+f"(d[27]), "+f"(d[28]), "+f"(d[29]), "+f"(d[30]), "+f"(d[31]),
      "+f"(d[32]), "+f"(d[33]), "+f"(d[34]), "+f"(d[35]), "+f"(d[36]), "+f"(d[37]), "+f"(d[38]), "+f"(d[39]),
      "+f"(d[40]), "+f"(d[41]), "+f"(d[42]), "+f"(d[43]), "+f"(d[44]), "+f"(d[45]), "+f"(d[46]), "+f"(d[47]),
      "+f"(d[48]), "+f"(d[49]), "+f"(d[50]), "+f"(d[51]), "+f"(d[52]), "+f"(d[53]), "+f"(d[54]), "+f"(d[55]),
      "+f"(d[56]), "+f"(d[57]), "+f"(d[58]), "+f"(d[59]), "+f"(d[60]), "+f"(d[61]), "+f"(d[62]), "+f"(d[63]),
      "+f"(d[64]), "+f"(d[65]), "+f"(d[66]), "+f"(d[67]), "+f"(d[68]), "+f"(d[69]), "+f"(d[70]), "+f"(d[71]),
      "+f"(d[72]), "+f"(d[73]), "+f"(d[74]), "+f"(d[75]), "+f"(d[76]), "+f"(d[77]), "+f"(d[78]), "+f"(d[79]),
      "+f"(d[80]), "+f"(d[81]), "+f"(d[82]), "+f"(d[83]), "+f"(d[84]), "+f"(d[85]), "+f"(d[86]), "+f"(d[87]),
      "+f"(d[88]), "+f"(d[89]), "+f"(d[90]), "+f"(d[91]), "+f"(d[92]), "+f"(d[93]), "+f"(d[94]), "+f"(d[95]),
      "+f"(d[96]), "+f"(d[97]), "+f"(d[98]), "+f"(d[99]), "+f"(d[100]), "+f"(d[101]), "+f"(d[102]), "+f"(d[103]),
      "+f"(d[104]), "+f"(d[105]), "+f"(d[106]), "+f"(d[107]), "+f"(d[108]), "+f"(d[109]), "+f"(d[110]), "+f"(d[111]),
      "+f"(d[112]), "+f"(d[113]), "+f"(d[114]), "+f"(d[115]), "+f"(d[116]), "+f"(d[117]), "+f"(d[118]), "+f"(d[119]),
      "+f"(d[120]), "+f"(d[121]), "+f"(d[122]), "+f"(d[123]), "+f"(d[124]), "+f"(d[125]), "+f"(d[126]), "+f"(d[127])
    : "l"(da), "l"(db), "r"(scale_d));
}
__device__ __forceinline__ void wgmma_g1(float (&d)[128], uint64_t da, uint64_t db, int scale_d) { wgmma_n256(d, da, db, scale_d); }
__device__ __forceinline__ void wgmma_g1(float (&d)[120], uint64_t da, uint64_t db, int scale_d) {
  asm volatile("{\n.reg .pred p;\nsetp.ne.b32 p, %122, 0;\n"
    "wgmma.mma_async.sync.aligned.m64n240k16.f32.bf16.bf16 "
    "{%0, %1, %2, %3, %4, %5, %6, %7, %8, %9, %10, %11, %12, %13, %14, %15, %16, %17, %18, %19, %20, %21, %22, %23, %24, %25, %26, %27, %28, %29, %30, %31, %32, %33, %34, %35, %36, %37, %38, %39, %40, %41, %42, %43, %44, %45, %46, %47, %48, %49, %50, %51, %52, %53, %54, %55, %56, %57, %58, %59, %60, %61, %62, %63, %64, %65, %66, %67, %68, %69, %70, %71, %72, %73, %74, %75, %76, %77, %78, %79, %80, %81, %82, %83, %84, %85, %86, %87, %88, %89, %90, %91, %92, %93, %94, %95, %96, %97, %98, %99, %100, %101, %102, %103, %104, %105, %106, %107, %108, %109, %110, %111, %112, %113, %114, %115, %116, %117, %118, %119}, "
    "%120, %121, p, 1, 1, 0, 0;\n}\n"
    : "+f"(d[0]), "+f"(d[1]), "+f"(d[2]), "+f"(d[3]), "+f"(d[4]), "+f"(d[5]), "+f"(d[6]), "+f"(d[7]), "+f"(d[8]), "+f"(d[9]), "+f"(d[10]), "+f"(d[11]), "+f"(d[12]), "+f"(d[13]), "+f"(d[14]), "+f"(d[15]), "+f"(d[16]), "+f"(d[17]), "+f"(d[18]), "+f"(d[19]), "+f"(d[20]), "+f"(d[21]), "+f"(d[22]), "+f"(d[23]), "+f"(d[24]), "+f"(d[25]), "+f"(d[26]), "+f"(d[27]), "+f"(d[28]), "+f"(d[29]), "+f"(d[30]), "+f"(d[31]), "+f"(d[32]), "+f"(d[33]), "+f"(d[34]), "+f"(d[35]), "+f"(d[36]), "+f"(d[37]), "+f"(d[38]), "+f"(d[39]), "+f"(d[40]), "+f"(d[41]), "+f"(d[42]), "+f"(d[43]), "+f"(d[44]), "+f"(d[45]), "+f"(d[46]), "+f"(d[47]), "+f"(d[48]), "+f"(d[49]), "+f"(d[50]), "+f"(d[51]), "+f"(d[52]), "+f"(d[53]), "+f"(d[54]), "+f"(d[55]), "+f"(d[56]), "+f"(d[57]), "+f"(d[58]), "+f"(d[59]), "+f"(d[60]), "+f"(d[61]), "+f"(d[62]), "+f"(d[63]), "+f"(d[64]), "+f"(d[65]), "+f"(d[66]), "+f"(d[67]), "+f"(d[68]), "+f"(d[69]), "+f"(d[70]), "+f"(d[71]), "+f"(d[72]), "+f"(d[73]), "+f"(d[74]), "+f"(d[75]), "+f"(d[76]), "+f"(d[77]), "+f"(d[78]), "+f"(d[79]), "+f"(d[80]), "+f"(d[81]), "+f"(d[82]), "+f"(d[83]), "+f"(d[84]), "+f"(d[85]), "+f"(d[86]), "+f"(d[87]), "+f"(d[88]), "+f"(d[89]), "+f"(d[90]), "+f"(d[91]), "+f"(d[92]), "+f"(d[93]), "+f"(d[94]), "+f"(d[95]), "+f"(d[96]), "+f"(d[97]), "+f"(d[98]), "+f"(d[99]), "+f"(d[100]), "+f"(d[101]), "+f"(d[102]), "+f"(d[103]), "+f"(d[104]), "+f"(d[105]), "+f"(d[106]), "+f"(d[107]), "+f"(d[108]), "+f"(d[109]), "+f"(d[110]), "+f"(d[111]), "+f"(d[112]), "+f"(d[113]), "+f"(d[114]), "+f"(d[115]), "+f"(d[116]), "+f"(d[117]), "+f"(d[118]), "+f"(d[119])
    : "l"(da), "l"(db), "r"(scale_d));
}
__device__ __forceinline__ void wgmma_g1(float (&d)[32], uint64_t da, uint64_t db, int scale_d) {
  asm volatile("{\n.reg .pred p;\nsetp.ne.b32 p, %34, 0;\n"
    "wgmma.mma_async.sync.aligned.m64n64k16.f32.bf16.bf16 "
    "{%0, %1, %2, %3, %4, %5, %6, %7, %8, %9, %10, %11, %12, %13, %14, %15, %16, %17, %18, %19, %20, %21, %22, %23, %24, %25, %26, %27, %28, %29, %30, %31}, "
    "%32, %33, p, 1, 1, 0, 0;\n}\n"
    : "+f"(d[0]), "+f"(d[1]), "+f"(d[2]), "+f"(d[3]), "+f"(d[4]), "+f"(d[5]), "+f"(d[6]), "+f"(d[7]), "+f"(d[8]), "+f"(d[9]), "+f"(d[10]), "+f"(d[11]), "+f"(d[12]), "+f"(d[13]), "+f"(d[14]), "+f"(d[15]), "+f"(d[16]), "+f"(d[17]), "+f"(d[18]), "+f"(d[19]), "+f"(d[20]), "+f"(d[21]), "+f"(d[22]), "+f"(d[23]), "+f"(d[24]), "+f"(d[25]), "+f"(d[26]), "+f"(d[27]), "+f"(d[28]), "+f"(d[29]), "+f"(d[30]), "+f"(d[31])
    : "l"(da), "l"(db), "r"(scale_d));
}
__device__ __forceinline__ void wgmma_g1(float (&d)[88], uint64_t da, uint64_t db, int scale_d) {
  asm volatile("{\n.reg .pred p;\nsetp.ne.b32 p, %90, 0;\n"
    "wgmma.mma_async.sync.aligned.m64n176k16.f32.bf16.bf16 "
    "{%0, %1, %2, %3, %4, %5, %6, %7, %8, %9, %10, %11, %12, %13, %14, %15, %16, %17, %18, %19, %20, %21, %22, %23, %24, %25, %26, %27, %28, %29, %30, %31, %32, %33, %34, %35, %36, %37, %38, %39, %40, %41, %42, %43, %44, %45, %46, %47, %48, %49, %50, %51, %52, %53, %54, %55, %56, %57, %58, %59, %60, %61, %62, %63, %64, %65, %66, %67, %68, %69, %70, %71, %72, %73, %74, %75, %76, %77, %78, %79, %80, %81, %82, %83, %84, %85, %86, %87}, "
    "%88, %89, p, 1, 1, 0, 0;\n}\n"
    : "+f"(d[0]), "+f"(d[1]), "+f"(d[2]), "+f"(d[3]), "+f"(d[4]), "+f"(d[5]), "+f"(d[6]), "+f"(d[7]), "+f"(d[8]), "+f"(d[9]), "+f"(d[10]), "+f"(d[11]), "+f"(d[12]), "+f"(d[13]), "+f"(d[14]), "+f"(d[15]), "+f"(d[16]), "+f"(d[17]), "+f"(d[18]), "+f"(d[19]), "+f"(d[20]), "+f"(d[21]), "+f"(d[22]), "+f"(d[23]), "+f"(d[24]), "+f"(d[25]), "+f"(d[26]), "+f"(d[27]), "+f"(d[28]), "+f"(d[29]), "+f"(d[30]), "+f"(d[31]), "+f"(d[32]), "+f"(d[33]), "+f"(d[34]), "+f"(d[35]), "+f"(d[36]), "+f"(d[37]), "+f"(d[38]), "+f"(d[39]), "+f"(d[40]), "+f"(d[41]), "+f"(d[42]), "+f"(d[43]), "+f"(d[44]), "+f"(d[45]), "+f"(d[46]), "+f"(d[47]), "+f"(d[48]), "+f"(d[49]), "+f"(d[50]), "+f"(d[51]), "+f"(d[52]), "+f"(d[53]), "+f"(d[54]), "+f"(d[55]), "+f"(d[56]), "+f"(d[57]), "+f"(d[58]), "+f"(d[59]), "+f"(d[60]), "+f"(d[61]), "+f"(d[62]), "+f"(d[63]), "+f"(d[64]), "+f"(d[65]), "+f"(d[66]), "+f"(d[67]), "+f"(d[68]), "+f"(d[69]), "+f"(d[70]), "+f"(d[71]), "+f"(d[72]), "+f"(d[73]), "+f"(d[74]), "+f"(d[75]), "+f"(d[76]), "+f"(d[77]), "+f"(d[78]), "+f"(d[79]), "+f"(d[80]), "+f"(d[81]), "+f"(d[82]), "+f"(d[83]), "+f"(d[84]), "+f"(d[85]), "+f"(d[86]), "+f"(d[87])
    : "l"(da), "l"(db), "r"(scale_d));
}
__device__ __forceinline__ void wgmma_g1(float (&d)[96], uint64_t da, uint64_t db, int scale_d) {
  asm volatile("{\n.reg .pred p;\nsetp.ne.b32 p, %98, 0;\n"
    "wgmma.mma_async.sync.aligned.m64n192k16.f32.bf16.bf16 "
    "{%0, %1, %2, %3, %4, %5, %6, %7, %8, %9, %10, %11, %12, %13, %14, %15, %16, %17, %18, %19, %20, %21, %22, %23, %24, %25, %26, %27, %28, %29, %30, %31, %32, %33, %34, %35, %36, %37, %38, %39, %40, %41, %42, %43, %44, %45, %46, %47, %48, %49, %50, %51, %52, %53, %54, %55, %56, %57, %58, %59, %60, %61, %62, %63, %64, %65, %66, %67, %68, %69, %70, %71, %72, %73, %74, %75, %76, %77, %78, %79, %80, %81, %82, %83, %84, %85, %86, %87, %88, %89, %90, %91, %92, %93, %94, %95}, "
    "%96, %97, p, 1, 1, 0, 0;\n}\n"
    : "+f"(d[0]), "+f"(d[1]), "+f"(d[2]), "+f"(d[3]), "+f"(d[4]), "+f"(d[5]), "+f"(d[6]), "+f"(d[7]), "+f"(d[8]), "+f"(d[9]), "+f"(d[10]), "+f"(d[11]), "+f"(d[12]), "+f"(d[13]), "+f"(d[14]), "+f"(d[15]), "+f"(d[16]), "+f"(d[17]), "+f"(d[18]), "+f"(d[19]), "+f"(d[20]), "+f"(d[21]), "+f"(d[22]), "+f"(d[23]), "+f"(d[24]), "+f"(d[25]), "+f"(d[26]), "+f"(d[27]), "+f"(d[28]), "+f"(d[29]), "+f"(d[30]), "+f"(d[31]), "+f"(d[32]), "+f"(d[33]), "+f"(d[34]), "+f"(d[35]), "+f"(d[36]), "+f"(d[37]), "+f"(d[38]), "+f"(d[39]), "+f"(d[40]), "+f"(d[41]), "+f"(d[42]), "+f"(d[43]), "+f"(d[44]), "+f"(d[45]), "+f"(d[46]), "+f"(d[47]), "+f"(d[48]), "+f"(d[49]), "+f"(d[50]), "+f"(d[51]), "+f"(d[52]), "+f"(d[53]), "+f"(d[54]), "+f"(d[55]), "+f"(d[56]), "+f"(d[57]), "+f"(d[58]), "+f"(d[59]), "+f"(d[60]), "+f"(d[61]), "+f"(d[62]), "+f"(d[63]), "+f"(d[64]), "+f"(d[65]), "+f"(d[66]), "+f"(d[67]), "+f"(d[68]), "+f"(d[69]), "+f"(d[70]), "+f"(d[71]), "+f"(d[72]), "+f"(d[73]), "+f"(d[74]), "+f"(d[75]), "+f"(d[76]), "+f"(d[77]), "+f"(d[78]), "+f"(d[79]), "+f"(d[80]), "+f"(d[81]), "+f"(d[82]), "+f"(d[83]), "+f"(d[84]), "+f"(d[85]), "+f"(d[86]), "+f"(d[87]), "+f"(d[88]), "+f"(d[89]), "+f"(d[90]), "+f"(d[91]), "+f"(d[92]), "+f"(d[93]), "+f"(d[94]), "+f"(d[95])
    : "l"(da), "l"(db), "r"(scale_d));
}
__device__ __forceinline__ void wgmma_n256_rs(float (&d)[128], uint32_t a0, uint32_t a1, uint32_t a2, uint32_t a3, uint64_t db, int scale_d) {
  asm volatile("{\n.reg .pred p;\nsetp.ne.b32 p, %133, 0;\n"
    "wgmma.mma_async.sync.aligned.m64n256k16.f32.bf16.bf16 "
    "{%0, %1, %2, %3, %4, %5, %6, %7, %8, %9, %10, %11, %12, %13, %14, %15, %16, %17, %18, %19, %20, %21, %22, %23, %24, %25, %26, %27, %28, %29, %30, %31, "
    "%32, %33, %34, %35, %36, %37, %38, %39, %40, %41, %42, %43, %44, %45, %46, %47, %48, %49, %50, %51, %52, %53, %54, %55, %56, %57, %58, %59, %60, %61, %62, %63, "
    "%64, %65, %66, %67, %68, %69, %70, %71, %72, %73, %74, %75, %76, %77, %78, %79, %80, %81, %82, %83, %84, %85, %86, %87, %88, %89, %90, %91, %92, %93, %94, %95, "
    "%96, %97, %98, %99, %100, %101, %102, %103, %104, %105, %106, %107, %108, %109, %110, %111, %112, %113, %114, %115, %116, %117, %118, %119, %120, %121, %122, %123, %124, %125, %126, %127}, "
    "{%128, %129, %130, %131}, %132, p, 1, 1, 0;\n}\n"
    : "+f"(d[0]), "+f"(d[1]), "+f"(d[2]), "+f"(d[3]), "+f"(d[4]), "+f"(d[5]), "+f"(d[6]), "+f"(d[7]),
      "+f"(d[8]), "+f"(d[9]), "+f"(d[10]), "+f"(d[11]), "+f"(d[12]), "+f"(d[13]), "+f"(d[14]), "+f"(d[15]),
      "+f"(d[16]), "+f"(d[17]), "+f"(d[18]), "+f"(d[19]), "+f"(d[20]), "+f"(d[21]), "+f"(d[22]), "+f"(d[23]),
      "+f"(d[24]), "+f"(d[25]), "+f"(d[26]), "+f"(d[27]), "+f"(d[28]), "+f"(d[29]), "+f"(d[30]), "+f"(d[31]),
      "+f"(d[32]), "+f"(d[33]), "+f"(d[34]), "+f"(d[35]), "+f"(d[36]), "+f"(d[37]), "+f"(d[38]), "+f"(d[39]),
      "+f"(d[40]), "+f"(d[41]), "+f"(d[42]), "+f"(d[43]), "+f"(d[44]), "+f"(d[45]), "+f"(d[46]), "+f"(d[47]),
      "+f"(d[48]), "+f"(d[49]), "+f"(d[50]), "+f"(d[51]), "+f"(d[52]), "+f"(d[53]), "+f"(d[54]), "+f"(d[55]),
      "+f"(d[56]), "+f"(d[57]), "+f"(d[58]), "+f"(d[59]), "+f"(d[60]), "+f"(d[61]), "+f"(d[62]), "+f"(d[63]),
      "+f"(d[64]), "+f"(d[65]), "+f"(d[66]), "+f"(d[67]), "+f"(d[68]), "+f"(d[69]), "+f"(d[70]), "+f"(d[71]),
      "+f"(d[72]), "+f"(d[73]), "+f"(d[74]), "+f"(d[75]), "+f"(d[76]), "+f"(d[77]), "+f"(d[78]), "+f"(d[79]),
      "+f"(d[80]), "+f"(d[81]), "+f"(d[82]), "+f"(d[83]), "+f"(d[84]), "+f"(d[85]), "+f"(d[86]), "+f"(d[87]),
      "+f"(d[88]), "+f"(d[89]), "+f"(d[90]), "+f"(d[91]), "+f"(d[92]), "+f"(d[93]), "+f"(d[94]), "+f"(d[95]),
      "+f"(d[96]), "+f"(d[97]), "+f"(d[98]), "+f"(d[99]), "+f"(d[100]), "+f"(d[101]), "+f"(d[102]), "+f"(d[103]),
      "+f"(d[104]), "+f"(d[105]), "+f"(d[106]), "+f"(d[107]), "+f"(d[108]), "+f"(d[109]), "+f"(d[110]), "+f"(d[111]),
      "+f"(d[112]), "+f"(d[113]), "+f"(d[114]), "+f"(d[115]), "+f"(d[116]), "+f"(d[117]), "+f"(d[118]), "+f"(d[119]),
      "+f"(d[120]), "+f"(d[121]), "+f"(d[122]), "+f"(d[123]), "+f"(d[124]), "+f"(d[125]), "+f"(d[126]), "+f"(d[127])
    : "r"(a0), "r"(a1), "r"(a2), "r"(a3), "l"(db), "r"(scale_d));
}
__device__ __forceinline__ void wgmma_n128(float (&d)[64], uint64_t da, uint64_t db, int scale_d = 1) {
  asm volatile("{\n.reg .pred p;\nsetp.ne.b32 p, %66, 0;\n"
    "wgmma.mma_async.sync.aligned.m64n128k16.f32.bf16.bf16 "
    "{%0, %1, %2, %3, %4, %5, %6, %7, %8, %9, %10, %11, %12, %13, %14, %15, %16, %17, %18, %19, %20, %21, %22, %23, %24, %25, %26, %27, %28, %29, %30, %31, %32, %33, %34, %35, %36, %37, %38, %39, %40, %41, %42, %43, %44, %45, %46, %47, %48, %49, %50, %51, %52, %53, %54, %55, %56, %57, %58, %59, %60, %61, %62, %63}, "
    "%64, %65, p, 1, 1, 0, 0;\n}\n"
    : "+f"(d[0]), "+f"(d[1]), "+f"(d[2]), "+f"(d[3]), "+f"(d[4]), "+f"(d[5]), "+f"(d[6]), "+f"(d[7]), "+f"(d[8]), "+f"(d[9]), "+f"(d[10]), "+f"(d[11]), "+f"(d[12]), "+f"(d[13]), "+f"(d[14]), "+f"(d[15]), "+f"(d[16]), "+f"(d[17]), "+f"(d[18]), "+f"(d[19]), "+f"(d[20]), "+f"(d[21]), "+f"(d[22]), "+f"(d[23]), "+f"(d[24]), "+f"(d[25]), "+f"(d[26]), "+f"(d[27]), "+f"(d[28]), "+f"(d[29]), "+f"(d[30]), "+f"(d[31]), "+f"(d[32]), "+f"(d[33]), "+f"(d[34]), "+f"(d[35]), "+f"(d[36]), "+f"(d[37]), "+f"(d[38]), "+f"(d[39]), "+f"(d[40]), "+f"(d[41]), "+f"(d[42]), "+f"(d[43]), "+f"(d[44]), "+f"(d[45]), "+f"(d[46]), "+f"(d[47]), "+f"(d[48]), "+f"(d[49]), "+f"(d[50]), "+f"(d[51]), "+f"(d[52]), "+f"(d[53]), "+f"(d[54]), "+f"(d[55]), "+f"(d[56]), "+f"(d[57]), "+f"(d[58]), "+f"(d[59]), "+f"(d[60]), "+f"(d[61]), "+f"(d[62]), "+f"(d[63])
    : "l"(da), "l"(db), "r"(scale_d));
}
template<int N> __device__ __forceinline__ void fence_acc(float (&d)[N]) {
#pragma unroll
  for (int i = 0; i < N; i++) asm volatile("" : "+f"(d[i]) :: "memory");
}

template<int N, int I = 0, class F> __device__ __forceinline__ void static_for(F&& f) {
  if constexpr (I < N) { f(std::integral_constant<int, I>()); static_for<N, I + 1>(f); }
}

__device__ __forceinline__ void ldsm_x4_t(uint32_t addr, uint32_t& a, uint32_t& b, uint32_t& c, uint32_t& d) {
  asm volatile("ldmatrix.sync.aligned.m8n8.x4.trans.shared.b16 {%0, %1, %2, %3}, [%4];" : "=r"(a), "=r"(b), "=r"(c), "=r"(d) : "r"(addr));
}
__device__ __forceinline__ void sts128(uint32_t addr, uint32_t a, uint32_t b, uint32_t c, uint32_t d) {
  asm volatile("st.shared.v4.b32 [%0], {%1, %2, %3, %4};" :: "r"(addr), "r"(a), "r"(b), "r"(c), "r"(d));
}
__device__ __forceinline__ void mma16816(float (&c)[4], uint32_t a0, uint32_t a1, uint32_t a2, uint32_t a3, uint32_t b0, uint32_t b1) {
  asm volatile("mma.sync.aligned.m16n8k16.row.col.f32.bf16.bf16.f32 {%0, %1, %2, %3}, {%4, %5, %6, %7}, {%8, %9}, {%0, %1, %2, %3};"
      : "+f"(c[0]), "+f"(c[1]), "+f"(c[2]), "+f"(c[3]) : "r"(a0), "r"(a1), "r"(a2), "r"(a3), "r"(b0), "r"(b1));
}
__device__ __forceinline__ void mma1688(float (&c)[4], uint32_t a0, uint32_t a1, uint32_t b0) {
  asm volatile("mma.sync.aligned.m16n8k8.row.col.f32.bf16.bf16.f32 {%0, %1, %2, %3}, {%4, %5}, {%6}, {%0, %1, %2, %3};"
      : "+f"(c[0]), "+f"(c[1]), "+f"(c[2]), "+f"(c[3]) : "r"(a0), "r"(a1), "r"(b0));
}
__device__ __forceinline__ uint32_t keep_awake() {
  float c0;
  asm volatile("{\n.reg .f32 c1, c2, c3, z;\n.reg .b32 a;\nmov.b32 a, 0;\nmov.f32 z, 0f00000000;\n"
               "mma.sync.aligned.m16n8k8.row.col.f32.bf16.bf16.f32 {%0, c1, c2, c3}, {a, a}, {a}, {z, z, z, z};\n}\n" : "=f"(c0));
  return __float_as_uint(c0);
}
__device__ __forceinline__ void pin(uint32_t& v) { asm volatile("shfl.sync.bfly.b32 %0, %0, 0, 0x1f, 0xffffffff;" : "+r"(v)); }
template<class T> __device__ __forceinline__ void pin(T*& v) {
  uint32_t lo = (uint32_t)(uint64_t)v, hi = (uint32_t)((uint64_t)v >> 32);
  pin(lo); pin(hi);
  v = (T*)(((uint64_t)hi << 32) | lo);
}
__device__ __forceinline__ float sel4(int q, float a, float b, float c, float d) {
  float r;
  asm("{\n.reg .pred p, o;\n.reg .f32 x, y;\n.reg .b32 t;\nand.b32 t, %1, 1;\nsetp.ne.b32 p, t, 0;\nsetp.gt.s32 o, %1, 1;\n"
      "selp.f32 x, %3, %2, p;\nselp.f32 y, %5, %4, p;\nselp.f32 %0, y, x, o;\n}\n" : "=f"(r) : "r"(q), "f"(a), "f"(b), "f"(c), "f"(d));
  return r;
}
__device__ __forceinline__ uint32_t bfma2(uint32_t a, uint32_t b, uint32_t c) { uint32_t r; asm("fma.rn.bf16x2 %0, %1, %2, %3;" : "=r"(r) : "r"(a), "r"(b), "r"(c)); return r; }
__device__ __forceinline__ void tma_load_5d(uint32_t dst, const CUtensorMap* tm, uint32_t bar, int c0, int c4) {
  asm volatile("cp.async.bulk.tensor.5d.shared::cluster.global.mbarrier::complete_tx::bytes [%0], [%1, {%3, %4, %4, %4, %5}], [%2];"
    :: "r"(dst), "l"(tm), "r"(bar), "r"(c0), "r"(0), "r"(c4) : "memory");
}
__device__ __forceinline__ void tma_load_4d(uint32_t dst, const CUtensorMap* tm, uint32_t bar, int c0, int c3) {
  asm volatile("cp.async.bulk.tensor.4d.shared::cluster.global.mbarrier::complete_tx::bytes [%0], [%1, {%3, %4, %4, %5}], [%2];"
    :: "r"(dst), "l"(tm), "r"(bar), "r"(c0), "r"(0), "r"(c3) : "memory");
}
__device__ __forceinline__ void tma_load_4d_hint(uint32_t dst, const CUtensorMap* tm, uint32_t bar, int c0, int c3, uint64_t pol) {
  asm volatile("cp.async.bulk.tensor.4d.shared::cluster.global.mbarrier::complete_tx::bytes.L2::cache_hint [%0], [%1, {%3, %4, %4, %5}], [%2], %6;"
    :: "r"(dst), "l"(tm), "r"(bar), "r"(c0), "r"(0), "r"(c3), "l"(pol) : "memory");
}
__device__ __forceinline__ void tma_prefetch_4d(const CUtensorMap* tm, int c0, int c3) {
  asm volatile("cp.async.bulk.prefetch.tensor.4d.L2.global.tile [%0, {%1, %2, %2, %3}];" :: "l"(tm), "r"(c0), "r"(0), "r"(c3) : "memory");
}
__device__ __forceinline__ void tma_store_5d(const CUtensorMap* tm, uint32_t src, int c0, int c4) {
  asm volatile("cp.async.bulk.tensor.5d.global.shared::cta.bulk_group [%0, {%2, %3, %3, %3, %4}], [%1];" :: "l"(tm), "r"(src), "r"(c0), "r"(0), "r"(c4) : "memory");
}
__device__ __forceinline__ float rcp_fast(float x) { float r; asm("rcp.approx.ftz.f32 %0, %1;" : "=f"(r) : "f"(x)); return r; }
__device__ __forceinline__ float sigmoid_fast(float x) { float e; asm("ex2.approx.ftz.f32 %0, %1;" : "=f"(e) : "f"(x * -1.4426950408889634f)); return rcp_fast(1.f + e); }
__device__ __forceinline__ float sqrt_fast(float x) { float r; asm("sqrt.approx.ftz.f32 %0, %1;" : "=f"(r) : "f"(x)); return r; }
__device__ __forceinline__ float ln_sd(float var) { return bf16r(sqrt_fast(bf16r(bf16r(fmaxf(var, 0.f)) + 1e-5f))); }
__device__ __forceinline__ uint32_t norm2(uint32_t h, uint32_t neg_mean2, float inv_sd) {
  const uint32_t d = badd2(h, neg_mean2);
  return pack_bf16(bf_lo(d) * inv_sd, bf_hi(d) * inv_sd);
}
template<int N> __device__ __forceinline__ void delay_clk() {
  if constexpr (N > 0) { const uint32_t t0 = clock(); while ((uint32_t)clock() - t0 < N) {} }
}
__device__ __forceinline__ void put_xstat(uint32_t rs, uint32_t exb, int col, uint32_t mean_rstd, int m) {
  smem_at<uint16_t>(rs + ((col & 7) >> 1) * 144 + (col >> 3) * 4 + (col & 1) * 2) = (uint16_t)(mean_rstd ^ (m << 15));
  const uint32_t nm = (mean_rstd >> 16) ^ 0x8000u;
  smem_at<uint4>(exb + (col >> 3) * 256 + (col & 7) * 16) = make_uint4(nm | (nm << 16), nm, 0, 0);
  smem_at<uint4>(exb + (col >> 3) * 256 + 128 + (col & 7) * 16) = make_uint4(0, 0, 0, 0);
}
__device__ __forceinline__ void put_dsum(uint32_t exa, int e, float c) {
  const float hi = bf16r(c), mid = bf16r(c - hi), lo = bf16r((c - hi) - mid);
  smem_at<uint4>(exa + (e >> 3) * 256 + (e & 7) * 16) = make_uint4((__float_as_uint(hi) >> 16) | (__float_as_uint(mid) & 0xFFFF0000u), __float_as_uint(lo) >> 16, 0, 0);
  smem_at<uint4>(exa + (e >> 3) * 256 + 128 + (e & 7) * 16) = make_uint4(0, 0, 0, 0);
}
__host__ __device__ constexpr int min_c(int a, int b) { return a < b ? a : b; }
template<int V> using IC = std::integral_constant<int, V>;

#define CT(slot) do {} while (0)
#define PT(slot) do {} while (0)

template<int MAP>
__global__ void __cluster_dims__(2, 1, 1) __launch_bounds__(384, 1)
fnet_moe_kernel(const __grid_constant__ Params p) {
  constexpr int NX = MAP == 0 ? NX0 : 256;
  constexpr int G1_BYTES = A_BYTES + NX * 128;
  uint32_t sb;
  asm volatile("mov.u32 %0, %1;" : "=r"(sb) : "r"(smem_u32(smem_raw)));
  const int m = blockIdx.x & 1;
  int tau, eps;
  bool helper = false;
  if (MAP == 0) {
    uint32_t smid;
    asm volatile("mov.u32 %0, %%smid;" : "=r"(smid));
    const int c = smid >> 1, e7 = ((c - 32) * 37) >> 8;
    helper = c == 60 || c == 61;
    tau = c < 32 ? (c & 7) : (c < 60 ? c - 31 - 7 * e7 : 0);
    eps = c < 32 ? (c >> 3) : (c < 60 ? 4 + e7 : c - 58);
  } else {
    tau = (blockIdx.x >> 1) & 7; eps = blockIdx.x >> 4;
  }
  const int cid = tau * 16 + eps * 2 + m;
  const bool moe = tau > 0;
  auto BAR = [&](int i) { return sb + OFF_BAR + 8 * i; };
  const CUtensorMap* tmD = m ? &p.tmD1 : &p.tmD0;
  const uint64_t pol_ef = policy_evict_first();
#define LOAD_STREAM(d, tm, bar, c0, c1) tma_load_2d_hint(d, tm, bar, c0, c1, pol_ef)
#define LOAD_W(d, tm, bar, c0, grp) tma_load_4d_hint(d, tm, bar, c0, (grp) * 32, pol_ef)
  auto helper_load = [&](int k) {
    const uint32_t sa = sb + slot_of(k) * ST_BYTES, bar = BAR(B_FULL + slot_of(k));
    const CUtensorMap* tm = eps == 3 ? &p.tmD1 : &p.tmD0;
    tma_load_5d(sa, &p.tmXh, bar, (k & 15) * 64, 0);
    tma_load_2d(sa + A_BYTES, tm, bar, (k & 15) * 64, m * 512 + (k >> 4) * 256);
    tma_load_2d(sa + A_BYTES + 16384, tm, bar, (k & 15) * 64, m * 512 + (k >> 4) * 256 + 128);
  };
  if (threadIdx.x < 32 && elect_one()) {
    mbar_init(BAR(B_FULL), 1);
    asm volatile("fence.mbarrier_init.release.cluster;" ::: "memory");
    if (!helper) {
      tma_load_2d(sb + A_BYTES, &p.tmX, BAR(B_FULL), 0, tau * 256);
      tma_load_2d(sb, tmD, BAR(B_FULL), 0, eps * 128);
    }
    PT(52);
#pragma unroll
    for (int k = 1; k < 4; k++) mbar_init(BAR(B_FULL + k), 1);
    asm volatile("fence.mbarrier_init.release.cluster;" ::: "memory");
#pragma unroll
    for (int k = 0; k < 4; k++) mbar_expect_tx(BAR(B_FULL + k), helper ? ST_BYTES : G1_BYTES);
    if (!helper) {
#pragma unroll
      for (int k = 1; k < 4; k++) {
        tma_load_2d(sb + k * ST_BYTES + A_BYTES, &p.tmX, BAR(B_FULL + k), k * 64, tau * 256);
        LOAD_STREAM(sb + k * ST_BYTES, tmD, BAR(B_FULL + k), k * 64, eps * 128);
      }
    } else {
#pragma unroll 1
      for (int k = 0; k < 4; k++) helper_load(k);
    }
    PT(0);
  }
  __syncwarp();
  const int warp = __shfl_sync(0xffffffffu, threadIdx.x >> 5, 0);
  if (warp == 8) {
    if (elect_one()) {
#pragma unroll
      for (int b = B_EMPTY; b < B_COUNT; b++)
        mbar_init(BAR(b), b < B_EPI ? 2 : (b == B_EPI || b == B_EPI0B) ? 4 : (b < B_STD || b == B_OUT) ? 8 : (b == B_STAT || b == B_XS) ? 3 : 1);
      asm volatile("fence.mbarrier_init.release.cluster;" ::: "memory");
      mbar_expect_tx(BAR(B_XCH), 32768);
      SM_(uint32_t, OFF_SEEN) = 0;
    }
  }
  __syncthreads();

  if (warp >= 8) {
    reg_dec<REG_P>();
    asm volatile("barrier.cluster.arrive.relaxed.aligned;" ::: "memory");
    const int abrow = m * 1024 + eps * 128;
    const int f0 = (cid - 16) * 32;
    const CUtensorMap* tmWM = m ? &p.tmWM1 : &p.tmWM0;
    auto side_first = [&](int k) {
      if (NX < 256 && k == MINI_LOAD_K) {
        static_assert(mr_k(NREG_H + 1) <= MINI_LOAD_K && (NREG_H & 1) == 1, "first half of the staging buffer must be free");
        mbar_wait(BAR(B_STD + 2), 0);
        uint32_t n = 0;
        while (!((*(volatile uint32_t*)&SM_(uint32_t, OFF_SEEN) >> (4 * tau + 1)) & 1) && ++n < SPIN_LIMIT * 16) {}
        if (elect_one()) {
          mbar_expect_tx(BAR(B_MINI), 12288);
          tma_load_2d(sb + OFF_MINI, &p.tmAbM, BAR(B_MINI), tau * 256 + 240, abrow);
          LOAD_W(sb + OFF_MINI + 4096, tmWM, BAR(B_MINI), tau * 256 + 240, tau * 2 + m);
          LOAD_W(sb + OFF_MINI + 8192, tmWM, BAR(B_MINI), tau * 256 + 240, tau * 2 + 1 - m);
        }
      }
    };
    auto side = [&](int k) {
      if (NX < 256 && k == MINI_PF_K && elect_one()) tma_prefetch_4d(tmWM, tau * 256 + 240, tau * 64 + (eps & 1) * 32);
      if (k == WPF2_K && eps < WPF2_N && elect_one()) tma_prefetch_4d(m ? &p.tmW1 : &p.tmW0, kblock(tau, 31 - (eps >> 1)) * 64, tau * 64 + (eps & 1) * 32);
      if (!moe) return;
      const int i = k - MR_K0, r2 = i / (4 + MR_LAG), u = i - (4 + MR_LAG) * r2;
      const int h = k == MINI_K + 4 ? NREG_H + 1 : 2 * r2 + (u >> 1);
      if (k == MINI_K + 4 || (i >= 0 && (u == 0 || u == 2) && h <= NREG_H)) {
        if (h < 2) mbar_wait(BAR(B_STD + 2 + h), 0);
        if (elect_one()) {
          const uint32_t bar = BAR(h < NREG_H ? B_MR + (h & 1) : B_GU);
          if (h < NREG_H) mbar_expect_tx(bar, 16384);
          LOAD_STREAM(sb + OFF_XCH + (h & 1) * 16384, &p.tmG, bar, f0, h * 128);
          LOAD_STREAM(sb + OFF_XCH + (h & 1) * 16384 + 8192, &p.tmU, bar, f0, h * 128);
        }
      }
      if (k >= PF_K1 && !(k & 1) && elect_one()) {
        const int j = PF_N0 + ((k - PF_K1) >> 1);
        if (j < 8) tma_prefetch_2d(m ? &p.tmU : &p.tmG, f0, j * 128);
        else if (j < 12) asm volatile("cp.async.bulk.prefetch.L2.global [%0], %1;" :: "l"(p.wdown + (size_t)f0 * 1024 + (j - 8) * 8192), "r"(16384) : "memory");
      }
    };
    if (MAP == 0 && helper) {
      if (warp == 8) {
#pragma unroll 1
        for (int k = 4; k < 32; k++) {
          mbar_wait(BAR(B_EMPTY + slot_of(k)), (use_of(k) & 1) ^ 1);
          if (elect_one()) {
            mbar_expect_tx(BAR(B_FULL + slot_of(k)), ST_BYTES);
            helper_load(k);
            if (k == 12) mbar_arrive(BAR(B_LATE));
          }
        }
      } else {
        const int i0 = threadIdx.x - 288, lane = threadIdx.x & 31, col0 = (eps - 2) * 8 + m * 4;
        mbar_wait(BAR(B_LATE), 0);
        const uint32_t tag = ld_relaxed32(&p.s->epoch) + 1;
        if (i0 < 8) pkt_st128(&p.s->hflag[col0 * 2 + i0], 0, 0, 0, 0);
        SM_(uint32_t, OFF_TAG) = tag;
#pragma unroll 1
        for (int j0 = i0; j0 < 768; j0 += 384) {
          uint2 v[4]; uint32_t n = 0;
          while (true) {
#pragma unroll
            for (int z = 0; z < 4; z++) {
              const int j = j0 + 96 * z;
              v[z] = pkt_ld64(p.s->xstat + (j < 128 ? 256 * (j >> 4) + 240 + 2 * (j & 6) + ((j >> 2) & 2) + (j & 1)
                                          : j < 640 ? 2048 + col0 * 128 + j - 128 : (j - 640) * 16));
            }
            if (__all_sync(0xffffffffu, v[0].y == tag && v[1].y == tag && v[2].y == tag && v[3].y == tag) || ++n > SPIN_LIMIT) break;
            __nanosleep(300);
          }
#pragma unroll
          for (int z = 0; z < 4; z++) {
            const int j = j0 + 96 * z;
            if (j < 128) put_xstat(sb + OFF_RS, sb + OFF_XCH + 16384, j, v[z].x, eps - 2);
            else if (j < 640) put_dsum(sb + OFF_XCH, j - 128, __uint_as_float(v[z].x));
          }
        }
        fence_async_smem();
        __syncwarp();
        if (lane == 0) mbar_arrive(BAR(B_STAT));
      }
    } else if (warp == 8) {
      const CUtensorMap* tmW = m ? &p.tmW1 : &p.tmW0;
      const int gA = tau * 2 + m, gB = tau * 2 + 1 - m;
      auto wait_slot = [&](int k) {
        mbar_wait(BAR(B_EMPTY + slot_of(k)), (use_of(k) & 1) ^ 1);
        PT(64 + k);
      };
#pragma unroll 1
      for (int k = 4; k < 24; k++) {
        const int s = slot_of(k);
        const uint32_t sa = sb + s * ST_BYTES, sbb = sa + A_BYTES;
        const int kb = kblock(tau, k - 16);
        wait_slot(k);
        if (elect_one()) {
          mbar_expect_tx(BAR(B_FULL + s), k < 16 ? G1_BYTES : (k >> 1) == 9 ? B_BYTES : ST_BYTES);
          if (k < 16) {
            LOAD_STREAM(sa, tmD, BAR(B_FULL + s), k * 64, eps * 128);
            tma_load_2d(sbb, &p.tmX, BAR(B_FULL + s), k * 64, tau * 256);
          } else {
            LOAD_W(sbb, tmW, BAR(B_FULL + s), kb * 64, gA);
            LOAD_W(sbb + 16384, tmW, BAR(B_FULL + s), kb * 64, gB);
            if (k < 18) {
              tma_load_4d(sa, &p.tmXr, BAR(B_FULL + s), eps * 128, gA * 32 + s * 16);
              tma_load_4d(sa + 8192, &p.tmXr, BAR(B_FULL + s), eps * 128 + 64, gA * 32 + s * 16);
            }
          }
          if (k == PUB_K1) mbar_arrive(BAR(B_LATE));
          if (k >= WPF_K0 && k < WPF_K0 + WPF_N && (eps >> 1) == ((k - WPF_K0) & 3))
            tma_prefetch_4d(tmW, kblock(tau, k - WPF_K0) * 64, tau * 64 + (eps & 1) * 32);
          if (moe && k >= PF_K0 && k < PF_K0 + 2 * PF_N0 && !(k & 1)) tma_prefetch_2d(m ? &p.tmU : &p.tmG, f0, (k - PF_K0) * 64);
        }
      }
      uint32_t seen = 0;
#pragma unroll 1
      for (int k = 24; k < 48; k++) {
        const int s = slot_of(k);
        const uint32_t sa = sb + s * ST_BYTES, sbb = sa + A_BYTES;
        const int kb = kblock(tau, k - 16);
        const uint32_t need = (1u << kb) | ((kb & 3) == 3 ? 2u << (4 * tau) : 0u);
        wait_slot(k);
        side_first(k);
        if (elect_one()) {
          mbar_expect_tx(BAR(B_FULL + s), ST_BYTES);
          LOAD_W(sbb, tmW, BAR(B_FULL + s), kb * 64, gA);
          LOAD_W(sbb + 16384, tmW, BAR(B_FULL + s), kb * 64, gB);
        }
        uint32_t n = 0;
        while ((seen & need) != need && ++n < SPIN_LIMIT * 16) seen = *(volatile uint32_t*)&SM_(uint32_t, OFF_SEEN);
        if (elect_one()) tma_load_2d(sa, &p.tmAbL, BAR(B_FULL + s), kb * 64, abrow);
        side(k);
      }
      if (moe) {
        mbar_wait(BAR(B_EMPTY + 0), 1);
        if (elect_one()) { mbar_expect_tx(BAR(B_GU), (8 - NREG_H) * 16384); mbar_expect_tx(BAR(B_DN), 65536); }
#pragma unroll 1
        for (int i = 0; i < 10 - NREG_H; i++) {
          if (i == 3) mbar_wait(BAR(B_EMPTY + 1), 1);
          if (i == 4) {
            mbar_wait(BAR(B_EMPTY + 2), 1);
            mbar_wait(BAR(B_XCH), 0);
            PT(53);
          }
          const uint32_t dst = sb + late_off(i);
          if (elect_one()) {
            if (i < 6 - NREG_H) {
              LOAD_STREAM(dst, &p.tmG, BAR(B_GU), f0, (NREG_H + 2 + i) * 128);
              LOAD_STREAM(dst + 8192, &p.tmU, BAR(B_GU), f0, (NREG_H + 2 + i) * 128);
            } else {
#pragma unroll
              for (int b = 0; b < 4; b++) LOAD_STREAM(dst + b * 4096, &p.tmDn, BAR(B_DN), (4 * (i - 6 + NREG_H) + b) * 64, f0);
            }
          }
          const long long t0 = clock64();
          while (i < 9 - NREG_H && clock64() - t0 < MOE_PACE_CLK) {}
        }
      }
      const int lane = threadIdx.x & 31;
      mbar_wait(BAR(B_OUT), 0);
      const uint32_t km = SM_(uint32_t, OFF_WKEY + (lane & 7) * 8);
      const uint32_t bk = __reduce_max_sync(0xffffffffu, km);
      const int ww = __ffs(__ballot_sync(0xffffffffu, km == bk)) - 1;
#pragma unroll 1
      for (int i = 1; i <= 8; i++) {
        const int W = (ww + i) & 7;
        if (i == 8) {
          mbar_wait(BAR(B_XS), 0);
          if (SM_(uint32_t, OFF_KV) == bk) {
#pragma unroll 2
            for (int j = lane; j < 256; j += 32) {
              const int rho = j >> 4, row = row_of(gA * 128 + 32 * (W >> 1) + 8 * ((rho & 7) >> 1) + 4 * (W & 1) + 2 * (rho >> 3) + (rho & 1));
              const uint4 v = lds128_v(sb + OFF_OUT + (j & 8) * 2048 + (16 * W + rho) * 128 + (((j ^ rho) & 7) << 4));
              if (row != 0xFFFF - (int)(bk & 0xFFFFu))
                asm volatile("st.global.v4.b32 [%0], {%1, %2, %3, %4};" :: "l"(p.out + (size_t)row * 1024 + eps * 128 + (j & 15) * 8), "r"(v.x), "r"(v.y), "r"(v.z), "r"(v.w));
            }
            break;
          }
        }
        if (lane == 0) {
          tma_store_5d(&p.tmOut, sb + OFF_OUT + W * 2048, eps * 128, row_of(gA * 128 + 32 * (W >> 1) + 4 * (W & 1)));
          tma_store_5d(&p.tmOut, sb + OFF_OUT + 16384 + W * 2048, eps * 128 + 64, row_of(gA * 128 + 32 * (W >> 1) + 4 * (W & 1)));
        }
        const long long t0 = clock64();
        while (i < 7 && clock64() - t0 < OUT_PACE_CLK) {}
      }
      if (lane == 0) { bulk_commit(); bulk_wait_all(); }
      PT(22);
    } else {
      const int a = warp - 9;
      const int lane = threadIdx.x & 31;
      auto stage = [&](const bf16* src, int g) {
        if (elect_one()) {
          mbar_expect_tx(BAR(B_AUX + g), 16384);
          bulk_load(sb + OFF_XCH + g * 16384, src + g * 8192, 16384, BAR(B_AUX + g));
        }
      };
      uint32_t tag = 0;
#pragma unroll 1
      for (int i = 0; i < 3; i++) { i += keep_awake(); delay_clk<300>(); }
      mbar_wait(BAR(B_FULL + 0), 0);
      delay_clk<AUX_DELAY>();
      if (a == 0) PT(1);
      if (a == 1) mbar_wait(BAR(B_AUX + 0), 0);
      if (a < 2) stage(p.x + (size_t)cid * 16 * 1024, a);
#pragma unroll 1
      for (int it = 0; it < 4; it++) {
        const int g = it & 1;
        mbar_wait(BAR(B_AUX + g), it >> 1);
        if (a == 0) PT(2 + it);
        if (it == 2) tag = ld_relaxed32(&p.s->epoch) + 1;
        if (it == 2 && a == 2 && lane < 16) asm volatile("prefetch.global.L2 [%0];" :: "l"(p.wr + lane * 64));
        const uint32_t ad = sb + OFF_XCH + g * 16384 + (lane >> 2) * 2048;
        float s0 = 0.f, s1 = 0.f, q0 = 0.f, q1 = 0.f;
        auto row = [&](auto sq) {
#pragma unroll
          for (int i = 0; i < 11; i++) {
            if (i == 10 && a == 2) break;
            const uint4 v = lds128_v(ad + (((a * 44 + 4 * i + lane) & 127) << 4));
            const uint32_t ww[4] = {v.x, v.y, v.z, v.w};
#pragma unroll
            for (int z = 0; z < 4; z++) {
              const float d0 = bf_lo(ww[z]), d1 = bf_hi(ww[z]);
              s0 += d0; s1 += d1;
              if (decltype(sq)::value) { q0 = fmaf(d0, d0, q0); q1 = fmaf(d1, d1, q1); }
            }
          }
        };
        if (it < 2) row(IC<1>()); else row(IC<0>());
        s0 += s1; q0 += q1;
#pragma unroll
        for (int o = 1; o < 4; o <<= 1) { s0 += __shfl_xor_sync(0xffffffffu, s0, o); q0 += __shfl_xor_sync(0xffffffffu, q0, o); }
        if ((lane & 3) == 0) SM_(float2, OFF_PUB + a * 256 + it * 64 + (lane >> 2) * 8) = make_float2(s0, q0);
        if (it != 2) bar_sync(NB_AUX, 96);
        if (it < 2 && a == 2) stage(cid < 64 ? p.Dre + (size_t)cid * 16 * 1024 : p.Dim + (size_t)(cid - 64) * 16 * 1024, g);
      }
      if (a == 1) {
        const float2 v0 = SM_(float2, OFF_PUB + lane * 8), v1 = SM_(float2, OFF_PUB + 256 + lane * 8), v2 = SM_(float2, OFF_PUB + 512 + lane * 8);
        const float s = v0.x + v1.x + v2.x, mean = s * (1.f / 1024.f);
        const float rs = rcp_fast(ln_sd((v0.y + v1.y + v2.y) * (1.f / 1024.f) - mean * mean));
        pkt_st64((lane < 16 ? p.s->xstat : p.s->dsum) + cid * 16 + (lane & 15), lane < 16 ? pack_bf16(rs, mean) : __float_as_uint(s), tag);
        PT(6);
      }
      if (a == 2) {
        float s = 0.f;
#pragma unroll
        for (int q = 0; q < 4; q++) {
          const uint4 v = ldg_nc128(p.wr + (q * 32 + lane) * 8);
          s += ((bf_lo(v.x) + bf_hi(v.x)) + (bf_lo(v.y) + bf_hi(v.y))) + ((bf_lo(v.z) + bf_hi(v.z)) + (bf_lo(v.w) + bf_hi(v.w)));
          const int ch = q * 32 + lane - eps * 16;
          if (ch >= 0 && ch < 16) {
            SM_(uint32_t, OFF_WR + ch * 4) = v.x; SM_(uint32_t, OFF_WR + 80 + ch * 4) = v.y;
            SM_(uint32_t, OFF_WR + 160 + ch * 4) = v.z; SM_(uint32_t, OFF_WR + 240 + ch * 4) = v.w;
          }
        }
        s = warp_sum(s);
        if (lane == 0) { SM_(float, OFF_WSUM) = s; SM_(uint32_t, OFF_TAG) = tag; }
      }
      if (a < 2) __nanosleep(GATHER_NS);
      {
        const int i0 = a * 32 + lane;
        uint2 v[3], c0, c1; uint32_t n = 0;
        const uint2* dp = &p.s->dsum[abrow];
        while (true) {
#pragma unroll
          for (int q = 0; q < 3; q++) v[q] = pkt_ld64(&p.s->xstat[tau * 256 + min(i0 + 96 * q, 255)]);
          c0 = pkt_ld64(dp + i0); c1 = pkt_ld64(dp + min(i0 + 96, 127));
          if (__all_sync(0xffffffffu, v[0].y == tag && v[1].y == tag && v[2].y == tag && c0.y == tag && c1.y == tag) || ++n > SPIN_LIMIT) break;
          __nanosleep(200);
        }
#pragma unroll
        for (int q = 0; q < 3; q++) put_xstat(sb + OFF_RS, sb + OFF_EXB, min(i0 + 96 * q, 255), v[q].x, m);
        put_dsum(sb + OFF_EXA, i0, __uint_as_float(c0.x));
        put_dsum(sb + OFF_EXA, min(i0 + 96, 127), __uint_as_float(c1.x));
        fence_async_smem();
      }
      __syncwarp();
      if (lane == 0) mbar_arrive(BAR(B_STAT));
      if (a == 0) PT(7);
      if (a == 0) {
        const uint32_t* flg = reinterpret_cast<const uint32_t*>(&p.s->abflag[((eps * 2 + m) * 8 + (lane >> 2)) * 2]) + (lane & 3);
        if (NX < 256 && lane == 4 * tau + 1) flg = reinterpret_cast<const uint32_t*>(&p.s->hflag[(m * 8 + eps) * 2]);
        uint32_t seen = 0;
        auto fetch = [&](int s, uint32_t dst) {
          const int tile = sigma_of(tau, s);
          uint32_t n = 0;
          while (!((seen >> (4 * tile)) & 1) && ++n < SPIN_LIMIT) seen = __ballot_sync(0xffffffffu, ld_acquire32(flg) == tag);
          asm volatile("fence.proxy.async.global;" ::: "memory");
          PT(16 + s);
          if (elect_one()) tma_load_2d(dst, &p.tmAbL, BAR(B_FULL + s), tile * 256, abrow);
        };
        mbar_wait(BAR(B_EPI), 0);
#pragma unroll
        for (int s = 0; s < 4; s++) mbar_wait(BAR(B_FULL + s), 0);
        fetch(0, sb + OFF_XCH);
        mbar_wait(BAR(B_STD + 0), 0);
        delay_clk<GAP1>();
        fetch(1, sb + OFF_XCH + 16384);
        if (elect_one()) mbar_arrive(BAR(B_PUB1));
        delay_clk<GAP2>();
        fetch(2, sb + 2 * ST_BYTES);
        mbar_wait(BAR(B_STD + 1), 0);
        fetch(3, sb + 3 * ST_BYTES);
        uint32_t n = 0, told = 0;
        while (true) {
          if (seen != told) {
            asm volatile("fence.proxy.async.global;" ::: "memory");
            *(volatile uint32_t*)&SM_(uint32_t, OFF_SEEN) = seen;
            told = seen;
          }
          if (seen == 0xFFFFFFFFu || ++n > SPIN_LIMIT) break;
          __nanosleep(100);
          seen = __ballot_sync(0xffffffffu, ld_acquire32(flg) == tag);
        }
        PT(58);
      } else {
        uint32_t* flag = reinterpret_cast<uint32_t*>(&p.s->abflag[((eps * 2 + m) * 8 + tau) * 2]);
        if (a == 1) {
          mbar_wait(BAR(B_EPI), 0);
          PT(8);
          if (lane == 0) tma_store_2d(&p.tmAbS, sb + chunk_off(0, 0), tau * 256, abrow);
          mbar_wait(BAR(B_EPI0B), 0);
          if (lane == 0) {
            tma_store_2d(&p.tmAbS, sb + chunk_off(0, 1), tau * 256, abrow + 64);
            bulk_commit();
            bulk_wait_all();
            mbar_arrive(BAR(B_STD));
            bulk_wait_release();
            st_relaxed32(flag, tag);
          }
          PT(12);
          mbar_wait(BAR(B_EPI + 1), 0);
          mbar_wait(BAR(B_LATE), 0);
          mbar_wait(BAR(B_PUB1), 0);
          PT(9);
          if (lane == 0) {
            tma_store_2d(&p.tmAbS, sb + chunk_off(1, 0), tau * 256 + 64, abrow);
            tma_store_2d(&p.tmAbS, sb + chunk_off(1, 1), tau * 256 + 64, abrow + 64);
            bulk_commit();
            bulk_wait_all();
            mbar_arrive(BAR(B_STD + 1));
            bulk_wait_release();
            st_relaxed32(flag + 1, tag);
          }
          PT(13);
        }
        auto copy_out = [&](int c) {
          mbar_wait(BAR(B_EPI + c), 0);
          PT(8 + c);
          bf16* dst = p.s->abT + (size_t)(abrow + (lane >> 3)) * 2048 + tau * 256 + c * 64 + (lane & 7) * 8;
          const uint32_t src = sb + chunk_off(c, 0) + (lane >> 3) * 128 + (((lane & 7) ^ (lane >> 3)) << 4);
          const uint32_t on = c * 64 + (lane & 7) * 8 < NX;
#pragma unroll 4
          for (int i = 0; i < 32; i++) {
            const uint4 v = lds128_v((src ^ ((i & 1) << 6)) + i * 512);
            asm volatile("{\n.reg .pred p;\nsetp.ne.b32 p, %5, 0;\n@p st.global.v4.b32 [%0], {%1, %2, %3, %4};\n}\n"
                         :: "l"(dst + i * 4 * 2048), "r"(v.x), "r"(v.y), "r"(v.z), "r"(v.w), "r"(on));
          }
          __syncwarp();
          if (lane == 0) mbar_arrive(BAR(B_STD + c));
        };
        if (a == 2) {
#pragma unroll 1
          for (int c = 2; c < 4; c++) copy_out(c);
          asm volatile("fence.acq_rel.gpu;" ::: "memory");
          __syncwarp();
          if (lane < 2) st_relaxed32(flag + 2 + lane, tag);
          PT(15);
        }
      }
      {
        mbar_wait(BAR(B_LATE), 1);
        const int grp = tau * 2 + m;
#pragma unroll 1
        for (int i = a; i < 14; i += 3) {
          uint4* dst = i < 8 ? &p.s->ypart[cid * 256 + i * 32 + lane] : i < 12 ? &p.s->hstat[(grp * 8 + eps) * 128 + (i - 8) * 32 + lane]
                     : i == 12 ? &p.s->cand[grp * 256 + eps * 32 + lane] : &p.s->key[(((lane >> 1) & 7) * 16 + grp) * 2 + (lane & 1)];
          if (i < 13 || eps == 0) pkt_st128(dst, 0, 0, 0, 0);
          __nanosleep(200);
        }
        __syncwarp();
        if (lane == 0) mbar_arrive(BAR(B_STAT));
      }
      {
        const uint4* kp = &p.s->key[(tau * 16 + (lane & 15)) * 2];
        const int i0 = a * 32 + lane;
        mbar_wait(BAR(B_KEY), 0);
        if (a == 0) PT(43);
        uint4 kq = pkt_ld128(kp), cv[3] = {};
        uint32_t n = 0, kv;
        int gspec = -1;
        while (true) {
          const bool ok = kq.y == tag && kq.w == tag;
          kv = __reduce_max_sync(0xffffffffu, ok ? kq.x : 0u);
          const int gs = group_of(0xFFFF - (int)(kv & 0xFFFFu));
          const bool cok = gs == gspec && cv[0].y == tag && cv[0].w == tag && cv[1].y == tag && cv[1].w == tag && cv[2].y == tag && cv[2].w == tag;
          if (__all_sync(0xffffffffu, ok && cok) || ++n > SPIN_LIMIT) break;
          if (!ok) kq = pkt_ld128(kp);
          n += keep_awake();
          const bool spec = __popc(__ballot_sync(0xffffffffu, ok)) >= 2 * SPEC_MIN;
          if (!cok && spec) {
#pragma unroll
            for (int i = 0; i < 3; i++) cv[i] = pkt_ld128(&p.s->cand[gs * 256 + min(i0 + 96 * i, 255)]);
          }
          if (spec) gspec = gs;
        }
        if (a == 0) PT(45);
        const uint32_t ms = __shfl_sync(0xffffffffu, kq.z, gspec);
        const uint32_t nm = ((ms & 0xFFFFu) ^ 0x8000u) * 0x10001u;
        const float is = rcp_fast(bf_hi(ms));
#pragma unroll
        for (int i = 0; i < 3; i++) {
          const int j = min(i0 + 96 * i, 255);
          SM_(uint2, OFF_XSEL + j * 8) = make_uint2(norm2(cv[i].x, nm, is), norm2(cv[i].z, nm, is));
        }
#pragma unroll
        for (int i = 0; i < 3; i++) SM_(uint2, OFF_HSEL + min(i0 + 96 * i, 255) * 8) = make_uint2(cv[i].x, cv[i].z);
        SM_(uint32_t, OFF_KV) = kv;
        __syncwarp();
        if (lane == 0) mbar_arrive(BAR(B_XS));
      }
    }
    asm volatile("barrier.cluster.wait.aligned;" ::: "memory");
  } else {
    reg_inc<REG_C>();
    const int tid = __shfl_sync(0xffffffffu, threadIdx.x, threadIdx.x & 31), lane = tid & 31;
    const int w = warp >> 2, wi = warp & 3, t = tid & 127;
    const int g = lane >> 2, q = lane & 3;
    const int turn_me = NB_TURN0 + w, turn_other = NB_TURN1 - w;
    auto release = [&](int s) { if (t == 0) mbar_arrive(BAR(B_EMPTY + s)); };
    if (MAP == 0 && helper) {
      asm volatile("barrier.cluster.arrive.relaxed.aligned;" ::: "memory");
      float s0[64], s1[64];
#pragma unroll
      for (int i = 0; i < 64; i++) { s0[i] = 0.f; s1[i] = 0.f; }
      if (w == 1) bar_arrive(NB_TURN0, 256);
      uint32_t o[32][2] = {};
      const int col = (eps - 2) * 8 + m * 4 + w;
      auto put = [&](auto tc, uint32_t buf) {
        constexpr int tl = decltype(tc)::value;
#pragma unroll
        for (int i = 0; i < 4; i++)
          smem_at<uint2>(buf + ((i >> 1) * 64 + wi * 16 + (i & 1) * 8 + g) * 32 + ((q * 8) ^ ((g & 4) << 2))) = make_uint2(o[8 * i + tl][0], o[8 * i + tl][1]);
      };
      auto mma_step = [&](int k) {
        const int s = slot_of(k);
        const uint64_t da = make_desc(sb + s * ST_BYTES + A_BYTES + w * 16384), db = make_desc(sb + s * ST_BYTES);
        wgmma_fence();
#pragma unroll
        for (int kk = 0; kk < 4; kk++) {
          wgmma_n128(s0, da + kk * 2, db + kk * 2, kk > 0 || (k & 15));
          wgmma_n128(s1, da + 512 + kk * 2, db + kk * 2, kk > 0 || (k & 15));
        }
        wgmma_commit();
      };
#pragma unroll 1
      for (int pass = 0; pass < 2; pass++) {
#pragma unroll 1
        for (int k = 16 * pass; k < (pass ? 32 - HL_N : 16); k++) {
          mbar_wait(BAR(B_FULL + slot_of(k)), use_of(k) & 1);
          bar_sync(turn_me, 256);
          mma_step(k);
          bar_arrive(turn_other, 256);
          if (pass && k < 24) {
            const uint32_t buf = sb + OFF_XCH + ((k & 1) ? 0 : 20480) + w * 4096;
            static_for<8>([&](auto ic) { if (k == 16 + decltype(ic)::value) put(ic, buf); });
            fence_async_smem();
            bar_sync(NB_WG0 + w, 128);
            if (t == 0) { tma_store_2d(&p.tmAbM, buf, (k - 16) * 256 + 240, col * 128); bulk_commit(); }
          }
          wgmma_wait0();
          release(slot_of(k));
          if (t == 0) asm volatile("cp.async.bulk.wait_group.read 1;" ::: "memory");
        }
        if (pass) {
          bar_sync(turn_me, 256);
#pragma unroll
          for (int k = 32 - HL_N; k < 32; k++) {
            mbar_wait(BAR(B_FULL + slot_of(k)), 1);
            mma_step(k);
          }
        }
        mbar_wait(BAR(B_STAT), 0);
        wgmma_fence();
        wgmma_n128(s0, make_desc_noswz(sb + OFF_XCH + pass * 8192 + w * 4096), make_desc_noswz(sb + OFF_XCH + 16384));
        wgmma_n128(s1, make_desc_noswz(sb + OFF_XCH + pass * 8192 + w * 4096 + 2048), make_desc_noswz(sb + OFF_XCH + 16384));
        wgmma_commit();
        if (pass && w == 0) bar_arrive(turn_other, 256);
        uint4 rs[4];
#pragma unroll
        for (int i = 0; i < 4; i++) rs[i] = lds128_v(sb + OFF_RS + q * 144 + i * 16);
        wgmma_wait0();
        fence_acc(s0); fence_acc(s1);
#pragma unroll
        for (int i = 0; i < 32; i++) {
          const int tl = i & 7, hr = (i >> 3) & 1;
          const float* ac = (i >> 4) ? &s1[8 * tl + 2 * hr] : &s0[8 * tl + 2 * hr];
          o[i][0] = bmul2(pack_bf16(ac[0], ac[1]), (tl & 1) ? rs[tl >> 1].z : rs[tl >> 1].x);
          o[i][1] = bmul2(pack_bf16(ac[4], ac[5]), (tl & 1) ? rs[tl >> 1].w : rs[tl >> 1].y);
        }
      }
      static_for<8>([&](auto ic) { put(ic, sb + (w * 8 + decltype(ic)::value) * 4096); });
      fence_async_smem();
      bar_sync(NB_WG0 + w, 128);
      if (t == 0) {
#pragma unroll 1
        for (int i = 0; i < 8; i++) tma_store_2d(&p.tmAbM, sb + (w * 8 + i) * 4096, i * 256 + 240, (col + 2) * 128);
        bulk_commit();
        bulk_wait_release();
        st_relaxed32(&p.s->hflag[col * 2], SM_(uint32_t, OFF_TAG));
        st_relaxed32(&p.s->hflag[(col + 2) * 2], SM_(uint32_t, OFF_TAG));
      }
      asm volatile("barrier.cluster.wait.aligned;" ::: "memory");
      return;
    }
    float acc[128], a1[NX / 2];
#pragma unroll
    for (int i = 0; i < NX / 2; i++) a1[i] = 0.f;
    if (w == 1) bar_arrive(NB_TURN0, 256);
    auto kstep = [&](auto& d, int k, bool first, bool a_in_xch = false, bool mini = false) {
      const int s = slot_of(k);
      mbar_wait(BAR(B_FULL + s), use_of(k) & 1);
      CT(64 + k);
      bar_sync(turn_me, 256);
      const uint64_t da = make_desc(sb + (a_in_xch ? OFF_XCH + s * 16384 : s * ST_BYTES) + w * 8192), db = make_desc(sb + s * ST_BYTES + A_BYTES);
      wgmma_fence();
      wgmma_g1(d, da, db, !first);
#pragma unroll
      for (int kk = 1; kk < 4; kk++) wgmma_g1(d, da + kk * 2, db + kk * 2, 1);
      wgmma_commit();
      if (mini) {
        CT(29);
        mbar_wait(BAR(B_MINI), 0);
        CT(30);
        wgmma_fence();
        wgmma_g1(d, make_desc_32b(sb + OFF_MINI + w * 2048), make_desc_32b(sb + OFF_MINI + 4096), 1);
        wgmma_commit();
      }
      bar_arrive(turn_other, 256);
    };
    auto kdone = [&](int k) { wgmma_wait0(); release(slot_of(k)); };
    auto wgmma_wait1 = [&]() { asm volatile("wgmma.wait_group.sync.aligned 1;" ::: "memory"); };

#pragma unroll 1
    for (int k = 0; k < 13; k++) {
      kstep(a1, k, k == 0);
      if (k == 0) CT(0);
      if (k == 8 && warp == 2 && lane < 2) pkt_st128(&p.s->abflag[((eps * 2 + m) * 8 + tau) * 2 + lane], 0, 0, 0, 0);
      kdone(k);
    }
    uint32_t R[64];
    kstep(a1, 13, false);
    mbar_wait(BAR(B_STAT), 0);
    const uint32_t tag = SM_(uint32_t, OFF_TAG);
#pragma unroll
    for (int i = 0; i < 8; i++) { const uint4 v = lds128_v(sb + OFF_RS + q * 144 + i * 16); R[8 * i] = v.x; R[8 * i + 2] = v.y; R[8 * i + 4] = v.z; R[8 * i + 6] = v.w; }
    kdone(13);
    float p0[32], p1[NX / 2 - 32];
    auto pack = [&](auto cc) {
      constexpr int c = decltype(cc)::value;
#pragma unroll
      for (int j = 8 * c; j < min_c(8 * c + 8, NX / 8); j++) {
        const uint32_t rs = R[2 * j];
        const float* ac = c ? &p1[4 * j - 32] : &p0[4 * j];
        R[2 * j] = bmul2(pack_bf16(ac[0], ac[1]), rs);
        R[2 * j + 1] = bmul2(pack_bf16(ac[2], ac[3]), rs);
      }
    };
    auto put_chunk = [&](auto cc) {
      constexpr int c = decltype(cc)::value;
      const int rho = 16 * wi + (lane & 15);
#pragma unroll
      for (int j = 8 * c; j < min_c(8 * c + 8, NX / 8); j += 2) {
        const int chunk = (j & 7) + (lane >> 4);
        stsm_x4(sb + chunk_off(c, w) + rho * 128 + ((chunk ^ (lane & 7)) << 4), R[2 * j], R[2 * j + 1], R[2 * j + 2], R[2 * j + 3]);
      }
    };
    auto staged = [&](int bar) {
      fence_async_smem();
      __syncwarp();
      if (lane == 0) mbar_arrive(BAR(bar));
    };
    auto mma_rs = [&](auto cc, auto k0, auto k1) {
      constexpr int c = decltype(cc)::value;
      const uint64_t db = make_desc(sb + c * ST_BYTES + A_BYTES);
#pragma unroll
      for (int kk = decltype(k0)::value; kk < decltype(k1)::value; kk++)
        wgmma_n256_rs(acc, R[16 * c + 4 * kk], R[16 * c + 4 * kk + 1], R[16 * c + 4 * kk + 2], R[16 * c + 4 * kk + 3], db + kk * 2, c + kk > 0);
      wgmma_commit();
    };
    auto kdone_x = [&](int k, auto ic) {
      constexpr int i = decltype(ic)::value;
      uint32_t r[8];
#pragma unroll
      for (int z = 0; z < 2; z++) {
        const int tr = 32 * (i & 1) + 16 * z + 8 * (lane >> 4) + (lane & 7), chunk = 2 * wi + ((lane >> 3) & 1);
        ldsm_x4_t(sb + (i >> 1) * ST_BYTES + w * 8192 + tr * 128 + ((chunk ^ (lane & 7)) << 4), r[4 * z], r[4 * z + 1], r[4 * z + 2], r[4 * z + 3]);
      }
      float f[16];
#pragma unroll
      for (int z = 0; z < 8; z++) { f[2 * z] = bf_lo(r[z]); f[2 * z + 1] = bf_hi(r[z]); }
#pragma unroll
      for (int z = 0; z < 16; z++) asm volatile("" : "+f"(f[z]));
      kdone(k);
#pragma unroll
      for (int z = 0; z < 16; z++) asm volatile("add.f32 %0, %0, %1;" : "+f"(acc[16 * i + z]) : "f"(f[z]));
    };
    {
      const uint64_t da2 = make_desc(sb + 2 * ST_BYTES + w * 8192), db2 = make_desc(sb + 2 * ST_BYTES + A_BYTES);
      const uint64_t da3 = make_desc(sb + 3 * ST_BYTES + w * 8192), db3 = make_desc(sb + 3 * ST_BYTES + A_BYTES);
      const uint64_t dax = make_desc_noswz(sb + OFF_EXA + w * 2048), dbx = make_desc_noswz(sb + OFF_EXB);
      fence_acc(a1);
#pragma unroll
      for (int i = 0; i < 32; i++) asm volatile("mov.b32 %0, %1;" : "=f"(p0[i]) : "f"(a1[i]));
#pragma unroll
      for (int i = 32; i < NX / 2; i++) asm volatile("mov.b32 %0, %1;" : "=f"(p1[i - 32]) : "f"(a1[i]));
      mbar_wait(BAR(B_FULL + 2), 1);
      CT(64 + 14);
      bar_sync(turn_me, 256);
      wgmma_fence();
#pragma unroll
      for (int kk = 0; kk < 4; kk++) wgmma_g1(p0, da2 + kk * 2, db2 + kk * 2, 1);
      wgmma_commit();
      mbar_wait(BAR(B_FULL + 3), 1);
      CT(64 + 15);
      wgmma_fence();
#pragma unroll
      for (int kk = 0; kk < 4; kk++) wgmma_g1(p0, da3 + kk * 2, db3 + kk * 2, 1);
      wgmma_g1(p0, dax, dbx, 1);
      wgmma_commit();
      bar_arrive(turn_other, 256);
      wgmma_wait0();
      fence_acc(p0);
      pack(IC<0>());
      put_chunk(IC<0>());
      CT(20);
      bar_sync(turn_me, 256);
      wgmma_fence();
#pragma unroll
      for (int kk = 0; kk < 4; kk++) wgmma_g1(p1, da2 + kk * 2, db2 + 512 + kk * 2, 1);
      wgmma_commit();
      staged(w ? B_EPI0B : B_EPI);
      CT(21);
      wgmma_fence();
#pragma unroll
      for (int kk = 0; kk < 4; kk++) wgmma_g1(p1, da3 + kk * 2, db3 + 512 + kk * 2, 1);
      wgmma_g1(p1, dax, dbx + 128, 1);
      wgmma_commit();
      bar_arrive(turn_other, 256);
      wgmma_wait1();
      release(2);
      kdone(15);
      mbar_wait(BAR(B_STAT), 0);
    }
    fence_acc(p1);
    CT(1);
    pack(IC<1>());
    pack(IC<2>());
    pack(IC<3>());
#pragma unroll
    for (int i = 16; i < NX / 4; i++) asm volatile("" : "+r"(R[i]));
#pragma unroll
    for (int i = 0; i < 128; i++) asm volatile("" : "=f"(acc[i]));
    mbar_wait(BAR(B_FULL + 0), 0);
    CT(2);
    static_for<4>([&](auto ic) {
      constexpr int c = decltype(ic)::value;
      if (c) mbar_wait(BAR(B_FULL + c), 0);
      CT(64 + 16 + c);
      bar_sync(turn_me, 256);
      wgmma_fence();
      mma_rs(IC<c>(), IC<0>(), IC<min_c(4, NX / 16 - 4 * c)>());
      bar_arrive(turn_other, 256);
      if constexpr (c == 0) { put_chunk(IC<1>()); staged(B_EPI + 1); kdone(16); } else kdone_x(16 + c, IC<c - 1>());
    });
#pragma unroll 1
    for (int k = 20; k < 23; k++) {
      kstep(acc, k, false, k < 22);
      if (k == 20) {
        kdone_x(k, IC<3>());
      } else {
        if (k == 21) put_chunk(IC<2>()); else put_chunk(IC<3>());
        __syncwarp();
        if (lane == 0) mbar_arrive(BAR(B_EPI + k - 19));
        kdone(k);
      }
    }
    uint32_t wf[32][4];
    auto load_wf = [&](auto hc) {
      constexpr int h = decltype(hc)::value;
      const int d = w * 64 + (lane >> 4) * 8 + (lane & 7);
      const uint32_t ad = sb + round_off(h) + (lane & 8) * 1024 + d * 64 + ((wi ^ ((lane >> 1) & 3)) << 4);
#pragma unroll
      for (int i = 0; i < 4; i++) ldsm_x4_t(ad + i * 1024, wf[4 * h + i][0], wf[4 * h + i][1], wf[4 * h + i][2], wf[4 * h + i][3]);
    };
    auto load_wf_rest = [&]() { static_for<8 - NREG_H>([&](auto ic) { load_wf(IC<NREG_H + decltype(ic)::value>()); }); };
#pragma unroll
    for (int i = 0; i < 4 * NREG_H; i++) { wf[i][0] = 0; wf[i][1] = 0; wf[i][2] = 0; wf[i][3] = 0; }
    const int grp = tau * 2 + m;
#pragma unroll 1
    for (int k = 23; k < 46; k++) {
      kstep(acc, k, false, false, NX < 256 && k == MINI_K);
      if (moe) {
        static_for<NREG_H>([&](auto hc) {
          constexpr int h = decltype(hc)::value;
          if (k == mr_k(h) - 1 + MR_LAG) { mbar_wait(BAR(B_MR + (h & 1)), (h >> 1) & 1); CT(32 + h); load_wf(hc); }
        });
      }
      if (k == RESET_K && tid == 0) mbar_arrive(BAR(B_LATE));
      kdone(k);
    }
    asm volatile("barrier.cluster.arrive.relaxed.aligned;" ::: "memory");
    mbar_wait(BAR(B_STAT), 1);
    uint32_t wa[16][2];
    uint32_t cd = code_of(tag);
    uint4* hp_pub = &p.s->hstat[(grp * 8 + eps) * 128 + warp * 16 + g];
    const uint4* hp_poll = &p.s->hstat[(grp * 8 + 2 * q) * 128 + warp * 16 + g];
    const uint32_t vec_off = (2 * wi) * 512 + q * 128 + ((g ^ (2 * q)) << 4);
    {
      float as[64], ak[64];
      fence_acc(acc);
#pragma unroll
      for (int i = 0; i < 64; i++) asm volatile("mov.b32 %0, %1;" : "=f"(as[i]) : "f"(acc[64 + i]));
#pragma unroll
      for (int i = 0; i < 64; i++) asm volatile("mov.b32 %0, %1;" : "=f"(ak[i]) : "f"(acc[i]));
      const uint64_t da1 = make_desc(sb + 2 * ST_BYTES + w * 8192), db1 = make_desc(sb + 2 * ST_BYTES + A_BYTES);
      const uint64_t da2 = make_desc(sb + 3 * ST_BYTES + w * 8192), db2 = make_desc(sb + 3 * ST_BYTES + A_BYTES);
      mbar_wait(BAR(B_FULL + 2), 1);
      CT(64 + 46);
      bar_sync(turn_me, 256);
      wgmma_fence();
#pragma unroll
      for (int kk = 0; kk < 4; kk++) wgmma_n128(as, da1 + kk * 2, db1 + 1024 + kk * 2);
      wgmma_commit();
      mbar_wait(BAR(B_FULL + 3), 1);
      CT(64 + 47);
      wgmma_fence();
#pragma unroll
      for (int kk = 0; kk < 4; kk++) wgmma_n128(as, da2 + kk * 2, db2 + 1024 + kk * 2);
      wgmma_commit();
      bar_arrive(turn_other, 256);
      const uint32_t rx = mapa(sb + OFF_PEER + w * 4096 + vec_off, 1 - m), rb = mapa(BAR(B_XCH), 1 - m);
      asm volatile("barrier.cluster.wait.aligned;" ::: "memory");
      CT(24);
      wgmma_wait0();
      fence_acc(as);
      CT(25);
      auto keep = [&]() {
        bar_sync(turn_me, 256);
        wgmma_fence();
#pragma unroll
        for (int kk = 0; kk < 4; kk++) wgmma_n128(ak, da1 + kk * 2, db1 + kk * 2);
        wgmma_commit();
#pragma unroll
        for (int kk = 0; kk < 4; kk++) wgmma_n128(ak, da2 + kk * 2, db2 + kk * 2);
        wgmma_commit();
        if (w == 0) bar_arrive(turn_other, 256);
      };
#pragma unroll
      for (int i = 0; i < 8; i++) {
        if (i == SEND_FIRST) keep();
        const float* ac = &as[16 * (i >> 1) + 2 * (i & 1)];
        st_async_v4(rx + (i >> 1) * 8192 + (i & 1) * 512, rb, pack_bf16(ac[0], ac[1]), pack_bf16(ac[4], ac[5]), pack_bf16(ac[8], ac[9]), pack_bf16(ac[12], ac[13]));
      }
      CT(26);
#pragma unroll
      for (int i = 0; i < 4; i++) {
        const uint4 v = lds128_v(sb + OFF_WR + q * 80 + i * 16);
        const uint32_t vv[4] = {v.x, v.y, v.z, v.w};
#pragma unroll
        for (int z = 0; z < 4; z++) {
          asm volatile("{\n.reg .pred p;\nsetp.ne.b32 p, %2, 0;\nselp.b32 %0, %1, 0x3F803F80, p;\n}" : "=r"(wa[4 * i + z][0]) : "r"(vv[z]), "r"(g & 1));
          asm volatile("{\n.reg .pred p;\nsetp.ne.b32 p, %2, 0;\nselp.b32 %0, %1, 0x3F803F80, p;\n}" : "=r"(wa[4 * i + z][1]) : "r"(vv[z]), "r"(g & 1));
        }
      }
      pin(cd); pin(hp_pub); pin(hp_poll);
      CT(27);
      wgmma_wait1();
      release(2);
      wgmma_wait0();
      fence_acc(ak);
      CT(3);
#pragma unroll
      for (int i = 0; i < 8; i++) {
        const float* ac = &ak[16 * (i >> 1) + 2 * (i & 1)];
        sts128(sb + (2 + (i >> 2)) * ST_BYTES + w * 8192 + ((i >> 1) & 1) * 4096 + (i & 1) * 512 + vec_off,
               pack_bf16(ac[0], ac[1]), pack_bf16(ac[4], ac[5]), pack_bf16(ac[8], ac[9]), pack_bf16(ac[12], ac[13]));
      }
    }
    uint32_t h[8][4];
    {
      const int qq = 2 * (warp & 1) + ((lane >> 3) & 1);
      const uint32_t lo = (lane >> 4) * 512 + qq * 128 + (((lane & 7) ^ (2 * qq)) << 4);
      bar_sync(NB_BOTH, 256);
#pragma unroll
      for (int ks = 0; ks < 8; ks++)
        ldsm_x4_t(sb + (2 + w) * ST_BYTES + (ks >> 2) * 8192 + (wi >> 1) * 4096 + (ks & 3) * 1024 + lo, h[ks][0], h[ks][1], h[ks][2], h[ks][3]);
      CT(28);
      mbar_wait_cluster(BAR(B_XCH), 0);
      CT(4);
      uint32_t r[8][4];
#pragma unroll
      for (int ks = 0; ks < 8; ks++) ldsm_x4_t(sb + OFF_PEER + (warp >> 1) * 8192 + ks * 1024 + lo, r[ks][0], r[ks][1], r[ks][2], r[ks][3]);
      float d[4][4] = {};
#pragma unroll
      for (int ks = 0; ks < 8; ks++) {
#pragma unroll
        for (int i = 0; i < 4; i++) {
          h[ks][i] = badd2(h[ks][i], r[ks][i]);
          mma1688(d[i], h[ks][i], wa[2 * ks + (i >> 1)][i & 1], h[ks][i]);
        }
      }
#pragma unroll
      for (int i = 0; i < 2; i++) {
        const float sq = (g & 1) ? d[i][1] + d[i + 2][1] : d[i][0] + d[i + 2][0];
        const float e0 = d[i][2] + d[i + 2][2], e1 = d[i][3] + d[i + 2][3];
        const float other = __shfl_xor_sync(0xffffffffu, (g & 1) ? e0 : e1, 4);
        if (q == (g >> 1)) pkt_st128(hp_pub + 8 * i, with_bit((g & 1) ? other : e0, cd), with_bit(sq, cd >> 1), __float_as_uint((g & 1) ? e1 : other), tag);
      }
    }
    CT(5);
    if (tid == 0) mbar_arrive(BAR(B_KEY));
    delay_clk<HOP1_DELAY>();
    float m_bf, sd, inv_sd, r_bf;
    uint4* key_pub = &p.s->key[((lane & 7) * 16 + grp) * 2];
    uint4* cand_pub = &p.s->cand[grp * 256 + eps * 32 + q];
    uint32_t trow_inv = 0xFFFFu - (uint32_t)row_of(grp * 128 + 32 * (warp >> 1) + 8 * (g >> 1) + 4 * (warp & 1) + (q & 2) + (g & 1));
    {
      uint4 u[4];
#pragma unroll
      for (int i = 0; i < 4; i++) u[i] = pkt_ld128(hp_poll + (i & 1) * 128 + (i >> 1) * 8);
      const float wsum = SM_(float, OFF_WSUM);
      pin(key_pub); pin(cand_pub); pin(trow_inv);
      uint32_t n = 0;
      while (true) {
        bool ok[4];
#pragma unroll
        for (int i = 0; i < 4; i++) ok[i] = u[i].w == tag && pair_code(u[i].x, u[i].y) == cd;
        const bool all = __all_sync(0xffffffffu, ok[0] && ok[1] && ok[2] && ok[3]);
        if (all || ++n > SPIN_LIMIT) break;
#pragma unroll
        for (int i = 0; i < 4; i++) pkt_ld128_if(u[i], hp_poll + (i & 1) * 128 + (i >> 1) * 8, !ok[i]);
      }
      CT(6);
      float a[3], b[3];
      a[0] = __uint_as_float(u[0].x & ~1u) + __uint_as_float(u[1].x & ~1u); b[0] = __uint_as_float(u[2].x & ~1u) + __uint_as_float(u[3].x & ~1u);
      a[1] = __uint_as_float(u[0].y & ~1u) + __uint_as_float(u[1].y & ~1u); b[1] = __uint_as_float(u[2].y & ~1u) + __uint_as_float(u[3].y & ~1u);
      a[2] = __uint_as_float(u[0].z) + __uint_as_float(u[1].z); b[2] = __uint_as_float(u[2].z) + __uint_as_float(u[3].z);
#pragma unroll
      for (int i = 0; i < 3; i++) {
        a[i] = ((q & 2) ? b[i] : a[i]) + __shfl_xor_sync(0xffffffffu, (q & 2) ? a[i] : b[i], 2);
        a[i] += __shfl_xor_sync(0xffffffffu, a[i], 1);
      }
      const float mu = a[0] * (1.f / 1024.f);
      m_bf = bf16r(mu);
      sd = ln_sd(a[1] * (1.f / 1024.f) - mu * mu);
      inv_sd = rcp_fast(sd);
      r_bf = bf16r((a[2] - m_bf * wsum) * inv_sd);
    }
    {
      const uint32_t u = __float_as_uint(r_bf);
      const uint32_t ord = (u & 0x80000000u) ? ~u : (u | 0x80000000u);
      const uint32_t key = (ord & 0xFFFF0000u) | trow_inv;
      const uint32_t wk = __reduce_max_sync(0xffffffffu, key);
      if (key == wk) SM_(uint2, OFF_WKEY + warp * 8) = make_uint2(wk, (__float_as_uint(m_bf) >> 16) | __float_as_uint(sd));
      const uint32_t wmask = __ballot_sync(0xffffffffu, key == wk);
      const bool hi = (wmask & 0xCCCCCCCCu) != 0;
      uint32_t c[16];
#pragma unroll
      for (int ks = 0; ks < 8; ks++) { c[2 * ks] = hi ? h[ks][1] : h[ks][0]; c[2 * ks + 1] = hi ? h[ks][3] : h[ks][2]; }
      bar_sync(NB_BOTH, 256);
      const uint2 km = SM_(uint2, OFF_WKEY + (lane & 7) * 8);
      const uint32_t bk = __reduce_max_sync(0xffffffffu, km.x);
      if (wk == bk) {
        if ((wmask >> (lane & 28)) & 15) {
#pragma unroll
          for (int ks = 0; ks < 8; ks++) pkt_st128(cand_pub + ks * 4, c[2 * ks], tag, c[2 * ks + 1], tag);
        }
      } else if (eps == 0) {
        const uint32_t kx = __shfl_sync(0xffffffffu, km.x, warp ^ 1), ms = __shfl_sync(0xffffffffu, km.y, warp ^ 1);
        if (kx == bk && lane < 8) pkt_st128(key_pub, bk, tag, ms, tag);
      }
      CT(7);
    }
    {
      const float ih = bf16r(inv_sd);
      const uint32_t nm = pack_bf16(-m_bf, -m_bf), iv = pack_bf16(ih, inv_sd - ih);
      const uint32_t nm_o = __shfl_xor_sync(0xffffffffu, nm, 2), iv_o = __shfl_xor_sync(0xffffffffu, iv, 2);
      const uint32_t nm2[2] = {(q & 2) ? nm_o : nm, (q & 2) ? nm : nm_o}, iv2[2] = {(q & 2) ? iv_o : iv, (q & 2) ? iv : iv_o};
      const uint32_t hi2[2] = {__byte_perm(iv2[0], 0, 0x1010), __byte_perm(iv2[1], 0, 0x1010)}, lo2[2] = {__byte_perm(iv2[0], 0, 0x3232), __byte_perm(iv2[1], 0, 0x3232)};
      const uint32_t oa = sb + OFF_OUT + (warp * 16 + (lane & 15)) * 128;
#pragma unroll
      for (int ks = 0; ks < 8; ks++) {
        uint32_t o[4];
#pragma unroll
        for (int i = 0; i < 4; i++) {
          const uint32_t dd = badd2(h[ks][i], nm2[i & 1]);
          o[i] = badd2(h[ks][i], bfma2(dd, hi2[i & 1], bmul2(dd, lo2[i & 1])));
        }
        stsm_x4(oa + (ks >> 2) * 16384 + (((2 * (ks & 3) + (lane >> 4)) ^ (lane & 7)) << 4), o[0], o[1], o[2], o[3]);
      }
      staged(B_OUT);
    }
    CT(8);
    uint32_t df[16][4];
    auto load_df = [&]() {
      const int frow = (lane & 7) + ((lane >> 4) << 3), hi = (lane >> 3) & 1;
      const uint32_t base = sb + down_off(warp >> 1) + (warp & 1) * 8192 + frow * 128;
#pragma unroll
      for (int mt = 0; mt < 8; mt++) {
#pragma unroll
        for (int ks = 0; ks < 2; ks++)
          ldsm_x4_t(base + (mt >> 2) * 4096 + ks * 2048 + (((2 * (mt & 3) + hi) ^ (lane & 7)) << 4),
                    df[2 * mt + ks][0], df[2 * mt + ks][1], df[2 * mt + ks][2], df[2 * mt + ks][3]);
      }
    };
    if (moe) {
      mbar_wait(BAR(B_GU), 0);
      load_wf_rest();
      mbar_wait(BAR(B_DN), 0);
      load_df();
    }
    uint4* y_pub = &p.s->ypart[cid * 256 + tid];
    uint32_t xs_ad = sb + OFF_XSEL + (8 * (g >> 2) + 4 * w + (g & 3)) * 32 + q * 8, gp_ad = sb + OFF_GP + (wi * 8 + g) * 16 + w * 8 + (q >> 1) * 4;
    pin(y_pub); pin(xs_ad); pin(gp_ad);
    mbar_wait(BAR(B_XS), 0);
    CT(9);
    if (moe) {
      float gd[8][4] = {};
      uint2 bx[4];
#pragma unroll
      for (int r = 0; r < 4; r++) bx[r] = smem_at<uint2>(xs_ad + r * 512);
#pragma unroll
      for (int r = 0; r < 4; r++) {
#pragma unroll
        for (int i = 0; i < 8; i++) mma16816(gd[i], wf[8 * r + i][0], wf[8 * r + i][1], wf[8 * r + i][2], wf[8 * r + i][3], bx[r].x, bx[r].y);
      }
      const float gs = sel4(q, gd[0][0] + gd[1][1], gd[2][0] + gd[3][1], gd[4][0] + gd[5][1], gd[6][0] + gd[7][1]);
      const float us = sel4(q, gd[0][2] + gd[1][3], gd[2][2] + gd[3][3], gd[4][2] + gd[5][3], gd[6][2] + gd[7][3]);
      float v = ((q & 2) ? us : gs) + __shfl_xor_sync(0xffffffffu, (q & 2) ? gs : us, 2);
      v += __shfl_xor_sync(0xffffffffu, v, 1);
      smem_at<float>(gp_ad) = v;
      CT(10);
      bar_sync(NB_BOTH, 256);
      uint32_t bq[4];
      {
        const float4 p0 = SM_(float4, OFF_GP + lane * 16);
        const float gt = bf16r(p0.x + p0.z), up = bf16r(p0.y + p0.w);
        const float act = bf16r(gt * sigmoid_fast(gt)) * up;
        const uint32_t pr = pack_bf16(act, __shfl_down_sync(0xffffffffu, act, 1));
#pragma unroll
        for (int i = 0; i < 4; i++) bq[i] = __shfl_sync(0xffffffffu, pr, 8 * i + 2 * q);
      }
      CT(11);
      float yd[8][4] = {};
#pragma unroll
      for (int ks = 0; ks < 2; ks++) {
#pragma unroll
        for (int mt = 0; mt < 8; mt++) mma16816(yd[mt], df[2 * mt + ks][0], df[2 * mt + ks][1], df[2 * mt + ks][2], df[2 * mt + ks][3], bq[2 * ks], bq[2 * ks + 1]);
      }
      pkt_st128(y_pub, with_bit(sel4(q, yd[0][0], yd[2][0], yd[4][0], yd[6][0]), cd), with_bit(sel4(q, yd[0][2], yd[2][2], yd[4][2], yd[6][2]), cd >> 1),
                with_bit(sel4(q, yd[1][0], yd[3][0], yd[5][0], yd[7][0]), cd), with_bit(sel4(q, yd[1][2], yd[3][2], yd[5][2], yd[7][2]), cd >> 1));
    } else {
      const long long tw = clock64();
      while (clock64() - tw < IDLE_WAIT_CLK) __nanosleep(100);
    }
    CT(12);
    const uint32_t kv = SM_(uint32_t, OFF_KV);
    const int tsel = (int)(~kv & 2047u);
    const float r_sel = __uint_as_float((kv & 0x80000000u) ? (kv & 0x7FFF0000u) : (~kv & 0xFFFF0000u));
    const float sig = bf16r(sigmoid_fast(r_sel));
    const int pfin = 2 * cid + (tid & 1);
    const int col_fin = (pfin >> 5) * 128 + (pfin & 3) * 32 + ((pfin & 31) >> 2) + 8 * ((tid >> 1) & 3);
    const int sel_off = (col_fin >> 4) * 32 + ((col_fin & 7) >> 1) * 8 + ((col_fin >> 3) & 1) * 4 + (col_fin & 1) * 2;
    const float hn_fin = __uint_as_float((uint32_t)SM_(uint16_t, OFF_XSEL + sel_off) << 16), h_fin = __uint_as_float((uint32_t)SM_(uint16_t, OFF_HSEL + sel_off) << 16);
    bf16* out_fin = p.out + (size_t)tsel * 1024 + col_fin;
    {
      const uint4* src = &p.s->ypart[(16 + (tid >> 1)) * 256 + pfin];
      pin(src); pin(out_fin);
      uint4 v = make_uint4(0, 0, 0, 0);
      if (warp < 7) {
        delay_clk<HOP3_DELAY>();
        uint32_t n = 0;
        bool ok = false;
        do {
          pkt_ld128_if(v, src, !ok);
          ok = pair_code(v.x, v.y) == cd && pair_code(v.z, v.w) == cd;
        } while (!__all_sync(0xffffffffu, ok) && ++n < SPIN_LIMIT);
      }
      CT(13);
      const float y0 = __uint_as_float(v.x & ~1u), y1 = __uint_as_float(v.y & ~1u), y2 = __uint_as_float(v.z & ~1u), y3 = __uint_as_float(v.w & ~1u);
      const float a0 = ((lane & 2) ? y1 : y0) + __shfl_xor_sync(0xffffffffu, (lane & 2) ? y0 : y1, 2);
      const float a1 = ((lane & 2) ? y3 : y2) + __shfl_xor_sync(0xffffffffu, (lane & 2) ? y2 : y3, 2);
      float b = ((lane & 4) ? a1 : a0) + __shfl_xor_sync(0xffffffffu, (lane & 4) ? a0 : a1, 4);
      b += __shfl_xor_sync(0xffffffffu, b, 8);
      b += __shfl_xor_sync(0xffffffffu, b, 16);
      if (lane < 8) SM_(float, OFF_FIN + lane * 32 + warp * 4) = b;
    }
    bar_sync(NB_BOTH, 256);
    if (tid < 8) {
      const float4 y0 = SM_(float4, OFF_FIN + tid * 32), y1 = SM_(float4, OFF_FIN + tid * 32 + 16);
      const float y = ((y0.x + y0.y) + (y0.z + y0.w)) + ((y1.x + y1.y) + y1.z);
      *out_fin = __float2bfloat16_rn(h_fin + bf16r(hn_fin + bf16r(bf16r(y) * sig)));
      if (cid == 0 && tid == 0) st_relaxed32(&p.s->epoch, tag);
    }
    CT(14);
  }
}

__global__ void __launch_bounds__(384, 1) occupancy_probe_kernel() {}

typedef CUresult (*EncodeFn)(CUtensorMap*, CUtensorMapDataType, cuuint32_t, void*, const cuuint64_t*, const cuuint64_t*, const cuuint32_t*, const cuuint32_t*,
                             CUtensorMapInterleave, CUtensorMapSwizzle, CUtensorMapL2promotion, CUtensorMapFloatOOBfill);

static void make_tm(EncodeFn enc, CUtensorMap* tm, const void* ptr, uint64_t rows, uint64_t cols, uint32_t brows, uint32_t bcols, CUtensorMapSwizzle sw,
                    CUtensorMapL2promotion promo = CU_TENSOR_MAP_L2_PROMOTION_L2_128B) {
  cuuint64_t dims[2] = {cols, rows};
  cuuint64_t strides[1] = {cols * 2};
  cuuint32_t box[2] = {bcols, brows};
  cuuint32_t es[2] = {1, 1};
  enc(tm, CU_TENSOR_MAP_DATA_TYPE_BFLOAT16, 2, const_cast<void*>(ptr), dims, strides, box, es, CU_TENSOR_MAP_INTERLEAVE_NONE, sw,
      promo, CU_TENSOR_MAP_FLOAT_OOB_FILL_NONE);
}

static void make_tm_rows(EncodeFn enc, CUtensorMap* tm, const void* ptr, uint64_t cols, uint32_t brows, uint32_t bcols, CUtensorMapSwizzle sw,
                         CUtensorMapL2promotion promo = CU_TENSOR_MAP_L2_PROMOTION_L2_128B) {
  cuuint64_t dims[4] = {cols, 2, 2, 512};
  cuuint64_t strides[3] = {row_of(1) * cols * 2, row_of(2) * cols * 2, row_of(4) * cols * 2};
  cuuint32_t box[4] = {bcols, 2, 2, brows / 4};
  cuuint32_t es[4] = {1, 1, 1, 1};
  enc(tm, CU_TENSOR_MAP_DATA_TYPE_BFLOAT16, 4, const_cast<void*>(ptr), dims, strides, box, es, CU_TENSOR_MAP_INTERLEAVE_NONE, sw, promo,
      CU_TENSOR_MAP_FLOAT_OOB_FILL_NONE);
}

extern "C" void kernel_launch(void* const* d_in, const int* in_sizes, int n_in, void* d_out, int out_size) {
  (void)in_sizes; (void)n_in; (void)out_size;
  static EncodeFn enc = nullptr;
  static void* abT = nullptr;
  static int map = 0;
  if (!enc) {
    void* fn = nullptr; cudaDriverEntryPointQueryResult st;
    cudaGetDriverEntryPoint("cuTensorMapEncodeTiled", &fn, cudaEnableDefault, &st);
    enc = (EncodeFn)fn;
    cudaGetSymbolAddress(&abT, g_scratch);
    cudaFuncSetAttribute(fnet_moe_kernel<0>, cudaFuncAttributeMaxDynamicSharedMemorySize, SMEM_TOTAL);
    cudaFuncSetAttribute(fnet_moe_kernel<1>, cudaFuncAttributeMaxDynamicSharedMemorySize, SMEM_TOTAL);
    cudaFuncSetAttribute(occupancy_probe_kernel, cudaFuncAttributeMaxDynamicSharedMemorySize, SMEM_TOTAL);
    cudaFuncSetAttribute(occupancy_probe_kernel, cudaFuncAttributeNonPortableClusterSizeAllowed, 1);
    auto max_clusters = [&](int size) {
      cudaLaunchConfig_t cfg = {};
      cfg.gridDim = dim3(128); cfg.blockDim = dim3(384); cfg.dynamicSmemBytes = SMEM_TOTAL;
      cudaLaunchAttribute at[1];
      at[0].id = cudaLaunchAttributeClusterDimension; at[0].val.clusterDim.x = size; at[0].val.clusterDim.y = 1; at[0].val.clusterDim.z = 1;
      cfg.attrs = at; cfg.numAttrs = 1;
      int ncl = 0;
      return cudaOccupancyMaxActiveClusters(&ncl, occupancy_probe_kernel, &cfg) == cudaSuccess ? ncl : 0;
    };
    int dev = 0, sms = 0;
    cudaGetDevice(&dev);
    cudaDeviceGetAttribute(&sms, cudaDevAttrMultiProcessorCount, dev);
    map = (sms == 132 && max_clusters(2) == 66 && max_clusters(16) == 7) ? 0 : 1;
    (void)cudaGetLastError();
  }
  Params p;
  const bf16* x = (const bf16*)d_in[0];
  make_tm(enc, &p.tmD0, d_in[3], 1024, 1024, 128, 64, CU_TENSOR_MAP_SWIZZLE_128B);
  make_tm(enc, &p.tmD1, d_in[4], 1024, 1024, 128, 64, CU_TENSOR_MAP_SWIZZLE_128B);
  make_tm(enc, &p.tmX, x, 2048, 1024, map == 0 ? NX0 : 256, 64, CU_TENSOR_MAP_SWIZZLE_128B);
  make_tm_rows(enc, &p.tmXr, x, 1024, 64, 64, CU_TENSOR_MAP_SWIZZLE_128B);
  make_tm(enc, &p.tmAbS, abT, 2048, 2048, 64, 64, CU_TENSOR_MAP_SWIZZLE_128B);
  make_tm(enc, &p.tmAbL, abT, 2048, 2048, 128, 64, CU_TENSOR_MAP_SWIZZLE_128B);
  make_tm_rows(enc, &p.tmW0, d_in[1], 2048, 128, 64, CU_TENSOR_MAP_SWIZZLE_128B);
  make_tm_rows(enc, &p.tmW1, d_in[2], 2048, 128, 64, CU_TENSOR_MAP_SWIZZLE_128B);
  {
    cuuint64_t dims[5] = {1024, 2, 4, 2, 2048};
    cuuint64_t strides[4] = {row_of(1) * 2048, row_of(8) * 2048, row_of(2) * 2048, 2048};
    cuuint32_t box[5] = {64, 2, 4, 2, 1};
    cuuint32_t es[5] = {1, 1, 1, 1, 1};
    enc(&p.tmOut, CU_TENSOR_MAP_DATA_TYPE_BFLOAT16, 5, d_out, dims, strides, box, es, CU_TENSOR_MAP_INTERLEAVE_NONE, CU_TENSOR_MAP_SWIZZLE_128B,
        CU_TENSOR_MAP_L2_PROMOTION_NONE, CU_TENSOR_MAP_FLOAT_OOB_FILL_NONE);
  }
  {
    cuuint64_t dims[5] = {1024, 2, 4, 2, 8};
    cuuint64_t strides[4] = {2048, 4 * 2048, 2 * 2048, 256 * 2048};
    cuuint32_t box[5] = {64, 2, 4, 2, 8};
    cuuint32_t es[5] = {1, 1, 1, 1, 1};
    enc(&p.tmXh, CU_TENSOR_MAP_DATA_TYPE_BFLOAT16, 5, const_cast<bf16*>(x) + 240 * 1024, dims, strides, box, es, CU_TENSOR_MAP_INTERLEAVE_NONE,
        CU_TENSOR_MAP_SWIZZLE_128B, CU_TENSOR_MAP_L2_PROMOTION_L2_128B, CU_TENSOR_MAP_FLOAT_OOB_FILL_NONE);
  }
  make_tm(enc, &p.tmAbM, abT, 2048, 2048, 128, 16, CU_TENSOR_MAP_SWIZZLE_32B, CU_TENSOR_MAP_L2_PROMOTION_NONE);
  make_tm_rows(enc, &p.tmWM0, d_in[1], 2048, 128, 16, CU_TENSOR_MAP_SWIZZLE_32B);
  make_tm_rows(enc, &p.tmWM1, d_in[2], 2048, 128, 16, CU_TENSOR_MAP_SWIZZLE_32B);
  make_tm(enc, &p.tmG, d_in[7], 1024, 3584, 128, 32, CU_TENSOR_MAP_SWIZZLE_64B);
  make_tm(enc, &p.tmU, d_in[8], 1024, 3584, 128, 32, CU_TENSOR_MAP_SWIZZLE_64B);
  make_tm(enc, &p.tmDn, d_in[9], 3584, 1024, 32, 64, CU_TENSOR_MAP_SWIZZLE_128B);
  p.x = x; p.Dre = (const bf16*)d_in[3]; p.Dim = (const bf16*)d_in[4];
  p.wr = (const bf16*)d_in[6]; p.wdown = (const bf16*)d_in[9]; p.wgate = (const bf16*)d_in[7]; p.wup = (const bf16*)d_in[8];
  p.out = (bf16*)d_out; p.s = (Scratch*)abT;
  if (map == 1) fnet_moe_kernel<1><<<128, 384, SMEM_TOTAL>>>(p);
  else fnet_moe_kernel<0><<<132, 384, SMEM_TOTAL>>>(p);
}
```
